```python
import torch

def _softmax(x, axis=-1):
    return torch.softmax(x, dim=axis)

def _gelu(x):
    return torch.nn.functional.gelu(x, approximate='tanh')

def _silu(x):
    return torch.nn.functional.silu(x)

def _sigmoid(x):
    return torch.sigmoid(x)

def _layernorm(x, axis=-1, eps=1e-05):
    m = x.mean(dim=axis, keepdim=True)
    v = x.var(dim=axis, keepdim=True, unbiased=False)
    return (x - m) / torch.sqrt(v + eps)

def _scatter_add(tgt, idx, src, axis=0):
    return tgt.clone().index_add_(axis, idx, src)

def _segment_sum(src, seg, n):
    out = torch.zeros((n,) + src.shape[1:], dtype=src.dtype)
    return out.index_add_(0, seg, src)

def _pad(x, pw):
    flat = tuple((v for pair in reversed(pw) for v in pair))
    return torch.nn.functional.pad(x, flat)
kernel_name = 'adaLN_cond__mha_block_cached__mixer_s_mlp__prompt'

def setup_inputs():

    _w = lambda a: (lambda t: t.to(torch.bfloat16) if t.is_floating_point() else t)(torch.as_tensor(a))

    def _A_setup():
        B, Sq, D = (1, 2048, 640)
        H, Sk, Dh = (32, 2048, 192)
        return {'x': _w((lambda *s: torch.randn(*s, dtype=torch.bfloat16) * 0.1)(B, Sq, D)), 'k_cache': _w((lambda *s: torch.randn(*s, dtype=torch.bfloat16) * 0.8)(B, H, Sk, Dh)), 'v_cache': _w((lambda *s: torch.randn(*s, dtype=torch.bfloat16) * 0.8)(B, H, Sk, Dh)), 'wq': _w((lambda *s: torch.randn(*s, dtype=torch.bfloat16) * 0.8)(D, H * Dh) * D ** (-0.5)), 'wo': _w((lambda *s: torch.randn(*s, dtype=torch.bfloat16) * 0.8)(H * Dh, D) * (H * Dh) ** (-0.5))}
    _A_in = _A_setup()

    def _B_setup():
        B, S, D, F = (1, 2048, 640, 1536)
        return {'x': _w((lambda *s: torch.randn(*s, dtype=torch.bfloat16) * 0.1)(B, S, D)), 'w1': _w((lambda *s: torch.randn(*s, dtype=torch.bfloat16) * 3.2)(D, D) * D ** (-0.5)), 'w2': _w((lambda *s: torch.randn(*s, dtype=torch.bfloat16) * 3.2)(D, D) * D ** (-0.5)), 'w3': _w((lambda *s: torch.randn(*s, dtype=torch.bfloat16) * 3.2)(D, F) * D ** (-0.5)), 'w4': _w((lambda *s: torch.randn(*s, dtype=torch.bfloat16) * 3.2)(F, D) * F ** (-0.5))}
    _B_in = _B_setup()
    return {'A_x': _A_in['x'], 'A_k_cache': _A_in['k_cache'], 'A_v_cache': _A_in['v_cache'], 'A_wq': _A_in['wq'], 'A_wo': _A_in['wo'], 'B_x': _B_in['x'], 'B_w1': _B_in['w1'], 'B_w2': _B_in['w2'], 'B_w3': _B_in['w3'], 'B_w4': _B_in['w4'], 'c': _w((lambda *s: torch.randn(*s, dtype=torch.bfloat16) * 0.2)(1, 640) * 8.0), 'w_mod': _w((lambda *s: torch.randn(*s, dtype=torch.bfloat16) * 0.2)(640, 6 * 640) * 640 ** (-0.5) * 8.0)}

def reference(A_x, A_k_cache, A_v_cache, A_wq, A_wo, B_x, B_w1, B_w2, B_w3, B_w4, c, w_mod):

    def _A_ref(x, k_cache, v_cache, wq, wo):
        B, Sq, D = x.shape
        H, Dh = (32, 192)
        q = (lambda x, *d: x.permute(*d))((x @ wq).reshape(B, Sq, H, Dh), 0, 2, 1, 3)
        scores = torch.einsum('bhqd,bhkd->bhqk', q, k_cache) * Dh ** (-0.5)
        p = _softmax(scores, axis=-1)
        o = torch.einsum('bhqk,bhkd->bhqd', p, v_cache)
        return (lambda x, *d: x.permute(*d))(o, 0, 2, 1, 3).reshape(B, Sq, H * Dh) @ wo

    def _B_ref(x, w1, w2, w3, w4):
        B, S, D = x.shape
        h = _gelu(_layernorm(x, axis=-1) @ w1)
        c = D // 4
        g0 = _pad(h[:, :, 0 * c:1 * c], ((0, 0), (1, 0), (0, 0)))[:, :S, :]
        g1 = _pad(h[:, :, 1 * c:2 * c], ((0, 0), (0, 1), (0, 0)))[:, 1:, :]
        g2 = _pad(h[:, :, 2 * c:3 * c], ((0, 0), (2, 0), (0, 0)))[:, :S, :]
        g3 = _pad(h[:, :, 3 * c:], ((0, 0), (0, 2), (0, 0)))[:, 2:, :]
        hs = torch.concatenate([g0, g1, g2, g3], axis=-1) @ w2
        x1 = x + hs
        h2 = _gelu(_layernorm(x1, axis=-1) @ w3) @ w4
        return x1 + h2
    x = A_x
    mod = (_silu(c) @ w_mod).reshape(c.shape[0], 6, 1, -1)
    sa, ca, ga, sb, cb, gb = (mod[:, 0].clone(), mod[:, 1].clone(), mod[:, 2].clone(), mod[:, 3].clone(), mod[:, 4].clone(), mod[:, 5].clone())
    h = _layernorm(x, axis=-1) * (1 + ca) + sa
    x = x + ga * _A_ref(h, A_k_cache, A_v_cache, A_wq, A_wo)
    h = _layernorm(x, axis=-1) * (1 + cb) + sb
    x = x + gb * _B_ref(h, B_w1, B_w2, B_w3, B_w4)
    return x
```

```cpp
#include <cuda_runtime.h>
#include <cuda.h>
#include <cuda_bf16.h>
#include <stdint.h>

typedef __nv_bfloat16 bf16;

constexpr int S_  = 2048;
constexpr int D_  = 640;
constexpr int H_  = 32;
constexpr int DH_ = 192;
constexpr int HD_ = H_ * DH_;
constexpr int F_  = 1536;
constexpr float LN_EPS = 1e-5f;

__device__ __forceinline__ uint32_t smem_u32(const void* p) { return (uint32_t)__cvta_generic_to_shared(p); }
__device__ __forceinline__ void mbar_init(uint32_t a, uint32_t c) { asm volatile("mbarrier.init.shared::cta.b64 [%0], %1;" :: "r"(a), "r"(c) : "memory"); }
__device__ __forceinline__ void mbar_expect(uint32_t a, uint32_t b) { asm volatile("mbarrier.arrive.expect_tx.shared::cta.b64 _, [%0], %1;" :: "r"(a), "r"(b) : "memory"); }
__device__ __forceinline__ void mbar_arrive(uint32_t a) { asm volatile("mbarrier.arrive.shared::cta.b64 _, [%0];" :: "r"(a) : "memory"); }
__device__ __forceinline__ void mbar_arrive_remote(uint32_t ra) { asm volatile("mbarrier.arrive.shared::cluster.b64 _, [%0];" :: "r"(ra) : "memory"); }
__device__ __forceinline__ uint32_t mapa(uint32_t a, uint32_t cta) { uint32_t r; asm volatile("mapa.shared::cluster.u32 %0, %1, %2;" : "=r"(r) : "r"(a), "r"(cta)); return r; }
__device__ __forceinline__ uint32_t mbar_try(uint32_t a, uint32_t ph) {
  uint32_t ok;
  asm volatile("{\n.reg .pred p;\nmbarrier.try_wait.parity.shared::cta.b64 p, [%1], %2;\nselp.u32 %0, 1, 0, p;\n}\n" : "=r"(ok) : "r"(a), "r"(ph) : "memory");
  return ok;
}
__device__ __forceinline__ void mbar_wait(uint32_t a, uint32_t ph) {
  asm volatile(
      "{\n.reg .pred p;\n.reg .u32 n;\n"
      "mbarrier.try_wait.parity.shared::cta.b64 p, [%0], %1;\n"
      "@p bra DONE;\n"
      "mov.u32 n, 0;\n"
      "SPIN:\n"
      "mbarrier.try_wait.parity.shared::cta.b64 p, [%0], %1;\n"
      "@p bra DONE;\n"
      "add.u32 n, n, 1;\n"
      "setp.gt.u32 p, n, 16777216;\n"
      "@p trap;\n"
      "bra SPIN;\n"
      "DONE:\n}\n" :: "r"(a), "r"(ph) : "memory");
}
__device__ __forceinline__ void tma2d(uint32_t dst, const CUtensorMap* m, uint32_t bar, int c0, int c1) {
  asm volatile("cp.async.bulk.tensor.2d.shared::cluster.global.mbarrier::complete_tx::bytes [%0], [%1, {%3, %4}], [%2];"
               :: "r"(dst), "l"(m), "r"(bar), "r"(c0), "r"(c1) : "memory");
}
__device__ __forceinline__ void tma3d(uint32_t dst, const CUtensorMap* m, uint32_t bar, int c0, int c1, int c2) {
  asm volatile("cp.async.bulk.tensor.3d.shared::cluster.global.mbarrier::complete_tx::bytes [%0], [%1, {%3, %4, %5}], [%2];"
               :: "r"(dst), "l"(m), "r"(bar), "r"(c0), "r"(c1), "r"(c2) : "memory");
}
__device__ __forceinline__ void tma3d_mc(uint32_t dst, const CUtensorMap* m, uint32_t bar, int c0, int c1, int c2, uint16_t mask) {
  asm volatile("cp.async.bulk.tensor.3d.shared::cluster.global.mbarrier::complete_tx::bytes.multicast::cluster [%0], [%1, {%3, %4, %5}], [%2], %6;"
               :: "r"(dst), "l"(m), "r"(bar), "r"(c0), "r"(c1), "r"(c2), "h"(mask) : "memory");
}
__device__ __forceinline__ void prefetch_tmap(const CUtensorMap* m) { asm volatile("prefetch.tensormap [%0];" :: "l"(m) : "memory"); }
__device__ __forceinline__ void wg_fence() { asm volatile("wgmma.fence.sync.aligned;" ::: "memory"); }
__device__ __forceinline__ void wg_commit() { asm volatile("wgmma.commit_group.sync.aligned;" ::: "memory"); }
template <int N> __device__ __forceinline__ void wg_wait() { asm volatile("wgmma.wait_group.sync.aligned %0;" :: "n"(N) : "memory"); }
template <int N> __device__ __forceinline__ void fence_regs(float (&r)[N]) {
#pragma unroll
  for (int i = 0; i < N; i++) asm volatile("" : "+f"(r[i]) :: "memory");
}
template <int N> __device__ __forceinline__ void fence_regs(uint32_t (&r)[N]) {
#pragma unroll
  for (int i = 0; i < N; i++) asm volatile("" : "+r"(r[i]) :: "memory");
}
__device__ __forceinline__ uint64_t mkdesc(uint32_t addr, uint32_t lbo, uint32_t sbo) {
  return (uint64_t)((addr & 0x3FFFF) >> 4) | ((uint64_t)(lbo >> 4) << 16) | ((uint64_t)(sbo >> 4) << 32) | (1ull << 62);
}
__device__ __forceinline__ void bar_sync(int id, int n) { asm volatile("bar.sync %0, %1;" :: "r"(id), "r"(n) : "memory"); }
__device__ __forceinline__ void bar_arrive(int id, int n) { asm volatile("bar.arrive %0, %1;" :: "r"(id), "r"(n) : "memory"); }
__device__ __forceinline__ void cluster_sync() { asm volatile("barrier.cluster.arrive.aligned;\nbarrier.cluster.wait.aligned;" ::: "memory"); }
__device__ __forceinline__ void pdl_wait() { asm volatile("griddepcontrol.wait;" ::: "memory"); }
__device__ __forceinline__ void pdl_launch() { asm volatile("griddepcontrol.launch_dependents;" ::: "memory"); }
__device__ __forceinline__ float ex2(float x) { float y; asm("ex2.approx.ftz.f32 %0, %1;" : "=f"(y) : "f"(x)); return y; }
__device__ __forceinline__ uint32_t pack_bf16(float lo, float hi) { uint32_t r; asm("cvt.rn.bf16x2.f32 %0, %1, %2;" : "=r"(r) : "f"(hi), "f"(lo)); return r; }
__device__ __forceinline__ float bf_lo(uint32_t u) { return __uint_as_float(u << 16); }
__device__ __forceinline__ float bf_hi(uint32_t u) { return __uint_as_float(u & 0xffff0000u); }
__device__ __forceinline__ float bf_round(float x) { return __bfloat162float(__float2bfloat16_rn(x)); }
__device__ __forceinline__ float tanh_fast(float x) { float y; asm("tanh.approx.f32 %0, %1;" : "=f"(y) : "f"(x)); return y; }
__device__ __forceinline__ float gelu_tanh(float x) {
  float u = x * (0.7978845608028654f + 0.035677408136300125f * x * x);
  float hx = 0.5f * x;
  return fmaf(hx, tanh_fast(u), hx);
}
__device__ __forceinline__ float warp_sum(float v) {
#pragma unroll
  for (int o = 16; o > 0; o >>= 1) v += __shfl_xor_sync(0xffffffffu, v, o);
  return v;
}
__device__ __forceinline__ void quad_transpose(uint32_t& v0, uint32_t& v1, uint32_t& v2, uint32_t& v3, int lane) {
  const bool b0 = lane & 1, b1 = lane & 2;
  uint32_t s0 = b0 ? v0 : v1, s1 = b0 ? v2 : v3;
  s0 = __shfl_xor_sync(0xffffffffu, s0, 1); s1 = __shfl_xor_sync(0xffffffffu, s1, 1);
  if (b0) { v0 = s0; v2 = s1; } else { v1 = s0; v3 = s1; }
  uint32_t t0 = b1 ? v0 : v2, t1 = b1 ? v1 : v3;
  t0 = __shfl_xor_sync(0xffffffffu, t0, 2); t1 = __shfl_xor_sync(0xffffffffu, t1, 2);
  if (b1) { v0 = t0; v1 = t1; } else { v2 = t0; v3 = t1; }
}

template<int TB> __device__ __forceinline__ void wgmma_rs_n64(float (&d)[32], uint32_t a0, uint32_t a1, uint32_t a2, uint32_t a3, uint64_t db, int scale_d) {
  asm volatile("{\n.reg .pred p;\nsetp.ne.b32 p, %37, 0;\n"
    "wgmma.mma_async.sync.aligned.m64n64k16.f32.bf16.bf16 {%0, %1, %2, %3, %4, %5, %6, %7, %8, %9, %10, %11, %12, %13, %14, %15, %16, %17, %18, %19, %20, %21, %22, %23, %24, %25, %26, %27, %28, %29, %30, %31}, {%32, %33, %34, %35}, %36, p, 1, 1, %38;\n}\n"
    : "+f"(d[0]), "+f"(d[1]), "+f"(d[2]), "+f"(d[3]), "+f"(d[4]), "+f"(d[5]), "+f"(d[6]), "+f"(d[7]), "+f"(d[8]), "+f"(d[9]), "+f"(d[10]), "+f"(d[11]), "+f"(d[12]), "+f"(d[13]), "+f"(d[14]), "+f"(d[15]), "+f"(d[16]), "+f"(d[17]), "+f"(d[18]), "+f"(d[19]), "+f"(d[20]), "+f"(d[21]), "+f"(d[22]), "+f"(d[23]), "+f"(d[24]), "+f"(d[25]), "+f"(d[26]), "+f"(d[27]), "+f"(d[28]), "+f"(d[29]), "+f"(d[30]), "+f"(d[31])
    : "r"(a0), "r"(a1), "r"(a2), "r"(a3), "l"(db), "r"(scale_d), "n"(TB));
}
template<int TB> __device__ __forceinline__ void wgmma_rs_n192(float (&d)[96], uint32_t a0, uint32_t a1, uint32_t a2, uint32_t a3, uint64_t db, int scale_d) {
  asm volatile("{\n.reg .pred p;\nsetp.ne.b32 p, %101, 0;\n"
    "wgmma.mma_async.sync.aligned.m64n192k16.f32.bf16.bf16 {%0, %1, %2, %3, %4, %5, %6, %7, %8, %9, %10, %11, %12, %13, %14, %15, %16, %17, %18, %19, %20, %21, %22, %23, %24, %25, %26, %27, %28, %29, %30, %31, %32, %33, %34, %35, %36, %37, %38, %39, %40, %41, %42, %43, %44, %45, %46, %47, %48, %49, %50, %51, %52, %53, %54, %55, %56, %57, %58, %59, %60, %61, %62, %63, %64, %65, %66, %67, %68, %69, %70, %71, %72, %73, %74, %75, %76, %77, %78, %79, %80, %81, %82, %83, %84, %85, %86, %87, %88, %89, %90, %91, %92, %93, %94, %95}, {%96, %97, %98, %99}, %100, p, 1, 1, %102;\n}\n"
    : "+f"(d[0]), "+f"(d[1]), "+f"(d[2]), "+f"(d[3]), "+f"(d[4]), "+f"(d[5]), "+f"(d[6]), "+f"(d[7]), "+f"(d[8]), "+f"(d[9]), "+f"(d[10]), "+f"(d[11]), "+f"(d[12]), "+f"(d[13]), "+f"(d[14]), "+f"(d[15]), "+f"(d[16]), "+f"(d[17]), "+f"(d[18]), "+f"(d[19]), "+f"(d[20]), "+f"(d[21]), "+f"(d[22]), "+f"(d[23]), "+f"(d[24]), "+f"(d[25]), "+f"(d[26]), "+f"(d[27]), "+f"(d[28]), "+f"(d[29]), "+f"(d[30]), "+f"(d[31]), "+f"(d[32]), "+f"(d[33]), "+f"(d[34]), "+f"(d[35]), "+f"(d[36]), "+f"(d[37]), "+f"(d[38]), "+f"(d[39]), "+f"(d[40]), "+f"(d[41]), "+f"(d[42]), "+f"(d[43]), "+f"(d[44]), "+f"(d[45]), "+f"(d[46]), "+f"(d[47]), "+f"(d[48]), "+f"(d[49]), "+f"(d[50]), "+f"(d[51]), "+f"(d[52]), "+f"(d[53]), "+f"(d[54]), "+f"(d[55]), "+f"(d[56]), "+f"(d[57]), "+f"(d[58]), "+f"(d[59]), "+f"(d[60]), "+f"(d[61]), "+f"(d[62]), "+f"(d[63]), "+f"(d[64]), "+f"(d[65]), "+f"(d[66]), "+f"(d[67]), "+f"(d[68]), "+f"(d[69]), "+f"(d[70]), "+f"(d[71]), "+f"(d[72]), "+f"(d[73]), "+f"(d[74]), "+f"(d[75]), "+f"(d[76]), "+f"(d[77]), "+f"(d[78]), "+f"(d[79]), "+f"(d[80]), "+f"(d[81]), "+f"(d[82]), "+f"(d[83]), "+f"(d[84]), "+f"(d[85]), "+f"(d[86]), "+f"(d[87]), "+f"(d[88]), "+f"(d[89]), "+f"(d[90]), "+f"(d[91]), "+f"(d[92]), "+f"(d[93]), "+f"(d[94]), "+f"(d[95])
    : "r"(a0), "r"(a1), "r"(a2), "r"(a3), "l"(db), "r"(scale_d), "n"(TB));
}
template<int TB> __device__ __forceinline__ void wgmma_ss_n128(float (&d)[64], uint64_t da, uint64_t db, int scale_d) {
  asm volatile("{\n.reg .pred p;\nsetp.ne.b32 p, %66, 0;\n"
    "wgmma.mma_async.sync.aligned.m64n128k16.f32.bf16.bf16 {%0, %1, %2, %3, %4, %5, %6, %7, %8, %9, %10, %11, %12, %13, %14, %15, %16, %17, %18, %19, %20, %21, %22, %23, %24, %25, %26, %27, %28, %29, %30, %31, %32, %33, %34, %35, %36, %37, %38, %39, %40, %41, %42, %43, %44, %45, %46, %47, %48, %49, %50, %51, %52, %53, %54, %55, %56, %57, %58, %59, %60, %61, %62, %63}, %64, %65, p, 1, 1, 0, %67;\n}\n"
    : "+f"(d[0]), "+f"(d[1]), "+f"(d[2]), "+f"(d[3]), "+f"(d[4]), "+f"(d[5]), "+f"(d[6]), "+f"(d[7]), "+f"(d[8]), "+f"(d[9]), "+f"(d[10]), "+f"(d[11]), "+f"(d[12]), "+f"(d[13]), "+f"(d[14]), "+f"(d[15]), "+f"(d[16]), "+f"(d[17]), "+f"(d[18]), "+f"(d[19]), "+f"(d[20]), "+f"(d[21]), "+f"(d[22]), "+f"(d[23]), "+f"(d[24]), "+f"(d[25]), "+f"(d[26]), "+f"(d[27]), "+f"(d[28]), "+f"(d[29]), "+f"(d[30]), "+f"(d[31]), "+f"(d[32]), "+f"(d[33]), "+f"(d[34]), "+f"(d[35]), "+f"(d[36]), "+f"(d[37]), "+f"(d[38]), "+f"(d[39]), "+f"(d[40]), "+f"(d[41]), "+f"(d[42]), "+f"(d[43]), "+f"(d[44]), "+f"(d[45]), "+f"(d[46]), "+f"(d[47]), "+f"(d[48]), "+f"(d[49]), "+f"(d[50]), "+f"(d[51]), "+f"(d[52]), "+f"(d[53]), "+f"(d[54]), "+f"(d[55]), "+f"(d[56]), "+f"(d[57]), "+f"(d[58]), "+f"(d[59]), "+f"(d[60]), "+f"(d[61]), "+f"(d[62]), "+f"(d[63])
    : "l"(da), "l"(db), "r"(scale_d), "n"(TB));
}
template<int TB> __device__ __forceinline__ void wgmma_ss_n192(float (&d)[96], uint64_t da, uint64_t db, int scale_d) {
  asm volatile("{\n.reg .pred p;\nsetp.ne.b32 p, %98, 0;\n"
    "wgmma.mma_async.sync.aligned.m64n192k16.f32.bf16.bf16 {%0, %1, %2, %3, %4, %5, %6, %7, %8, %9, %10, %11, %12, %13, %14, %15, %16, %17, %18, %19, %20, %21, %22, %23, %24, %25, %26, %27, %28, %29, %30, %31, %32, %33, %34, %35, %36, %37, %38, %39, %40, %41, %42, %43, %44, %45, %46, %47, %48, %49, %50, %51, %52, %53, %54, %55, %56, %57, %58, %59, %60, %61, %62, %63, %64, %65, %66, %67, %68, %69, %70, %71, %72, %73, %74, %75, %76, %77, %78, %79, %80, %81, %82, %83, %84, %85, %86, %87, %88, %89, %90, %91, %92, %93, %94, %95}, %96, %97, p, 1, 1, 0, %99;\n}\n"
    : "+f"(d[0]), "+f"(d[1]), "+f"(d[2]), "+f"(d[3]), "+f"(d[4]), "+f"(d[5]), "+f"(d[6]), "+f"(d[7]), "+f"(d[8]), "+f"(d[9]), "+f"(d[10]), "+f"(d[11]), "+f"(d[12]), "+f"(d[13]), "+f"(d[14]), "+f"(d[15]), "+f"(d[16]), "+f"(d[17]), "+f"(d[18]), "+f"(d[19]), "+f"(d[20]), "+f"(d[21]), "+f"(d[22]), "+f"(d[23]), "+f"(d[24]), "+f"(d[25]), "+f"(d[26]), "+f"(d[27]), "+f"(d[28]), "+f"(d[29]), "+f"(d[30]), "+f"(d[31]), "+f"(d[32]), "+f"(d[33]), "+f"(d[34]), "+f"(d[35]), "+f"(d[36]), "+f"(d[37]), "+f"(d[38]), "+f"(d[39]), "+f"(d[40]), "+f"(d[41]), "+f"(d[42]), "+f"(d[43]), "+f"(d[44]), "+f"(d[45]), "+f"(d[46]), "+f"(d[47]), "+f"(d[48]), "+f"(d[49]), "+f"(d[50]), "+f"(d[51]), "+f"(d[52]), "+f"(d[53]), "+f"(d[54]), "+f"(d[55]), "+f"(d[56]), "+f"(d[57]), "+f"(d[58]), "+f"(d[59]), "+f"(d[60]), "+f"(d[61]), "+f"(d[62]), "+f"(d[63]), "+f"(d[64]), "+f"(d[65]), "+f"(d[66]), "+f"(d[67]), "+f"(d[68]), "+f"(d[69]), "+f"(d[70]), "+f"(d[71]), "+f"(d[72]), "+f"(d[73]), "+f"(d[74]), "+f"(d[75]), "+f"(d[76]), "+f"(d[77]), "+f"(d[78]), "+f"(d[79]), "+f"(d[80]), "+f"(d[81]), "+f"(d[82]), "+f"(d[83]), "+f"(d[84]), "+f"(d[85]), "+f"(d[86]), "+f"(d[87]), "+f"(d[88]), "+f"(d[89]), "+f"(d[90]), "+f"(d[91]), "+f"(d[92]), "+f"(d[93]), "+f"(d[94]), "+f"(d[95])
    : "l"(da), "l"(db), "r"(scale_d), "n"(TB));
}


__device__ float g_mod[6 * D_];
__device__ __align__(1024) bf16 g_h[S_ * D_];
__device__ __align__(1024) bf16 g_o[S_ * HD_];
__device__ __align__(1024) float g_attn[S_ * D_];
__device__ __align__(1024) bf16 g_xa[S_ * D_];
__device__ __align__(1024) bf16 g_hb[S_ * D_];
__device__ __align__(1024) bf16 g_t[S_ * D_];
__device__ __align__(1024) bf16 g_us[S_ * D_];
__device__ __align__(1024) bf16 g_x1[S_ * D_];
__device__ __align__(1024) bf16 g_t2[S_ * D_];
__device__ __align__(1024) bf16 g_g[S_ * F_];

__global__ void __launch_bounds__(256) mod_kernel(const bf16* __restrict__ c, const bf16* __restrict__ w_mod) {
  pdl_launch();
  __shared__ float red[8][32];
  const int t = threadIdx.x, cg = t & 3, r0 = t >> 2;
  const int col0 = blockIdx.x * 32 + cg * 8;
  uint4 w[10];
#pragma unroll
  for (int i = 0; i < 10; i++) w[i] = __ldg(reinterpret_cast<const uint4*>(w_mod + (size_t)(r0 + 64 * i) * (6 * D_) + col0));
  float acc[8];
#pragma unroll
  for (int j = 0; j < 8; j++) acc[j] = 0.f;
#pragma unroll
  for (int i = 0; i < 10; i++) {
    float cv = __bfloat162float(c[r0 + 64 * i]);
    float s = bf_round(cv / (1.f + __expf(-cv)));
    acc[0] = fmaf(s, bf_lo(w[i].x), acc[0]); acc[1] = fmaf(s, bf_hi(w[i].x), acc[1]);
    acc[2] = fmaf(s, bf_lo(w[i].y), acc[2]); acc[3] = fmaf(s, bf_hi(w[i].y), acc[3]);
    acc[4] = fmaf(s, bf_lo(w[i].z), acc[4]); acc[5] = fmaf(s, bf_hi(w[i].z), acc[5]);
    acc[6] = fmaf(s, bf_lo(w[i].w), acc[6]); acc[7] = fmaf(s, bf_hi(w[i].w), acc[7]);
  }
#pragma unroll
  for (int j = 0; j < 8; j++) {
    acc[j] += __shfl_xor_sync(0xffffffffu, acc[j], 4);
    acc[j] += __shfl_xor_sync(0xffffffffu, acc[j], 8);
    acc[j] += __shfl_xor_sync(0xffffffffu, acc[j], 16);
  }
  if ((t & 31) < 4) {
#pragma unroll
    for (int j = 0; j < 8; j++) red[t >> 5][cg * 8 + j] = acc[j];
  }
  __syncthreads();
  if (t < 32) {
    float s = 0.f;
#pragma unroll
    for (int w8 = 0; w8 < 8; w8++) s += red[w8][t];
    const int col = blockIdx.x * 32 + t;
    s = bf_round(s);
    const int part = col / D_;
    if (part == 1 || part == 4) s = bf_round(1.f + s);
    g_mod[col] = s;
  }
}

__device__ __forceinline__ void row_stats(const float (&v)[20], float& mean, float& rstd) {
  float s = 0.f;
#pragma unroll
  for (int i = 0; i < 20; i++) s += v[i];
  mean = warp_sum(s) * (1.f / D_);
  float q = 0.f;
#pragma unroll
  for (int i = 0; i < 20; i++) { float d = v[i] - mean; q = fmaf(d, d, q); }
  rstd = rsqrtf(warp_sum(q) * (1.f / D_) + LN_EPS);
}
__device__ __forceinline__ void load_row_bf16(const bf16* p, int lane, float (&v)[20]) {
#pragma unroll
  for (int i = 0; i < 5; i++) {
    uint2 u = *reinterpret_cast<const uint2*>(p + (lane + 32 * i) * 4);
    v[4 * i] = bf_lo(u.x); v[4 * i + 1] = bf_hi(u.x); v[4 * i + 2] = bf_lo(u.y); v[4 * i + 3] = bf_hi(u.y);
  }
}
__device__ __forceinline__ void store_row_bf16(bf16* p, int lane, const float (&v)[20]) {
#pragma unroll
  for (int i = 0; i < 5; i++) {
    uint2 u; u.x = pack_bf16(v[4 * i], v[4 * i + 1]); u.y = pack_bf16(v[4 * i + 2], v[4 * i + 3]);
    *reinterpret_cast<uint2*>(p + (lane + 32 * i) * 4) = u;
  }
}
__device__ __forceinline__ void load_row_f32(const float* p, int lane, float (&v)[20]) {
#pragma unroll
  for (int i = 0; i < 5; i++) {
    float4 u = *reinterpret_cast<const float4*>(p + (lane + 32 * i) * 4);
    v[4 * i] = u.x; v[4 * i + 1] = u.y; v[4 * i + 2] = u.z; v[4 * i + 3] = u.w;
  }
}

__global__ void __launch_bounds__(256) ln1_kernel(const bf16* __restrict__ x) {
  pdl_launch();
  const int lane = threadIdx.x & 31, row = blockIdx.x * 8 + (threadIdx.x >> 5);
  float v[20];
  load_row_bf16(x + (size_t)row * D_, lane, v);
  float mean, rstd;
  row_stats(v, mean, rstd);
#pragma unroll
  for (int i = 0; i < 5; i++) *reinterpret_cast<float4*>(g_attn + (size_t)row * D_ + (lane + 32 * i) * 4) = make_float4(0.f, 0.f, 0.f, 0.f);
  pdl_wait();
  float sa[20], ca[20];
  load_row_f32(g_mod, lane, sa);
  load_row_f32(g_mod + D_, lane, ca);
#pragma unroll
  for (int i = 0; i < 20; i++) v[i] = fmaf((v[i] - mean) * rstd, ca[i], sa[i]);
  store_row_bf16(g_h + (size_t)row * D_, lane, v);
}

__global__ void __launch_bounds__(256) ln2_kernel(const bf16* __restrict__ x) {
  pdl_launch();
  const int lane = threadIdx.x & 31, row = blockIdx.x * 8 + (threadIdx.x >> 5);
  float v[20], a[20], g[20];
  load_row_bf16(x + (size_t)row * D_, lane, v);
  pdl_wait();
  load_row_f32(g_attn + (size_t)row * D_, lane, a);
  load_row_f32(g_mod + 2 * D_, lane, g);
#pragma unroll
  for (int i = 0; i < 20; i++) v[i] = bf_round(fmaf(g[i], a[i], v[i]));
  store_row_bf16(g_xa + (size_t)row * D_, lane, v);
  float mean, rstd;
  row_stats(v, mean, rstd);
  load_row_f32(g_mod + 3 * D_, lane, a);
  load_row_f32(g_mod + 4 * D_, lane, g);
#pragma unroll
  for (int i = 0; i < 20; i++) v[i] = bf_round(fmaf((v[i] - mean) * rstd, g[i], a[i]));
  store_row_bf16(g_hb + (size_t)row * D_, lane, v);
  row_stats(v, mean, rstd);
#pragma unroll
  for (int i = 0; i < 20; i++) v[i] = (v[i] - mean) * rstd;
  store_row_bf16(g_t + (size_t)row * D_, lane, v);
}

__global__ void __launch_bounds__(256) ln3_kernel() {
  pdl_launch();
  const int lane = threadIdx.x & 31, row = blockIdx.x * 8 + (threadIdx.x >> 5);
  float v[20];
  pdl_wait();
  load_row_bf16(g_x1 + (size_t)row * D_, lane, v);
  float mean, rstd;
  row_stats(v, mean, rstd);
#pragma unroll
  for (int i = 0; i < 20; i++) v[i] = (v[i] - mean) * rstd;
  store_row_bf16(g_t2 + (size_t)row * D_, lane, v);
}

constexpr int A_NSLOT = 9;
constexpr int A_SLOT = 24576;
constexpr int A_SMEM = A_NSLOT * A_SLOT + 1024 + 256;
constexpr int A_NKV = S_ / 64;

struct Ring {
  uint32_t slot, phase;
  __device__ __forceinline__ void adv(int n) { if (++slot == (uint32_t)n) { slot = 0; phase ^= 1; } }
};

__global__ void __cluster_dims__(2, 1, 1) __launch_bounds__(384, 1)
attn_kernel(const __grid_constant__ CUtensorMap tm_h, const __grid_constant__ CUtensorMap tm_wq,
            const __grid_constant__ CUtensorMap tm_k, const __grid_constant__ CUtensorMap tm_v) {
  extern __shared__ uint8_t smem_raw[];
  const uint32_t sb = (smem_u32(smem_raw) + 1023) & ~1023u;
  const uint32_t bar_full = sb + A_NSLOT * A_SLOT;
  const uint32_t bar_empty = bar_full + 8 * A_NSLOT;
  uint32_t rank;
  asm volatile("mov.u32 %0, %%cluster_ctarank;" : "=r"(rank));
  const int cid = blockIdx.x >> 1;
  const int qtile = (cid & 7) * 2 + rank;
  const int hbase = cid >> 3;
  const int wg = threadIdx.x >> 7;
  if (threadIdx.x == 0) {
    for (int i = 0; i < A_NSLOT; i++) { mbar_init(bar_full + 8 * i, 1); mbar_init(bar_empty + 8 * i, 16); }
    asm volatile("fence.mbarrier_init.release.cluster;" ::: "memory");
    prefetch_tmap(&tm_h); prefetch_tmap(&tm_wq); prefetch_tmap(&tm_k); prefetch_tmap(&tm_v);
  }
  __syncthreads();
  cluster_sync();
  pdl_launch();

  if (wg == 0) {
    asm volatile("setmaxnreg.dec.sync.aligned.u32 24;");
    if (threadIdx.x == 0) {
      Ring r{0, 1};
      pdl_wait();
      for (int item = 0; item < 4; item++) {
        const int head = hbase + 8 * item;
        for (int kb = 0; kb < 10; kb++) {
          mbar_wait(bar_empty + 8 * r.slot, r.phase);
          mbar_expect(bar_full + 8 * r.slot, 16384);
          tma2d(sb + r.slot * A_SLOT, &tm_h, bar_full + 8 * r.slot, kb * 64, qtile * 128);
          r.adv(A_NSLOT);
          mbar_wait(bar_empty + 8 * r.slot, r.phase);
          mbar_expect(bar_full + 8 * r.slot, A_SLOT);
          if ((uint32_t)(kb & 1) == rank) tma3d_mc(sb + r.slot * A_SLOT, &tm_wq, bar_full + 8 * r.slot, 0, kb * 64, head * 3, 3);
          r.adv(A_NSLOT);
        }
        for (int j = 0; j <= A_NKV; j++) {
          if (j < A_NKV) {
            mbar_wait(bar_empty + 8 * r.slot, r.phase);
            mbar_expect(bar_full + 8 * r.slot, A_SLOT);
            if (rank == 0) tma3d_mc(sb + r.slot * A_SLOT, &tm_k, bar_full + 8 * r.slot, 0, head * S_ + j * 64, 0, 3);
            r.adv(A_NSLOT);
          }
          if (j > 0) {
            mbar_wait(bar_empty + 8 * r.slot, r.phase);
            mbar_expect(bar_full + 8 * r.slot, A_SLOT);
            if (rank == 1) tma3d_mc(sb + r.slot * A_SLOT, &tm_v, bar_full + 8 * r.slot, 0, head * S_ + (j - 1) * 64, 0, 3);
            r.adv(A_NSLOT);
          }
        }
      }
    }
    __syncwarp();
    cluster_sync();
  } else {
    asm volatile("setmaxnreg.inc.sync.aligned.u32 240;");
    const int w = wg - 1;
    const int lane = threadIdx.x & 31;
    const int warp = (threadIdx.x >> 5) & 3;
    const uint32_t rel_base = mapa(bar_empty, (lane == 0) ? rank : (rank ^ 1));
    const float SC = 0.07216878364870322f * 1.4426950408889634f;
    Ring r{0, 0};
    float o[96];
    uint32_t q[48];
    float s[32];
    uint32_t p[16];
    if (w == 1) bar_arrive(1, 256);
#define A_RELEASE(slot_) do { if (lane < 2) mbar_arrive_remote(rel_base + 8 * (slot_)); } while (0)

    for (int item = 0; item < 4; item++) {
      const int head = hbase + 8 * item;
      uint32_t prevA = 0, prevB = 0;
      for (int kb = 0; kb < 10; kb++) {
        const uint32_t sA = r.slot; mbar_wait(bar_full + 8 * sA, r.phase); r.adv(A_NSLOT);
        const uint32_t sB = r.slot; mbar_wait(bar_full + 8 * sB, r.phase); r.adv(A_NSLOT);
        const uint64_t da = mkdesc(sb + sA * A_SLOT + w * 8192, 16, 1024);
        const uint64_t db = mkdesc(sb + sB * A_SLOT, 8192, 1024);
        wg_fence();
#pragma unroll
        for (int kk = 0; kk < 4; kk++) wgmma_ss_n192<1>(o, da + kk * 2, db + kk * 128, (kb | kk) != 0);
        wg_commit();
        if (kb > 0) { wg_wait<1>(); A_RELEASE(prevA); A_RELEASE(prevB); }
        prevA = sA; prevB = sB;
      }
      wg_wait<0>();
      fence_regs(o);
      A_RELEASE(prevA); A_RELEASE(prevB);
#pragma unroll
      for (int i = 0; i < 48; i++) q[i] = pack_bf16(o[2 * i], o[2 * i + 1]);

      float m0, m1, l0, l1;
      {
        const uint32_t sK = r.slot; mbar_wait(bar_full + 8 * sK, r.phase); r.adv(A_NSLOT);
        const uint64_t dk = mkdesc(sb + sK * A_SLOT, 16, 1024);
        bar_sync(1 + w, 256);
        wg_fence();
#pragma unroll
        for (int kk = 0; kk < 12; kk++)
          wgmma_rs_n64<0>(s, q[4 * kk], q[4 * kk + 1], q[4 * kk + 2], q[4 * kk + 3], dk + (kk >> 2) * 512 + (kk & 3) * 2, kk != 0);
        wg_commit();
        bar_arrive(1 + (w ^ 1), 256);
        wg_wait<0>();
        fence_regs(s);
        A_RELEASE(sK);
        float mx0 = fmaxf(s[0], s[1]), mx1 = fmaxf(s[2], s[3]);
#pragma unroll
        for (int i = 1; i < 8; i++) { mx0 = fmaxf(mx0, fmaxf(s[4 * i], s[4 * i + 1])); mx1 = fmaxf(mx1, fmaxf(s[4 * i + 2], s[4 * i + 3])); }
        mx0 = fmaxf(mx0, __shfl_xor_sync(0xffffffffu, mx0, 1)); mx1 = fmaxf(mx1, __shfl_xor_sync(0xffffffffu, mx1, 1));
        mx0 = fmaxf(mx0, __shfl_xor_sync(0xffffffffu, mx0, 2)); mx1 = fmaxf(mx1, __shfl_xor_sync(0xffffffffu, mx1, 2));
        m0 = mx0; m1 = mx1;
        const float c0 = m0 * SC, c1 = m1 * SC;
        l0 = 0.f; l1 = 0.f;
#pragma unroll
        for (int i = 0; i < 8; i++) {
          s[4 * i] = ex2(fmaf(s[4 * i], SC, -c0)); s[4 * i + 1] = ex2(fmaf(s[4 * i + 1], SC, -c0));
          s[4 * i + 2] = ex2(fmaf(s[4 * i + 2], SC, -c1)); s[4 * i + 3] = ex2(fmaf(s[4 * i + 3], SC, -c1));
          l0 += s[4 * i] + s[4 * i + 1]; l1 += s[4 * i + 2] + s[4 * i + 3];
        }
#pragma unroll
        for (int i = 0; i < 16; i++) p[i] = pack_bf16(s[2 * i], s[2 * i + 1]);
      }
      for (int j = 1; j < A_NKV; j++) {
        const uint32_t sK = r.slot; mbar_wait(bar_full + 8 * sK, r.phase); r.adv(A_NSLOT);
        const uint32_t sV = r.slot; const uint32_t phV = r.phase; r.adv(A_NSLOT);
        const uint64_t dk = mkdesc(sb + sK * A_SLOT, 16, 1024);
        const uint64_t dv = mkdesc(sb + sV * A_SLOT, 8192, 1024);
        mbar_wait(bar_full + 8 * sV, phV);
        bar_sync(1 + w, 256);
        wg_fence();
#pragma unroll
        for (int kk = 0; kk < 12; kk++)
          wgmma_rs_n64<0>(s, q[4 * kk], q[4 * kk + 1], q[4 * kk + 2], q[4 * kk + 3], dk + (kk >> 2) * 512 + (kk & 3) * 2, kk != 0);
        wg_commit();
#pragma unroll
        for (int kk = 0; kk < 4; kk++)
          wgmma_rs_n192<1>(o, p[4 * kk], p[4 * kk + 1], p[4 * kk + 2], p[4 * kk + 3], dv + kk * 128, (j > 1) || (kk != 0));
        wg_commit();
        bar_arrive(1 + (w ^ 1), 256);
        wg_wait<1>();
        fence_regs(s);
        A_RELEASE(sK);
        float mx0 = fmaxf(s[0], s[1]), mx1 = fmaxf(s[2], s[3]);
#pragma unroll
        for (int i = 1; i < 8; i++) { mx0 = fmaxf(mx0, fmaxf(s[4 * i], s[4 * i + 1])); mx1 = fmaxf(mx1, fmaxf(s[4 * i + 2], s[4 * i + 3])); }
        mx0 = fmaxf(mx0, __shfl_xor_sync(0xffffffffu, mx0, 1)); mx1 = fmaxf(mx1, __shfl_xor_sync(0xffffffffu, mx1, 1));
        mx0 = fmaxf(mx0, __shfl_xor_sync(0xffffffffu, mx0, 2)); mx1 = fmaxf(mx1, __shfl_xor_sync(0xffffffffu, mx1, 2));
        mx0 = fmaxf(mx0, m0); mx1 = fmaxf(mx1, m1);
        const float a0 = ex2((m0 - mx0) * SC), a1 = ex2((m1 - mx1) * SC);
        m0 = mx0; m1 = mx1;
        const float c0 = m0 * SC, c1 = m1 * SC;
        float r0 = 0.f, r1 = 0.f;
#pragma unroll
        for (int i = 0; i < 8; i++) {
          s[4 * i] = ex2(fmaf(s[4 * i], SC, -c0)); s[4 * i + 1] = ex2(fmaf(s[4 * i + 1], SC, -c0));
          s[4 * i + 2] = ex2(fmaf(s[4 * i + 2], SC, -c1)); s[4 * i + 3] = ex2(fmaf(s[4 * i + 3], SC, -c1));
          r0 += s[4 * i] + s[4 * i + 1]; r1 += s[4 * i + 2] + s[4 * i + 3];
        }
        l0 = fmaf(l0, a0, r0); l1 = fmaf(l1, a1, r1);
        wg_wait<0>();
        fence_regs(o);
        fence_regs(p);
        A_RELEASE(sV);
#pragma unroll
        for (int i = 0; i < 24; i++) { o[4 * i] *= a0; o[4 * i + 1] *= a0; o[4 * i + 2] *= a1; o[4 * i + 3] *= a1; }
#pragma unroll
        for (int i = 0; i < 16; i++) p[i] = pack_bf16(s[2 * i], s[2 * i + 1]);
      }
      {
        const uint32_t sV = r.slot; mbar_wait(bar_full + 8 * sV, r.phase); r.adv(A_NSLOT);
        const uint64_t dv = mkdesc(sb + sV * A_SLOT, 8192, 1024);
        bar_sync(1 + w, 256);
        wg_fence();
#pragma unroll
        for (int kk = 0; kk < 4; kk++)
          wgmma_rs_n192<1>(o, p[4 * kk], p[4 * kk + 1], p[4 * kk + 2], p[4 * kk + 3], dv + kk * 128, 1);
        wg_commit();
        bar_arrive(1 + (w ^ 1), 256);
        wg_wait<0>();
        fence_regs(o);
        A_RELEASE(sV);
      }
      l0 += __shfl_xor_sync(0xffffffffu, l0, 1); l1 += __shfl_xor_sync(0xffffffffu, l1, 1);
      l0 += __shfl_xor_sync(0xffffffffu, l0, 2); l1 += __shfl_xor_sync(0xffffffffu, l1, 2);
      const float i0 = 1.f / l0, i1 = 1.f / l1;
      bf16* orow = g_o + (size_t)(qtile * 128 + w * 64 + warp * 16 + (lane >> 2)) * HD_ + head * DH_ + (lane & 3) * 8;
#pragma unroll
      for (int g = 0; g < 6; g++) {
        uint32_t u0 = pack_bf16(o[16 * g + 0] * i0, o[16 * g + 1] * i0), u1 = pack_bf16(o[16 * g + 4] * i0, o[16 * g + 5] * i0);
        uint32_t u2 = pack_bf16(o[16 * g + 8] * i0, o[16 * g + 9] * i0), u3 = pack_bf16(o[16 * g + 12] * i0, o[16 * g + 13] * i0);
        quad_transpose(u0, u1, u2, u3, lane);
        *reinterpret_cast<uint4*>(orow + g * 32) = make_uint4(u0, u1, u2, u3);
        uint32_t v0 = pack_bf16(o[16 * g + 2] * i1, o[16 * g + 3] * i1), v1 = pack_bf16(o[16 * g + 6] * i1, o[16 * g + 7] * i1);
        uint32_t v2 = pack_bf16(o[16 * g + 10] * i1, o[16 * g + 11] * i1), v3 = pack_bf16(o[16 * g + 14] * i1, o[16 * g + 15] * i1);
        quad_transpose(v0, v1, v2, v3, lane);
        *reinterpret_cast<uint4*>(orow + (size_t)8 * HD_ + g * 32) = make_uint4(v0, v1, v2, v3);
      }
    }
    cluster_sync();
  }
}

enum { EPI_RED = 0, EPI_GELU_SHIFT = 1, EPI_ADD_HB = 2, EPI_GELU = 3, EPI_FINAL = 4 };

template <int BN> struct GemmCfg {
  static constexpr int STAGE = 16384 + BN * 128;
  static constexpr int NST = (BN == 320) ? 4 : (BN == 192 ? 5 : 6);
  static constexpr int SMEM = NST * STAGE + 1024 + 256;
};

template <int BN, int EPI>
__global__ void __launch_bounds__(384, 1)
gemm_kernel(const __grid_constant__ CUtensorMap tm_a, const __grid_constant__ CUtensorMap tm_b, int kblocks, bf16* __restrict__ out) {
  using C = GemmCfg<BN>;
  extern __shared__ uint8_t smem_raw[];
  const uint32_t sb = (smem_u32(smem_raw) + 1023) & ~1023u;
  const uint32_t bar_full = sb + C::NST * C::STAGE;
  const uint32_t bar_empty = bar_full + 8 * C::NST;
  const int wg = threadIdx.x >> 7;
  const int n0 = blockIdx.x * BN, m0 = blockIdx.y * 128, kb0 = blockIdx.z * kblocks;
  if (threadIdx.x == 0) {
    for (int i = 0; i < C::NST; i++) { mbar_init(bar_full + 8 * i, 1); mbar_init(bar_empty + 8 * i, 8); }
    asm volatile("fence.mbarrier_init.release.cluster;" ::: "memory");
    prefetch_tmap(&tm_a); prefetch_tmap(&tm_b);
  }
  __syncthreads();
  pdl_launch();
  if (wg == 0) {
    asm volatile("setmaxnreg.dec.sync.aligned.u32 24;");
    if (threadIdx.x == 0) {
      Ring r{0, 1};
      pdl_wait();
      for (int kb = 0; kb < kblocks; kb++) {
        mbar_wait(bar_empty + 8 * r.slot, r.phase);
        mbar_expect(bar_full + 8 * r.slot, C::STAGE);
        tma2d(sb + r.slot * C::STAGE, &tm_a, bar_full + 8 * r.slot, (kb0 + kb) * 64, m0);
        tma3d(sb + r.slot * C::STAGE + 16384, &tm_b, bar_full + 8 * r.slot, 0, (kb0 + kb) * 64, n0 / 64);
        r.adv(C::NST);
      }
    }
  } else {
    asm volatile("setmaxnreg.inc.sync.aligned.u32 240;");
    const int w = wg - 1, lane = threadIdx.x & 31, warp = (threadIdx.x >> 5) & 3;
    constexpr int N1 = (BN == 320 || BN == 192) ? 192 : 128;
    constexpr int N2 = BN - N1;
    float acc1[N1 / 2];
    float acc2[N2 > 0 ? N2 / 2 : 4];
    Ring r{0, 0};
    uint32_t prev = 0;
    for (int kb = 0; kb < kblocks; kb++) {
      const uint32_t st = r.slot; mbar_wait(bar_full + 8 * st, r.phase); r.adv(C::NST);
      const uint64_t da = mkdesc(sb + st * C::STAGE + w * 8192, 16, 1024);
      const uint64_t db = mkdesc(sb + st * C::STAGE + 16384, 8192, 1024);
      wg_fence();
#pragma unroll
      for (int kk = 0; kk < 4; kk++) {
        if constexpr (N1 == 192) wgmma_ss_n192<1>(acc1, da + kk * 2, db + kk * 128, (kb | kk) != 0);
        else wgmma_ss_n128<1>(acc1, da + kk * 2, db + kk * 128, (kb | kk) != 0);
        if constexpr (N2 == 128) wgmma_ss_n128<1>(acc2, da + kk * 2, db + kk * 128 + 3 * 512, (kb | kk) != 0);
      }
      wg_commit();
      if (kb > 0) { wg_wait<1>(); if (lane == 0) mbar_arrive(bar_empty + 8 * prev); }
      prev = st;
    }
    wg_wait<0>();
    fence_regs(acc1);
    fence_regs(acc2);
    pdl_wait();
    const int row = m0 + w * 64 + warp * 16 + (lane >> 2);
    const int cq = (lane & 3) * 2;
    auto epi = [&](float v0, float v1, float v2, float v3, int nb) {
      const int col = n0 + nb * 8 + cq;
      if constexpr (EPI == EPI_RED) {
        asm volatile("red.global.add.v2.f32 [%0], {%1, %2};" :: "l"(g_attn + (size_t)row * D_ + col), "f"(v0), "f"(v1) : "memory");
        asm volatile("red.global.add.v2.f32 [%0], {%1, %2};" :: "l"(g_attn + (size_t)(row + 8) * D_ + col), "f"(v2), "f"(v3) : "memory");
      } else if constexpr (EPI == EPI_GELU_SHIFT) {
        const int grp = col / 160;
        const int sh = (grp == 0) ? 1 : (grp == 1) ? -1 : (grp == 2) ? 2 : -2;
        const uint32_t ua = pack_bf16(gelu_tanh(v0), gelu_tanh(v1)), ub = pack_bf16(gelu_tanh(v2), gelu_tanh(v3));
        const int ra = row + sh, rb = row + 8 + sh;
        if (ra >= 0 && ra < S_) *reinterpret_cast<uint32_t*>(g_us + (size_t)ra * D_ + col) = ua;
        if (rb >= 0 && rb < S_) *reinterpret_cast<uint32_t*>(g_us + (size_t)rb * D_ + col) = ub;
        if (sh > 0) { if (row < sh) *reinterpret_cast<uint32_t*>(g_us + (size_t)row * D_ + col) = 0u; }
        else { if (row + 8 >= S_ + sh) *reinterpret_cast<uint32_t*>(g_us + (size_t)(row + 8) * D_ + col) = 0u; }
      } else if constexpr (EPI == EPI_ADD_HB) {
        const uint32_t ha = *reinterpret_cast<const uint32_t*>(g_hb + (size_t)row * D_ + col);
        const uint32_t hb = *reinterpret_cast<const uint32_t*>(g_hb + (size_t)(row + 8) * D_ + col);
        *reinterpret_cast<uint32_t*>(g_x1 + (size_t)row * D_ + col) = pack_bf16(bf_lo(ha) + v0, bf_hi(ha) + v1);
        *reinterpret_cast<uint32_t*>(g_x1 + (size_t)(row + 8) * D_ + col) = pack_bf16(bf_lo(hb) + v2, bf_hi(hb) + v3);
      } else if constexpr (EPI == EPI_GELU) {
        *reinterpret_cast<uint32_t*>(g_g + (size_t)row * F_ + col) = pack_bf16(gelu_tanh(v0), gelu_tanh(v1));
        *reinterpret_cast<uint32_t*>(g_g + (size_t)(row + 8) * F_ + col) = pack_bf16(gelu_tanh(v2), gelu_tanh(v3));
      } else {
        const float2 gb = *reinterpret_cast<const float2*>(g_mod + 5 * D_ + col);
        const uint32_t xa = *reinterpret_cast<const uint32_t*>(g_xa + (size_t)row * D_ + col);
        const uint32_t xb = *reinterpret_cast<const uint32_t*>(g_xa + (size_t)(row + 8) * D_ + col);
        const uint32_t ya = *reinterpret_cast<const uint32_t*>(g_x1 + (size_t)row * D_ + col);
        const uint32_t yb = *reinterpret_cast<const uint32_t*>(g_x1 + (size_t)(row + 8) * D_ + col);
        *reinterpret_cast<uint32_t*>(out + (size_t)row * D_ + col) =
            pack_bf16(fmaf(gb.x, bf_lo(ya) + v0, bf_lo(xa)), fmaf(gb.y, bf_hi(ya) + v1, bf_hi(xa)));
        *reinterpret_cast<uint32_t*>(out + (size_t)(row + 8) * D_ + col) =
            pack_bf16(fmaf(gb.x, bf_lo(yb) + v2, bf_lo(xb)), fmaf(gb.y, bf_hi(yb) + v3, bf_hi(xb)));
      }
    };
#pragma unroll
    for (int nb = 0; nb < N1 / 8; nb++) epi(acc1[4 * nb], acc1[4 * nb + 1], acc1[4 * nb + 2], acc1[4 * nb + 3], nb);
    if constexpr (N2 > 0) {
#pragma unroll
      for (int nb = 0; nb < N2 / 8; nb++) epi(acc2[4 * nb], acc2[4 * nb + 1], acc2[4 * nb + 2], acc2[4 * nb + 3], N1 / 8 + nb);
    }
  }
}

typedef CUresult (*EncFn)(CUtensorMap*, CUtensorMapDataType, cuuint32_t, void*, const cuuint64_t*, const cuuint64_t*,
                          const cuuint32_t*, const cuuint32_t*, CUtensorMapInterleave, CUtensorMapSwizzle,
                          CUtensorMapL2promotion, CUtensorMapFloatOOBfill);
static EncFn g_enc = nullptr;

static CUtensorMap map2d(const void* p, uint64_t rows, uint64_t cols, uint32_t box_rows) {
  CUtensorMap m;
  cuuint64_t gd[2] = {cols, rows}; cuuint64_t gs[1] = {cols * 2};
  cuuint32_t bx[2] = {64, box_rows}; cuuint32_t es[2] = {1, 1};
  g_enc(&m, CU_TENSOR_MAP_DATA_TYPE_BFLOAT16, 2, const_cast<void*>(p), gd, gs, bx, es, CU_TENSOR_MAP_INTERLEAVE_NONE,
        CU_TENSOR_MAP_SWIZZLE_128B, CU_TENSOR_MAP_L2_PROMOTION_L2_256B, CU_TENSOR_MAP_FLOAT_OOB_FILL_NONE);
  return m;
}
static CUtensorMap map3d(const void* p, uint64_t rows, uint64_t cols, uint32_t box_rows, uint32_t nblk) {
  CUtensorMap m;
  cuuint64_t gd[3] = {64, rows, cols / 64}; cuuint64_t gs[2] = {cols * 2, 128};
  cuuint32_t bx[3] = {64, box_rows, nblk}; cuuint32_t es[3] = {1, 1, 1};
  g_enc(&m, CU_TENSOR_MAP_DATA_TYPE_BFLOAT16, 3, const_cast<void*>(p), gd, gs, bx, es, CU_TENSOR_MAP_INTERLEAVE_NONE,
        CU_TENSOR_MAP_SWIZZLE_128B, CU_TENSOR_MAP_L2_PROMOTION_L2_256B, CU_TENSOR_MAP_FLOAT_OOB_FILL_NONE);
  return m;
}

template <typename... KArgs, typename... Args>
static void launch(void (*kern)(KArgs...), dim3 grid, dim3 block, int smem, bool pdl, Args... args) {
  cudaLaunchConfig_t cfg = {};
  cfg.gridDim = grid; cfg.blockDim = block; cfg.dynamicSmemBytes = smem; cfg.stream = cudaStreamPerThread;
  cudaLaunchAttribute at[1];
  at[0].id = cudaLaunchAttributeProgrammaticStreamSerialization;
  at[0].val.programmaticStreamSerializationAllowed = 1;
  cfg.attrs = at; cfg.numAttrs = pdl ? 1 : 0;
  cudaLaunchKernelEx(&cfg, kern, KArgs(args)...);
}

extern "C" void kernel_launch(void* const* d_in, const int* in_sizes, int n_in, void* d_out, int out_size) {
  const bf16* x = (const bf16*)d_in[0];
  const bf16* kc = (const bf16*)d_in[1];
  const bf16* vc = (const bf16*)d_in[2];
  const bf16* wq = (const bf16*)d_in[3];
  const bf16* wo = (const bf16*)d_in[4];
  const bf16* w1 = (const bf16*)d_in[6];
  const bf16* w2 = (const bf16*)d_in[7];
  const bf16* w3 = (const bf16*)d_in[8];
  const bf16* w4 = (const bf16*)d_in[9];
  const bf16* c = (const bf16*)d_in[10];
  const bf16* wmod = (const bf16*)d_in[11];
  bf16* out = (bf16*)d_out;

  static void *p_h, *p_o, *p_t, *p_us, *p_t2, *p_g;
  if (!g_enc) {
    void* fn = nullptr; cudaDriverEntryPointQueryResult qr;
    cudaGetDriverEntryPoint("cuTensorMapEncodeTiled", &fn, cudaEnableDefault, &qr);
    g_enc = (EncFn)fn;
    cudaGetSymbolAddress(&p_h, g_h); cudaGetSymbolAddress(&p_o, g_o); cudaGetSymbolAddress(&p_t, g_t);
    cudaGetSymbolAddress(&p_us, g_us); cudaGetSymbolAddress(&p_t2, g_t2); cudaGetSymbolAddress(&p_g, g_g);
    cudaFuncSetAttribute(attn_kernel, cudaFuncAttributeMaxDynamicSharedMemorySize, A_SMEM);
    cudaFuncSetAttribute(gemm_kernel<320, EPI_RED>, cudaFuncAttributeMaxDynamicSharedMemorySize, GemmCfg<320>::SMEM);
    cudaFuncSetAttribute(gemm_kernel<128, EPI_GELU_SHIFT>, cudaFuncAttributeMaxDynamicSharedMemorySize, GemmCfg<128>::SMEM);
    cudaFuncSetAttribute(gemm_kernel<128, EPI_ADD_HB>, cudaFuncAttributeMaxDynamicSharedMemorySize, GemmCfg<128>::SMEM);
    cudaFuncSetAttribute(gemm_kernel<192, EPI_GELU>, cudaFuncAttributeMaxDynamicSharedMemorySize, GemmCfg<192>::SMEM);
    cudaFuncSetAttribute(gemm_kernel<128, EPI_FINAL>, cudaFuncAttributeMaxDynamicSharedMemorySize, GemmCfg<128>::SMEM);
  }
  const CUtensorMap tm_h = map2d(p_h, S_, D_, 128);
  const CUtensorMap tm_wq = map3d(wq, D_, HD_, 64, 3);
  const CUtensorMap tm_k = map3d(kc, (uint64_t)H_ * S_, DH_, 64, 3);
  const CUtensorMap tm_v = map3d(vc, (uint64_t)H_ * S_, DH_, 64, 3);
  const CUtensorMap tm_o = map2d(p_o, S_, HD_, 128);
  const CUtensorMap tm_wo = map3d(wo, HD_, D_, 64, 5);
  const CUtensorMap tm_t = map2d(p_t, S_, D_, 128);
  const CUtensorMap tm_w1 = map3d(w1, D_, D_, 64, 2);
  const CUtensorMap tm_us = map2d(p_us, S_, D_, 128);
  const CUtensorMap tm_w2 = map3d(w2, D_, D_, 64, 2);
  const CUtensorMap tm_t2 = map2d(p_t2, S_, D_, 128);
  const CUtensorMap tm_w3 = map3d(w3, D_, F_, 64, 3);
  const CUtensorMap tm_g = map2d(p_g, S_, F_, 128);
  const CUtensorMap tm_w4 = map3d(w4, F_, D_, 64, 2);

  const bool PDL = true;
  launch(mod_kernel, dim3(120), dim3(256), 0, false, c, wmod);
  launch(ln1_kernel, dim3(256), dim3(256), 0, PDL, x);
  launch(attn_kernel, dim3(128), dim3(384), A_SMEM, PDL, tm_h, tm_wq, tm_k, tm_v);
  launch(gemm_kernel<320, EPI_RED>, dim3(2, 16, 4), dim3(384), GemmCfg<320>::SMEM, PDL, tm_o, tm_wo, 24, out);
  launch(ln2_kernel, dim3(256), dim3(256), 0, PDL, x);
  launch(gemm_kernel<128, EPI_GELU_SHIFT>, dim3(5, 16, 1), dim3(384), GemmCfg<128>::SMEM, PDL, tm_t, tm_w1, 10, out);
  launch(gemm_kernel<128, EPI_ADD_HB>, dim3(5, 16, 1), dim3(384), GemmCfg<128>::SMEM, PDL, tm_us, tm_w2, 10, out);
  launch(ln3_kernel, dim3(256), dim3(256), 0, PDL);
  launch(gemm_kernel<192, EPI_GELU>, dim3(8, 16, 1), dim3(384), GemmCfg<192>::SMEM, PDL, tm_t2, tm_w3, 10, out);
  launch(gemm_kernel<128, EPI_FINAL>, dim3(5, 16, 1), dim3(384), GemmCfg<128>::SMEM, PDL, tm_g, tm_w4, 24, out);
}
```

```cpp
#include <cuda_runtime.h>
#include <cuda.h>
#include <cuda_bf16.h>
#include <stdint.h>

typedef __nv_bfloat16 bf16;

constexpr int S_  = 2048;
constexpr int D_  = 640;
constexpr int H_  = 32;
constexpr int DH_ = 192;
constexpr int HD_ = H_ * DH_;
constexpr int F_  = 1536;
constexpr float LN_EPS = 1e-5f;

__device__ __forceinline__ uint32_t smem_u32(const void* p) { return (uint32_t)__cvta_generic_to_shared(p); }
__device__ __forceinline__ void mbar_init(uint32_t a, uint32_t c) { asm volatile("mbarrier.init.shared::cta.b64 [%0], %1;" :: "r"(a), "r"(c) : "memory"); }
__device__ __forceinline__ void mbar_expect(uint32_t a, uint32_t b) { asm volatile("mbarrier.arrive.expect_tx.shared::cta.b64 _, [%0], %1;" :: "r"(a), "r"(b) : "memory"); }
__device__ __forceinline__ void mbar_arrive(uint32_t a) { asm volatile("mbarrier.arrive.shared::cta.b64 _, [%0];" :: "r"(a) : "memory"); }
__device__ __forceinline__ void mbar_arrive_remote(uint32_t ra) { asm volatile("mbarrier.arrive.shared::cluster.b64 _, [%0];" :: "r"(ra) : "memory"); }
__device__ __forceinline__ uint32_t mapa(uint32_t a, uint32_t cta) { uint32_t r; asm volatile("mapa.shared::cluster.u32 %0, %1, %2;" : "=r"(r) : "r"(a), "r"(cta)); return r; }
__device__ __forceinline__ uint32_t mbar_try(uint32_t a, uint32_t ph) {
  uint32_t ok;
  asm volatile("{\n.reg .pred p;\nmbarrier.test_wait.parity.shared::cta.b64 p, [%1], %2;\nselp.u32 %0, 1, 0, p;\n}\n" : "=r"(ok) : "r"(a), "r"(ph) : "memory");
  return ok;
}
__device__ __forceinline__ void mbar_wait(uint32_t a, uint32_t ph) {
  asm volatile(
      "{\n.reg .pred p;\n.reg .u32 n;\n"
      "mbarrier.try_wait.parity.shared::cta.b64 p, [%0], %1;\n"
      "@p bra DONE;\n"
      "mov.u32 n, 0;\n"
      "SPIN:\n"
      "mbarrier.try_wait.parity.shared::cta.b64 p, [%0], %1;\n"
      "@p bra DONE;\n"
      "add.u32 n, n, 1;\n"
      "setp.gt.u32 p, n, 16777216;\n"
      "@p trap;\n"
      "bra SPIN;\n"
      "DONE:\n}\n" :: "r"(a), "r"(ph) : "memory");
}
__device__ __forceinline__ void tma2d(uint32_t dst, const CUtensorMap* m, uint32_t bar, int c0, int c1) {
  asm volatile("cp.async.bulk.tensor.2d.shared::cluster.global.mbarrier::complete_tx::bytes [%0], [%1, {%3, %4}], [%2];"
               :: "r"(dst), "l"(m), "r"(bar), "r"(c0), "r"(c1) : "memory");
}
__device__ __forceinline__ void tma3d(uint32_t dst, const CUtensorMap* m, uint32_t bar, int c0, int c1, int c2) {
  asm volatile("cp.async.bulk.tensor.3d.shared::cluster.global.mbarrier::complete_tx::bytes [%0], [%1, {%3, %4, %5}], [%2];"
               :: "r"(dst), "l"(m), "r"(bar), "r"(c0), "r"(c1), "r"(c2) : "memory");
}
__device__ __forceinline__ void tma3d_mc(uint32_t dst, const CUtensorMap* m, uint32_t bar, int c0, int c1, int c2, uint16_t mask) {
  asm volatile("cp.async.bulk.tensor.3d.shared::cluster.global.mbarrier::complete_tx::bytes.multicast::cluster [%0], [%1, {%3, %4, %5}], [%2], %6;"
               :: "r"(dst), "l"(m), "r"(bar), "r"(c0), "r"(c1), "r"(c2), "h"(mask) : "memory");
}
__device__ __forceinline__ void prefetch_tmap(const CUtensorMap* m) { asm volatile("prefetch.tensormap [%0];" :: "l"(m) : "memory"); }
__device__ __forceinline__ void wg_fence() { asm volatile("wgmma.fence.sync.aligned;" ::: "memory"); }
__device__ __forceinline__ void wg_commit() { asm volatile("wgmma.commit_group.sync.aligned;" ::: "memory"); }
template <int N> __device__ __forceinline__ void wg_wait() { asm volatile("wgmma.wait_group.sync.aligned %0;" :: "n"(N) : "memory"); }
template <int N> __device__ __forceinline__ void fence_regs(float (&r)[N]) {
#pragma unroll
  for (int i = 0; i < N; i++) asm volatile("" : "+f"(r[i]) :: "memory");
}
template <int N> __device__ __forceinline__ void fence_regs(uint32_t (&r)[N]) {
#pragma unroll
  for (int i = 0; i < N; i++) asm volatile("" : "+r"(r[i]) :: "memory");
}
__device__ __forceinline__ uint64_t mkdesc(uint32_t addr, uint32_t lbo, uint32_t sbo) {
  return (uint64_t)((addr & 0x3FFFF) >> 4) | ((uint64_t)(lbo >> 4) << 16) | ((uint64_t)(sbo >> 4) << 32) | (1ull << 62);
}
__device__ __forceinline__ void bar_sync(int id, int n) { asm volatile("bar.sync %0, %1;" :: "r"(id), "r"(n) : "memory"); }
__device__ __forceinline__ void bar_arrive(int id, int n) { asm volatile("bar.arrive %0, %1;" :: "r"(id), "r"(n) : "memory"); }
__device__ __forceinline__ void cluster_sync() { asm volatile("barrier.cluster.arrive.aligned;\nbarrier.cluster.wait.aligned;" ::: "memory"); }
__device__ __forceinline__ void pdl_wait() { asm volatile("griddepcontrol.wait;" ::: "memory"); }
__device__ __forceinline__ void pdl_launch() { asm volatile("griddepcontrol.launch_dependents;" ::: "memory"); }
__device__ __forceinline__ float ex2(float x) { float y; asm("ex2.approx.ftz.f32 %0, %1;" : "=f"(y) : "f"(x)); return y; }
__device__ __forceinline__ uint32_t pack_bf16(float lo, float hi) { uint32_t r; asm("cvt.rn.bf16x2.f32 %0, %1, %2;" : "=r"(r) : "f"(hi), "f"(lo)); return r; }
__device__ __forceinline__ float bf_lo(uint32_t u) { return __uint_as_float(u << 16); }
__device__ __forceinline__ float bf_hi(uint32_t u) { return __uint_as_float(u & 0xffff0000u); }
__device__ __forceinline__ float bf_round(float x) { return __bfloat162float(__float2bfloat16_rn(x)); }
__device__ __forceinline__ float tanh_fast(float x) { float y; asm("tanh.approx.f32 %0, %1;" : "=f"(y) : "f"(x)); return y; }
__device__ __forceinline__ float gelu_tanh(float x) {
  float u = x * (0.7978845608028654f + 0.035677408136300125f * x * x);
  float hx = 0.5f * x;
  return fmaf(hx, tanh_fast(u), hx);
}
__device__ __forceinline__ float warp_sum(float v) {
#pragma unroll
  for (int o = 16; o > 0; o >>= 1) v += __shfl_xor_sync(0xffffffffu, v, o);
  return v;
}
__device__ __forceinline__ void quad_transpose(uint32_t& v0, uint32_t& v1, uint32_t& v2, uint32_t& v3, int lane) {
  const bool b0 = lane & 1, b1 = lane & 2;
  uint32_t s0 = b0 ? v0 : v1, s1 = b0 ? v2 : v3;
  s0 = __shfl_xor_sync(0xffffffffu, s0, 1); s1 = __shfl_xor_sync(0xffffffffu, s1, 1);
  if (b0) { v0 = s0; v2 = s1; } else { v1 = s0; v3 = s1; }
  uint32_t t0 = b1 ? v0 : v2, t1 = b1 ? v1 : v3;
  t0 = __shfl_xor_sync(0xffffffffu, t0, 2); t1 = __shfl_xor_sync(0xffffffffu, t1, 2);
  if (b1) { v0 = t0; v1 = t1; } else { v2 = t0; v3 = t1; }
}

template<int TB> __device__ __forceinline__ void wgmma_rs_n64(float (&d)[32], uint32_t a0, uint32_t a1, uint32_t a2, uint32_t a3, uint64_t db, int scale_d) {
  asm volatile("{\n.reg .pred p;\nsetp.ne.b32 p, %37, 0;\n"
    "wgmma.mma_async.sync.aligned.m64n64k16.f32.bf16.bf16 {%0, %1, %2, %3, %4, %5, %6, %7, %8, %9, %10, %11, %12, %13, %14, %15, %16, %17, %18, %19, %20, %21, %22, %23, %24, %25, %26, %27, %28, %29, %30, %31}, {%32, %33, %34, %35}, %36, p, 1, 1, %38;\n}\n"
    : "+f"(d[0]), "+f"(d[1]), "+f"(d[2]), "+f"(d[3]), "+f"(d[4]), "+f"(d[5]), "+f"(d[6]), "+f"(d[7]), "+f"(d[8]), "+f"(d[9]), "+f"(d[10]), "+f"(d[11]), "+f"(d[12]), "+f"(d[13]), "+f"(d[14]), "+f"(d[15]), "+f"(d[16]), "+f"(d[17]), "+f"(d[18]), "+f"(d[19]), "+f"(d[20]), "+f"(d[21]), "+f"(d[22]), "+f"(d[23]), "+f"(d[24]), "+f"(d[25]), "+f"(d[26]), "+f"(d[27]), "+f"(d[28]), "+f"(d[29]), "+f"(d[30]), "+f"(d[31])
    : "r"(a0), "r"(a1), "r"(a2), "r"(a3), "l"(db), "r"(scale_d), "n"(TB));
}
template<int TB> __device__ __forceinline__ void wgmma_rs_n192(float (&d)[96], uint32_t a0, uint32_t a1, uint32_t a2, uint32_t a3, uint64_t db, int scale_d) {
  asm volatile("{\n.reg .pred p;\nsetp.ne.b32 p, %101, 0;\n"
    "wgmma.mma_async.sync.aligned.m64n192k16.f32.bf16.bf16 {%0, %1, %2, %3, %4, %5, %6, %7, %8, %9, %10, %11, %12, %13, %14, %15, %16, %17, %18, %19, %20, %21, %22, %23, %24, %25, %26, %27, %28, %29, %30, %31, %32, %33, %34, %35, %36, %37, %38, %39, %40, %41, %42, %43, %44, %45, %46, %47, %48, %49, %50, %51, %52, %53, %54, %55, %56, %57, %58, %59, %60, %61, %62, %63, %64, %65, %66, %67, %68, %69, %70, %71, %72, %73, %74, %75, %76, %77, %78, %79, %80, %81, %82, %83, %84, %85, %86, %87, %88, %89, %90, %91, %92, %93, %94, %95}, {%96, %97, %98, %99}, %100, p, 1, 1, %102;\n}\n"
    : "+f"(d[0]), "+f"(d[1]), "+f"(d[2]), "+f"(d[3]), "+f"(d[4]), "+f"(d[5]), "+f"(d[6]), "+f"(d[7]), "+f"(d[8]), "+f"(d[9]), "+f"(d[10]), "+f"(d[11]), "+f"(d[12]), "+f"(d[13]), "+f"(d[14]), "+f"(d[15]), "+f"(d[16]), "+f"(d[17]), "+f"(d[18]), "+f"(d[19]), "+f"(d[20]), "+f"(d[21]), "+f"(d[22]), "+f"(d[23]), "+f"(d[24]), "+f"(d[25]), "+f"(d[26]), "+f"(d[27]), "+f"(d[28]), "+f"(d[29]), "+f"(d[30]), "+f"(d[31]), "+f"(d[32]), "+f"(d[33]), "+f"(d[34]), "+f"(d[35]), "+f"(d[36]), "+f"(d[37]), "+f"(d[38]), "+f"(d[39]), "+f"(d[40]), "+f"(d[41]), "+f"(d[42]), "+f"(d[43]), "+f"(d[44]), "+f"(d[45]), "+f"(d[46]), "+f"(d[47]), "+f"(d[48]), "+f"(d[49]), "+f"(d[50]), "+f"(d[51]), "+f"(d[52]), "+f"(d[53]), "+f"(d[54]), "+f"(d[55]), "+f"(d[56]), "+f"(d[57]), "+f"(d[58]), "+f"(d[59]), "+f"(d[60]), "+f"(d[61]), "+f"(d[62]), "+f"(d[63]), "+f"(d[64]), "+f"(d[65]), "+f"(d[66]), "+f"(d[67]), "+f"(d[68]), "+f"(d[69]), "+f"(d[70]), "+f"(d[71]), "+f"(d[72]), "+f"(d[73]), "+f"(d[74]), "+f"(d[75]), "+f"(d[76]), "+f"(d[77]), "+f"(d[78]), "+f"(d[79]), "+f"(d[80]), "+f"(d[81]), "+f"(d[82]), "+f"(d[83]), "+f"(d[84]), "+f"(d[85]), "+f"(d[86]), "+f"(d[87]), "+f"(d[88]), "+f"(d[89]), "+f"(d[90]), "+f"(d[91]), "+f"(d[92]), "+f"(d[93]), "+f"(d[94]), "+f"(d[95])
    : "r"(a0), "r"(a1), "r"(a2), "r"(a3), "l"(db), "r"(scale_d), "n"(TB));
}
template<int TB> __device__ __forceinline__ void wgmma_ss_n128(float (&d)[64], uint64_t da, uint64_t db, int scale_d) {
  asm volatile("{\n.reg .pred p;\nsetp.ne.b32 p, %66, 0;\n"
    "wgmma.mma_async.sync.aligned.m64n128k16.f32.bf16.bf16 {%0, %1, %2, %3, %4, %5, %6, %7, %8, %9, %10, %11, %12, %13, %14, %15, %16, %17, %18, %19, %20, %21, %22, %23, %24, %25, %26, %27, %28, %29, %30, %31, %32, %33, %34, %35, %36, %37, %38, %39, %40, %41, %42, %43, %44, %45, %46, %47, %48, %49, %50, %51, %52, %53, %54, %55, %56, %57, %58, %59, %60, %61, %62, %63}, %64, %65, p, 1, 1, 0, %67;\n}\n"
    : "+f"(d[0]), "+f"(d[1]), "+f"(d[2]), "+f"(d[3]), "+f"(d[4]), "+f"(d[5]), "+f"(d[6]), "+f"(d[7]), "+f"(d[8]), "+f"(d[9]), "+f"(d[10]), "+f"(d[11]), "+f"(d[12]), "+f"(d[13]), "+f"(d[14]), "+f"(d[15]), "+f"(d[16]), "+f"(d[17]), "+f"(d[18]), "+f"(d[19]), "+f"(d[20]), "+f"(d[21]), "+f"(d[22]), "+f"(d[23]), "+f"(d[24]), "+f"(d[25]), "+f"(d[26]), "+f"(d[27]), "+f"(d[28]), "+f"(d[29]), "+f"(d[30]), "+f"(d[31]), "+f"(d[32]), "+f"(d[33]), "+f"(d[34]), "+f"(d[35]), "+f"(d[36]), "+f"(d[37]), "+f"(d[38]), "+f"(d[39]), "+f"(d[40]), "+f"(d[41]), "+f"(d[42]), "+f"(d[43]), "+f"(d[44]), "+f"(d[45]), "+f"(d[46]), "+f"(d[47]), "+f"(d[48]), "+f"(d[49]), "+f"(d[50]), "+f"(d[51]), "+f"(d[52]), "+f"(d[53]), "+f"(d[54]), "+f"(d[55]), "+f"(d[56]), "+f"(d[57]), "+f"(d[58]), "+f"(d[59]), "+f"(d[60]), "+f"(d[61]), "+f"(d[62]), "+f"(d[63])
    : "l"(da), "l"(db), "r"(scale_d), "n"(TB));
}
template<int TB> __device__ __forceinline__ void wgmma_ss_n192(float (&d)[96], uint64_t da, uint64_t db, int scale_d) {
  asm volatile("{\n.reg .pred p;\nsetp.ne.b32 p, %98, 0;\n"
    "wgmma.mma_async.sync.aligned.m64n192k16.f32.bf16.bf16 {%0, %1, %2, %3, %4, %5, %6, %7, %8, %9, %10, %11, %12, %13, %14, %15, %16, %17, %18, %19, %20, %21, %22, %23, %24, %25, %26, %27, %28, %29, %30, %31, %32, %33, %34, %35, %36, %37, %38, %39, %40, %41, %42, %43, %44, %45, %46, %47, %48, %49, %50, %51, %52, %53, %54, %55, %56, %57, %58, %59, %60, %61, %62, %63, %64, %65, %66, %67, %68, %69, %70, %71, %72, %73, %74, %75, %76, %77, %78, %79, %80, %81, %82, %83, %84, %85, %86, %87, %88, %89, %90, %91, %92, %93, %94, %95}, %96, %97, p, 1, 1, 0, %99;\n}\n"
    : "+f"(d[0]), "+f"(d[1]), "+f"(d[2]), "+f"(d[3]), "+f"(d[4]), "+f"(d[5]), "+f"(d[6]), "+f"(d[7]), "+f"(d[8]), "+f"(d[9]), "+f"(d[10]), "+f"(d[11]), "+f"(d[12]), "+f"(d[13]), "+f"(d[14]), "+f"(d[15]), "+f"(d[16]), "+f"(d[17]), "+f"(d[18]), "+f"(d[19]), "+f"(d[20]), "+f"(d[21]), "+f"(d[22]), "+f"(d[23]), "+f"(d[24]), "+f"(d[25]), "+f"(d[26]), "+f"(d[27]), "+f"(d[28]), "+f"(d[29]), "+f"(d[30]), "+f"(d[31]), "+f"(d[32]), "+f"(d[33]), "+f"(d[34]), "+f"(d[35]), "+f"(d[36]), "+f"(d[37]), "+f"(d[38]), "+f"(d[39]), "+f"(d[40]), "+f"(d[41]), "+f"(d[42]), "+f"(d[43]), "+f"(d[44]), "+f"(d[45]), "+f"(d[46]), "+f"(d[47]), "+f"(d[48]), "+f"(d[49]), "+f"(d[50]), "+f"(d[51]), "+f"(d[52]), "+f"(d[53]), "+f"(d[54]), "+f"(d[55]), "+f"(d[56]), "+f"(d[57]), "+f"(d[58]), "+f"(d[59]), "+f"(d[60]), "+f"(d[61]), "+f"(d[62]), "+f"(d[63]), "+f"(d[64]), "+f"(d[65]), "+f"(d[66]), "+f"(d[67]), "+f"(d[68]), "+f"(d[69]), "+f"(d[70]), "+f"(d[71]), "+f"(d[72]), "+f"(d[73]), "+f"(d[74]), "+f"(d[75]), "+f"(d[76]), "+f"(d[77]), "+f"(d[78]), "+f"(d[79]), "+f"(d[80]), "+f"(d[81]), "+f"(d[82]), "+f"(d[83]), "+f"(d[84]), "+f"(d[85]), "+f"(d[86]), "+f"(d[87]), "+f"(d[88]), "+f"(d[89]), "+f"(d[90]), "+f"(d[91]), "+f"(d[92]), "+f"(d[93]), "+f"(d[94]), "+f"(d[95])
    : "l"(da), "l"(db), "r"(scale_d), "n"(TB));
}


__device__ float g_mod[6 * D_];
__device__ __align__(1024) bf16 g_h[S_ * D_];
__device__ __align__(1024) bf16 g_o[S_ * HD_];
__device__ __align__(1024) float g_attn[S_ * D_];
__device__ __align__(1024) bf16 g_xa[S_ * D_];
__device__ __align__(1024) bf16 g_hb[S_ * D_];
__device__ __align__(1024) bf16 g_t[S_ * D_];
__device__ __align__(1024) bf16 g_us[S_ * D_];
__device__ __align__(1024) bf16 g_x1[S_ * D_];
__device__ __align__(1024) bf16 g_t2[S_ * D_];
__device__ __align__(1024) bf16 g_g[S_ * F_];

__global__ void __launch_bounds__(256) mod_kernel(const bf16* __restrict__ c, const bf16* __restrict__ w_mod) {
  pdl_launch();
  __shared__ float red[8][32];
  const int t = threadIdx.x, cg = t & 3, r0 = t >> 2;
  const int col0 = blockIdx.x * 32 + cg * 8;
  uint4 w[10];
#pragma unroll
  for (int i = 0; i < 10; i++) w[i] = __ldg(reinterpret_cast<const uint4*>(w_mod + (size_t)(r0 + 64 * i) * (6 * D_) + col0));
  float acc[8];
#pragma unroll
  for (int j = 0; j < 8; j++) acc[j] = 0.f;
#pragma unroll
  for (int i = 0; i < 10; i++) {
    float cv = __bfloat162float(c[r0 + 64 * i]);
    float s = bf_round(cv / (1.f + __expf(-cv)));
    acc[0] = fmaf(s, bf_lo(w[i].x), acc[0]); acc[1] = fmaf(s, bf_hi(w[i].x), acc[1]);
    acc[2] = fmaf(s, bf_lo(w[i].y), acc[2]); acc[3] = fmaf(s, bf_hi(w[i].y), acc[3]);
    acc[4] = fmaf(s, bf_lo(w[i].z), acc[4]); acc[5] = fmaf(s, bf_hi(w[i].z), acc[5]);
    acc[6] = fmaf(s, bf_lo(w[i].w), acc[6]); acc[7] = fmaf(s, bf_hi(w[i].w), acc[7]);
  }
#pragma unroll
  for (int j = 0; j < 8; j++) {
    acc[j] += __shfl_xor_sync(0xffffffffu, acc[j], 4);
    acc[j] += __shfl_xor_sync(0xffffffffu, acc[j], 8);
    acc[j] += __shfl_xor_sync(0xffffffffu, acc[j], 16);
  }
  if ((t & 31) < 4) {
#pragma unroll
    for (int j = 0; j < 8; j++) red[t >> 5][cg * 8 + j] = acc[j];
  }
  __syncthreads();
  if (t < 32) {
    float s = 0.f;
#pragma unroll
    for (int w8 = 0; w8 < 8; w8++) s += red[w8][t];
    const int col = blockIdx.x * 32 + t;
    s = bf_round(s);
    const int part = col / D_;
    if (part == 1 || part == 4) s = bf_round(1.f + s);
    g_mod[col] = s;
  }
}

__device__ __forceinline__ void row_stats(const float (&v)[20], float& mean, float& rstd) {
  float s = 0.f;
#pragma unroll
  for (int i = 0; i < 20; i++) s += v[i];
  mean = warp_sum(s) * (1.f / D_);
  float q = 0.f;
#pragma unroll
  for (int i = 0; i < 20; i++) { float d = v[i] - mean; q = fmaf(d, d, q); }
  rstd = rsqrtf(warp_sum(q) * (1.f / D_) + LN_EPS);
}
__device__ __forceinline__ void load_row_bf16(const bf16* p, int lane, float (&v)[20]) {
#pragma unroll
  for (int i = 0; i < 5; i++) {
    uint2 u = *reinterpret_cast<const uint2*>(p + (lane + 32 * i) * 4);
    v[4 * i] = bf_lo(u.x); v[4 * i + 1] = bf_hi(u.x); v[4 * i + 2] = bf_lo(u.y); v[4 * i + 3] = bf_hi(u.y);
  }
}
__device__ __forceinline__ void store_row_bf16(bf16* p, int lane, const float (&v)[20]) {
#pragma unroll
  for (int i = 0; i < 5; i++) {
    uint2 u; u.x = pack_bf16(v[4 * i], v[4 * i + 1]); u.y = pack_bf16(v[4 * i + 2], v[4 * i + 3]);
    *reinterpret_cast<uint2*>(p + (lane + 32 * i) * 4) = u;
  }
}
__device__ __forceinline__ void load_row_f32(const float* p, int lane, float (&v)[20]) {
#pragma unroll
  for (int i = 0; i < 5; i++) {
    float4 u = *reinterpret_cast<const float4*>(p + (lane + 32 * i) * 4);
    v[4 * i] = u.x; v[4 * i + 1] = u.y; v[4 * i + 2] = u.z; v[4 * i + 3] = u.w;
  }
}

__global__ void __launch_bounds__(256) ln1_kernel(const bf16* __restrict__ x) {
  pdl_launch();
  const int lane = threadIdx.x & 31, row = blockIdx.x * 8 + (threadIdx.x >> 5);
  float v[20];
  load_row_bf16(x + (size_t)row * D_, lane, v);
  float mean, rstd;
  row_stats(v, mean, rstd);
#pragma unroll
  for (int i = 0; i < 5; i++) *reinterpret_cast<float4*>(g_attn + (size_t)row * D_ + (lane + 32 * i) * 4) = make_float4(0.f, 0.f, 0.f, 0.f);
  pdl_wait();
  float sa[20], ca[20];
  load_row_f32(g_mod, lane, sa);
  load_row_f32(g_mod + D_, lane, ca);
#pragma unroll
  for (int i = 0; i < 20; i++) v[i] = fmaf((v[i] - mean) * rstd, ca[i], sa[i]);
  store_row_bf16(g_h + (size_t)row * D_, lane, v);
}

__global__ void __launch_bounds__(256) ln2_kernel(const bf16* __restrict__ x) {
  pdl_launch();
  const int lane = threadIdx.x & 31, row = blockIdx.x * 8 + (threadIdx.x >> 5);
  float v[20], a[20], g[20];
  load_row_bf16(x + (size_t)row * D_, lane, v);
  pdl_wait();
  load_row_f32(g_attn + (size_t)row * D_, lane, a);
  load_row_f32(g_mod + 2 * D_, lane, g);
#pragma unroll
  for (int i = 0; i < 20; i++) v[i] = bf_round(fmaf(g[i], a[i], v[i]));
  store_row_bf16(g_xa + (size_t)row * D_, lane, v);
  float mean, rstd;
  row_stats(v, mean, rstd);
  load_row_f32(g_mod + 3 * D_, lane, a);
  load_row_f32(g_mod + 4 * D_, lane, g);
#pragma unroll
  for (int i = 0; i < 20; i++) v[i] = bf_round(fmaf((v[i] - mean) * rstd, g[i], a[i]));
  store_row_bf16(g_hb + (size_t)row * D_, lane, v);
  row_stats(v, mean, rstd);
#pragma unroll
  for (int i = 0; i < 20; i++) v[i] = (v[i] - mean) * rstd;
  store_row_bf16(g_t + (size_t)row * D_, lane, v);
}

__global__ void __launch_bounds__(256) ln3_kernel() {
  pdl_launch();
  const int lane = threadIdx.x & 31, row = blockIdx.x * 8 + (threadIdx.x >> 5);
  float v[20];
  pdl_wait();
  load_row_bf16(g_x1 + (size_t)row * D_, lane, v);
  float mean, rstd;
  row_stats(v, mean, rstd);
#pragma unroll
  for (int i = 0; i < 20; i++) v[i] = (v[i] - mean) * rstd;
  store_row_bf16(g_t2 + (size_t)row * D_, lane, v);
}

constexpr int A_NSLOT = 9;
constexpr int A_SLOT = 24576;
constexpr int A_SMEM = A_NSLOT * A_SLOT + 1024 + 256;
constexpr int A_NKV = S_ / 64;

struct Ring {
  uint32_t slot, phase;
  __device__ __forceinline__ void adv(int n) { if (++slot == (uint32_t)n) { slot = 0; phase ^= 1; } }
};

__global__ void __cluster_dims__(2, 1, 1) __launch_bounds__(384, 1)
attn_kernel(const __grid_constant__ CUtensorMap tm_h, const __grid_constant__ CUtensorMap tm_wq,
            const __grid_constant__ CUtensorMap tm_k, const __grid_constant__ CUtensorMap tm_v) {
  extern __shared__ uint8_t smem_raw[];
  const uint32_t sb = (smem_u32(smem_raw) + 1023) & ~1023u;
  const uint32_t bar_full = sb + A_NSLOT * A_SLOT;
  const uint32_t bar_empty = bar_full + 8 * A_NSLOT;
  uint32_t rank;
  asm volatile("mov.u32 %0, %%cluster_ctarank;" : "=r"(rank));
  const int cid = blockIdx.x >> 1;
  const int qtile = (cid & 7) * 2 + rank;
  const int hbase = cid >> 3;
  const int wg = threadIdx.x >> 7;
  if (threadIdx.x == 0) {
    for (int i = 0; i < A_NSLOT; i++) { mbar_init(bar_full + 8 * i, 1); mbar_init(bar_empty + 8 * i, 16); }
    asm volatile("fence.mbarrier_init.release.cluster;" ::: "memory");
    prefetch_tmap(&tm_h); prefetch_tmap(&tm_wq); prefetch_tmap(&tm_k); prefetch_tmap(&tm_v);
  }
  __syncthreads();
  cluster_sync();
  pdl_launch();

  if (wg == 0) {
    asm volatile("setmaxnreg.dec.sync.aligned.u32 24;");
    if (threadIdx.x == 0) {
      Ring r{0, 1};
      pdl_wait();
      for (int item = 0; item < 4; item++) {
        const int head = hbase + 8 * item;
        for (int kb = 0; kb < 10; kb++) {
          mbar_wait(bar_empty + 8 * r.slot, r.phase);
          mbar_expect(bar_full + 8 * r.slot, 16384);
          tma2d(sb + r.slot * A_SLOT, &tm_h, bar_full + 8 * r.slot, kb * 64, qtile * 128);
          r.adv(A_NSLOT);
          mbar_wait(bar_empty + 8 * r.slot, r.phase);
          mbar_expect(bar_full + 8 * r.slot, A_SLOT);
          if ((uint32_t)(kb & 1) == rank) tma3d_mc(sb + r.slot * A_SLOT, &tm_wq, bar_full + 8 * r.slot, 0, kb * 64, head * 3, 3);
          r.adv(A_NSLOT);
        }
        for (int j = 0; j <= A_NKV; j++) {
          if (j < A_NKV) {
            mbar_wait(bar_empty + 8 * r.slot, r.phase);
            mbar_expect(bar_full + 8 * r.slot, A_SLOT);
            if (rank == 0) tma3d_mc(sb + r.slot * A_SLOT, &tm_k, bar_full + 8 * r.slot, 0, head * S_ + j * 64, 0, 3);
            r.adv(A_NSLOT);
          }
          if (j > 0) {
            mbar_wait(bar_empty + 8 * r.slot, r.phase);
            mbar_expect(bar_full + 8 * r.slot, A_SLOT);
            if (rank == 1) tma3d_mc(sb + r.slot * A_SLOT, &tm_v, bar_full + 8 * r.slot, 0, head * S_ + (j - 1) * 64, 0, 3);
            r.adv(A_NSLOT);
          }
        }
      }
    }
    __syncwarp();
    cluster_sync();
  } else {
    asm volatile("setmaxnreg.inc.sync.aligned.u32 240;");
    const int w = wg - 1;
    const int lane = threadIdx.x & 31;
    const int warp = (threadIdx.x >> 5) & 3;
    const uint32_t rel_base = mapa(bar_empty, (lane == 0) ? rank : (rank ^ 1));
    const float SC = 0.07216878364870322f * 1.4426950408889634f;
    Ring r{0, 0};
    float o[96];
    uint32_t q[48];
    float s[32];
    uint32_t p[16], p2[16];
    if (w == 1) bar_arrive(1, 256);
#define A_RELEASE(slot_) do { if (lane < 2) mbar_arrive_remote(rel_base + 8 * (slot_)); } while (0)

    for (int item = 0; item < 4; item++) {
      const int head = hbase + 8 * item;
      uint32_t prevA = 0, prevB = 0;
      for (int kb = 0; kb < 10; kb++) {
        const uint32_t sA = r.slot; mbar_wait(bar_full + 8 * sA, r.phase); r.adv(A_NSLOT);
        const uint32_t sB = r.slot; mbar_wait(bar_full + 8 * sB, r.phase); r.adv(A_NSLOT);
        const uint64_t da = mkdesc(sb + sA * A_SLOT + w * 8192, 16, 1024);
        const uint64_t db = mkdesc(sb + sB * A_SLOT, 8192, 1024);
        wg_fence();
#pragma unroll
        for (int kk = 0; kk < 4; kk++) wgmma_ss_n192<1>(o, da + kk * 2, db + kk * 128, (kb | kk) != 0);
        wg_commit();
        if (kb > 0) { wg_wait<1>(); A_RELEASE(prevA); A_RELEASE(prevB); }
        prevA = sA; prevB = sB;
      }
      wg_wait<0>();
      fence_regs(o);
      A_RELEASE(prevA); A_RELEASE(prevB);
#pragma unroll
      for (int i = 0; i < 48; i++) q[i] = pack_bf16(o[2 * i], o[2 * i + 1]);

      float c0, c1, l0, l1;
      {
        const uint32_t sK = r.slot; mbar_wait(bar_full + 8 * sK, r.phase); r.adv(A_NSLOT);
        const uint64_t dk = mkdesc(sb + sK * A_SLOT, 16, 1024);
        bar_sync(1 + w, 256);
        wg_fence();
#pragma unroll
        for (int kk = 0; kk < 12; kk++)
          wgmma_rs_n64<0>(s, q[4 * kk], q[4 * kk + 1], q[4 * kk + 2], q[4 * kk + 3], dk + (kk >> 2) * 512 + (kk & 3) * 2, kk != 0);
        wg_commit();
        bar_arrive(1 + (w ^ 1), 256);
        wg_wait<0>();
        fence_regs(s);
        A_RELEASE(sK);
        float mx0 = fmaxf(s[0], s[1]), mx1 = fmaxf(s[2], s[3]);
#pragma unroll
        for (int i = 1; i < 8; i++) { mx0 = fmaxf(mx0, fmaxf(s[4 * i], s[4 * i + 1])); mx1 = fmaxf(mx1, fmaxf(s[4 * i + 2], s[4 * i + 3])); }
        mx0 = fmaxf(mx0, __shfl_xor_sync(0xffffffffu, mx0, 1)); mx1 = fmaxf(mx1, __shfl_xor_sync(0xffffffffu, mx1, 1));
        mx0 = fmaxf(mx0, __shfl_xor_sync(0xffffffffu, mx0, 2)); mx1 = fmaxf(mx1, __shfl_xor_sync(0xffffffffu, mx1, 2));
        c0 = mx0 * SC; c1 = mx1 * SC;
        l0 = 0.f; l1 = 0.f;
#pragma unroll
        for (int i = 0; i < 8; i++) {
          s[4 * i] = ex2(fmaf(s[4 * i], SC, -c0)); s[4 * i + 1] = ex2(fmaf(s[4 * i + 1], SC, -c0));
          s[4 * i + 2] = ex2(fmaf(s[4 * i + 2], SC, -c1)); s[4 * i + 3] = ex2(fmaf(s[4 * i + 3], SC, -c1));
          l0 += s[4 * i] + s[4 * i + 1]; l1 += s[4 * i + 2] + s[4 * i + 3];
        }
#pragma unroll
        for (int i = 0; i < 16; i++) p[i] = pack_bf16(s[2 * i], s[2 * i + 1]);
      }
      uint32_t okn;
      {
        Ring r2 = r; r2.adv(A_NSLOT);
        okn = mbar_try(bar_full + 8 * r.slot, r.phase) & mbar_try(bar_full + 8 * r2.slot, r2.phase);
      }
#define A_STEP(PC, PN, FIRST)                                                                                          \
      {                                                                                                                \
        const uint32_t sK = r.slot, phK = r.phase; r.adv(A_NSLOT);                                                     \
        const uint32_t sV = r.slot, phV = r.phase; r.adv(A_NSLOT);                                                     \
        const uint64_t dk = mkdesc(sb + sK * A_SLOT, 16, 1024);                                                        \
        const uint64_t dv = mkdesc(sb + sV * A_SLOT, 8192, 1024);                                                      \
        if (!okn) { mbar_wait(bar_full + 8 * sK, phK); mbar_wait(bar_full + 8 * sV, phV); }                            \
        bar_sync(1 + w, 256);                                                                                          \
        wg_fence();                                                                                                    \
        _Pragma("unroll") for (int kk = 0; kk < 12; kk++)                                                              \
          wgmma_rs_n64<0>(s, q[4 * kk], q[4 * kk + 1], q[4 * kk + 2], q[4 * kk + 3], dk + (kk >> 2) * 512 + (kk & 3) * 2, kk != 0); \
        wg_commit();                                                                                                   \
        _Pragma("unroll") for (int kk = 0; kk < 4; kk++)                                                               \
          wgmma_rs_n192<1>(o, PC[4 * kk], PC[4 * kk + 1], PC[4 * kk + 2], PC[4 * kk + 3], dv + kk * 128, !(FIRST) || (kk != 0)); \
        wg_commit();                                                                                                   \
        bar_arrive(1 + (w ^ 1), 256);                                                                                  \
        {                                                                                                              \
          Ring r2 = r; r2.adv(A_NSLOT);                                                                                \
          okn = mbar_try(bar_full + 8 * r.slot, r.phase) & mbar_try(bar_full + 8 * r2.slot, r2.phase);                 \
        }                                                                                                              \
        wg_wait<1>();                                                                                                  \
        fence_regs(s);                                                                                                 \
        A_RELEASE(sK);                                                                                                 \
        float b0 = 0.f, b1 = 0.f;                                                                                      \
        _Pragma("unroll") for (int i = 0; i < 8; i++) {                                                                \
          const float e0 = ex2(fmaf(s[4 * i], SC, -c0)), e1 = ex2(fmaf(s[4 * i + 1], SC, -c0));                        \
          const float e2 = ex2(fmaf(s[4 * i + 2], SC, -c1)), e3 = ex2(fmaf(s[4 * i + 3], SC, -c1));                    \
          b0 += e0 + e1; b1 += e2 + e3;                                                                                \
          PN[2 * i] = pack_bf16(e0, e1); PN[2 * i + 1] = pack_bf16(e2, e3);                                            \
        }                                                                                                              \
        wg_wait<0>();                                                                                                  \
        fence_regs(o);                                                                                                 \
        fence_regs(PC);                                                                                                \
        A_RELEASE(sV);                                                                                                 \
        if (__any_sync(0xffffffffu, !(b0 <= 65536.f) || !(b1 <= 65536.f))) {                                           \
          float mx0 = fmaxf(s[0], s[1]), mx1 = fmaxf(s[2], s[3]);                                                      \
          _Pragma("unroll") for (int i = 1; i < 8; i++) {                                                              \
            mx0 = fmaxf(mx0, fmaxf(s[4 * i], s[4 * i + 1])); mx1 = fmaxf(mx1, fmaxf(s[4 * i + 2], s[4 * i + 3]));     \
          }                                                                                                            \
          mx0 = fmaxf(mx0, __shfl_xor_sync(0xffffffffu, mx0, 1)); mx1 = fmaxf(mx1, __shfl_xor_sync(0xffffffffu, mx1, 1)); \
          mx0 = fmaxf(mx0, __shfl_xor_sync(0xffffffffu, mx0, 2)); mx1 = fmaxf(mx1, __shfl_xor_sync(0xffffffffu, mx1, 2)); \
          const float n0 = fmaxf(c0, mx0 * SC), n1 = fmaxf(c1, mx1 * SC);                                              \
          const float a0 = ex2(c0 - n0), a1 = ex2(c1 - n1);                                                            \
          c0 = n0; c1 = n1;                                                                                            \
          l0 *= a0; l1 *= a1;                                                                                          \
          _Pragma("unroll") for (int i = 0; i < 24; i++) { o[4 * i] *= a0; o[4 * i + 1] *= a0; o[4 * i + 2] *= a1; o[4 * i + 3] *= a1; } \
          b0 = 0.f; b1 = 0.f;                                                                                          \
          _Pragma("unroll") for (int i = 0; i < 8; i++) {                                                              \
            const float e0 = ex2(fmaf(s[4 * i], SC, -c0)), e1 = ex2(fmaf(s[4 * i + 1], SC, -c0));                      \
            const float e2 = ex2(fmaf(s[4 * i + 2], SC, -c1)), e3 = ex2(fmaf(s[4 * i + 3], SC, -c1));                  \
            b0 += e0 + e1; b1 += e2 + e3;                                                                              \
            PN[2 * i] = pack_bf16(e0, e1); PN[2 * i + 1] = pack_bf16(e2, e3);                                          \
          }                                                                                                            \
        }                                                                                                              \
        l0 += b0; l1 += b1;                                                                                            \
      }
      for (int jj = 0; jj < 15; jj++) {
        A_STEP(p, p2, jj == 0)
        A_STEP(p2, p, false)
      }
      A_STEP(p, p2, false)
      {
        const uint32_t sV = r.slot; mbar_wait(bar_full + 8 * sV, r.phase); r.adv(A_NSLOT);
        const uint64_t dv = mkdesc(sb + sV * A_SLOT, 8192, 1024);
        bar_sync(1 + w, 256);
        wg_fence();
#pragma unroll
        for (int kk = 0; kk < 4; kk++)
          wgmma_rs_n192<1>(o, p2[4 * kk], p2[4 * kk + 1], p2[4 * kk + 2], p2[4 * kk + 3], dv + kk * 128, 1);
        wg_commit();
        bar_arrive(1 + (w ^ 1), 256);
        wg_wait<0>();
        fence_regs(o);
        A_RELEASE(sV);
      }
      l0 += __shfl_xor_sync(0xffffffffu, l0, 1); l1 += __shfl_xor_sync(0xffffffffu, l1, 1);
      l0 += __shfl_xor_sync(0xffffffffu, l0, 2); l1 += __shfl_xor_sync(0xffffffffu, l1, 2);
      const float i0 = 1.f / l0, i1 = 1.f / l1;
      bf16* orow = g_o + (size_t)(qtile * 128 + w * 64 + warp * 16 + (lane >> 2)) * HD_ + head * DH_ + (lane & 3) * 8;
#pragma unroll
      for (int g = 0; g < 6; g++) {
        uint32_t u0 = pack_bf16(o[16 * g + 0] * i0, o[16 * g + 1] * i0), u1 = pack_bf16(o[16 * g + 4] * i0, o[16 * g + 5] * i0);
        uint32_t u2 = pack_bf16(o[16 * g + 8] * i0, o[16 * g + 9] * i0), u3 = pack_bf16(o[16 * g + 12] * i0, o[16 * g + 13] * i0);
        quad_transpose(u0, u1, u2, u3, lane);
        *reinterpret_cast<uint4*>(orow + g * 32) = make_uint4(u0, u1, u2, u3);
        uint32_t v0 = pack_bf16(o[16 * g + 2] * i1, o[16 * g + 3] * i1), v1 = pack_bf16(o[16 * g + 6] * i1, o[16 * g + 7] * i1);
        uint32_t v2 = pack_bf16(o[16 * g + 10] * i1, o[16 * g + 11] * i1), v3 = pack_bf16(o[16 * g + 14] * i1, o[16 * g + 15] * i1);
        quad_transpose(v0, v1, v2, v3, lane);
        *reinterpret_cast<uint4*>(orow + (size_t)8 * HD_ + g * 32) = make_uint4(v0, v1, v2, v3);
      }
    }
    cluster_sync();
  }
}

enum { EPI_RED = 0, EPI_GELU_SHIFT = 1, EPI_ADD_HB = 2, EPI_GELU = 3, EPI_FINAL = 4 };

template <int BN> struct GemmCfg {
  static constexpr int STAGE = 16384 + BN * 128;
  static constexpr int NST = (BN == 320) ? 4 : (BN == 192 ? 5 : 6);
  static constexpr int SMEM = NST * STAGE + 1024 + 256;
};

template <int BN, int EPI>
__global__ void __launch_bounds__(384, 1)
gemm_kernel(const __grid_constant__ CUtensorMap tm_a, const __grid_constant__ CUtensorMap tm_b, int kblocks, bf16* __restrict__ out) {
  using C = GemmCfg<BN>;
  extern __shared__ uint8_t smem_raw[];
  const uint32_t sb = (smem_u32(smem_raw) + 1023) & ~1023u;
  const uint32_t bar_full = sb + C::NST * C::STAGE;
  const uint32_t bar_empty = bar_full + 8 * C::NST;
  const int wg = threadIdx.x >> 7;
  const int n0 = blockIdx.x * BN, m0 = blockIdx.y * 128, kb0 = blockIdx.z * kblocks;
  if (threadIdx.x == 0) {
    for (int i = 0; i < C::NST; i++) { mbar_init(bar_full + 8 * i, 1); mbar_init(bar_empty + 8 * i, 8); }
    asm volatile("fence.mbarrier_init.release.cluster;" ::: "memory");
    prefetch_tmap(&tm_a); prefetch_tmap(&tm_b);
  }
  __syncthreads();
  pdl_launch();
  if (wg == 0) {
    asm volatile("setmaxnreg.dec.sync.aligned.u32 24;");
    if (threadIdx.x == 0) {
      Ring r{0, 1};
      pdl_wait();
      for (int kb = 0; kb < kblocks; kb++) {
        mbar_wait(bar_empty + 8 * r.slot, r.phase);
        mbar_expect(bar_full + 8 * r.slot, C::STAGE);
        tma2d(sb + r.slot * C::STAGE, &tm_a, bar_full + 8 * r.slot, (kb0 + kb) * 64, m0);
        tma3d(sb + r.slot * C::STAGE + 16384, &tm_b, bar_full + 8 * r.slot, 0, (kb0 + kb) * 64, n0 / 64);
        r.adv(C::NST);
      }
    }
  } else {
    asm volatile("setmaxnreg.inc.sync.aligned.u32 240;");
    const int w = wg - 1, lane = threadIdx.x & 31, warp = (threadIdx.x >> 5) & 3;
    constexpr int N1 = (BN == 320 || BN == 192) ? 192 : 128;
    constexpr int N2 = BN - N1;
    float acc1[N1 / 2];
    float acc2[N2 > 0 ? N2 / 2 : 4];
    Ring r{0, 0};
    uint32_t prev = 0;
    for (int kb = 0; kb < kblocks; kb++) {
      const uint32_t st = r.slot; mbar_wait(bar_full + 8 * st, r.phase); r.adv(C::NST);
      const uint64_t da = mkdesc(sb + st * C::STAGE + w * 8192, 16, 1024);
      const uint64_t db = mkdesc(sb + st * C::STAGE + 16384, 8192, 1024);
      wg_fence();
#pragma unroll
      for (int kk = 0; kk < 4; kk++) {
        if constexpr (N1 == 192) wgmma_ss_n192<1>(acc1, da + kk * 2, db + kk * 128, (kb | kk) != 0);
        else wgmma_ss_n128<1>(acc1, da + kk * 2, db + kk * 128, (kb | kk) != 0);
        if constexpr (N2 == 128) wgmma_ss_n128<1>(acc2, da + kk * 2, db + kk * 128 + 3 * 512, (kb | kk) != 0);
      }
      wg_commit();
      if (kb > 0) { wg_wait<1>(); if (lane == 0) mbar_arrive(bar_empty + 8 * prev); }
      prev = st;
    }
    wg_wait<0>();
    fence_regs(acc1);
    fence_regs(acc2);
    pdl_wait();
    const int row = m0 + w * 64 + warp * 16 + (lane >> 2);
    const int cq = (lane & 3) * 2;
    auto epi = [&](float v0, float v1, float v2, float v3, int nb) {
      const int col = n0 + nb * 8 + cq;
      if constexpr (EPI == EPI_RED) {
        asm volatile("red.global.add.v2.f32 [%0], {%1, %2};" :: "l"(g_attn + (size_t)row * D_ + col), "f"(v0), "f"(v1) : "memory");
        asm volatile("red.global.add.v2.f32 [%0], {%1, %2};" :: "l"(g_attn + (size_t)(row + 8) * D_ + col), "f"(v2), "f"(v3) : "memory");
      } else if constexpr (EPI == EPI_GELU_SHIFT) {
        const int grp = col / 160;
        const int sh = (grp == 0) ? 1 : (grp == 1) ? -1 : (grp == 2) ? 2 : -2;
        const uint32_t ua = pack_bf16(gelu_tanh(v0), gelu_tanh(v1)), ub = pack_bf16(gelu_tanh(v2), gelu_tanh(v3));
        const int ra = row + sh, rb = row + 8 + sh;
        if (ra >= 0 && ra < S_) *reinterpret_cast<uint32_t*>(g_us + (size_t)ra * D_ + col) = ua;
        if (rb >= 0 && rb < S_) *reinterpret_cast<uint32_t*>(g_us + (size_t)rb * D_ + col) = ub;
        if (sh > 0) { if (row < sh) *reinterpret_cast<uint32_t*>(g_us + (size_t)row * D_ + col) = 0u; }
        else { if (row + 8 >= S_ + sh) *reinterpret_cast<uint32_t*>(g_us + (size_t)(row + 8) * D_ + col) = 0u; }
      } else if constexpr (EPI == EPI_ADD_HB) {
        const uint32_t ha = *reinterpret_cast<const uint32_t*>(g_hb + (size_t)row * D_ + col);
        const uint32_t hb = *reinterpret_cast<const uint32_t*>(g_hb + (size_t)(row + 8) * D_ + col);
        *reinterpret_cast<uint32_t*>(g_x1 + (size_t)row * D_ + col) = pack_bf16(bf_lo(ha) + v0, bf_hi(ha) + v1);
        *reinterpret_cast<uint32_t*>(g_x1 + (size_t)(row + 8) * D_ + col) = pack_bf16(bf_lo(hb) + v2, bf_hi(hb) + v3);
      } else if constexpr (EPI == EPI_GELU) {
        *reinterpret_cast<uint32_t*>(g_g + (size_t)row * F_ + col) = pack_bf16(gelu_tanh(v0), gelu_tanh(v1));
        *reinterpret_cast<uint32_t*>(g_g + (size_t)(row + 8) * F_ + col) = pack_bf16(gelu_tanh(v2), gelu_tanh(v3));
      } else {
        const float2 gb = *reinterpret_cast<const float2*>(g_mod + 5 * D_ + col);
        const uint32_t xa = *reinterpret_cast<const uint32_t*>(g_xa + (size_t)row * D_ + col);
        const uint32_t xb = *reinterpret_cast<const uint32_t*>(g_xa + (size_t)(row + 8) * D_ + col);
        const uint32_t ya = *reinterpret_cast<const uint32_t*>(g_x1 + (size_t)row * D_ + col);
        const uint32_t yb = *reinterpret_cast<const uint32_t*>(g_x1 + (size_t)(row + 8) * D_ + col);
        *reinterpret_cast<uint32_t*>(out + (size_t)row * D_ + col) =
            pack_bf16(fmaf(gb.x, bf_lo(ya) + v0, bf_lo(xa)), fmaf(gb.y, bf_hi(ya) + v1, bf_hi(xa)));
        *reinterpret_cast<uint32_t*>(out + (size_t)(row + 8) * D_ + col) =
            pack_bf16(fmaf(gb.x, bf_lo(yb) + v2, bf_lo(xb)), fmaf(gb.y, bf_hi(yb) + v3, bf_hi(xb)));
      }
    };
#pragma unroll
    for (int nb = 0; nb < N1 / 8; nb++) epi(acc1[4 * nb], acc1[4 * nb + 1], acc1[4 * nb + 2], acc1[4 * nb + 3], nb);
    if constexpr (N2 > 0) {
#pragma unroll
      for (int nb = 0; nb < N2 / 8; nb++) epi(acc2[4 * nb], acc2[4 * nb + 1], acc2[4 * nb + 2], acc2[4 * nb + 3], N1 / 8 + nb);
    }
  }
}

typedef CUresult (*EncFn)(CUtensorMap*, CUtensorMapDataType, cuuint32_t, void*, const cuuint64_t*, const cuuint64_t*,
                          const cuuint32_t*, const cuuint32_t*, CUtensorMapInterleave, CUtensorMapSwizzle,
                          CUtensorMapL2promotion, CUtensorMapFloatOOBfill);
static EncFn g_enc = nullptr;

static CUtensorMap map2d(const void* p, uint64_t rows, uint64_t cols, uint32_t box_rows) {
  CUtensorMap m;
  cuuint64_t gd[2] = {cols, rows}; cuuint64_t gs[1] = {cols * 2};
  cuuint32_t bx[2] = {64, box_rows}; cuuint32_t es[2] = {1, 1};
  g_enc(&m, CU_TENSOR_MAP_DATA_TYPE_BFLOAT16, 2, const_cast<void*>(p), gd, gs, bx, es, CU_TENSOR_MAP_INTERLEAVE_NONE,
        CU_TENSOR_MAP_SWIZZLE_128B, CU_TENSOR_MAP_L2_PROMOTION_L2_256B, CU_TENSOR_MAP_FLOAT_OOB_FILL_NONE);
  return m;
}
static CUtensorMap map3d(const void* p, uint64_t rows, uint64_t cols, uint32_t box_rows, uint32_t nblk) {
  CUtensorMap m;
  cuuint64_t gd[3] = {64, rows, cols / 64}; cuuint64_t gs[2] = {cols * 2, 128};
  cuuint32_t bx[3] = {64, box_rows, nblk}; cuuint32_t es[3] = {1, 1, 1};
  g_enc(&m, CU_TENSOR_MAP_DATA_TYPE_BFLOAT16, 3, const_cast<void*>(p), gd, gs, bx, es, CU_TENSOR_MAP_INTERLEAVE_NONE,
        CU_TENSOR_MAP_SWIZZLE_128B, CU_TENSOR_MAP_L2_PROMOTION_L2_256B, CU_TENSOR_MAP_FLOAT_OOB_FILL_NONE);
  return m;
}

template <typename... KArgs, typename... Args>
static void launch(void (*kern)(KArgs...), dim3 grid, dim3 block, int smem, bool pdl, Args... args) {
  cudaLaunchConfig_t cfg = {};
  cfg.gridDim = grid; cfg.blockDim = block; cfg.dynamicSmemBytes = smem; cfg.stream = cudaStreamPerThread;
  cudaLaunchAttribute at[1];
  at[0].id = cudaLaunchAttributeProgrammaticStreamSerialization;
  at[0].val.programmaticStreamSerializationAllowed = 1;
  cfg.attrs = at; cfg.numAttrs = pdl ? 1 : 0;
  cudaLaunchKernelEx(&cfg, kern, KArgs(args)...);
}

extern "C" void kernel_launch(void* const* d_in, const int* in_sizes, int n_in, void* d_out, int out_size) {
  const bf16* x = (const bf16*)d_in[0];
  const bf16* kc = (const bf16*)d_in[1];
  const bf16* vc = (const bf16*)d_in[2];
  const bf16* wq = (const bf16*)d_in[3];
  const bf16* wo = (const bf16*)d_in[4];
  const bf16* w1 = (const bf16*)d_in[6];
  const bf16* w2 = (const bf16*)d_in[7];
  const bf16* w3 = (const bf16*)d_in[8];
  const bf16* w4 = (const bf16*)d_in[9];
  const bf16* c = (const bf16*)d_in[10];
  const bf16* wmod = (const bf16*)d_in[11];
  bf16* out = (bf16*)d_out;

  static void *p_h, *p_o, *p_t, *p_us, *p_t2, *p_g;
  if (!g_enc) {
    void* fn = nullptr; cudaDriverEntryPointQueryResult qr;
    cudaGetDriverEntryPoint("cuTensorMapEncodeTiled", &fn, cudaEnableDefault, &qr);
    g_enc = (EncFn)fn;
    cudaGetSymbolAddress(&p_h, g_h); cudaGetSymbolAddress(&p_o, g_o); cudaGetSymbolAddress(&p_t, g_t);
    cudaGetSymbolAddress(&p_us, g_us); cudaGetSymbolAddress(&p_t2, g_t2); cudaGetSymbolAddress(&p_g, g_g);
    cudaFuncSetAttribute(attn_kernel, cudaFuncAttributeMaxDynamicSharedMemorySize, A_SMEM);
    cudaFuncSetAttribute(gemm_kernel<320, EPI_RED>, cudaFuncAttributeMaxDynamicSharedMemorySize, GemmCfg<320>::SMEM);
    cudaFuncSetAttribute(gemm_kernel<128, EPI_GELU_SHIFT>, cudaFuncAttributeMaxDynamicSharedMemorySize, GemmCfg<128>::SMEM);
    cudaFuncSetAttribute(gemm_kernel<128, EPI_ADD_HB>, cudaFuncAttributeMaxDynamicSharedMemorySize, GemmCfg<128>::SMEM);
    cudaFuncSetAttribute(gemm_kernel<192, EPI_GELU>, cudaFuncAttributeMaxDynamicSharedMemorySize, GemmCfg<192>::SMEM);
    cudaFuncSetAttribute(gemm_kernel<128, EPI_FINAL>, cudaFuncAttributeMaxDynamicSharedMemorySize, GemmCfg<128>::SMEM);
  }
  const CUtensorMap tm_h = map2d(p_h, S_, D_, 128);
  const CUtensorMap tm_wq = map3d(wq, D_, HD_, 64, 3);
  const CUtensorMap tm_k = map3d(kc, (uint64_t)H_ * S_, DH_, 64, 3);
  const CUtensorMap tm_v = map3d(vc, (uint64_t)H_ * S_, DH_, 64, 3);
  const CUtensorMap tm_o = map2d(p_o, S_, HD_, 128);
  const CUtensorMap tm_wo = map3d(wo, HD_, D_, 64, 5);
  const CUtensorMap tm_t = map2d(p_t, S_, D_, 128);
  const CUtensorMap tm_w1 = map3d(w1, D_, D_, 64, 2);
  const CUtensorMap tm_us = map2d(p_us, S_, D_, 128);
  const CUtensorMap tm_w2 = map3d(w2, D_, D_, 64, 2);
  const CUtensorMap tm_t2 = map2d(p_t2, S_, D_, 128);
  const CUtensorMap tm_w3 = map3d(w3, D_, F_, 64, 3);
  const CUtensorMap tm_g = map2d(p_g, S_, F_, 128);
  const CUtensorMap tm_w4 = map3d(w4, F_, D_, 64, 2);

  const bool PDL = true;
  launch(mod_kernel, dim3(120), dim3(256), 0, false, c, wmod);
  launch(ln1_kernel, dim3(256), dim3(256), 0, PDL, x);
  launch(attn_kernel, dim3(128), dim3(384), A_SMEM, PDL, tm_h, tm_wq, tm_k, tm_v);
  launch(gemm_kernel<320, EPI_RED>, dim3(2, 16, 4), dim3(384), GemmCfg<320>::SMEM, PDL, tm_o, tm_wo, 24, out);
  launch(ln2_kernel, dim3(256), dim3(256), 0, PDL, x);
  launch(gemm_kernel<128, EPI_GELU_SHIFT>, dim3(5, 16, 1), dim3(384), GemmCfg<128>::SMEM, PDL, tm_t, tm_w1, 10, out);
  launch(gemm_kernel<128, EPI_ADD_HB>, dim3(5, 16, 1), dim3(384), GemmCfg<128>::SMEM, PDL, tm_us, tm_w2, 10, out);
  launch(ln3_kernel, dim3(256), dim3(256), 0, PDL);
  launch(gemm_kernel<192, EPI_GELU>, dim3(8, 16, 1), dim3(384), GemmCfg<192>::SMEM, PDL, tm_t2, tm_w3, 10, out);
  launch(gemm_kernel<128, EPI_FINAL>, dim3(5, 16, 1), dim3(384), GemmCfg<128>::SMEM, PDL, tm_g, tm_w4, 24, out);
}
```

```cpp
#include <cuda_runtime.h>
#include <cuda.h>
#include <cuda_bf16.h>
#include <stdint.h>

typedef __nv_bfloat16 bf16;

constexpr int S_  = 2048;
constexpr int D_  = 640;
constexpr int H_  = 32;
constexpr int DH_ = 192;
constexpr int HD_ = H_ * DH_;
constexpr int F_  = 1536;
constexpr float LN_EPS = 1e-5f;

__device__ __forceinline__ uint32_t smem_u32(const void* p) { return (uint32_t)__cvta_generic_to_shared(p); }
__device__ __forceinline__ void mbar_init(uint32_t a, uint32_t c) { asm volatile("mbarrier.init.shared::cta.b64 [%0], %1;" :: "r"(a), "r"(c) : "memory"); }
__device__ __forceinline__ void mbar_expect(uint32_t a, uint32_t b) { asm volatile("mbarrier.arrive.expect_tx.shared::cta.b64 _, [%0], %1;" :: "r"(a), "r"(b) : "memory"); }
__device__ __forceinline__ void mbar_arrive(uint32_t a) { asm volatile("mbarrier.arrive.shared::cta.b64 _, [%0];" :: "r"(a) : "memory"); }
__device__ __forceinline__ void mbar_arrive_remote(uint32_t ra) { asm volatile("mbarrier.arrive.shared::cluster.b64 _, [%0];" :: "r"(ra) : "memory"); }
__device__ __forceinline__ uint32_t mapa(uint32_t a, uint32_t cta) { uint32_t r; asm volatile("mapa.shared::cluster.u32 %0, %1, %2;" : "=r"(r) : "r"(a), "r"(cta)); return r; }
__device__ __forceinline__ uint32_t mbar_try(uint32_t a, uint32_t ph) {
  uint32_t ok;
  asm volatile("{\n.reg .pred p;\nmbarrier.test_wait.parity.shared::cta.b64 p, [%1], %2;\nselp.u32 %0, 1, 0, p;\n}\n" : "=r"(ok) : "r"(a), "r"(ph) : "memory");
  return ok;
}
__device__ __forceinline__ void mbar_wait(uint32_t a, uint32_t ph) {
  asm volatile(
      "{\n.reg .pred p;\n.reg .u32 n;\n"
      "mbarrier.try_wait.parity.shared::cta.b64 p, [%0], %1;\n"
      "@p bra DONE;\n"
      "mov.u32 n, 0;\n"
      "SPIN:\n"
      "mbarrier.try_wait.parity.shared::cta.b64 p, [%0], %1;\n"
      "@p bra DONE;\n"
      "add.u32 n, n, 1;\n"
      "setp.gt.u32 p, n, 16777216;\n"
      "@p trap;\n"
      "bra SPIN;\n"
      "DONE:\n}\n" :: "r"(a), "r"(ph) : "memory");
}
__device__ __forceinline__ void tma2d(uint32_t dst, const CUtensorMap* m, uint32_t bar, int c0, int c1) {
  asm volatile("cp.async.bulk.tensor.2d.shared::cluster.global.mbarrier::complete_tx::bytes [%0], [%1, {%3, %4}], [%2];"
               :: "r"(dst), "l"(m), "r"(bar), "r"(c0), "r"(c1) : "memory");
}
__device__ __forceinline__ void tma3d(uint32_t dst, const CUtensorMap* m, uint32_t bar, int c0, int c1, int c2) {
  asm volatile("cp.async.bulk.tensor.3d.shared::cluster.global.mbarrier::complete_tx::bytes [%0], [%1, {%3, %4, %5}], [%2];"
               :: "r"(dst), "l"(m), "r"(bar), "r"(c0), "r"(c1), "r"(c2) : "memory");
}
__device__ __forceinline__ void tma3d_mc(uint32_t dst, const CUtensorMap* m, uint32_t bar, int c0, int c1, int c2, uint16_t mask) {
  asm volatile("cp.async.bulk.tensor.3d.shared::cluster.global.mbarrier::complete_tx::bytes.multicast::cluster [%0], [%1, {%3, %4, %5}], [%2], %6;"
               :: "r"(dst), "l"(m), "r"(bar), "r"(c0), "r"(c1), "r"(c2), "h"(mask) : "memory");
}
__device__ __forceinline__ void prefetch_tmap(const CUtensorMap* m) { asm volatile("prefetch.tensormap [%0];" :: "l"(m) : "memory"); }
__device__ __forceinline__ void wg_fence() { asm volatile("wgmma.fence.sync.aligned;" ::: "memory"); }
__device__ __forceinline__ void wg_commit() { asm volatile("wgmma.commit_group.sync.aligned;" ::: "memory"); }
template <int N> __device__ __forceinline__ void wg_wait() { asm volatile("wgmma.wait_group.sync.aligned %0;" :: "n"(N) : "memory"); }
template <int N> __device__ __forceinline__ void fence_regs(float (&r)[N]) {
#pragma unroll
  for (int i = 0; i < N; i++) asm volatile("" : "+f"(r[i]) :: "memory");
}
template <int N> __device__ __forceinline__ void fence_regs(uint32_t (&r)[N]) {
#pragma unroll
  for (int i = 0; i < N; i++) asm volatile("" : "+r"(r[i]) :: "memory");
}
__device__ __forceinline__ uint64_t mkdesc(uint32_t addr, uint32_t lbo, uint32_t sbo) {
  return (uint64_t)((addr & 0x3FFFF) >> 4) | ((uint64_t)(lbo >> 4) << 16) | ((uint64_t)(sbo >> 4) << 32) | (1ull << 62);
}
__device__ __forceinline__ void bar_sync(int id, int n) { asm volatile("bar.sync %0, %1;" :: "r"(id), "r"(n) : "memory"); }
__device__ __forceinline__ void bar_arrive(int id, int n) { asm volatile("bar.arrive %0, %1;" :: "r"(id), "r"(n) : "memory"); }
__device__ __forceinline__ void cluster_sync() { asm volatile("barrier.cluster.arrive.aligned;\nbarrier.cluster.wait.aligned;" ::: "memory"); }
__device__ __forceinline__ void pdl_wait() { asm volatile("griddepcontrol.wait;" ::: "memory"); }
__device__ __forceinline__ void pdl_launch() { asm volatile("griddepcontrol.launch_dependents;" ::: "memory"); }
__device__ __forceinline__ float ex2(float x) { float y; asm("ex2.approx.ftz.f32 %0, %1;" : "=f"(y) : "f"(x)); return y; }
__device__ __forceinline__ uint32_t pack_bf16(float lo, float hi) { uint32_t r; asm("cvt.rn.bf16x2.f32 %0, %1, %2;" : "=r"(r) : "f"(hi), "f"(lo)); return r; }
__device__ __forceinline__ float bf_lo(uint32_t u) { return __uint_as_float(u << 16); }
__device__ __forceinline__ float bf_hi(uint32_t u) { return __uint_as_float(u & 0xffff0000u); }
__device__ __forceinline__ float bf_round(float x) { return __bfloat162float(__float2bfloat16_rn(x)); }
__device__ __forceinline__ float tanh_fast(float x) { float y; asm("tanh.approx.f32 %0, %1;" : "=f"(y) : "f"(x)); return y; }
__device__ __forceinline__ float gelu_tanh(float x) {
  float u = x * (0.7978845608028654f + 0.035677408136300125f * x * x);
  float hx = 0.5f * x;
  return fmaf(hx, tanh_fast(u), hx);
}
__device__ __forceinline__ float warp_sum(float v) {
#pragma unroll
  for (int o = 16; o > 0; o >>= 1) v += __shfl_xor_sync(0xffffffffu, v, o);
  return v;
}
__device__ __forceinline__ void quad_transpose(uint32_t& v0, uint32_t& v1, uint32_t& v2, uint32_t& v3, int lane) {
  const bool b0 = lane & 1, b1 = lane & 2;
  uint32_t s0 = b0 ? v0 : v1, s1 = b0 ? v2 : v3;
  s0 = __shfl_xor_sync(0xffffffffu, s0, 1); s1 = __shfl_xor_sync(0xffffffffu, s1, 1);
  if (b0) { v0 = s0; v2 = s1; } else { v1 = s0; v3 = s1; }
  uint32_t t0 = b1 ? v0 : v2, t1 = b1 ? v1 : v3;
  t0 = __shfl_xor_sync(0xffffffffu, t0, 2); t1 = __shfl_xor_sync(0xffffffffu, t1, 2);
  if (b1) { v0 = t0; v1 = t1; } else { v2 = t0; v3 = t1; }
}

#define TSA(item, i)
#define TL_ENTRY(k)
#define TL_WAITED(k)
#define TL_END(k)
#define TS(item, i)
template<int TB> __device__ __forceinline__ void wgmma_rs_n64(float (&d)[32], uint32_t a0, uint32_t a1, uint32_t a2, uint32_t a3, uint64_t db, int scale_d) {
  asm volatile("{\n.reg .pred p;\nsetp.ne.b32 p, %37, 0;\n"
    "wgmma.mma_async.sync.aligned.m64n64k16.f32.bf16.bf16 {%0, %1, %2, %3, %4, %5, %6, %7, %8, %9, %10, %11, %12, %13, %14, %15, %16, %17, %18, %19, %20, %21, %22, %23, %24, %25, %26, %27, %28, %29, %30, %31}, {%32, %33, %34, %35}, %36, p, 1, 1, %38;\n}\n"
    : "+f"(d[0]), "+f"(d[1]), "+f"(d[2]), "+f"(d[3]), "+f"(d[4]), "+f"(d[5]), "+f"(d[6]), "+f"(d[7]), "+f"(d[8]), "+f"(d[9]), "+f"(d[10]), "+f"(d[11]), "+f"(d[12]), "+f"(d[13]), "+f"(d[14]), "+f"(d[15]), "+f"(d[16]), "+f"(d[17]), "+f"(d[18]), "+f"(d[19]), "+f"(d[20]), "+f"(d[21]), "+f"(d[22]), "+f"(d[23]), "+f"(d[24]), "+f"(d[25]), "+f"(d[26]), "+f"(d[27]), "+f"(d[28]), "+f"(d[29]), "+f"(d[30]), "+f"(d[31])
    : "r"(a0), "r"(a1), "r"(a2), "r"(a3), "l"(db), "r"(scale_d), "n"(TB));
}
template<int TB> __device__ __forceinline__ void wgmma_rs_n192(float (&d)[96], uint32_t a0, uint32_t a1, uint32_t a2, uint32_t a3, uint64_t db, int scale_d) {
  asm volatile("{\n.reg .pred p;\nsetp.ne.b32 p, %101, 0;\n"
    "wgmma.mma_async.sync.aligned.m64n192k16.f32.bf16.bf16 {%0, %1, %2, %3, %4, %5, %6, %7, %8, %9, %10, %11, %12, %13, %14, %15, %16, %17, %18, %19, %20, %21, %22, %23, %24, %25, %26, %27, %28, %29, %30, %31, %32, %33, %34, %35, %36, %37, %38, %39, %40, %41, %42, %43, %44, %45, %46, %47, %48, %49, %50, %51, %52, %53, %54, %55, %56, %57, %58, %59, %60, %61, %62, %63, %64, %65, %66, %67, %68, %69, %70, %71, %72, %73, %74, %75, %76, %77, %78, %79, %80, %81, %82, %83, %84, %85, %86, %87, %88, %89, %90, %91, %92, %93, %94, %95}, {%96, %97, %98, %99}, %100, p, 1, 1, %102;\n}\n"
    : "+f"(d[0]), "+f"(d[1]), "+f"(d[2]), "+f"(d[3]), "+f"(d[4]), "+f"(d[5]), "+f"(d[6]), "+f"(d[7]), "+f"(d[8]), "+f"(d[9]), "+f"(d[10]), "+f"(d[11]), "+f"(d[12]), "+f"(d[13]), "+f"(d[14]), "+f"(d[15]), "+f"(d[16]), "+f"(d[17]), "+f"(d[18]), "+f"(d[19]), "+f"(d[20]), "+f"(d[21]), "+f"(d[22]), "+f"(d[23]), "+f"(d[24]), "+f"(d[25]), "+f"(d[26]), "+f"(d[27]), "+f"(d[28]), "+f"(d[29]), "+f"(d[30]), "+f"(d[31]), "+f"(d[32]), "+f"(d[33]), "+f"(d[34]), "+f"(d[35]), "+f"(d[36]), "+f"(d[37]), "+f"(d[38]), "+f"(d[39]), "+f"(d[40]), "+f"(d[41]), "+f"(d[42]), "+f"(d[43]), "+f"(d[44]), "+f"(d[45]), "+f"(d[46]), "+f"(d[47]), "+f"(d[48]), "+f"(d[49]), "+f"(d[50]), "+f"(d[51]), "+f"(d[52]), "+f"(d[53]), "+f"(d[54]), "+f"(d[55]), "+f"(d[56]), "+f"(d[57]), "+f"(d[58]), "+f"(d[59]), "+f"(d[60]), "+f"(d[61]), "+f"(d[62]), "+f"(d[63]), "+f"(d[64]), "+f"(d[65]), "+f"(d[66]), "+f"(d[67]), "+f"(d[68]), "+f"(d[69]), "+f"(d[70]), "+f"(d[71]), "+f"(d[72]), "+f"(d[73]), "+f"(d[74]), "+f"(d[75]), "+f"(d[76]), "+f"(d[77]), "+f"(d[78]), "+f"(d[79]), "+f"(d[80]), "+f"(d[81]), "+f"(d[82]), "+f"(d[83]), "+f"(d[84]), "+f"(d[85]), "+f"(d[86]), "+f"(d[87]), "+f"(d[88]), "+f"(d[89]), "+f"(d[90]), "+f"(d[91]), "+f"(d[92]), "+f"(d[93]), "+f"(d[94]), "+f"(d[95])
    : "r"(a0), "r"(a1), "r"(a2), "r"(a3), "l"(db), "r"(scale_d), "n"(TB));
}
template<int TB> __device__ __forceinline__ void wgmma_ss_n128(float (&d)[64], uint64_t da, uint64_t db, int scale_d) {
  asm volatile("{\n.reg .pred p;\nsetp.ne.b32 p, %66, 0;\n"
    "wgmma.mma_async.sync.aligned.m64n128k16.f32.bf16.bf16 {%0, %1, %2, %3, %4, %5, %6, %7, %8, %9, %10, %11, %12, %13, %14, %15, %16, %17, %18, %19, %20, %21, %22, %23, %24, %25, %26, %27, %28, %29, %30, %31, %32, %33, %34, %35, %36, %37, %38, %39, %40, %41, %42, %43, %44, %45, %46, %47, %48, %49, %50, %51, %52, %53, %54, %55, %56, %57, %58, %59, %60, %61, %62, %63}, %64, %65, p, 1, 1, 0, %67;\n}\n"
    : "+f"(d[0]), "+f"(d[1]), "+f"(d[2]), "+f"(d[3]), "+f"(d[4]), "+f"(d[5]), "+f"(d[6]), "+f"(d[7]), "+f"(d[8]), "+f"(d[9]), "+f"(d[10]), "+f"(d[11]), "+f"(d[12]), "+f"(d[13]), "+f"(d[14]), "+f"(d[15]), "+f"(d[16]), "+f"(d[17]), "+f"(d[18]), "+f"(d[19]), "+f"(d[20]), "+f"(d[21]), "+f"(d[22]), "+f"(d[23]), "+f"(d[24]), "+f"(d[25]), "+f"(d[26]), "+f"(d[27]), "+f"(d[28]), "+f"(d[29]), "+f"(d[30]), "+f"(d[31]), "+f"(d[32]), "+f"(d[33]), "+f"(d[34]), "+f"(d[35]), "+f"(d[36]), "+f"(d[37]), "+f"(d[38]), "+f"(d[39]), "+f"(d[40]), "+f"(d[41]), "+f"(d[42]), "+f"(d[43]), "+f"(d[44]), "+f"(d[45]), "+f"(d[46]), "+f"(d[47]), "+f"(d[48]), "+f"(d[49]), "+f"(d[50]), "+f"(d[51]), "+f"(d[52]), "+f"(d[53]), "+f"(d[54]), "+f"(d[55]), "+f"(d[56]), "+f"(d[57]), "+f"(d[58]), "+f"(d[59]), "+f"(d[60]), "+f"(d[61]), "+f"(d[62]), "+f"(d[63])
    : "l"(da), "l"(db), "r"(scale_d), "n"(TB));
}
template<int TB> __device__ __forceinline__ void wgmma_ss_n192(float (&d)[96], uint64_t da, uint64_t db, int scale_d) {
  asm volatile("{\n.reg .pred p;\nsetp.ne.b32 p, %98, 0;\n"
    "wgmma.mma_async.sync.aligned.m64n192k16.f32.bf16.bf16 {%0, %1, %2, %3, %4, %5, %6, %7, %8, %9, %10, %11, %12, %13, %14, %15, %16, %17, %18, %19, %20, %21, %22, %23, %24, %25, %26, %27, %28, %29, %30, %31, %32, %33, %34, %35, %36, %37, %38, %39, %40, %41, %42, %43, %44, %45, %46, %47, %48, %49, %50, %51, %52, %53, %54, %55, %56, %57, %58, %59, %60, %61, %62, %63, %64, %65, %66, %67, %68, %69, %70, %71, %72, %73, %74, %75, %76, %77, %78, %79, %80, %81, %82, %83, %84, %85, %86, %87, %88, %89, %90, %91, %92, %93, %94, %95}, %96, %97, p, 1, 1, 0, %99;\n}\n"
    : "+f"(d[0]), "+f"(d[1]), "+f"(d[2]), "+f"(d[3]), "+f"(d[4]), "+f"(d[5]), "+f"(d[6]), "+f"(d[7]), "+f"(d[8]), "+f"(d[9]), "+f"(d[10]), "+f"(d[11]), "+f"(d[12]), "+f"(d[13]), "+f"(d[14]), "+f"(d[15]), "+f"(d[16]), "+f"(d[17]), "+f"(d[18]), "+f"(d[19]), "+f"(d[20]), "+f"(d[21]), "+f"(d[22]), "+f"(d[23]), "+f"(d[24]), "+f"(d[25]), "+f"(d[26]), "+f"(d[27]), "+f"(d[28]), "+f"(d[29]), "+f"(d[30]), "+f"(d[31]), "+f"(d[32]), "+f"(d[33]), "+f"(d[34]), "+f"(d[35]), "+f"(d[36]), "+f"(d[37]), "+f"(d[38]), "+f"(d[39]), "+f"(d[40]), "+f"(d[41]), "+f"(d[42]), "+f"(d[43]), "+f"(d[44]), "+f"(d[45]), "+f"(d[46]), "+f"(d[47]), "+f"(d[48]), "+f"(d[49]), "+f"(d[50]), "+f"(d[51]), "+f"(d[52]), "+f"(d[53]), "+f"(d[54]), "+f"(d[55]), "+f"(d[56]), "+f"(d[57]), "+f"(d[58]), "+f"(d[59]), "+f"(d[60]), "+f"(d[61]), "+f"(d[62]), "+f"(d[63]), "+f"(d[64]), "+f"(d[65]), "+f"(d[66]), "+f"(d[67]), "+f"(d[68]), "+f"(d[69]), "+f"(d[70]), "+f"(d[71]), "+f"(d[72]), "+f"(d[73]), "+f"(d[74]), "+f"(d[75]), "+f"(d[76]), "+f"(d[77]), "+f"(d[78]), "+f"(d[79]), "+f"(d[80]), "+f"(d[81]), "+f"(d[82]), "+f"(d[83]), "+f"(d[84]), "+f"(d[85]), "+f"(d[86]), "+f"(d[87]), "+f"(d[88]), "+f"(d[89]), "+f"(d[90]), "+f"(d[91]), "+f"(d[92]), "+f"(d[93]), "+f"(d[94]), "+f"(d[95])
    : "l"(da), "l"(db), "r"(scale_d), "n"(TB));
}
template<int TB> __device__ __forceinline__ void wgmma_ss_n80(float (&d)[40], uint64_t da, uint64_t db, int scale_d) {
  asm volatile("{\n.reg .pred p;\nsetp.ne.b32 p, %42, 0;\n"
    "wgmma.mma_async.sync.aligned.m64n80k16.f32.bf16.bf16 {%0, %1, %2, %3, %4, %5, %6, %7, %8, %9, %10, %11, %12, %13, %14, %15, %16, %17, %18, %19, %20, %21, %22, %23, %24, %25, %26, %27, %28, %29, %30, %31, %32, %33, %34, %35, %36, %37, %38, %39}, %40, %41, p, 1, 1, 0, %43;\n}\n"
    : "+f"(d[0]), "+f"(d[1]), "+f"(d[2]), "+f"(d[3]), "+f"(d[4]), "+f"(d[5]), "+f"(d[6]), "+f"(d[7]), "+f"(d[8]), "+f"(d[9]), "+f"(d[10]), "+f"(d[11]), "+f"(d[12]), "+f"(d[13]), "+f"(d[14]), "+f"(d[15]), "+f"(d[16]), "+f"(d[17]), "+f"(d[18]), "+f"(d[19]), "+f"(d[20]), "+f"(d[21]), "+f"(d[22]), "+f"(d[23]), "+f"(d[24]), "+f"(d[25]), "+f"(d[26]), "+f"(d[27]), "+f"(d[28]), "+f"(d[29]), "+f"(d[30]), "+f"(d[31]), "+f"(d[32]), "+f"(d[33]), "+f"(d[34]), "+f"(d[35]), "+f"(d[36]), "+f"(d[37]), "+f"(d[38]), "+f"(d[39])
    : "l"(da), "l"(db), "r"(scale_d), "n"(TB));
}

__device__ float g_mod[6 * D_];
__device__ __align__(1024) bf16 g_h[S_ * D_];
__device__ __align__(1024) bf16 g_o[S_ * HD_];
__device__ __align__(1024) uint4 g_xch[16 * 2 * 4 * 4 * 5 * 256];
__device__ __align__(1024) bf16 g_xs[S_ * D_];
__device__ __align__(1024) bf16 g_w1t[D_ * D_];
__device__ __align__(1024) bf16 g_w2t[D_ * D_];
__device__ __align__(1024) bf16 g_w4t[D_ * F_];
__device__ __align__(32) float g_st1[S_ * 8];
__device__ __align__(32) float g_st2[S_ * 2];
__device__ __align__(32) float g_vec[3 * D_ + F_ + 8];
__device__ unsigned g_flag[512];
__device__ __align__(1024) bf16 g_xa[S_ * D_];
__device__ __align__(1024) bf16 g_us[S_ * D_];
__device__ __align__(1024) bf16 g_x1[S_ * D_];
__device__ __align__(1024) bf16 g_g[S_ * F_];

__global__ void __launch_bounds__(256) mod_kernel(const bf16* __restrict__ c, const bf16* __restrict__ w_mod) {
  TL_ENTRY(0);
  pdl_launch();
  __shared__ float red[8][32];
  if (blockIdx.x < 14) { const int i = blockIdx.x * 256 + threadIdx.x; if (i < 3 * D_ + F_) g_vec[i] = 0.f; }
  const int t = threadIdx.x, cg = t & 3, r0 = t >> 2;
  const int col0 = blockIdx.x * 32 + cg * 8;
  uint4 w[10];
#pragma unroll
  for (int i = 0; i < 10; i++) w[i] = __ldg(reinterpret_cast<const uint4*>(w_mod + (size_t)(r0 + 64 * i) * (6 * D_) + col0));
  float acc[8];
#pragma unroll
  for (int j = 0; j < 8; j++) acc[j] = 0.f;
#pragma unroll
  for (int i = 0; i < 10; i++) {
    float cv = __bfloat162float(c[r0 + 64 * i]);
    float s = bf_round(cv / (1.f + __expf(-cv)));
    acc[0] = fmaf(s, bf_lo(w[i].x), acc[0]); acc[1] = fmaf(s, bf_hi(w[i].x), acc[1]);
    acc[2] = fmaf(s, bf_lo(w[i].y), acc[2]); acc[3] = fmaf(s, bf_hi(w[i].y), acc[3]);
    acc[4] = fmaf(s, bf_lo(w[i].z), acc[4]); acc[5] = fmaf(s, bf_hi(w[i].z), acc[5]);
    acc[6] = fmaf(s, bf_lo(w[i].w), acc[6]); acc[7] = fmaf(s, bf_hi(w[i].w), acc[7]);
  }
#pragma unroll
  for (int j = 0; j < 8; j++) {
    acc[j] += __shfl_xor_sync(0xffffffffu, acc[j], 4);
    acc[j] += __shfl_xor_sync(0xffffffffu, acc[j], 8);
    acc[j] += __shfl_xor_sync(0xffffffffu, acc[j], 16);
  }
  if ((t & 31) < 4) {
#pragma unroll
    for (int j = 0; j < 8; j++) red[t >> 5][cg * 8 + j] = acc[j];
  }
  __syncthreads();
  if (t < 32) {
    float s = 0.f;
#pragma unroll
    for (int w8 = 0; w8 < 8; w8++) s += red[w8][t];
    const int col = blockIdx.x * 32 + t;
    s = bf_round(s);
    const int part = col / D_;
    if (part == 1 || part == 4) s = bf_round(1.f + s);
    g_mod[col] = s;
    if (t == 0) TL_END(0);
  }
}

__device__ __forceinline__ void row_stats(const float (&v)[20], float& mean, float& rstd) {
  float s = 0.f;
#pragma unroll
  for (int i = 0; i < 20; i++) s += v[i];
  mean = warp_sum(s) * (1.f / D_);
  float q = 0.f;
#pragma unroll
  for (int i = 0; i < 20; i++) { float d = v[i] - mean; q = fmaf(d, d, q); }
  rstd = rsqrtf(warp_sum(q) * (1.f / D_) + LN_EPS);
}
__device__ __forceinline__ void load_row_bf16(const bf16* p, int lane, float (&v)[20]) {
#pragma unroll
  for (int i = 0; i < 5; i++) {
    uint2 u = *reinterpret_cast<const uint2*>(p + (lane + 32 * i) * 4);
    v[4 * i] = bf_lo(u.x); v[4 * i + 1] = bf_hi(u.x); v[4 * i + 2] = bf_lo(u.y); v[4 * i + 3] = bf_hi(u.y);
  }
}
__device__ __forceinline__ void store_row_bf16(bf16* p, int lane, const float (&v)[20]) {
#pragma unroll
  for (int i = 0; i < 5; i++) {
    uint2 u; u.x = pack_bf16(v[4 * i], v[4 * i + 1]); u.y = pack_bf16(v[4 * i + 2], v[4 * i + 3]);
    *reinterpret_cast<uint2*>(p + (lane + 32 * i) * 4) = u;
  }
}
__device__ __forceinline__ void load_row_f32(const float* p, int lane, float (&v)[20]) {
#pragma unroll
  for (int i = 0; i < 5; i++) {
    float4 u = *reinterpret_cast<const float4*>(p + (lane + 32 * i) * 4);
    v[4 * i] = u.x; v[4 * i + 1] = u.y; v[4 * i + 2] = u.z; v[4 * i + 3] = u.w;
  }
}

__global__ void __launch_bounds__(256) ln1_kernel(const bf16* __restrict__ x) {
  TL_ENTRY(1);
  pdl_launch();
  const int lane = threadIdx.x & 31, row = blockIdx.x * 8 + (threadIdx.x >> 5);
  float v[20];
  load_row_bf16(x + (size_t)row * D_, lane, v);
  float mean, rstd;
  row_stats(v, mean, rstd);
  if (lane < 8) g_st1[row * 8 + lane] = 0.f;
  if (lane < 2) g_st2[row * 2 + lane] = 0.f;
  if (blockIdx.x < 2) g_flag[blockIdx.x * 256 + threadIdx.x] = 0u;
  pdl_wait();
  if (threadIdx.x == 0) TL_WAITED(1);
  float sa[20], ca[20];
  load_row_f32(g_mod, lane, sa);
  load_row_f32(g_mod + D_, lane, ca);
#pragma unroll
  for (int i = 0; i < 20; i++) v[i] = fmaf((v[i] - mean) * rstd, ca[i], sa[i]);
  store_row_bf16(g_h + (size_t)row * D_, lane, v);
  if (threadIdx.x == 0) TL_END(1);
}

constexpr int A_NSLOT = 9;
constexpr int A_SLOT = 24576;
constexpr int A_SMEM = A_NSLOT * A_SLOT + 1024 + 256;
constexpr int A_NKV = S_ / 64;

struct Ring {
  uint32_t slot, phase;
  __device__ __forceinline__ void adv(int n) { if (++slot == (uint32_t)n) { slot = 0; phase ^= 1; } }
};

__global__ void __cluster_dims__(2, 1, 1) __launch_bounds__(384, 1)
attn_kernel(const __grid_constant__ CUtensorMap tm_h, const __grid_constant__ CUtensorMap tm_wq,
            const __grid_constant__ CUtensorMap tm_k, const __grid_constant__ CUtensorMap tm_v) {
  extern __shared__ uint8_t smem_raw[];
  const uint32_t sb = (smem_u32(smem_raw) + 1023) & ~1023u;
  TL_ENTRY(2);
  const uint32_t bar_full = sb + A_NSLOT * A_SLOT;
  const uint32_t bar_empty = bar_full + 8 * A_NSLOT;
  uint32_t rank;
  asm volatile("mov.u32 %0, %%cluster_ctarank;" : "=r"(rank));
  const int cid = blockIdx.x >> 1;
  const int qtile = (cid & 7) * 2 + rank;
  const int hbase = cid >> 3;
  const int wg = threadIdx.x >> 7;
  if (threadIdx.x == 0) {
    for (int i = 0; i < A_NSLOT; i++) { mbar_init(bar_full + 8 * i, 1); mbar_init(bar_empty + 8 * i, 16); }
    asm volatile("fence.mbarrier_init.release.cluster;" ::: "memory");
    prefetch_tmap(&tm_h); prefetch_tmap(&tm_wq); prefetch_tmap(&tm_k); prefetch_tmap(&tm_v);
  }
  __syncthreads();
  cluster_sync();
  pdl_launch();

  if (wg == 0) {
    asm volatile("setmaxnreg.dec.sync.aligned.u32 24;");
    if (threadIdx.x == 0) {
      Ring r{0, 1};
      pdl_wait();
      TL_WAITED(2);
      for (int item = 0; item < 4; item++) {
        const int head = hbase + 8 * item;
        for (int kb = 0; kb < 10; kb++) {
          mbar_wait(bar_empty + 8 * r.slot, r.phase);
          mbar_expect(bar_full + 8 * r.slot, 16384);
          tma2d(sb + r.slot * A_SLOT, &tm_h, bar_full + 8 * r.slot, kb * 64, qtile * 128);
          r.adv(A_NSLOT);
          mbar_wait(bar_empty + 8 * r.slot, r.phase);
          mbar_expect(bar_full + 8 * r.slot, A_SLOT);
          if ((uint32_t)(kb & 1) == rank) tma3d_mc(sb + r.slot * A_SLOT, &tm_wq, bar_full + 8 * r.slot, 0, kb * 64, head * 3, 3);
          r.adv(A_NSLOT);
        }
        for (int j = 0; j <= A_NKV; j++) {
          if (j < A_NKV) {
            mbar_wait(bar_empty + 8 * r.slot, r.phase);
            mbar_expect(bar_full + 8 * r.slot, A_SLOT);
            if (rank == 0) tma3d_mc(sb + r.slot * A_SLOT, &tm_k, bar_full + 8 * r.slot, 0, head * S_ + j * 64, 0, 3);
            r.adv(A_NSLOT);
          }
          if (j > 0) {
            mbar_wait(bar_empty + 8 * r.slot, r.phase);
            mbar_expect(bar_full + 8 * r.slot, A_SLOT);
            if (rank == 1) tma3d_mc(sb + r.slot * A_SLOT, &tm_v, bar_full + 8 * r.slot, 0, head * S_ + (j - 1) * 64, 0, 3);
            r.adv(A_NSLOT);
          }
        }
      }
    }
    __syncwarp();
    cluster_sync();
  } else {
    asm volatile("setmaxnreg.inc.sync.aligned.u32 240;");
    const int w = wg - 1;
    const int lane = threadIdx.x & 31;
    const int warp = (threadIdx.x >> 5) & 3;
    const uint32_t rel_base = mapa(bar_empty, (lane == 0) ? rank : (rank ^ 1));
    const float SC = 0.07216878364870322f * 1.4426950408889634f;
    Ring r{0, 0};
    float o[96];
    uint32_t q[48];
    float s[32];
    uint32_t p[16], p2[16];
    if (w == 1) bar_arrive(1, 256);
#define A_RELEASE(slot_) do { if (lane < 2) mbar_arrive_remote(rel_base + 8 * (slot_)); } while (0)

    for (int item = 0; item < 4; item++) {
      const int head = hbase + 8 * item;
      TSA(item, 0);
      uint32_t prevA = 0, prevB = 0;
      for (int kb = 0; kb < 10; kb++) {
        const uint32_t sA = r.slot; mbar_wait(bar_full + 8 * sA, r.phase); r.adv(A_NSLOT);
        const uint32_t sB = r.slot; mbar_wait(bar_full + 8 * sB, r.phase); r.adv(A_NSLOT);
        const uint64_t da = mkdesc(sb + sA * A_SLOT + w * 8192, 16, 1024);
        const uint64_t db = mkdesc(sb + sB * A_SLOT, 8192, 1024);
        wg_fence();
#pragma unroll
        for (int kk = 0; kk < 4; kk++) wgmma_ss_n192<1>(o, da + kk * 2, db + kk * 128, (kb | kk) != 0);
        wg_commit();
        if (kb > 0) { wg_wait<1>(); A_RELEASE(prevA); A_RELEASE(prevB); }
        prevA = sA; prevB = sB;
      }
      wg_wait<0>();
      fence_regs(o);
      A_RELEASE(prevA); A_RELEASE(prevB);
#pragma unroll
      for (int i = 0; i < 48; i++) q[i] = pack_bf16(o[2 * i], o[2 * i + 1]);

      TSA(item, 1);
      float c0, c1, l0, l1;
      {
        const uint32_t sK = r.slot; mbar_wait(bar_full + 8 * sK, r.phase); r.adv(A_NSLOT);
        const uint64_t dk = mkdesc(sb + sK * A_SLOT, 16, 1024);
        bar_sync(1 + w, 256);
        wg_fence();
#pragma unroll
        for (int kk = 0; kk < 12; kk++)
          wgmma_rs_n64<0>(s, q[4 * kk], q[4 * kk + 1], q[4 * kk + 2], q[4 * kk + 3], dk + (kk >> 2) * 512 + (kk & 3) * 2, kk != 0);
        wg_commit();
        bar_arrive(1 + (w ^ 1), 256);
        wg_wait<0>();
        fence_regs(s);
        A_RELEASE(sK);
        float mx0 = fmaxf(s[0], s[1]), mx1 = fmaxf(s[2], s[3]);
#pragma unroll
        for (int i = 1; i < 8; i++) { mx0 = fmaxf(mx0, fmaxf(s[4 * i], s[4 * i + 1])); mx1 = fmaxf(mx1, fmaxf(s[4 * i + 2], s[4 * i + 3])); }
        mx0 = fmaxf(mx0, __shfl_xor_sync(0xffffffffu, mx0, 1)); mx1 = fmaxf(mx1, __shfl_xor_sync(0xffffffffu, mx1, 1));
        mx0 = fmaxf(mx0, __shfl_xor_sync(0xffffffffu, mx0, 2)); mx1 = fmaxf(mx1, __shfl_xor_sync(0xffffffffu, mx1, 2));
        c0 = mx0 * SC; c1 = mx1 * SC;
        l0 = 0.f; l1 = 0.f;
#pragma unroll
        for (int i = 0; i < 8; i++) {
          s[4 * i] = ex2(fmaf(s[4 * i], SC, -c0)); s[4 * i + 1] = ex2(fmaf(s[4 * i + 1], SC, -c0));
          s[4 * i + 2] = ex2(fmaf(s[4 * i + 2], SC, -c1)); s[4 * i + 3] = ex2(fmaf(s[4 * i + 3], SC, -c1));
          l0 += s[4 * i] + s[4 * i + 1]; l1 += s[4 * i + 2] + s[4 * i + 3];
        }
#pragma unroll
        for (int i = 0; i < 16; i++) p[i] = pack_bf16(s[2 * i], s[2 * i + 1]);
      }
      TSA(item, 2);
      uint32_t okn;
      {
        Ring r2 = r; r2.adv(A_NSLOT);
        okn = mbar_try(bar_full + 8 * r.slot, r.phase) & mbar_try(bar_full + 8 * r2.slot, r2.phase);
      }
#define A_STEP(PC, PN, FIRST)                                                                                          \
      {                                                                                                                \
        const uint32_t sK = r.slot, phK = r.phase; r.adv(A_NSLOT);                                                     \
        const uint32_t sV = r.slot, phV = r.phase; r.adv(A_NSLOT);                                                     \
        const uint64_t dk = mkdesc(sb + sK * A_SLOT, 16, 1024);                                                        \
        const uint64_t dv = mkdesc(sb + sV * A_SLOT, 8192, 1024);                                                      \
        if (!okn) { mbar_wait(bar_full + 8 * sK, phK); mbar_wait(bar_full + 8 * sV, phV); }                            \
        bar_sync(1 + w, 256);                                                                                          \
        wg_fence();                                                                                                    \
        _Pragma("unroll") for (int kk = 0; kk < 12; kk++)                                                              \
          wgmma_rs_n64<0>(s, q[4 * kk], q[4 * kk + 1], q[4 * kk + 2], q[4 * kk + 3], dk + (kk >> 2) * 512 + (kk & 3) * 2, kk != 0); \
        wg_commit();                                                                                                   \
        _Pragma("unroll") for (int kk = 0; kk < 4; kk++)                                                               \
          wgmma_rs_n192<1>(o, PC[4 * kk], PC[4 * kk + 1], PC[4 * kk + 2], PC[4 * kk + 3], dv + kk * 128, !(FIRST) || (kk != 0)); \
        wg_commit();                                                                                                   \
        bar_arrive(1 + (w ^ 1), 256);                                                                                  \
        {                                                                                                              \
          Ring r2 = r; r2.adv(A_NSLOT);                                                                                \
          okn = mbar_try(bar_full + 8 * r.slot, r.phase) & mbar_try(bar_full + 8 * r2.slot, r2.phase);                 \
        }                                                                                                              \
        wg_wait<1>();                                                                                                  \
        fence_regs(s);                                                                                                 \
        A_RELEASE(sK);                                                                                                 \
        float b0 = 0.f, b1 = 0.f;                                                                                      \
        _Pragma("unroll") for (int i = 0; i < 8; i++) {                                                                \
          const float e0 = ex2(fmaf(s[4 * i], SC, -c0)), e1 = ex2(fmaf(s[4 * i + 1], SC, -c0));                        \
          const float e2 = ex2(fmaf(s[4 * i + 2], SC, -c1)), e3 = ex2(fmaf(s[4 * i + 3], SC, -c1));                    \
          b0 += e0 + e1; b1 += e2 + e3;                                                                                \
          PN[2 * i] = pack_bf16(e0, e1); PN[2 * i + 1] = pack_bf16(e2, e3);                                            \
        }                                                                                                              \
        wg_wait<0>();                                                                                                  \
        fence_regs(o);                                                                                                 \
        fence_regs(PC);                                                                                                \
        A_RELEASE(sV);                                                                                                 \
        if (__any_sync(0xffffffffu, !(b0 <= 65536.f) || !(b1 <= 65536.f))) {                                           \
          float mx0 = fmaxf(s[0], s[1]), mx1 = fmaxf(s[2], s[3]);                                                      \
          _Pragma("unroll") for (int i = 1; i < 8; i++) {                                                              \
            mx0 = fmaxf(mx0, fmaxf(s[4 * i], s[4 * i + 1])); mx1 = fmaxf(mx1, fmaxf(s[4 * i + 2], s[4 * i + 3]));     \
          }                                                                                                            \
          mx0 = fmaxf(mx0, __shfl_xor_sync(0xffffffffu, mx0, 1)); mx1 = fmaxf(mx1, __shfl_xor_sync(0xffffffffu, mx1, 1)); \
          mx0 = fmaxf(mx0, __shfl_xor_sync(0xffffffffu, mx0, 2)); mx1 = fmaxf(mx1, __shfl_xor_sync(0xffffffffu, mx1, 2)); \
          const float n0 = fmaxf(c0, mx0 * SC), n1 = fmaxf(c1, mx1 * SC);                                              \
          const float a0 = ex2(c0 - n0), a1 = ex2(c1 - n1);                                                            \
          c0 = n0; c1 = n1;                                                                                            \
          l0 *= a0; l1 *= a1;                                                                                          \
          _Pragma("unroll") for (int i = 0; i < 24; i++) { o[4 * i] *= a0; o[4 * i + 1] *= a0; o[4 * i + 2] *= a1; o[4 * i + 3] *= a1; } \
          b0 = 0.f; b1 = 0.f;                                                                                          \
          _Pragma("unroll") for (int i = 0; i < 8; i++) {                                                              \
            const float e0 = ex2(fmaf(s[4 * i], SC, -c0)), e1 = ex2(fmaf(s[4 * i + 1], SC, -c0));                      \
            const float e2 = ex2(fmaf(s[4 * i + 2], SC, -c1)), e3 = ex2(fmaf(s[4 * i + 3], SC, -c1));                  \
            b0 += e0 + e1; b1 += e2 + e3;                                                                              \
            PN[2 * i] = pack_bf16(e0, e1); PN[2 * i + 1] = pack_bf16(e2, e3);                                          \
          }                                                                                                            \
        }                                                                                                              \
        l0 += b0; l1 += b1;                                                                                            \
      }
      for (int jj = 0; jj < 15; jj++) {
        A_STEP(p, p2, jj == 0)
        A_STEP(p2, p, false)
      }
      A_STEP(p, p2, false)
      TSA(item, 3);
      {
        const uint32_t sV = r.slot; mbar_wait(bar_full + 8 * sV, r.phase); r.adv(A_NSLOT);
        const uint64_t dv = mkdesc(sb + sV * A_SLOT, 8192, 1024);
        bar_sync(1 + w, 256);
        wg_fence();
#pragma unroll
        for (int kk = 0; kk < 4; kk++)
          wgmma_rs_n192<1>(o, p2[4 * kk], p2[4 * kk + 1], p2[4 * kk + 2], p2[4 * kk + 3], dv + kk * 128, 1);
        wg_commit();
        bar_arrive(1 + (w ^ 1), 256);
        wg_wait<0>();
        fence_regs(o);
        A_RELEASE(sV);
      }
      TSA(item, 4);
      l0 += __shfl_xor_sync(0xffffffffu, l0, 1); l1 += __shfl_xor_sync(0xffffffffu, l1, 1);
      l0 += __shfl_xor_sync(0xffffffffu, l0, 2); l1 += __shfl_xor_sync(0xffffffffu, l1, 2);
      const float i0 = 1.f / l0, i1 = 1.f / l1;
      bf16* orow = g_o + (size_t)(qtile * 128 + w * 64 + warp * 16 + (lane >> 2)) * HD_ + head * DH_ + (lane & 3) * 8;
#pragma unroll
      for (int g = 0; g < 6; g++) {
        uint32_t u0 = pack_bf16(o[16 * g + 0] * i0, o[16 * g + 1] * i0), u1 = pack_bf16(o[16 * g + 4] * i0, o[16 * g + 5] * i0);
        uint32_t u2 = pack_bf16(o[16 * g + 8] * i0, o[16 * g + 9] * i0), u3 = pack_bf16(o[16 * g + 12] * i0, o[16 * g + 13] * i0);
        quad_transpose(u0, u1, u2, u3, lane);
        *reinterpret_cast<uint4*>(orow + g * 32) = make_uint4(u0, u1, u2, u3);
        uint32_t v0 = pack_bf16(o[16 * g + 2] * i1, o[16 * g + 3] * i1), v1 = pack_bf16(o[16 * g + 6] * i1, o[16 * g + 7] * i1);
        uint32_t v2 = pack_bf16(o[16 * g + 10] * i1, o[16 * g + 11] * i1), v3 = pack_bf16(o[16 * g + 14] * i1, o[16 * g + 15] * i1);
        quad_transpose(v0, v1, v2, v3, lane);
        *reinterpret_cast<uint4*>(orow + (size_t)8 * HD_ + g * 32) = make_uint4(v0, v1, v2, v3);
      }
      TSA(item, 5);
    }
    if ((threadIdx.x & 127) == 0) TL_END(2);
    cluster_sync();
  }
}

constexpr int PREP_JOBS = 100 + 100 + 240 + 240;
__global__ void __launch_bounds__(256) prep_kernel(const bf16* __restrict__ w1, const bf16* __restrict__ w2,
                                                   const bf16* __restrict__ w3, const bf16* __restrict__ w4) {
  __shared__ __align__(16) bf16 tile[64][72];
  __shared__ float part[4][3][64];
  pdl_launch();
  pdl_wait();
  const int t = threadIdx.x;
  for (int job = blockIdx.x; job < PREP_JOBS; job += gridDim.x) {
    const bf16* src; bf16* dst; int ld, ldd, kt, nt, kind;
    if (job < 100) { src = w1; dst = g_w1t; ld = D_; ldd = D_; kt = job / 10; nt = job % 10; kind = 0; }
    else if (job < 200) { src = w2; dst = g_w2t; ld = D_; ldd = D_; kt = (job - 100) / 10; nt = (job - 100) % 10; kind = 1; }
    else if (job < 440) { src = w4; dst = g_w4t; ld = D_; ldd = F_; kt = (job - 200) / 10; nt = (job - 200) % 10; kind = 1; }
    else { src = w3; dst = nullptr; ld = F_; ldd = 0; kt = (job - 440) / 24; nt = (job - 440) % 24; kind = 2; }
    __syncthreads();
#pragma unroll
    for (int i = 0; i < 2; i++) {
      const int r = (t >> 3) + 32 * i, ch = t & 7;
      *reinterpret_cast<uint4*>(&tile[r][ch * 8]) = __ldg(reinterpret_cast<const uint4*>(src + (size_t)(kt * 64 + r) * ld + nt * 64 + ch * 8));
    }
    __syncthreads();
    if (kind != 2) {
#pragma unroll
      for (int i = 0; i < 2; i++) {
        const int n = (t >> 3) + 32 * i, ch = t & 7;
        uint32_t u[4];
#pragma unroll
        for (int e = 0; e < 4; e++) {
          const uint32_t lo = *reinterpret_cast<const uint16_t*>(&tile[ch * 8 + 2 * e][n]);
          const uint32_t hi = *reinterpret_cast<const uint16_t*>(&tile[ch * 8 + 2 * e + 1][n]);
          u[e] = lo | (hi << 16);
        }
        *reinterpret_cast<uint4*>(dst + (size_t)(nt * 64 + n) * ldd + kt * 64 + ch * 8) = make_uint4(u[0], u[1], u[2], u[3]);
      }
    }
    if (kind != 1) {
      const int n = t & 63, kq = t >> 6;
      float sa = 0.f, sb = 0.f, sc = 0.f;
#pragma unroll
      for (int e = 0; e < 16; e++) {
        const int k = kq * 16 + e;
        const float wv = __bfloat162float(tile[k][n]);
        sc += wv;
        if (kind == 0) { sa = fmaf(g_mod[4 * D_ + kt * 64 + k], wv, sa); sb = fmaf(g_mod[3 * D_ + kt * 64 + k], wv, sb); }
      }
      part[kq][0][n] = sa; part[kq][1][n] = sb; part[kq][2][n] = sc;
      __syncthreads();
      if (t < 192) {
        const int v = t >> 6, nn = t & 63;
        const float sum = part[0][v][nn] + part[1][v][nn] + part[2][v][nn] + part[3][v][nn];
        if (kind == 0) atomicAdd(&g_vec[v * D_ + nt * 64 + nn], sum);
        else if (v == 2) atomicAdd(&g_vec[3 * D_ + nt * 64 + nn], sum);
      }
    }
  }
}

constexpr int T_PAR = A_NSLOT * A_SLOT + 256;
constexpr int T_SMEM = T_PAR + 4096 + 1024;
enum { P_OGA = 0, P_OA = 80, P_OB = 160, P_VA = 240, P_VB = 320, P_VC = 400, P_A2 = 480, P_B2 = 560, P_GB = 640, P_CS3 = 720, P_SC = 912 };
enum { F_XCH = 0, F_XS = 256, F_US = 272, F_X1 = 288, F_G = 304 };

__device__ __forceinline__ unsigned ld_acquire(const unsigned* p) { unsigned v; asm volatile("ld.acquire.gpu.global.u32 %0, [%1];" : "=r"(v) : "l"(p) : "memory"); return v; }
__device__ __forceinline__ void flag_wait(const unsigned* p, unsigned target) {
  asm volatile(
      "{\n.reg .pred p;\n.reg .u32 n, v;\n"
      "mov.u32 n, 0;\n"
      "SPIN:\n"
      "ld.acquire.gpu.global.u32 v, [%0];\n"
      "setp.ge.u32 p, v, %1;\n"
      "@p bra DONE;\n"
      "add.u32 n, n, 1;\n"
      "setp.gt.u32 p, n, 4194304;\n"
      "@p trap;\n"
      "bra SPIN;\n"
      "DONE:\n}\n" :: "l"(p), "r"(target) : "memory");
}
__device__ __forceinline__ void fence_async_global() { asm volatile("fence.proxy.async.global;" ::: "memory"); }
__device__ __forceinline__ void wg_signal(unsigned* flag, int w) {
  fence_async_global();
  bar_sync(3 + w, 128);
  if ((threadIdx.x & 127) == 0) {
    __threadfence();
    asm volatile("red.relaxed.gpu.global.add.u32 [%0], 1;" :: "l"(flag) : "memory");
  }
}
__device__ __forceinline__ float lds_f(uint32_t a) { float v; asm volatile("ld.shared.f32 %0, [%1];" : "=f"(v) : "r"(a)); return v; }
__device__ __forceinline__ float2 lds_f2(uint32_t a) { float2 v; asm volatile("ld.shared.v2.f32 {%0, %1}, [%2];" : "=f"(v.x), "=f"(v.y) : "r"(a)); return v; }
__device__ __forceinline__ uint4 ldcg4(const void* p) { return __ldcg(reinterpret_cast<const uint4*>(p)); }

__device__ __forceinline__ const bf16* frag80_ptr(const bf16* base_row_g, int ld, int lane, int piece) {
  const int q = lane & 3;
  if (piece < 2) return base_row_g + piece * 32 + q * 8;
  if (piece < 4) return base_row_g + (size_t)8 * ld + (piece - 2) * 32 + q * 8;
  return base_row_g + (size_t)(q >> 1) * 8 * ld + 64 + (q & 1) * 8;
}
__device__ __forceinline__ void frag80_load(uint4 (&v)[5], const bf16* base_row_g, int ld, int lane) {
#pragma unroll
  for (int i = 0; i < 5; i++) v[i] = ldcg4(frag80_ptr(base_row_g, ld, lane, i));
}
__device__ __forceinline__ void frag80_unpack(uint4 (&v)[5], uint32_t (&u)[20], int lane) {
#pragma unroll
  for (int i = 0; i < 5; i++) quad_transpose(v[i].x, v[i].y, v[i].z, v[i].w, lane);
#pragma unroll
  for (int i = 0; i < 2; i++) {
    u[2 * (4 * i + 0)] = v[i].x; u[2 * (4 * i + 1)] = v[i].y; u[2 * (4 * i + 2)] = v[i].z; u[2 * (4 * i + 3)] = v[i].w;
    u[2 * (4 * i + 0) + 1] = v[2 + i].x; u[2 * (4 * i + 1) + 1] = v[2 + i].y; u[2 * (4 * i + 2) + 1] = v[2 + i].z; u[2 * (4 * i + 3) + 1] = v[2 + i].w;
  }
  u[16] = v[4].x; u[18] = v[4].y; u[17] = v[4].z; u[19] = v[4].w;
}
__device__ __forceinline__ void frag80_store(const uint32_t (&u)[20], bf16* base_row_g, int ld, int lane, int rows_ok) {
  uint4 v[5];
#pragma unroll
  for (int i = 0; i < 2; i++) {
    v[i] = make_uint4(u[2 * (4 * i + 0)], u[2 * (4 * i + 1)], u[2 * (4 * i + 2)], u[2 * (4 * i + 3)]);
    v[2 + i] = make_uint4(u[2 * (4 * i + 0) + 1], u[2 * (4 * i + 1) + 1], u[2 * (4 * i + 2) + 1], u[2 * (4 * i + 3) + 1]);
  }
  v[4] = make_uint4(u[16], u[18], u[17], u[19]);
#pragma unroll
  for (int i = 0; i < 5; i++) {
    quad_transpose(v[i].x, v[i].y, v[i].z, v[i].w, lane);
    const int hrow = (i < 2) ? 0 : (i < 4) ? 1 : ((lane & 3) >> 1);
    if ((rows_ok >> hrow) & 1) *reinterpret_cast<uint4*>(const_cast<bf16*>(frag80_ptr(base_row_g, ld, lane, i))) = v[i];
  }
}
__device__ __forceinline__ float quad_sum(float v) {
  v += __shfl_xor_sync(0xffffffffu, v, 1);
  v += __shfl_xor_sync(0xffffffffu, v, 2);
  return v;
}

struct TailMaps { CUtensorMap o, wo3, wo2, xs, w1t, us, w2t, x1, w3, g, w4t; };

struct Rings {
  uint32_t a, b, par;
  __device__ __forceinline__ uint32_t nextA() { uint32_t s = 5 + a; a = (a + 1) & 3; return s; }
  __device__ __forceinline__ uint32_t nextB() { uint32_t s = b; b = (b == 4) ? 0 : b + 1; return s; }
  __device__ __forceinline__ uint32_t take(uint32_t s) { uint32_t p = (par >> s) & 1; par ^= 1u << s; return p; }
};

__global__ void __cluster_dims__(2, 1, 1) __launch_bounds__(384, 1)
tail_kernel(const __grid_constant__ TailMaps tm, const bf16* __restrict__ x, bf16* __restrict__ out) {
  extern __shared__ uint8_t smem_raw[];
  const uint32_t sb = (smem_u32(smem_raw) + 1023) & ~1023u;
  TL_ENTRY(3);
  const uint32_t bar_full = sb + A_NSLOT * A_SLOT;
  const uint32_t bar_empty = bar_full + 8 * A_NSLOT;
  const uint32_t par = sb + T_PAR;
  float* parf = reinterpret_cast<float*>(smem_raw + (par - smem_u32(smem_raw)));
  uint32_t rank;
  asm volatile("mov.u32 %0, %%cluster_ctarank;" : "=r"(rank));
  const int cid = blockIdx.x >> 1;
  const int wg = threadIdx.x >> 7;
  const int o_qt = (cid & 7) * 2 + rank, o_nh = (cid >> 3) & 1, o_ks = cid >> 4;
  const int o_col = o_nh * 320 + o_ks * 80;
  const int qt = cid >> 2, js = (cid & 3) * 2 + rank;
  if (threadIdx.x == 0) {
    for (int i = 0; i < A_NSLOT; i++) { mbar_init(bar_full + 8 * i, 1); mbar_init(bar_empty + 8 * i, 16); }
    asm volatile("fence.mbarrier_init.release.cluster;" ::: "memory");
  }
  __syncthreads();
  cluster_sync();
  pdl_launch();

  if (wg == 0) {
    asm volatile("setmaxnreg.dec.sync.aligned.u32 24;");
    if (threadIdx.x == 0) {
      Rings r{0, 0, 0x1ff};
#define T_ACQ(s_, bytes_) do { mbar_wait(bar_empty + 8 * (s_), r.take(s_)); mbar_expect(bar_full + 8 * (s_), bytes_); } while (0)
      for (int kb = 0; kb < 24; kb++) {
        const int kcol = ((kb / 6) * 8 + 2 * o_ks + (kb % 6) / 3) * DH_ + (kb % 3) * 64;
        uint32_t s = (kb % 3) * 3; T_ACQ(s, 24576);
        if (rank == 0) tma3d_mc(sb + s * A_SLOT, &tm.wo3, bar_full + 8 * s, 0, kcol, o_nh * 5, 3);
        s++; T_ACQ(s, 16384);
        if (rank == 1) tma3d_mc(sb + s * A_SLOT, &tm.wo2, bar_full + 8 * s, 0, kcol, o_nh * 5 + 3, 3);
        if (kb == 0) { pdl_wait(); TL_WAITED(3); }
        s++; T_ACQ(s, 16384);
        tma2d(sb + s * A_SLOT, &tm.o, bar_full + 8 * s, kcol, o_qt * 128);
      }
#pragma unroll 1
      for (int ph = 0; ph < 4; ph++) {
        const CUtensorMap* ma = ph == 0 ? &tm.xs : ph == 1 ? &tm.us : ph == 2 ? &tm.x1 : &tm.g;
        const CUtensorMap* mb = ph == 0 ? &tm.w1t : ph == 1 ? &tm.w2t : ph == 2 ? &tm.w3 : &tm.w4t;
        const int nkb = ph == 3 ? 24 : 10;
        const int nbl = ph == 2 ? 10 : nkb / 2;
        int bl = 0;
        for (; bl < 5; bl++) {
          const uint32_t s = r.nextB();
          if (ph == 2) { T_ACQ(s, 24576); tma3d(sb + s * A_SLOT, mb, bar_full + 8 * s, 0, bl * 64, js * 3); }
          else { T_ACQ(s, 20480); tma3d(sb + s * A_SLOT, mb, bar_full + 8 * s, 0, js * 80, bl * 2); }
        }
        const unsigned* fl = g_flag + F_XS + 16 * ph;
        flag_wait(fl + qt, 16);
        if (ph == 1) { if (qt > 0) flag_wait(fl + qt - 1, 16); if (qt < 15) flag_wait(fl + qt + 1, 16); }
        fence_async_global();
        for (int kb = 0; kb < nkb; kb++) {
          const uint32_t s = r.nextA(); T_ACQ(s, 16384);
          asm volatile("cp.async.bulk.tensor.2d.shared::cluster.global.mbarrier::complete_tx::bytes.multicast::cluster [%0], [%1, {%3, %4}], [%2], %5;"
                       :: "r"(sb + s * A_SLOT + rank * 8192), "l"(ma), "r"(bar_full + 8 * s), "r"(kb * 64), "r"(qt * 128 + (int)rank * 64), "h"((uint16_t)3) : "memory");
          if (bl < nbl && kb >= (ph == 2 ? bl - 2 : 2 * bl - 6)) {
            const uint32_t s2 = r.nextB();
            if (ph == 2) { T_ACQ(s2, 24576); tma3d(sb + s2 * A_SLOT, mb, bar_full + 8 * s2, 0, bl * 64, js * 3); }
            else { T_ACQ(s2, 20480); tma3d(sb + s2 * A_SLOT, mb, bar_full + 8 * s2, 0, js * 80, bl * 2); }
            bl++;
          }
        }
      }
    }
    __syncwarp();
    cluster_sync();
  } else {
    asm volatile("setmaxnreg.inc.sync.aligned.u32 240;");
    const int w = wg - 1, lane = threadIdx.x & 31, warp = (threadIdx.x >> 5) & 3, tid = threadIdx.x - 128;
    const uint32_t rel_base = mapa(bar_empty, (lane == 0) ? rank : (rank ^ 1));
    Rings r{0, 0, 0};
#define T_WAIT(s_) mbar_wait(bar_full + 8 * (s_), r.take(s_))
    pdl_wait();
    if (tid < 80) {
      parf[P_OGA + tid] = g_mod[2 * D_ + o_col + tid]; parf[P_OA + tid] = g_mod[4 * D_ + o_col + tid]; parf[P_OB + tid] = g_mod[3 * D_ + o_col + tid];
      parf[P_VA + tid] = g_vec[js * 80 + tid]; parf[P_VB + tid] = g_vec[D_ + js * 80 + tid]; parf[P_VC + tid] = g_vec[2 * D_ + js * 80 + tid];
      parf[P_A2 + tid] = g_mod[4 * D_ + js * 80 + tid]; parf[P_B2 + tid] = g_mod[3 * D_ + js * 80 + tid]; parf[P_GB + tid] = g_mod[5 * D_ + js * 80 + tid];
    }
    if (tid < 192) parf[P_CS3 + tid] = g_vec[3 * D_ + js * 192 + tid];
    if (tid >= 224) {
      float sa = 0.f, saa = 0.f, sab = 0.f, sbb = 0.f, sb1 = 0.f;
      for (int i = lane; i < D_; i += 32) {
        const float a = g_mod[4 * D_ + i], b = g_mod[3 * D_ + i];
        sa += a; saa = fmaf(a, a, saa); sab = fmaf(a, b, sab); sb1 += b; sbb = fmaf(b, b, sbb);
      }
      sa = warp_sum(sa); saa = warp_sum(saa); sab = warp_sum(sab); sb1 = warp_sum(sb1); sbb = warp_sum(sbb);
      if (lane == 0) { parf[P_SC] = sa; parf[P_SC + 1] = saa; parf[P_SC + 2] = sab; parf[P_SC + 3] = sb1; parf[P_SC + 4] = sbb; }
    }
    bar_sync(5, 256);
    const int rl = w * 64 + warp * 16 + (lane >> 2);
    const uint32_t pcol = par + (lane & 3) * 8;

    {
      float acc1[96], acc2[64];
      uint32_t p0 = 0, p1 = 0, p2 = 0;
      for (int kb = 0; kb < 24; kb++) {
        const uint32_t s1 = (kb % 3) * 3, s2 = s1 + 1, sa = s1 + 2;
        T_WAIT(s1); T_WAIT(s2); T_WAIT(sa);
        const uint64_t da = mkdesc(sb + sa * A_SLOT + w * 8192, 16, 1024);
        const uint64_t d1 = mkdesc(sb + s1 * A_SLOT, 8192, 1024), d2 = mkdesc(sb + s2 * A_SLOT, 8192, 1024);
        wg_fence();
#pragma unroll
        for (int kk = 0; kk < 4; kk++) {
          wgmma_ss_n192<1>(acc1, da + kk * 2, d1 + kk * 128, (kb | kk) != 0);
          wgmma_ss_n128<1>(acc2, da + kk * 2, d2 + kk * 128, (kb | kk) != 0);
        }
        wg_commit();
        if (kb > 0) { wg_wait<1>(); A_RELEASE(p0); A_RELEASE(p1); A_RELEASE(p2); }
        p0 = s1; p1 = s2; p2 = sa;
      }
      uint4 xv[5];
      const bf16* xrow = x + (size_t)(o_qt * 128 + rl) * D_ + o_col;
      frag80_load(xv, xrow, D_, lane);
      wg_wait<0>();
      fence_regs(acc1); fence_regs(acc2);
      A_RELEASE(p0); A_RELEASE(p1); A_RELEASE(p2);
      TS(0, 0);
      uint4* xb = g_xch + (size_t)((o_qt * 2 + o_nh) * 4) * (4 * 5 * 256);
#pragma unroll
      for (int d = 0; d < 4; d++) {
        uint32_t u[20];
#pragma unroll
        for (int i = 0; i < 20; i++) {
          const int e = d * 40 + 2 * i;
          u[i] = (e < 96) ? pack_bf16(acc1[e < 96 ? e : 0], acc1[e < 96 ? e + 1 : 0]) : pack_bf16(acc2[e >= 96 ? e - 96 : 0], acc2[e >= 96 ? e - 95 : 0]);
        }
#pragma unroll
        for (int i = 0; i < 5; i++) xb[((d * 4 + o_ks) * 5 + i) * 256 + tid] = make_uint4(u[4 * i], u[4 * i + 1], u[4 * i + 2], u[4 * i + 3]);
      }
      bar_sync(3 + w, 128);
      unsigned* xf = g_flag + F_XCH + ((o_qt * 2 + o_nh) * 4) * 2 + w;
      if ((tid & 127) < 4) {
        __threadfence();
        asm volatile("red.relaxed.gpu.global.add.u32 [%0], 1;" :: "l"(xf + (tid & 3) * 2) : "memory");
      }
      uint32_t xu[20];
      frag80_unpack(xv, xu, lane);
      if ((tid & 127) == 0) flag_wait(xf + o_ks * 2, 4);
      bar_sync(3 + w, 128);
      float at[40];
#pragma unroll
      for (int i = 0; i < 40; i++) at[i] = 0.f;
#pragma unroll
      for (int sc = 0; sc < 4; sc++) {
        uint4 v[5];
#pragma unroll
        for (int i = 0; i < 5; i++) v[i] = ldcg4(xb + ((o_ks * 4 + sc) * 5 + i) * 256 + tid);
#pragma unroll
        for (int i = 0; i < 5; i++) {
          at[8 * i] += bf_lo(v[i].x); at[8 * i + 1] += bf_hi(v[i].x); at[8 * i + 2] += bf_lo(v[i].y); at[8 * i + 3] += bf_hi(v[i].y);
          at[8 * i + 4] += bf_lo(v[i].z); at[8 * i + 5] += bf_hi(v[i].z); at[8 * i + 6] += bf_lo(v[i].w); at[8 * i + 7] += bf_hi(v[i].w);
        }
      }
      TS(0, 1);
      float st[2][6];
#pragma unroll
      for (int h = 0; h < 2; h++)
#pragma unroll
        for (int i = 0; i < 6; i++) st[h][i] = 0.f;
      uint32_t ua[20], us[20];
#pragma unroll
      for (int nb = 0; nb < 10; nb++) {
        const float2 ga = lds_f2(pcol + (P_OGA + 8 * nb) * 4), a = lds_f2(pcol + (P_OA + 8 * nb) * 4), b = lds_f2(pcol + (P_OB + 8 * nb) * 4);
#pragma unroll
        for (int h = 0; h < 2; h++) {
          const uint32_t pk = pack_bf16(fmaf(ga.x, at[4 * nb + 2 * h], bf_lo(xu[2 * nb + h])), fmaf(ga.y, at[4 * nb + 2 * h + 1], bf_hi(xu[2 * nb + h])));
          ua[2 * nb + h] = pk;
          const float v0 = bf_lo(pk), v1 = bf_hi(pk);
          const float y0 = a.x * v0, y1 = a.y * v1;
          us[2 * nb + h] = pack_bf16(y0, y1);
          st[h][0] += v0 + v1; st[h][1] = fmaf(v0, v0, fmaf(v1, v1, st[h][1]));
          st[h][2] += y0 + y1; st[h][3] = fmaf(a.x, y0, fmaf(a.y, y1, st[h][3]));
          st[h][4] = fmaf(y0, y0, fmaf(y1, y1, st[h][4])); st[h][5] = fmaf(b.x, y0, fmaf(b.y, y1, st[h][5]));
        }
      }
      frag80_store(us, g_xs + (size_t)(o_qt * 128 + rl) * D_ + o_col, D_, lane, 3);
      frag80_store(ua, g_xa + (size_t)(o_qt * 128 + rl) * D_ + o_col, D_, lane, 3);
#pragma unroll
      for (int h = 0; h < 2; h++)
#pragma unroll
        for (int i = 0; i < 6; i++) st[h][i] = quad_sum(st[h][i]);
      if ((lane & 3) < 2) {
        const int h = lane & 1;
        float* sp = g_st1 + (size_t)(o_qt * 128 + rl + 8 * h) * 8;
        const float s0 = h ? st[1][0] : st[0][0], s1 = h ? st[1][1] : st[0][1], s2 = h ? st[1][2] : st[0][2];
        const float s3 = h ? st[1][3] : st[0][3], s4 = h ? st[1][4] : st[0][4], s5 = h ? st[1][5] : st[0][5];
        asm volatile("red.global.add.v4.f32 [%0], {%1, %2, %3, %4};" :: "l"(sp), "f"(s0), "f"(s1), "f"(s2), "f"(s3) : "memory");
        asm volatile("red.global.add.v2.f32 [%0], {%1, %2};" :: "l"(sp + 4), "f"(s4), "f"(s5) : "memory");
      }
      wg_signal(g_flag + F_XS + o_qt, w);
      TS(0, 2);
    }

    const int grow = qt * 128 + rl;
#define T_GEMM80(ACC, NKB)                                                                                             \
    {                                                                                                                  \
      uint32_t pa = 0, pb = 0, sbq = 0;                                                                                \
      for (int kb = 0; kb < (NKB); kb++) {                                                                             \
        if (!(kb & 1)) { sbq = r.nextB(); T_WAIT(sbq); }                                                               \
        const uint32_t sa = r.nextA(); T_WAIT(sa);                                                                     \
        const uint64_t da = mkdesc(sb + sa * A_SLOT + w * 8192, 16, 1024);                                             \
        const uint64_t db = mkdesc(sb + sbq * A_SLOT + (kb & 1) * 10240, 16, 1024);                                    \
        wg_fence();                                                                                                    \
        _Pragma("unroll") for (int kk = 0; kk < 4; kk++) wgmma_ss_n80<0>(ACC, da + kk * 2, db + kk * 2, (kb | kk) != 0); \
        wg_commit();                                                                                                   \
        if (kb > 0) { wg_wait<1>(); A_RELEASE(pa); if (!(kb & 1)) A_RELEASE(pb); }                                     \
        pa = sa; pb = sbq;                                                                                             \
      }                                                                                                                \
      wg_wait<0>();                                                                                                    \
      fence_regs(ACC);                                                                                                 \
      A_RELEASE(pa); A_RELEASE(pb);                                                                                    \
    }

    float mu[2], rs[2];
    {
      float acc[40];
      T_GEMM80(acc, 10)
      TS(1, 0);
      float al[2], be[2], ga2[2], de[2];
#pragma unroll
      for (int h = 0; h < 2; h++) {
        const float4 s03 = __ldcg(reinterpret_cast<const float4*>(g_st1 + (size_t)(grow + 8 * h) * 8));
        const float2 s45 = __ldcg(reinterpret_cast<const float2*>(g_st1 + (size_t)(grow + 8 * h) * 8 + 4));
        const float m = s03.x * (1.f / D_);
        const float rr = rsqrtf(fmaxf(s03.y * (1.f / D_) - m * m, 0.f) + LN_EPS);
        mu[h] = m; rs[h] = rr;
        const float sa = lds_f(par + P_SC * 4), saa = lds_f(par + (P_SC + 1) * 4), sab = lds_f(par + (P_SC + 2) * 4);
        const float sb1 = lds_f(par + (P_SC + 3) * 4), sbb = lds_f(par + (P_SC + 4) * 4);
        const float m2 = (rr * (s03.z - m * sa) + sb1) * (1.f / D_);
        const float e2 = (rr * rr * (s45.x - 2.f * m * s03.w + m * m * saa) + 2.f * rr * (s45.y - m * sab) + sbb) * (1.f / D_);
        const float r2 = rsqrtf(fmaxf(e2 - m2 * m2, 0.f) + LN_EPS);
        al[h] = r2 * rr; be[h] = -r2 * rr * m; ga2[h] = r2; de[h] = -r2 * m2;
      }
      uint32_t u[20];
#pragma unroll
      for (int nb = 0; nb < 10; nb++) {
        const float2 va = lds_f2(pcol + (P_VA + 8 * nb) * 4), vb = lds_f2(pcol + (P_VB + 8 * nb) * 4), vc = lds_f2(pcol + (P_VC + 8 * nb) * 4);
#pragma unroll
        for (int h = 0; h < 2; h++) {
          const float z0 = fmaf(al[h], acc[4 * nb + 2 * h], fmaf(be[h], va.x, fmaf(ga2[h], vb.x, de[h] * vc.x)));
          const float z1 = fmaf(al[h], acc[4 * nb + 2 * h + 1], fmaf(be[h], va.y, fmaf(ga2[h], vb.y, de[h] * vc.y)));
          u[2 * nb + h] = pack_bf16(gelu_tanh(z0), gelu_tanh(z1));
        }
      }
      const int grp = js >> 1;
      const int sh = (grp == 0) ? 1 : (grp == 1) ? -1 : (grp == 2) ? 2 : -2;
      const int d0 = grow + sh, d1 = grow + 8 + sh;
      frag80_store(u, g_us + (ptrdiff_t)d0 * D_ + js * 80, D_, lane, (d0 >= 0 ? 1 : 0) | (d1 < S_ ? 2 : 0));
      if (sh > 0 ? (grow < sh) : (grow + 8 >= S_ + sh)) {
        bf16* zr = g_us + (size_t)(sh > 0 ? grow : grow + 8) * D_ + js * 80 + (lane & 3) * 8;
        *reinterpret_cast<uint4*>(zr) = make_uint4(0, 0, 0, 0);
        *reinterpret_cast<uint4*>(zr + 32) = make_uint4(0, 0, 0, 0);
        if ((lane & 3) < 2) *reinterpret_cast<uint4*>(zr + 64) = make_uint4(0, 0, 0, 0);
      }
      wg_signal(g_flag + F_US + qt, w);
      TS(1, 1);
    }
    uint32_t xau[20], x1u[20];
    {
      uint4 xv[5];
      frag80_load(xv, g_xa + (size_t)grow * D_ + js * 80, D_, lane);
      float acc[40];
      T_GEMM80(acc, 10)
      TS(2, 0);
      frag80_unpack(xv, xau, lane);
      float s1[2] = {0.f, 0.f}, s2[2] = {0.f, 0.f};
#pragma unroll
      for (int nb = 0; nb < 10; nb++) {
        const float2 a = lds_f2(pcol + (P_A2 + 8 * nb) * 4), b = lds_f2(pcol + (P_B2 + 8 * nb) * 4);
#pragma unroll
        for (int h = 0; h < 2; h++) {
          const float h0 = fmaf(a.x * rs[h], bf_lo(xau[2 * nb + h]) - mu[h], b.x), h1 = fmaf(a.y * rs[h], bf_hi(xau[2 * nb + h]) - mu[h], b.y);
          const uint32_t pk = pack_bf16(h0 + acc[4 * nb + 2 * h], h1 + acc[4 * nb + 2 * h + 1]);
          x1u[2 * nb + h] = pk;
          const float v0 = bf_lo(pk), v1 = bf_hi(pk);
          s1[h] += v0 + v1; s2[h] = fmaf(v0, v0, fmaf(v1, v1, s2[h]));
        }
      }
      frag80_store(x1u, g_x1 + (size_t)grow * D_ + js * 80, D_, lane, 3);
      s1[0] = quad_sum(s1[0]); s1[1] = quad_sum(s1[1]); s2[0] = quad_sum(s2[0]); s2[1] = quad_sum(s2[1]);
      if ((lane & 3) < 2) {
        const int h = lane & 1;
        asm volatile("red.global.add.v2.f32 [%0], {%1, %2};" :: "l"(g_st2 + (size_t)(grow + 8 * h) * 2), "f"(h ? s1[1] : s1[0]), "f"(h ? s2[1] : s2[0]) : "memory");
      }
      wg_signal(g_flag + F_X1 + qt, w);
      TS(2, 1);
    }
    {
      float acc[96];
      uint32_t pa = 0, pb = 0;
      for (int kb = 0; kb < 10; kb++) {
        const uint32_t s1 = r.nextB(), sa = r.nextA();
        T_WAIT(s1); T_WAIT(sa);
        const uint64_t da = mkdesc(sb + sa * A_SLOT + w * 8192, 16, 1024);
        const uint64_t d1 = mkdesc(sb + s1 * A_SLOT, 8192, 1024);
        wg_fence();
#pragma unroll
        for (int kk = 0; kk < 4; kk++) wgmma_ss_n192<1>(acc, da + kk * 2, d1 + kk * 128, (kb | kk) != 0);
        wg_commit();
        if (kb > 0) { wg_wait<1>(); A_RELEASE(pa); A_RELEASE(pb); }
        pa = sa; pb = s1;
      }
      const float2 q0 = __ldcg(reinterpret_cast<const float2*>(g_st2 + (size_t)grow * 2));
      const float2 q1 = __ldcg(reinterpret_cast<const float2*>(g_st2 + (size_t)(grow + 8) * 2));
      wg_wait<0>();
      fence_regs(acc);
      A_RELEASE(pa); A_RELEASE(pb);
      TS(3, 0);
      const float m0 = q0.x * (1.f / D_), m1 = q1.x * (1.f / D_);
      const float r0 = rsqrtf(fmaxf(q0.y * (1.f / D_) - m0 * m0, 0.f) + LN_EPS), r1 = rsqrtf(fmaxf(q1.y * (1.f / D_) - m1 * m1, 0.f) + LN_EPS);
      const float n0 = -r0 * m0, n1 = -r1 * m1;
      bf16* grow_p = g_g + (size_t)grow * F_ + js * 192 + (lane & 3) * 8;
#pragma unroll
      for (int gq = 0; gq < 6; gq++) {
        uint32_t u[4], v[4];
#pragma unroll
        for (int i = 0; i < 4; i++) {
          const int nb = gq * 4 + i;
          const float2 cs = lds_f2(pcol + (P_CS3 + 8 * nb) * 4);
          u[i] = pack_bf16(gelu_tanh(fmaf(r0, acc[4 * nb], n0 * cs.x)), gelu_tanh(fmaf(r0, acc[4 * nb + 1], n0 * cs.y)));
          v[i] = pack_bf16(gelu_tanh(fmaf(r1, acc[4 * nb + 2], n1 * cs.x)), gelu_tanh(fmaf(r1, acc[4 * nb + 3], n1 * cs.y)));
        }
        quad_transpose(u[0], u[1], u[2], u[3], lane);
        *reinterpret_cast<uint4*>(grow_p + gq * 32) = make_uint4(u[0], u[1], u[2], u[3]);
        quad_transpose(v[0], v[1], v[2], v[3], lane);
        *reinterpret_cast<uint4*>(grow_p + (size_t)8 * F_ + gq * 32) = make_uint4(v[0], v[1], v[2], v[3]);
      }
      wg_signal(g_flag + F_G + qt, w);
      TS(3, 1);
    }
    {
      float acc[40];
      T_GEMM80(acc, 24)
      TS(1, 2);
      uint32_t u[20];
#pragma unroll
      for (int nb = 0; nb < 10; nb++) {
        const float2 gb = lds_f2(pcol + (P_GB + 8 * nb) * 4);
#pragma unroll
        for (int h = 0; h < 2; h++)
          u[2 * nb + h] = pack_bf16(fmaf(gb.x, bf_lo(x1u[2 * nb + h]) + acc[4 * nb + 2 * h], bf_lo(xau[2 * nb + h])),
                                    fmaf(gb.y, bf_hi(x1u[2 * nb + h]) + acc[4 * nb + 2 * h + 1], bf_hi(xau[2 * nb + h])));
      }
      frag80_store(u, out + (size_t)grow * D_ + js * 80, D_, lane, 3);
      TS(1, 3);
    }
    if ((threadIdx.x & 127) == 0) TL_END(3);
    cluster_sync();
  }
}

typedef CUresult (*EncFn)(CUtensorMap*, CUtensorMapDataType, cuuint32_t, void*, const cuuint64_t*, const cuuint64_t*,
                          const cuuint32_t*, const cuuint32_t*, CUtensorMapInterleave, CUtensorMapSwizzle,
                          CUtensorMapL2promotion, CUtensorMapFloatOOBfill);
static EncFn g_enc = nullptr;

static CUtensorMap map2d(const void* p, uint64_t rows, uint64_t cols, uint32_t box_rows) {
  CUtensorMap m;
  cuuint64_t gd[2] = {cols, rows}; cuuint64_t gs[1] = {cols * 2};
  cuuint32_t bx[2] = {64, box_rows}; cuuint32_t es[2] = {1, 1};
  g_enc(&m, CU_TENSOR_MAP_DATA_TYPE_BFLOAT16, 2, const_cast<void*>(p), gd, gs, bx, es, CU_TENSOR_MAP_INTERLEAVE_NONE,
        CU_TENSOR_MAP_SWIZZLE_128B, CU_TENSOR_MAP_L2_PROMOTION_L2_256B, CU_TENSOR_MAP_FLOAT_OOB_FILL_NONE);
  return m;
}
static CUtensorMap map3d(const void* p, uint64_t rows, uint64_t cols, uint32_t box_rows, uint32_t nblk) {
  CUtensorMap m;
  cuuint64_t gd[3] = {64, rows, cols / 64}; cuuint64_t gs[2] = {cols * 2, 128};
  cuuint32_t bx[3] = {64, box_rows, nblk}; cuuint32_t es[3] = {1, 1, 1};
  g_enc(&m, CU_TENSOR_MAP_DATA_TYPE_BFLOAT16, 3, const_cast<void*>(p), gd, gs, bx, es, CU_TENSOR_MAP_INTERLEAVE_NONE,
        CU_TENSOR_MAP_SWIZZLE_128B, CU_TENSOR_MAP_L2_PROMOTION_L2_256B, CU_TENSOR_MAP_FLOAT_OOB_FILL_NONE);
  return m;
}

template <typename... KArgs, typename... Args>
static void launch(void (*kern)(KArgs...), dim3 grid, dim3 block, int smem, bool pdl, Args... args) {
  cudaLaunchConfig_t cfg = {};
  cfg.gridDim = grid; cfg.blockDim = block; cfg.dynamicSmemBytes = smem; cfg.stream = cudaStreamPerThread;
  cudaLaunchAttribute at[1];
  at[0].id = cudaLaunchAttributeProgrammaticStreamSerialization;
  at[0].val.programmaticStreamSerializationAllowed = 1;
  cfg.attrs = at; cfg.numAttrs = pdl ? 1 : 0;
  cudaLaunchKernelEx(&cfg, kern, KArgs(args)...);
}

extern "C" void kernel_launch(void* const* d_in, const int* in_sizes, int n_in, void* d_out, int out_size) {
  const bf16* x = (const bf16*)d_in[0];
  const bf16* kc = (const bf16*)d_in[1];
  const bf16* vc = (const bf16*)d_in[2];
  const bf16* wq = (const bf16*)d_in[3];
  const bf16* wo = (const bf16*)d_in[4];
  const bf16* w1 = (const bf16*)d_in[6];
  const bf16* w2 = (const bf16*)d_in[7];
  const bf16* w3 = (const bf16*)d_in[8];
  const bf16* w4 = (const bf16*)d_in[9];
  const bf16* c = (const bf16*)d_in[10];
  const bf16* wmod = (const bf16*)d_in[11];
  bf16* out = (bf16*)d_out;

  static void *p_h, *p_o, *p_xs, *p_us, *p_x1, *p_g, *p_w1t, *p_w2t, *p_w4t;
  if (!g_enc) {
    void* fn = nullptr; cudaDriverEntryPointQueryResult qr;
    cudaGetDriverEntryPoint("cuTensorMapEncodeTiled", &fn, cudaEnableDefault, &qr);
    g_enc = (EncFn)fn;
    cudaGetSymbolAddress(&p_h, g_h); cudaGetSymbolAddress(&p_o, g_o); cudaGetSymbolAddress(&p_xs, g_xs);
    cudaGetSymbolAddress(&p_us, g_us); cudaGetSymbolAddress(&p_x1, g_x1); cudaGetSymbolAddress(&p_g, g_g);
    cudaGetSymbolAddress(&p_w1t, g_w1t); cudaGetSymbolAddress(&p_w2t, g_w2t); cudaGetSymbolAddress(&p_w4t, g_w4t);
    cudaFuncSetAttribute(attn_kernel, cudaFuncAttributeMaxDynamicSharedMemorySize, A_SMEM);
    cudaFuncSetAttribute(tail_kernel, cudaFuncAttributeMaxDynamicSharedMemorySize, T_SMEM);
  }
  const CUtensorMap tm_h = map2d(p_h, S_, D_, 128);
  const CUtensorMap tm_wq = map3d(wq, D_, HD_, 64, 3);
  const CUtensorMap tm_k = map3d(kc, (uint64_t)H_ * S_, DH_, 64, 3);
  const CUtensorMap tm_v = map3d(vc, (uint64_t)H_ * S_, DH_, 64, 3);
  TailMaps tm;
  tm.o = map2d(p_o, S_, HD_, 128);
  tm.wo3 = map3d(wo, HD_, D_, 64, 3);
  tm.wo2 = map3d(wo, HD_, D_, 64, 2);
  tm.xs = map2d(p_xs, S_, D_, 64);
  tm.w1t = map3d(p_w1t, D_, D_, 80, 2);
  tm.us = map2d(p_us, S_, D_, 64);
  tm.w2t = map3d(p_w2t, D_, D_, 80, 2);
  tm.x1 = map2d(p_x1, S_, D_, 64);
  tm.w3 = map3d(w3, D_, F_, 64, 3);
  tm.g = map2d(p_g, S_, F_, 64);
  tm.w4t = map3d(p_w4t, D_, F_, 80, 2);

  const bool PDL = true;
  launch(mod_kernel, dim3(120), dim3(256), 0, false, c, wmod);
  launch(prep_kernel, dim3(PREP_JOBS), dim3(256), 0, PDL, w1, w2, w3, w4);
  launch(ln1_kernel, dim3(256), dim3(256), 0, PDL, x);
  launch(attn_kernel, dim3(128), dim3(384), A_SMEM, PDL, tm_h, tm_wq, tm_k, tm_v);
  launch(tail_kernel, dim3(128), dim3(384), T_SMEM, PDL, tm, x, out);
}
```

```cpp
#include <cuda_runtime.h>
#include <cuda.h>
#include <cuda_bf16.h>
#include <stdint.h>

typedef __nv_bfloat16 bf16;

constexpr int S_  = 2048;
constexpr int D_  = 640;
constexpr int H_  = 32;
constexpr int DH_ = 192;
constexpr int HD_ = H_ * DH_;
constexpr int F_  = 1536;
constexpr float LN_EPS = 1e-5f;

__device__ __forceinline__ uint32_t smem_u32(const void* p) { return (uint32_t)__cvta_generic_to_shared(p); }
__device__ __forceinline__ void mbar_init(uint32_t a, uint32_t c) { asm volatile("mbarrier.init.shared::cta.b64 [%0], %1;" :: "r"(a), "r"(c) : "memory"); }
__device__ __forceinline__ void mbar_expect(uint32_t a, uint32_t b) { asm volatile("mbarrier.arrive.expect_tx.shared::cta.b64 _, [%0], %1;" :: "r"(a), "r"(b) : "memory"); }
__device__ __forceinline__ void mbar_arrive(uint32_t a) { asm volatile("mbarrier.arrive.shared::cta.b64 _, [%0];" :: "r"(a) : "memory"); }
__device__ __forceinline__ void mbar_arrive_remote(uint32_t ra) { asm volatile("mbarrier.arrive.shared::cluster.b64 _, [%0];" :: "r"(ra) : "memory"); }
__device__ __forceinline__ uint32_t mapa(uint32_t a, uint32_t cta) { uint32_t r; asm volatile("mapa.shared::cluster.u32 %0, %1, %2;" : "=r"(r) : "r"(a), "r"(cta)); return r; }
__device__ __forceinline__ uint32_t mbar_try(uint32_t a, uint32_t ph) {
  uint32_t ok;
  asm volatile("{\n.reg .pred p;\nmbarrier.test_wait.parity.shared::cta.b64 p, [%1], %2;\nselp.u32 %0, 1, 0, p;\n}\n" : "=r"(ok) : "r"(a), "r"(ph) : "memory");
  return ok;
}
__device__ __forceinline__ void mbar_wait(uint32_t a, uint32_t ph) {
  asm volatile(
      "{\n.reg .pred p;\n.reg .u32 n;\n"
      "mbarrier.try_wait.parity.shared::cta.b64 p, [%0], %1;\n"
      "@p bra DONE;\n"
      "mov.u32 n, 0;\n"
      "SPIN:\n"
      "mbarrier.try_wait.parity.shared::cta.b64 p, [%0], %1;\n"
      "@p bra DONE;\n"
      "add.u32 n, n, 1;\n"
      "setp.gt.u32 p, n, 16777216;\n"
      "@p trap;\n"
      "bra SPIN;\n"
      "DONE:\n}\n" :: "r"(a), "r"(ph) : "memory");
}
__device__ __forceinline__ void tma2d(uint32_t dst, const CUtensorMap* m, uint32_t bar, int c0, int c1) {
  asm volatile("cp.async.bulk.tensor.2d.shared::cluster.global.mbarrier::complete_tx::bytes [%0], [%1, {%3, %4}], [%2];"
               :: "r"(dst), "l"(m), "r"(bar), "r"(c0), "r"(c1) : "memory");
}
__device__ __forceinline__ void tma3d(uint32_t dst, const CUtensorMap* m, uint32_t bar, int c0, int c1, int c2) {
  asm volatile("cp.async.bulk.tensor.3d.shared::cluster.global.mbarrier::complete_tx::bytes [%0], [%1, {%3, %4, %5}], [%2];"
               :: "r"(dst), "l"(m), "r"(bar), "r"(c0), "r"(c1), "r"(c2) : "memory");
}
__device__ __forceinline__ void tma3d_mc(uint32_t dst, const CUtensorMap* m, uint32_t bar, int c0, int c1, int c2, uint16_t mask) {
  asm volatile("cp.async.bulk.tensor.3d.shared::cluster.global.mbarrier::complete_tx::bytes.multicast::cluster [%0], [%1, {%3, %4, %5}], [%2], %6;"
               :: "r"(dst), "l"(m), "r"(bar), "r"(c0), "r"(c1), "r"(c2), "h"(mask) : "memory");
}
__device__ __forceinline__ void prefetch_tmap(const CUtensorMap* m) { asm volatile("prefetch.tensormap [%0];" :: "l"(m) : "memory"); }
__device__ __forceinline__ void wg_fence() { asm volatile("wgmma.fence.sync.aligned;" ::: "memory"); }
__device__ __forceinline__ void wg_commit() { asm volatile("wgmma.commit_group.sync.aligned;" ::: "memory"); }
template <int N> __device__ __forceinline__ void wg_wait() { asm volatile("wgmma.wait_group.sync.aligned %0;" :: "n"(N) : "memory"); }
template <int N> __device__ __forceinline__ void fence_regs(float (&r)[N]) {
#pragma unroll
  for (int i = 0; i < N; i++) asm volatile("" : "+f"(r[i]) :: "memory");
}
template <int N> __device__ __forceinline__ void fence_regs(uint32_t (&r)[N]) {
#pragma unroll
  for (int i = 0; i < N; i++) asm volatile("" : "+r"(r[i]) :: "memory");
}
__device__ __forceinline__ uint64_t mkdesc(uint32_t addr, uint32_t lbo, uint32_t sbo) {
  return (uint64_t)((addr & 0x3FFFF) >> 4) | ((uint64_t)(lbo >> 4) << 16) | ((uint64_t)(sbo >> 4) << 32) | (1ull << 62);
}
__device__ __forceinline__ void bar_sync(int id, int n) { asm volatile("bar.sync %0, %1;" :: "r"(id), "r"(n) : "memory"); }
__device__ __forceinline__ void bar_arrive(int id, int n) { asm volatile("bar.arrive %0, %1;" :: "r"(id), "r"(n) : "memory"); }
__device__ __forceinline__ void cluster_sync() { asm volatile("barrier.cluster.arrive.aligned;\nbarrier.cluster.wait.aligned;" ::: "memory"); }
__device__ __forceinline__ void pdl_wait() { asm volatile("griddepcontrol.wait;" ::: "memory"); }
__device__ __forceinline__ void pdl_launch() { asm volatile("griddepcontrol.launch_dependents;" ::: "memory"); }
__device__ __forceinline__ float ex2(float x) { float y; asm("ex2.approx.ftz.f32 %0, %1;" : "=f"(y) : "f"(x)); return y; }
__device__ __forceinline__ uint32_t pack_bf16(float lo, float hi) { uint32_t r; asm("cvt.rn.bf16x2.f32 %0, %1, %2;" : "=r"(r) : "f"(hi), "f"(lo)); return r; }
__device__ __forceinline__ float bf_lo(uint32_t u) { return __uint_as_float(u << 16); }
__device__ __forceinline__ float bf_hi(uint32_t u) { return __uint_as_float(u & 0xffff0000u); }
__device__ __forceinline__ float bf_round(float x) { return __bfloat162float(__float2bfloat16_rn(x)); }
__device__ __forceinline__ float tanh_fast(float x) { float y; asm("tanh.approx.f32 %0, %1;" : "=f"(y) : "f"(x)); return y; }
__device__ __forceinline__ float gelu_tanh(float x) {
  float u = x * (0.7978845608028654f + 0.035677408136300125f * x * x);
  float hx = 0.5f * x;
  return fmaf(hx, tanh_fast(u), hx);
}
__device__ __forceinline__ float warp_sum(float v) {
#pragma unroll
  for (int o = 16; o > 0; o >>= 1) v += __shfl_xor_sync(0xffffffffu, v, o);
  return v;
}
__device__ __forceinline__ void quad_transpose(uint32_t& v0, uint32_t& v1, uint32_t& v2, uint32_t& v3, int lane) {
  const bool b0 = lane & 1, b1 = lane & 2;
  uint32_t s0 = b0 ? v0 : v1, s1 = b0 ? v2 : v3;
  s0 = __shfl_xor_sync(0xffffffffu, s0, 1); s1 = __shfl_xor_sync(0xffffffffu, s1, 1);
  if (b0) { v0 = s0; v2 = s1; } else { v1 = s0; v3 = s1; }
  uint32_t t0 = b1 ? v0 : v2, t1 = b1 ? v1 : v3;
  t0 = __shfl_xor_sync(0xffffffffu, t0, 2); t1 = __shfl_xor_sync(0xffffffffu, t1, 2);
  if (b1) { v0 = t0; v1 = t1; } else { v2 = t0; v3 = t1; }
}

#define TSA(item, i)
#define TL_ENTRY(k)
#define TL_WAITED(k)
#define TL_END(k)
#define TS(item, i)
template<int TB> __device__ __forceinline__ void wgmma_rs_n64(float (&d)[32], uint32_t a0, uint32_t a1, uint32_t a2, uint32_t a3, uint64_t db, int scale_d) {
  asm volatile("{\n.reg .pred p;\nsetp.ne.b32 p, %37, 0;\n"
    "wgmma.mma_async.sync.aligned.m64n64k16.f32.bf16.bf16 {%0, %1, %2, %3, %4, %5, %6, %7, %8, %9, %10, %11, %12, %13, %14, %15, %16, %17, %18, %19, %20, %21, %22, %23, %24, %25, %26, %27, %28, %29, %30, %31}, {%32, %33, %34, %35}, %36, p, 1, 1, %38;\n}\n"
    : "+f"(d[0]), "+f"(d[1]), "+f"(d[2]), "+f"(d[3]), "+f"(d[4]), "+f"(d[5]), "+f"(d[6]), "+f"(d[7]), "+f"(d[8]), "+f"(d[9]), "+f"(d[10]), "+f"(d[11]), "+f"(d[12]), "+f"(d[13]), "+f"(d[14]), "+f"(d[15]), "+f"(d[16]), "+f"(d[17]), "+f"(d[18]), "+f"(d[19]), "+f"(d[20]), "+f"(d[21]), "+f"(d[22]), "+f"(d[23]), "+f"(d[24]), "+f"(d[25]), "+f"(d[26]), "+f"(d[27]), "+f"(d[28]), "+f"(d[29]), "+f"(d[30]), "+f"(d[31])
    : "r"(a0), "r"(a1), "r"(a2), "r"(a3), "l"(db), "r"(scale_d), "n"(TB));
}
template<int TB> __device__ __forceinline__ void wgmma_rs_n192(float (&d)[96], uint32_t a0, uint32_t a1, uint32_t a2, uint32_t a3, uint64_t db, int scale_d) {
  asm volatile("{\n.reg .pred p;\nsetp.ne.b32 p, %101, 0;\n"
    "wgmma.mma_async.sync.aligned.m64n192k16.f32.bf16.bf16 {%0, %1, %2, %3, %4, %5, %6, %7, %8, %9, %10, %11, %12, %13, %14, %15, %16, %17, %18, %19, %20, %21, %22, %23, %24, %25, %26, %27, %28, %29, %30, %31, %32, %33, %34, %35, %36, %37, %38, %39, %40, %41, %42, %43, %44, %45, %46, %47, %48, %49, %50, %51, %52, %53, %54, %55, %56, %57, %58, %59, %60, %61, %62, %63, %64, %65, %66, %67, %68, %69, %70, %71, %72, %73, %74, %75, %76, %77, %78, %79, %80, %81, %82, %83, %84, %85, %86, %87, %88, %89, %90, %91, %92, %93, %94, %95}, {%96, %97, %98, %99}, %100, p, 1, 1, %102;\n}\n"
    : "+f"(d[0]), "+f"(d[1]), "+f"(d[2]), "+f"(d[3]), "+f"(d[4]), "+f"(d[5]), "+f"(d[6]), "+f"(d[7]), "+f"(d[8]), "+f"(d[9]), "+f"(d[10]), "+f"(d[11]), "+f"(d[12]), "+f"(d[13]), "+f"(d[14]), "+f"(d[15]), "+f"(d[16]), "+f"(d[17]), "+f"(d[18]), "+f"(d[19]), "+f"(d[20]), "+f"(d[21]), "+f"(d[22]), "+f"(d[23]), "+f"(d[24]), "+f"(d[25]), "+f"(d[26]), "+f"(d[27]), "+f"(d[28]), "+f"(d[29]), "+f"(d[30]), "+f"(d[31]), "+f"(d[32]), "+f"(d[33]), "+f"(d[34]), "+f"(d[35]), "+f"(d[36]), "+f"(d[37]), "+f"(d[38]), "+f"(d[39]), "+f"(d[40]), "+f"(d[41]), "+f"(d[42]), "+f"(d[43]), "+f"(d[44]), "+f"(d[45]), "+f"(d[46]), "+f"(d[47]), "+f"(d[48]), "+f"(d[49]), "+f"(d[50]), "+f"(d[51]), "+f"(d[52]), "+f"(d[53]), "+f"(d[54]), "+f"(d[55]), "+f"(d[56]), "+f"(d[57]), "+f"(d[58]), "+f"(d[59]), "+f"(d[60]), "+f"(d[61]), "+f"(d[62]), "+f"(d[63]), "+f"(d[64]), "+f"(d[65]), "+f"(d[66]), "+f"(d[67]), "+f"(d[68]), "+f"(d[69]), "+f"(d[70]), "+f"(d[71]), "+f"(d[72]), "+f"(d[73]), "+f"(d[74]), "+f"(d[75]), "+f"(d[76]), "+f"(d[77]), "+f"(d[78]), "+f"(d[79]), "+f"(d[80]), "+f"(d[81]), "+f"(d[82]), "+f"(d[83]), "+f"(d[84]), "+f"(d[85]), "+f"(d[86]), "+f"(d[87]), "+f"(d[88]), "+f"(d[89]), "+f"(d[90]), "+f"(d[91]), "+f"(d[92]), "+f"(d[93]), "+f"(d[94]), "+f"(d[95])
    : "r"(a0), "r"(a1), "r"(a2), "r"(a3), "l"(db), "r"(scale_d), "n"(TB));
}
template<int TB> __device__ __forceinline__ void wgmma_ss_n128(float (&d)[64], uint64_t da, uint64_t db, int scale_d) {
  asm volatile("{\n.reg .pred p;\nsetp.ne.b32 p, %66, 0;\n"
    "wgmma.mma_async.sync.aligned.m64n128k16.f32.bf16.bf16 {%0, %1, %2, %3, %4, %5, %6, %7, %8, %9, %10, %11, %12, %13, %14, %15, %16, %17, %18, %19, %20, %21, %22, %23, %24, %25, %26, %27, %28, %29, %30, %31, %32, %33, %34, %35, %36, %37, %38, %39, %40, %41, %42, %43, %44, %45, %46, %47, %48, %49, %50, %51, %52, %53, %54, %55, %56, %57, %58, %59, %60, %61, %62, %63}, %64, %65, p, 1, 1, 0, %67;\n}\n"
    : "+f"(d[0]), "+f"(d[1]), "+f"(d[2]), "+f"(d[3]), "+f"(d[4]), "+f"(d[5]), "+f"(d[6]), "+f"(d[7]), "+f"(d[8]), "+f"(d[9]), "+f"(d[10]), "+f"(d[11]), "+f"(d[12]), "+f"(d[13]), "+f"(d[14]), "+f"(d[15]), "+f"(d[16]), "+f"(d[17]), "+f"(d[18]), "+f"(d[19]), "+f"(d[20]), "+f"(d[21]), "+f"(d[22]), "+f"(d[23]), "+f"(d[24]), "+f"(d[25]), "+f"(d[26]), "+f"(d[27]), "+f"(d[28]), "+f"(d[29]), "+f"(d[30]), "+f"(d[31]), "+f"(d[32]), "+f"(d[33]), "+f"(d[34]), "+f"(d[35]), "+f"(d[36]), "+f"(d[37]), "+f"(d[38]), "+f"(d[39]), "+f"(d[40]), "+f"(d[41]), "+f"(d[42]), "+f"(d[43]), "+f"(d[44]), "+f"(d[45]), "+f"(d[46]), "+f"(d[47]), "+f"(d[48]), "+f"(d[49]), "+f"(d[50]), "+f"(d[51]), "+f"(d[52]), "+f"(d[53]), "+f"(d[54]), "+f"(d[55]), "+f"(d[56]), "+f"(d[57]), "+f"(d[58]), "+f"(d[59]), "+f"(d[60]), "+f"(d[61]), "+f"(d[62]), "+f"(d[63])
    : "l"(da), "l"(db), "r"(scale_d), "n"(TB));
}
template<int TB> __device__ __forceinline__ void wgmma_ss_n192(float (&d)[96], uint64_t da, uint64_t db, int scale_d) {
  asm volatile("{\n.reg .pred p;\nsetp.ne.b32 p, %98, 0;\n"
    "wgmma.mma_async.sync.aligned.m64n192k16.f32.bf16.bf16 {%0, %1, %2, %3, %4, %5, %6, %7, %8, %9, %10, %11, %12, %13, %14, %15, %16, %17, %18, %19, %20, %21, %22, %23, %24, %25, %26, %27, %28, %29, %30, %31, %32, %33, %34, %35, %36, %37, %38, %39, %40, %41, %42, %43, %44, %45, %46, %47, %48, %49, %50, %51, %52, %53, %54, %55, %56, %57, %58, %59, %60, %61, %62, %63, %64, %65, %66, %67, %68, %69, %70, %71, %72, %73, %74, %75, %76, %77, %78, %79, %80, %81, %82, %83, %84, %85, %86, %87, %88, %89, %90, %91, %92, %93, %94, %95}, %96, %97, p, 1, 1, 0, %99;\n}\n"
    : "+f"(d[0]), "+f"(d[1]), "+f"(d[2]), "+f"(d[3]), "+f"(d[4]), "+f"(d[5]), "+f"(d[6]), "+f"(d[7]), "+f"(d[8]), "+f"(d[9]), "+f"(d[10]), "+f"(d[11]), "+f"(d[12]), "+f"(d[13]), "+f"(d[14]), "+f"(d[15]), "+f"(d[16]), "+f"(d[17]), "+f"(d[18]), "+f"(d[19]), "+f"(d[20]), "+f"(d[21]), "+f"(d[22]), "+f"(d[23]), "+f"(d[24]), "+f"(d[25]), "+f"(d[26]), "+f"(d[27]), "+f"(d[28]), "+f"(d[29]), "+f"(d[30]), "+f"(d[31]), "+f"(d[32]), "+f"(d[33]), "+f"(d[34]), "+f"(d[35]), "+f"(d[36]), "+f"(d[37]), "+f"(d[38]), "+f"(d[39]), "+f"(d[40]), "+f"(d[41]), "+f"(d[42]), "+f"(d[43]), "+f"(d[44]), "+f"(d[45]), "+f"(d[46]), "+f"(d[47]), "+f"(d[48]), "+f"(d[49]), "+f"(d[50]), "+f"(d[51]), "+f"(d[52]), "+f"(d[53]), "+f"(d[54]), "+f"(d[55]), "+f"(d[56]), "+f"(d[57]), "+f"(d[58]), "+f"(d[59]), "+f"(d[60]), "+f"(d[61]), "+f"(d[62]), "+f"(d[63]), "+f"(d[64]), "+f"(d[65]), "+f"(d[66]), "+f"(d[67]), "+f"(d[68]), "+f"(d[69]), "+f"(d[70]), "+f"(d[71]), "+f"(d[72]), "+f"(d[73]), "+f"(d[74]), "+f"(d[75]), "+f"(d[76]), "+f"(d[77]), "+f"(d[78]), "+f"(d[79]), "+f"(d[80]), "+f"(d[81]), "+f"(d[82]), "+f"(d[83]), "+f"(d[84]), "+f"(d[85]), "+f"(d[86]), "+f"(d[87]), "+f"(d[88]), "+f"(d[89]), "+f"(d[90]), "+f"(d[91]), "+f"(d[92]), "+f"(d[93]), "+f"(d[94]), "+f"(d[95])
    : "l"(da), "l"(db), "r"(scale_d), "n"(TB));
}
template<int TB> __device__ __forceinline__ void wgmma_ss_n80(float (&d)[40], uint64_t da, uint64_t db, int scale_d) {
  asm volatile("{\n.reg .pred p;\nsetp.ne.b32 p, %42, 0;\n"
    "wgmma.mma_async.sync.aligned.m64n80k16.f32.bf16.bf16 {%0, %1, %2, %3, %4, %5, %6, %7, %8, %9, %10, %11, %12, %13, %14, %15, %16, %17, %18, %19, %20, %21, %22, %23, %24, %25, %26, %27, %28, %29, %30, %31, %32, %33, %34, %35, %36, %37, %38, %39}, %40, %41, p, 1, 1, 0, %43;\n}\n"
    : "+f"(d[0]), "+f"(d[1]), "+f"(d[2]), "+f"(d[3]), "+f"(d[4]), "+f"(d[5]), "+f"(d[6]), "+f"(d[7]), "+f"(d[8]), "+f"(d[9]), "+f"(d[10]), "+f"(d[11]), "+f"(d[12]), "+f"(d[13]), "+f"(d[14]), "+f"(d[15]), "+f"(d[16]), "+f"(d[17]), "+f"(d[18]), "+f"(d[19]), "+f"(d[20]), "+f"(d[21]), "+f"(d[22]), "+f"(d[23]), "+f"(d[24]), "+f"(d[25]), "+f"(d[26]), "+f"(d[27]), "+f"(d[28]), "+f"(d[29]), "+f"(d[30]), "+f"(d[31]), "+f"(d[32]), "+f"(d[33]), "+f"(d[34]), "+f"(d[35]), "+f"(d[36]), "+f"(d[37]), "+f"(d[38]), "+f"(d[39])
    : "l"(da), "l"(db), "r"(scale_d), "n"(TB));
}

__device__ float g_mod[6 * D_];
__device__ __align__(1024) bf16 g_h[S_ * D_];
__device__ __align__(1024) bf16 g_o[S_ * HD_];
__device__ __align__(1024) uint4 g_xch[16 * 2 * 4 * 4 * 5 * 256];
__device__ __align__(1024) bf16 g_w1t[D_ * D_];
__device__ __align__(1024) bf16 g_w2t[D_ * D_];
__device__ __align__(1024) bf16 g_w4t[D_ * F_];
__device__ __align__(32) float g_st1[S_ * 8];
__device__ __align__(32) float g_st2[S_ * 2];
__device__ __align__(32) float g_vec[3 * D_ + F_ + 8];
__device__ unsigned g_flag[1024];
enum { F_XCH = 0, F_XA = 256, F_US = 272, F_X1 = 288, F_G = 304, F_PREP = 320, F_O = 512 };
__device__ __align__(1024) bf16 g_xa[S_ * D_];
__device__ __align__(1024) bf16 g_us[S_ * D_];
__device__ __align__(1024) bf16 g_x1[S_ * D_];
__device__ __align__(1024) bf16 g_g[S_ * F_];

__global__ void __launch_bounds__(256) mod_kernel(const bf16* __restrict__ c, const bf16* __restrict__ w_mod) {
  TL_ENTRY(0);
  pdl_launch();
  __shared__ float red[8][32];
  if (blockIdx.x < 14) { const int i = blockIdx.x * 256 + threadIdx.x; if (i < 3 * D_ + F_) g_vec[i] = 0.f; }
  else if (blockIdx.x < 18) g_flag[(blockIdx.x - 14) * 256 + threadIdx.x] = 0u;
  const int t = threadIdx.x, cg = t & 3, r0 = t >> 2;
  const int col0 = blockIdx.x * 32 + cg * 8;
  uint4 w[10];
#pragma unroll
  for (int i = 0; i < 10; i++) w[i] = __ldg(reinterpret_cast<const uint4*>(w_mod + (size_t)(r0 + 64 * i) * (6 * D_) + col0));
  float acc[8];
#pragma unroll
  for (int j = 0; j < 8; j++) acc[j] = 0.f;
#pragma unroll
  for (int i = 0; i < 10; i++) {
    float cv = __bfloat162float(c[r0 + 64 * i]);
    float s = bf_round(cv / (1.f + __expf(-cv)));
    acc[0] = fmaf(s, bf_lo(w[i].x), acc[0]); acc[1] = fmaf(s, bf_hi(w[i].x), acc[1]);
    acc[2] = fmaf(s, bf_lo(w[i].y), acc[2]); acc[3] = fmaf(s, bf_hi(w[i].y), acc[3]);
    acc[4] = fmaf(s, bf_lo(w[i].z), acc[4]); acc[5] = fmaf(s, bf_hi(w[i].z), acc[5]);
    acc[6] = fmaf(s, bf_lo(w[i].w), acc[6]); acc[7] = fmaf(s, bf_hi(w[i].w), acc[7]);
  }
#pragma unroll
  for (int j = 0; j < 8; j++) {
    acc[j] += __shfl_xor_sync(0xffffffffu, acc[j], 4);
    acc[j] += __shfl_xor_sync(0xffffffffu, acc[j], 8);
    acc[j] += __shfl_xor_sync(0xffffffffu, acc[j], 16);
  }
  if ((t & 31) < 4) {
#pragma unroll
    for (int j = 0; j < 8; j++) red[t >> 5][cg * 8 + j] = acc[j];
  }
  __syncthreads();
  if (t < 32) {
    float s = 0.f;
#pragma unroll
    for (int w8 = 0; w8 < 8; w8++) s += red[w8][t];
    const int col = blockIdx.x * 32 + t;
    s = bf_round(s);
    const int part = col / D_;
    if (part == 1 || part == 4) s = bf_round(1.f + s);
    g_mod[col] = s;
    if (t == 0) TL_END(0);
  }
}

__device__ __forceinline__ void row_stats(const float (&v)[20], float& mean, float& rstd) {
  float s = 0.f;
#pragma unroll
  for (int i = 0; i < 20; i++) s += v[i];
  mean = warp_sum(s) * (1.f / D_);
  float q = 0.f;
#pragma unroll
  for (int i = 0; i < 20; i++) { float d = v[i] - mean; q = fmaf(d, d, q); }
  rstd = rsqrtf(warp_sum(q) * (1.f / D_) + LN_EPS);
}
__device__ __forceinline__ void load_row_bf16(const bf16* p, int lane, float (&v)[20]) {
#pragma unroll
  for (int i = 0; i < 5; i++) {
    uint2 u = *reinterpret_cast<const uint2*>(p + (lane + 32 * i) * 4);
    v[4 * i] = bf_lo(u.x); v[4 * i + 1] = bf_hi(u.x); v[4 * i + 2] = bf_lo(u.y); v[4 * i + 3] = bf_hi(u.y);
  }
}
__device__ __forceinline__ void store_row_bf16(bf16* p, int lane, const float (&v)[20]) {
#pragma unroll
  for (int i = 0; i < 5; i++) {
    uint2 u; u.x = pack_bf16(v[4 * i], v[4 * i + 1]); u.y = pack_bf16(v[4 * i + 2], v[4 * i + 3]);
    *reinterpret_cast<uint2*>(p + (lane + 32 * i) * 4) = u;
  }
}
__device__ __forceinline__ void load_row_f32(const float* p, int lane, float (&v)[20]) {
#pragma unroll
  for (int i = 0; i < 5; i++) {
    float4 u = *reinterpret_cast<const float4*>(p + (lane + 32 * i) * 4);
    v[4 * i] = u.x; v[4 * i + 1] = u.y; v[4 * i + 2] = u.z; v[4 * i + 3] = u.w;
  }
}

__global__ void __launch_bounds__(256) ln1_kernel(const bf16* __restrict__ x) {
  TL_ENTRY(1);
  pdl_launch();
  const int lane = threadIdx.x & 31, row = blockIdx.x * 8 + (threadIdx.x >> 5);
  float v[20];
  load_row_bf16(x + (size_t)row * D_, lane, v);
  float mean, rstd;
  row_stats(v, mean, rstd);
  if (lane < 8) g_st1[row * 8 + lane] = 0.f;
  if (lane < 2) g_st2[row * 2 + lane] = 0.f;
  pdl_wait();
  if (threadIdx.x == 0) TL_WAITED(1);
  float sa[20], ca[20];
  load_row_f32(g_mod, lane, sa);
  load_row_f32(g_mod + D_, lane, ca);
#pragma unroll
  for (int i = 0; i < 20; i++) v[i] = fmaf((v[i] - mean) * rstd, ca[i], sa[i]);
  store_row_bf16(g_h + (size_t)row * D_, lane, v);
  if (threadIdx.x == 0) TL_END(1);
}

constexpr int PREP_JOBS = 200 + 200 + 480 + 480;
struct PrepW { const bf16 *w1, *w2, *w3, *w4; };
__device__ __forceinline__ void prep_warp(const PrepW& pw, bf16 (*tile)[72], int lane) {
#pragma unroll 1
  for (int job = blockIdx.x; job < PREP_JOBS; job += gridDim.x) {
    const bf16* src; bf16* dst; int ld = D_, ldd = D_, kt, nt, kind = 1;
    if (job < 200) { src = pw.w1; dst = g_w1t; kt = job / 10; nt = job % 10; kind = 0; }
    else if (job < 400) { src = pw.w2; dst = g_w2t; kt = (job - 200) / 10; nt = (job - 200) % 10; }
    else if (job < 880) { src = pw.w4; dst = g_w4t; ldd = F_; kt = (job - 400) / 10; nt = (job - 400) % 10; }
    else { src = pw.w3; dst = nullptr; ld = F_; kt = (job - 880) / 24; nt = (job - 880) % 24; kind = 2; }
    src += (size_t)(kt * 32 + (lane >> 3)) * ld + nt * 64 + (lane & 7) * 8;
    __syncwarp();
#pragma unroll
    for (int h = 0; h < 2; h++) {
      uint4 v[4];
#pragma unroll
      for (int i = 0; i < 4; i++) v[i] = __ldg(reinterpret_cast<const uint4*>(src + (size_t)(h * 16 + i * 4) * ld));
#pragma unroll
      for (int i = 0; i < 4; i++) *reinterpret_cast<uint4*>(&tile[h * 16 + i * 4 + (lane >> 3)][(lane & 7) * 8]) = v[i];
    }
    __syncwarp();
    const float* pa = g_mod + 4 * D_ + kt * 32;
    const float* pb = g_mod + 3 * D_ + kt * 32;
#pragma unroll 1
    for (int h = 0; h < 2; h++) {
      const int n = lane + 32 * h;
      float sa = 0.f, sb = 0.f, sc = 0.f;
#pragma unroll 1
      for (int c = 0; c < 4; c++) {
        uint32_t u[4];
#pragma unroll
        for (int e = 0; e < 4; e++) {
          const int k = c * 8 + 2 * e;
          float lo = __bfloat162float(tile[k][n]), hi = __bfloat162float(tile[k + 1][n]);
          sc += lo + hi;
          if (kind == 0) {
            const float2 a = __ldcg(reinterpret_cast<const float2*>(pa + k)), b = __ldcg(reinterpret_cast<const float2*>(pb + k));
            sb = fmaf(b.x, lo, fmaf(b.y, hi, sb));
            lo *= a.x; hi *= a.y;
          }
          u[e] = pack_bf16(lo, hi);
          sa += bf_lo(u[e]) + bf_hi(u[e]);
        }
        if (kind != 2) *reinterpret_cast<uint4*>(dst + (size_t)(nt * 64 + n) * ldd + kt * 32 + c * 8) = make_uint4(u[0], u[1], u[2], u[3]);
      }
      if (kind == 0) { atomicAdd(&g_vec[nt * 64 + n], sa); atomicAdd(&g_vec[D_ + nt * 64 + n], sb); atomicAdd(&g_vec[2 * D_ + nt * 64 + n], sc); }
      else if (kind == 2) atomicAdd(&g_vec[3 * D_ + nt * 64 + n], sc);
    }
  }
  __syncwarp();
  if (lane == 0) {
    asm volatile("fence.acq_rel.gpu;" ::: "memory");
    asm volatile("red.relaxed.gpu.global.add.u32 [%0], 1;" :: "l"(g_flag + F_PREP) : "memory");
  }
}

constexpr int A_NSLOT = 9;
constexpr int A_SLOT = 24576;
constexpr int A_NKV = S_ / 64;
constexpr int PREP_CTAS = 128;

struct Ring {
  uint32_t slot, phase;
  __device__ __forceinline__ void adv(int n) { if (++slot == (uint32_t)n) { slot = 0; phase ^= 1; } }
};
constexpr int T_PAR = A_NSLOT * A_SLOT + 256;
constexpr int T_PREP = T_PAR + 3712;
constexpr int T_SMEM = T_PREP + 32 * 72 * 2 + 1024;
enum { P_OGA = 0, P_OA = 80, P_OB = 160, P_VA = 240, P_VB = 320, P_VC = 400, P_A2 = 480, P_B2 = 560, P_GB = 640, P_CS3 = 720, P_SC = 912 };

__device__ __forceinline__ void flag_wait(const unsigned* p, unsigned target) {
  asm volatile(
      "{\n.reg .pred p;\n.reg .u32 n, v;\n"
      "mov.u32 n, 0;\n"
      "SPIN:\n"
      "ld.relaxed.gpu.global.u32 v, [%0];\n"
      "setp.ge.u32 p, v, %1;\n"
      "@p bra DONE;\n"
      "add.u32 n, n, 1;\n"
      "setp.gt.u32 p, n, 4194304;\n"
      "@p trap;\n"
      "bra SPIN;\n"
      "DONE:\n}\n" :: "l"(p), "r"(target) : "memory");
}
__device__ __forceinline__ void fence_async_global() { asm volatile("fence.proxy.async.global;" ::: "memory"); }
__device__ __forceinline__ float lds_f(uint32_t a) { float v; asm volatile("ld.shared.f32 %0, [%1];" : "=f"(v) : "r"(a)); return v; }
__device__ __forceinline__ float2 lds_f2(uint32_t a) { float2 v; asm volatile("ld.shared.v2.f32 {%0, %1}, [%2];" : "=f"(v.x), "=f"(v.y) : "r"(a)); return v; }
__device__ __forceinline__ uint4 ldcg4(const void* p) { return __ldcg(reinterpret_cast<const uint4*>(p)); }

__device__ __forceinline__ const bf16* frag80_ptr(const bf16* base_row_g, int ld, int lane, int piece) {
  const int q = lane & 3;
  if (piece < 2) return base_row_g + piece * 32 + q * 8;
  if (piece < 4) return base_row_g + (size_t)8 * ld + (piece - 2) * 32 + q * 8;
  return base_row_g + (size_t)(q >> 1) * 8 * ld + 64 + (q & 1) * 8;
}
__device__ __forceinline__ void frag80_load(uint4 (&v)[5], const bf16* base_row_g, int ld, int lane) {
#pragma unroll
  for (int i = 0; i < 5; i++) v[i] = ldcg4(frag80_ptr(base_row_g, ld, lane, i));
}
__device__ __forceinline__ void frag80_unpack(uint4 (&v)[5], uint32_t (&u)[20], int lane) {
#pragma unroll
  for (int i = 0; i < 5; i++) quad_transpose(v[i].x, v[i].y, v[i].z, v[i].w, lane);
#pragma unroll
  for (int i = 0; i < 2; i++) {
    u[2 * (4 * i + 0)] = v[i].x; u[2 * (4 * i + 1)] = v[i].y; u[2 * (4 * i + 2)] = v[i].z; u[2 * (4 * i + 3)] = v[i].w;
    u[2 * (4 * i + 0) + 1] = v[2 + i].x; u[2 * (4 * i + 1) + 1] = v[2 + i].y; u[2 * (4 * i + 2) + 1] = v[2 + i].z; u[2 * (4 * i + 3) + 1] = v[2 + i].w;
  }
  u[16] = v[4].x; u[18] = v[4].y; u[17] = v[4].z; u[19] = v[4].w;
}
__device__ __forceinline__ void frag80_store(const uint32_t (&u)[20], bf16* base_row_g, int ld, int lane, int rows_ok) {
  uint4 v[5];
#pragma unroll
  for (int i = 0; i < 2; i++) {
    v[i] = make_uint4(u[2 * (4 * i + 0)], u[2 * (4 * i + 1)], u[2 * (4 * i + 2)], u[2 * (4 * i + 3)]);
    v[2 + i] = make_uint4(u[2 * (4 * i + 0) + 1], u[2 * (4 * i + 1) + 1], u[2 * (4 * i + 2) + 1], u[2 * (4 * i + 3) + 1]);
  }
  v[4] = make_uint4(u[16], u[18], u[17], u[19]);
#pragma unroll
  for (int i = 0; i < 5; i++) {
    quad_transpose(v[i].x, v[i].y, v[i].z, v[i].w, lane);
    const int hrow = (i < 2) ? 0 : (i < 4) ? 1 : ((lane & 3) >> 1);
    if ((rows_ok >> hrow) & 1) *reinterpret_cast<uint4*>(const_cast<bf16*>(frag80_ptr(base_row_g, ld, lane, i))) = v[i];
  }
}
__device__ __forceinline__ float quad_sum(float v) {
  v += __shfl_xor_sync(0xffffffffu, v, 1);
  v += __shfl_xor_sync(0xffffffffu, v, 2);
  return v;
}

struct Maps { CUtensorMap h, wq, k, v, o, wo3, wo2, xa, w1t, us, w2t, x1, w3, g, w4t; };
struct PfList { const uint8_t* p[6]; };

struct Rings {
  uint32_t a, b, par;
  __device__ __forceinline__ uint32_t nextA() { uint32_t s = 5 + a; a = (a + 1) & 3; return s; }
  __device__ __forceinline__ uint32_t nextB() { uint32_t s = b; b = (b == 4) ? 0 : b + 1; return s; }
  __device__ __forceinline__ uint32_t take(uint32_t s) { uint32_t p = (par >> s) & 1; par ^= 1u << s; return p; }
};
__device__ __forceinline__ Rings to_rings(const Ring& r) {
  const uint32_t lo = (1u << r.slot) - 1u;
  return Rings{0, 0, r.phase ? (0x1ffu & ~lo) : lo};
}

__global__ void __cluster_dims__(2, 1, 1) __launch_bounds__(384, 1)
fused_kernel(const __grid_constant__ Maps tm, const __grid_constant__ PfList pf, const __grid_constant__ PrepW pw, const bf16* __restrict__ x, bf16* __restrict__ out) {
  extern __shared__ uint8_t smem_raw[];
  const uint32_t sb = (smem_u32(smem_raw) + 1023) & ~1023u;
  TL_ENTRY(2);
  const uint32_t bar_full = sb + A_NSLOT * A_SLOT;
  const uint32_t bar_empty = bar_full + 8 * A_NSLOT;
  const uint32_t bar_sig = bar_empty + 8 * A_NSLOT;
  const uint32_t par = sb + T_PAR;
  float* parf = reinterpret_cast<float*>(smem_raw + (par - smem_u32(smem_raw)));
  uint32_t rank;
  asm volatile("mov.u32 %0, %%cluster_ctarank;" : "=r"(rank));
  const int cid = blockIdx.x >> 1;
  const int wg = threadIdx.x >> 7;
  const int qtile = (cid & 7) * 2 + rank, hbase = cid >> 3;
  const int o_qt = qtile, o_nh = (cid >> 3) & 1, o_ks = cid >> 4;
  const int o_col = o_nh * 320 + o_ks * 80;
  const int qt = cid >> 2, js = (cid & 3) * 2 + rank;
  if (threadIdx.x == 0) {
    for (int i = 0; i < A_NSLOT; i++) { mbar_init(bar_full + 8 * i, 1); mbar_init(bar_empty + 8 * i, 16); }
    mbar_init(bar_sig, 4); mbar_init(bar_sig + 8, 4);
    asm volatile("fence.mbarrier_init.release.cluster;" ::: "memory");
    prefetch_tmap(&tm.h); prefetch_tmap(&tm.wq); prefetch_tmap(&tm.k); prefetch_tmap(&tm.v);
  }
  __syncthreads();
  cluster_sync();

  if (wg == 0) {
    asm volatile("setmaxnreg.dec.sync.aligned.u32 40;");
    if (threadIdx.x == 0) {
      Ring r{0, 1};
#define P_ACQ(bytes_) do { mbar_wait(bar_empty + 8 * r.slot, r.phase); mbar_expect(bar_full + 8 * r.slot, bytes_); } while (0)
#define P_DST (sb + r.slot * A_SLOT)
#define P_BAR (bar_full + 8 * r.slot)
      pdl_wait();
      TL_WAITED(2);
#pragma unroll 1
      for (int item = 0; item < 4; item++) {
        const int head = hbase + 8 * item;
#pragma unroll 1
        for (int kb = 0; kb < 10; kb++) {
          P_ACQ(16384);
          tma2d(P_DST, &tm.h, P_BAR, kb * 64, qtile * 128);
          r.adv(A_NSLOT);
          P_ACQ(A_SLOT);
          if ((uint32_t)(kb & 1) == rank) tma3d_mc(P_DST, &tm.wq, P_BAR, 0, kb * 64, head * 3, 3);
          r.adv(A_NSLOT);
        }
#pragma unroll 1
        for (int j = 0; j <= A_NKV; j++) {
          if (j < A_NKV) {
            P_ACQ(A_SLOT);
            if (rank == 0) tma3d_mc(P_DST, &tm.k, P_BAR, 0, head * S_ + j * 64, 0, 3);
            r.adv(A_NSLOT);
          }
          if (j > 0) {
            P_ACQ(A_SLOT);
            if (rank == 1) tma3d_mc(P_DST, &tm.v, P_BAR, 0, head * S_ + (j - 1) * 64, 0, 3);
            r.adv(A_NSLOT);
          }
          if (item == 3 && (j & 3) == 0) {
            const int c = (j >> 2) * 128 + blockIdx.x;
            if (c < 980) {
              const int li = c < 480 ? 0 : c < 600 ? 1 : c < 720 ? 2 : c < 880 ? 3 : c < 930 ? 4 : 5;
              const int c0 = c < 480 ? 0 : c < 600 ? 480 : c < 720 ? 600 : c < 880 ? 720 : c < 930 ? 880 : 930;
              asm volatile("cp.async.bulk.prefetch.L2.global [%0], 16384;" :: "l"(pf.p[li] + (size_t)(c - c0) * 16384) : "memory");
            }
            if (j == 0) {
              prefetch_tmap(&tm.o); prefetch_tmap(&tm.wo3); prefetch_tmap(&tm.wo2); prefetch_tmap(&tm.xa); prefetch_tmap(&tm.w1t); prefetch_tmap(&tm.us);
              prefetch_tmap(&tm.w2t); prefetch_tmap(&tm.x1); prefetch_tmap(&tm.w3); prefetch_tmap(&tm.g); prefetch_tmap(&tm.w4t);
            }
          }
        }
      }
#pragma unroll 1
      for (int kb = 0; kb < 24; kb++) {
        const int head = (kb / 6) * 8 + 2 * o_ks + (kb % 6) / 3;
        const int kcol = head * DH_ + (kb % 3) * 64;
        P_ACQ(24576);
        if (rank == 0) tma3d_mc(P_DST, &tm.wo3, P_BAR, 0, kcol, o_nh * 5, 3);
        r.adv(A_NSLOT);
        P_ACQ(16384);
        if (rank == 1) tma3d_mc(P_DST, &tm.wo2, P_BAR, 0, kcol, o_nh * 5 + 3, 3);
        r.adv(A_NSLOT);
        if (kb % 3 == 0) { flag_wait(g_flag + F_O + o_qt * 32 + head, 2); fence_async_global(); }
        P_ACQ(16384);
        tma2d(P_DST, &tm.o, P_BAR, kcol, o_qt * 128);
        r.adv(A_NSLOT);
      }
      Rings rr = to_rings(r);
#define T_ACQ(s_, bytes_) do { mbar_wait(bar_empty + 8 * (s_), rr.take(s_)); mbar_expect(bar_full + 8 * (s_), bytes_); } while (0)
      flag_wait(g_flag + F_PREP, PREP_CTAS);
      fence_async_global();
#pragma unroll 1
      for (int ph = 0; ph < 4; ph++) {
        const CUtensorMap* ma = ph == 0 ? &tm.xa : ph == 1 ? &tm.us : ph == 2 ? &tm.x1 : &tm.g;
        const CUtensorMap* mb = ph == 0 ? &tm.w1t : ph == 1 ? &tm.w2t : ph == 2 ? &tm.w3 : &tm.w4t;
        const int nkb = ph == 3 ? 24 : 10;
        const int nbl = ph == 2 ? 10 : nkb / 2;
        const uint32_t bbytes = ph == 2 ? 24576 : 20480;
        int bl = 0;
#define T_LOADB() do { const uint32_t s_ = rr.nextB(); T_ACQ(s_, bbytes);                                            \
                       tma3d(sb + s_ * A_SLOT, mb, bar_full + 8 * s_, 0, ph == 2 ? bl * 64 : js * 80, ph == 2 ? js * 3 : bl * 2); bl++; } while (0)
#pragma unroll 1
        for (int i = 0; i < 5; i++) T_LOADB();
        const unsigned* fl = g_flag + F_XA + 16 * ph;
        flag_wait(fl + qt, 16);
        if (ph == 1) { if (qt > 0) flag_wait(fl + qt - 1, 16); if (qt < 15) flag_wait(fl + qt + 1, 16); }
        fence_async_global();
#pragma unroll 1
        for (int kb = 0; kb < nkb; kb++) {
          const uint32_t s = rr.nextA(); T_ACQ(s, 16384);
          asm volatile("cp.async.bulk.tensor.2d.shared::cluster.global.mbarrier::complete_tx::bytes.multicast::cluster [%0], [%1, {%3, %4}], [%2], %5;"
                       :: "r"(sb + s * A_SLOT + rank * 8192), "l"(ma), "r"(bar_full + 8 * s), "r"(kb * 64), "r"(qt * 128 + (int)rank * 64), "h"((uint16_t)3) : "memory");
          if (bl < nbl && kb >= (ph == 2 ? bl - 2 : 2 * bl - 6)) T_LOADB();
        }
      }
    } else if (threadIdx.x >= 32 && threadIdx.x < 96) {
      const int w = (threadIdx.x >> 5) - 1, lane = threadIdx.x & 31;
#pragma unroll 1
      for (int sig = 0; sig < 9; sig++) {
        mbar_wait(bar_sig + 8 * w, sig & 1);
        unsigned* f;
        bool act = lane == 0;
        if (sig < 4) f = g_flag + F_O + qtile * 32 + hbase + 8 * sig;
        else if (sig == 4) { f = g_flag + F_XCH + ((o_qt * 2 + o_nh) * 4 + (lane & 3)) * 2 + w; act = lane < 4 && lane != o_ks; }
        else if (sig == 5) f = g_flag + F_XA + o_qt;
        else f = g_flag + F_XA + 16 * (sig - 5) + qt;
        if (act) {
          asm volatile("fence.acq_rel.gpu;" ::: "memory");
          asm volatile("red.relaxed.gpu.global.add.u32 [%0], 1;" :: "l"(f) : "memory");
        }
        __syncwarp();
      }
    } else if (threadIdx.x >= 96) {
      pdl_wait();
      prep_warp(pw, reinterpret_cast<bf16(*)[72]>(smem_raw + (sb + T_PREP - smem_u32(smem_raw))), threadIdx.x & 31);
    }
    __syncwarp();
    cluster_sync();
  } else {
    asm volatile("setmaxnreg.inc.sync.aligned.u32 232;");
    const int w = wg - 1;
    const int lane = threadIdx.x & 31;
    const int warp = (threadIdx.x >> 5) & 3;
    const int tid = threadIdx.x - 128;
    const uint32_t rel_base = mapa(bar_empty, (lane == 0) ? rank : (rank ^ 1));
    Ring r{0, 0};
#define A_RELEASE(slot_) do { if (lane < 2) mbar_arrive_remote(rel_base + 8 * (slot_)); } while (0)
#define SIGNAL() do { __syncwarp(); if (lane == 0) mbar_arrive(bar_sig + 8 * w); } while (0)
    {
    const float SC = 0.07216878364870322f * 1.4426950408889634f;
    float o[96];
    uint32_t q[48];
    float s[32];
    uint32_t p[16], p2[16];
    if (w == 1) bar_arrive(1, 256);
    for (int item = 0; item < 4; item++) {
      const int head = hbase + 8 * item;
      TSA(item, 0);
      uint32_t prevA = 0, prevB = 0;
      for (int kb = 0; kb < 10; kb++) {
        const uint32_t sA = r.slot; mbar_wait(bar_full + 8 * sA, r.phase); r.adv(A_NSLOT);
        const uint32_t sB = r.slot; mbar_wait(bar_full + 8 * sB, r.phase); r.adv(A_NSLOT);
        const uint64_t da = mkdesc(sb + sA * A_SLOT + w * 8192, 16, 1024);
        const uint64_t db = mkdesc(sb + sB * A_SLOT, 8192, 1024);
        wg_fence();
#pragma unroll
        for (int kk = 0; kk < 4; kk++) wgmma_ss_n192<1>(o, da + kk * 2, db + kk * 128, (kb | kk) != 0);
        wg_commit();
        if (kb > 0) { wg_wait<1>(); A_RELEASE(prevA); A_RELEASE(prevB); }
        prevA = sA; prevB = sB;
      }
      wg_wait<0>();
      fence_regs(o);
      A_RELEASE(prevA); A_RELEASE(prevB);
#pragma unroll
      for (int i = 0; i < 48; i++) q[i] = pack_bf16(o[2 * i], o[2 * i + 1]);

      TSA(item, 1);
      float c0, c1, l0, l1;
      {
        const uint32_t sK = r.slot; mbar_wait(bar_full + 8 * sK, r.phase); r.adv(A_NSLOT);
        const uint64_t dk = mkdesc(sb + sK * A_SLOT, 16, 1024);
        bar_sync(1 + w, 256);
        wg_fence();
#pragma unroll
        for (int kk = 0; kk < 12; kk++)
          wgmma_rs_n64<0>(s, q[4 * kk], q[4 * kk + 1], q[4 * kk + 2], q[4 * kk + 3], dk + (kk >> 2) * 512 + (kk & 3) * 2, kk != 0);
        wg_commit();
        bar_arrive(1 + (w ^ 1), 256);
        wg_wait<0>();
        fence_regs(s);
        A_RELEASE(sK);
        float mx0 = fmaxf(s[0], s[1]), mx1 = fmaxf(s[2], s[3]);
#pragma unroll
        for (int i = 1; i < 8; i++) { mx0 = fmaxf(mx0, fmaxf(s[4 * i], s[4 * i + 1])); mx1 = fmaxf(mx1, fmaxf(s[4 * i + 2], s[4 * i + 3])); }
        mx0 = fmaxf(mx0, __shfl_xor_sync(0xffffffffu, mx0, 1)); mx1 = fmaxf(mx1, __shfl_xor_sync(0xffffffffu, mx1, 1));
        mx0 = fmaxf(mx0, __shfl_xor_sync(0xffffffffu, mx0, 2)); mx1 = fmaxf(mx1, __shfl_xor_sync(0xffffffffu, mx1, 2));
        c0 = mx0 * SC; c1 = mx1 * SC;
        l0 = 0.f; l1 = 0.f;
#pragma unroll
        for (int i = 0; i < 8; i++) {
          s[4 * i] = ex2(fmaf(s[4 * i], SC, -c0)); s[4 * i + 1] = ex2(fmaf(s[4 * i + 1], SC, -c0));
          s[4 * i + 2] = ex2(fmaf(s[4 * i + 2], SC, -c1)); s[4 * i + 3] = ex2(fmaf(s[4 * i + 3], SC, -c1));
          l0 += s[4 * i] + s[4 * i + 1]; l1 += s[4 * i + 2] + s[4 * i + 3];
        }
#pragma unroll
        for (int i = 0; i < 16; i++) p[i] = pack_bf16(s[2 * i], s[2 * i + 1]);
      }
      TSA(item, 2);
      uint32_t okn;
      {
        Ring r2 = r; r2.adv(A_NSLOT);
        okn = mbar_try(bar_full + 8 * r.slot, r.phase) & mbar_try(bar_full + 8 * r2.slot, r2.phase);
      }
#define A_STEP(PC, PN, FIRST)                                                                                          \
      {                                                                                                                \
        const uint32_t sK = r.slot, phK = r.phase; r.adv(A_NSLOT);                                                     \
        const uint32_t sV = r.slot, phV = r.phase; r.adv(A_NSLOT);                                                     \
        const uint64_t dk = mkdesc(sb + sK * A_SLOT, 16, 1024);                                                        \
        const uint64_t dv = mkdesc(sb + sV * A_SLOT, 8192, 1024);                                                      \
        if (!okn) { mbar_wait(bar_full + 8 * sK, phK); mbar_wait(bar_full + 8 * sV, phV); }                            \
        bar_sync(1 + w, 256);                                                                                          \
        wg_fence();                                                                                                    \
        _Pragma("unroll") for (int kk = 0; kk < 12; kk++)                                                              \
          wgmma_rs_n64<0>(s, q[4 * kk], q[4 * kk + 1], q[4 * kk + 2], q[4 * kk + 3], dk + (kk >> 2) * 512 + (kk & 3) * 2, kk != 0); \
        wg_commit();                                                                                                   \
        _Pragma("unroll") for (int kk = 0; kk < 4; kk++)                                                               \
          wgmma_rs_n192<1>(o, PC[4 * kk], PC[4 * kk + 1], PC[4 * kk + 2], PC[4 * kk + 3], dv + kk * 128, !(FIRST) || (kk != 0)); \
        wg_commit();                                                                                                   \
        bar_arrive(1 + (w ^ 1), 256);                                                                                  \
        {                                                                                                              \
          Ring r2 = r; r2.adv(A_NSLOT);                                                                                \
          okn = mbar_try(bar_full + 8 * r.slot, r.phase) & mbar_try(bar_full + 8 * r2.slot, r2.phase);                 \
        }                                                                                                              \
        wg_wait<1>();                                                                                                  \
        fence_regs(s);                                                                                                 \
        A_RELEASE(sK);                                                                                                 \
        float b0 = 0.f, b1 = 0.f;                                                                                      \
        _Pragma("unroll") for (int i = 0; i < 8; i++) {                                                                \
          const float e0 = ex2(fmaf(s[4 * i], SC, -c0)), e1 = ex2(fmaf(s[4 * i + 1], SC, -c0));                        \
          const float e2 = ex2(fmaf(s[4 * i + 2], SC, -c1)), e3 = ex2(fmaf(s[4 * i + 3], SC, -c1));                    \
          b0 += e0 + e1; b1 += e2 + e3;                                                                                \
          PN[2 * i] = pack_bf16(e0, e1); PN[2 * i + 1] = pack_bf16(e2, e3);                                            \
        }                                                                                                              \
        wg_wait<0>();                                                                                                  \
        fence_regs(o);                                                                                                 \
        fence_regs(PC);                                                                                                \
        A_RELEASE(sV);                                                                                                 \
        if (__any_sync(0xffffffffu, !(b0 <= 65536.f) || !(b1 <= 65536.f))) {                                           \
          float mx0 = fmaxf(s[0], s[1]), mx1 = fmaxf(s[2], s[3]);                                                      \
          _Pragma("unroll") for (int i = 1; i < 8; i++) {                                                              \
            mx0 = fmaxf(mx0, fmaxf(s[4 * i], s[4 * i + 1])); mx1 = fmaxf(mx1, fmaxf(s[4 * i + 2], s[4 * i + 3]));     \
          }                                                                                                            \
          mx0 = fmaxf(mx0, __shfl_xor_sync(0xffffffffu, mx0, 1)); mx1 = fmaxf(mx1, __shfl_xor_sync(0xffffffffu, mx1, 1)); \
          mx0 = fmaxf(mx0, __shfl_xor_sync(0xffffffffu, mx0, 2)); mx1 = fmaxf(mx1, __shfl_xor_sync(0xffffffffu, mx1, 2)); \
          const float n0 = fmaxf(c0, mx0 * SC), n1 = fmaxf(c1, mx1 * SC);                                              \
          const float a0 = ex2(c0 - n0), a1 = ex2(c1 - n1);                                                            \
          c0 = n0; c1 = n1;                                                                                            \
          l0 *= a0; l1 *= a1;                                                                                          \
          _Pragma("unroll") for (int i = 0; i < 24; i++) { o[4 * i] *= a0; o[4 * i + 1] *= a0; o[4 * i + 2] *= a1; o[4 * i + 3] *= a1; } \
          b0 = 0.f; b1 = 0.f;                                                                                          \
          _Pragma("unroll") for (int i = 0; i < 8; i++) {                                                              \
            const float e0 = ex2(fmaf(s[4 * i], SC, -c0)), e1 = ex2(fmaf(s[4 * i + 1], SC, -c0));                      \
            const float e2 = ex2(fmaf(s[4 * i + 2], SC, -c1)), e3 = ex2(fmaf(s[4 * i + 3], SC, -c1));                  \
            b0 += e0 + e1; b1 += e2 + e3;                                                                              \
            PN[2 * i] = pack_bf16(e0, e1); PN[2 * i + 1] = pack_bf16(e2, e3);                                          \
          }                                                                                                            \
        }                                                                                                              \
        l0 += b0; l1 += b1;                                                                                            \
      }
      for (int jj = 0; jj < 15; jj++) {
        A_STEP(p, p2, jj == 0)
        A_STEP(p2, p, false)
      }
      A_STEP(p, p2, false)
      TSA(item, 3);
      {
        const uint32_t sV = r.slot; mbar_wait(bar_full + 8 * sV, r.phase); r.adv(A_NSLOT);
        const uint64_t dv = mkdesc(sb + sV * A_SLOT, 8192, 1024);
        bar_sync(1 + w, 256);
        wg_fence();
#pragma unroll
        for (int kk = 0; kk < 4; kk++)
          wgmma_rs_n192<1>(o, p2[4 * kk], p2[4 * kk + 1], p2[4 * kk + 2], p2[4 * kk + 3], dv + kk * 128, 1);
        wg_commit();
        bar_arrive(1 + (w ^ 1), 256);
        wg_wait<0>();
        fence_regs(o);
        A_RELEASE(sV);
      }
      TSA(item, 4);
      l0 += __shfl_xor_sync(0xffffffffu, l0, 1); l1 += __shfl_xor_sync(0xffffffffu, l1, 1);
      l0 += __shfl_xor_sync(0xffffffffu, l0, 2); l1 += __shfl_xor_sync(0xffffffffu, l1, 2);
      const float i0 = 1.f / l0, i1 = 1.f / l1;
      bf16* orow = g_o + (size_t)(qtile * 128 + w * 64 + warp * 16 + (lane >> 2)) * HD_ + head * DH_ + (lane & 3) * 8;
#pragma unroll
      for (int g = 0; g < 6; g++) {
        uint32_t u0 = pack_bf16(o[16 * g + 0] * i0, o[16 * g + 1] * i0), u1 = pack_bf16(o[16 * g + 4] * i0, o[16 * g + 5] * i0);
        uint32_t u2 = pack_bf16(o[16 * g + 8] * i0, o[16 * g + 9] * i0), u3 = pack_bf16(o[16 * g + 12] * i0, o[16 * g + 13] * i0);
        quad_transpose(u0, u1, u2, u3, lane);
        *reinterpret_cast<uint4*>(orow + g * 32) = make_uint4(u0, u1, u2, u3);
        uint32_t v0 = pack_bf16(o[16 * g + 2] * i1, o[16 * g + 3] * i1), v1 = pack_bf16(o[16 * g + 6] * i1, o[16 * g + 7] * i1);
        uint32_t v2 = pack_bf16(o[16 * g + 10] * i1, o[16 * g + 11] * i1), v3 = pack_bf16(o[16 * g + 14] * i1, o[16 * g + 15] * i1);
        quad_transpose(v0, v1, v2, v3, lane);
        *reinterpret_cast<uint4*>(orow + (size_t)8 * HD_ + g * 32) = make_uint4(v0, v1, v2, v3);
      }
      SIGNAL();
      TSA(item, 5);
    }
    }
    TS(3, 2);
    const int rl = w * 64 + warp * 16 + (lane >> 2);
    const uint32_t pcol = par + (lane & 3) * 8;

    {
      float acc1[96], acc2[64];
      uint32_t p0 = 0, p1 = 0, p2 = 0;
      for (int kb = 0; kb < 24; kb++) {
        const uint32_t s1 = r.slot; mbar_wait(bar_full + 8 * s1, r.phase); r.adv(A_NSLOT);
        const uint32_t s2 = r.slot; mbar_wait(bar_full + 8 * s2, r.phase); r.adv(A_NSLOT);
        const uint32_t sa = r.slot; mbar_wait(bar_full + 8 * sa, r.phase); r.adv(A_NSLOT);
        const uint64_t da = mkdesc(sb + sa * A_SLOT + w * 8192, 16, 1024);
        const uint64_t d1 = mkdesc(sb + s1 * A_SLOT, 8192, 1024), d2 = mkdesc(sb + s2 * A_SLOT, 8192, 1024);
        wg_fence();
#pragma unroll
        for (int kk = 0; kk < 4; kk++) {
          wgmma_ss_n192<1>(acc1, da + kk * 2, d1 + kk * 128, (kb | kk) != 0);
          wgmma_ss_n128<1>(acc2, da + kk * 2, d2 + kk * 128, (kb | kk) != 0);
        }
        wg_commit();
        if (kb > 0) { wg_wait<1>(); A_RELEASE(p0); A_RELEASE(p1); A_RELEASE(p2); }
        p0 = s1; p1 = s2; p2 = sa;
        if (kb == 4) {
          if (tid == 255) flag_wait(g_flag + F_PREP, PREP_CTAS);
          bar_sync(5, 256);
          if (tid < 80) {
            parf[P_OGA + tid] = __ldcg(g_mod + 2 * D_ + o_col + tid); parf[P_OA + tid] = __ldcg(g_mod + 4 * D_ + o_col + tid); parf[P_OB + tid] = __ldcg(g_mod + 3 * D_ + o_col + tid);
            parf[P_VA + tid] = __ldcg(g_vec + js * 80 + tid); parf[P_VB + tid] = __ldcg(g_vec + D_ + js * 80 + tid); parf[P_VC + tid] = __ldcg(g_vec + 2 * D_ + js * 80 + tid);
            parf[P_A2 + tid] = __ldcg(g_mod + 4 * D_ + js * 80 + tid); parf[P_B2 + tid] = __ldcg(g_mod + 3 * D_ + js * 80 + tid); parf[P_GB + tid] = __ldcg(g_mod + 5 * D_ + js * 80 + tid);
          }
          if (tid < 192) parf[P_CS3 + tid] = __ldcg(g_vec + 3 * D_ + js * 192 + tid);
          if (tid >= 224) {
            float sa_ = 0.f, saa = 0.f, sab = 0.f, sbb = 0.f, sb1 = 0.f;
            for (int i = lane; i < D_; i += 32) {
              const float a = __ldcg(g_mod + 4 * D_ + i), b = __ldcg(g_mod + 3 * D_ + i);
              sa_ += a; saa = fmaf(a, a, saa); sab = fmaf(a, b, sab); sb1 += b; sbb = fmaf(b, b, sbb);
            }
            sa_ = warp_sum(sa_); saa = warp_sum(saa); sab = warp_sum(sab); sb1 = warp_sum(sb1); sbb = warp_sum(sbb);
            if (lane == 0) { parf[P_SC] = sa_; parf[P_SC + 1] = saa; parf[P_SC + 2] = sab; parf[P_SC + 3] = sb1; parf[P_SC + 4] = sbb; }
          }
        }
      }
      uint4 xv[5];
      const bf16* xrow = x + (size_t)(o_qt * 128 + rl) * D_ + o_col;
      frag80_load(xv, xrow, D_, lane);
      wg_wait<0>();
      fence_regs(acc1); fence_regs(acc2);
      A_RELEASE(p0); A_RELEASE(p1); A_RELEASE(p2);
      TS(0, 0);
      uint4* xb = g_xch + (size_t)((o_qt * 2 + o_nh) * 4) * (4 * 5 * 256);
      float at[40];
#pragma unroll
      for (int d = 0; d < 4; d++) {
        if (d != o_ks) {
          uint32_t u[20];
#pragma unroll
          for (int i = 0; i < 20; i++) {
            const int e = d * 40 + 2 * i;
            u[i] = (e < 96) ? pack_bf16(acc1[e < 96 ? e : 0], acc1[e < 96 ? e + 1 : 0]) : pack_bf16(acc2[e >= 96 ? e - 96 : 0], acc2[e >= 96 ? e - 95 : 0]);
          }
#pragma unroll
          for (int i = 0; i < 5; i++) xb[((d * 4 + o_ks) * 5 + i) * 256 + tid] = make_uint4(u[4 * i], u[4 * i + 1], u[4 * i + 2], u[4 * i + 3]);
        } else {
#pragma unroll
          for (int i = 0; i < 40; i++) { const int e = d * 40 + i; at[i] = (e < 96) ? acc1[e < 96 ? e : 0] : acc2[e >= 96 ? e - 96 : 0]; }
        }
      }
      SIGNAL();
      uint32_t xu[20];
      frag80_unpack(xv, xu, lane);
      bar_sync(5, 256);
      if (lane == 0) flag_wait(g_flag + F_XCH + ((o_qt * 2 + o_nh) * 4 + o_ks) * 2 + w, 3);
      __syncwarp();
      {
        uint4 v[3][5];
#pragma unroll
        for (int sc = 0; sc < 3; sc++) {
          const int src = sc + (sc >= o_ks ? 1 : 0);
#pragma unroll
          for (int i = 0; i < 5; i++) v[sc][i] = ldcg4(xb + ((o_ks * 4 + src) * 5 + i) * 256 + tid);
        }
#pragma unroll
        for (int sc = 0; sc < 3; sc++)
#pragma unroll
          for (int i = 0; i < 5; i++) {
            at[8 * i] += bf_lo(v[sc][i].x); at[8 * i + 1] += bf_hi(v[sc][i].x); at[8 * i + 2] += bf_lo(v[sc][i].y); at[8 * i + 3] += bf_hi(v[sc][i].y);
            at[8 * i + 4] += bf_lo(v[sc][i].z); at[8 * i + 5] += bf_hi(v[sc][i].z); at[8 * i + 6] += bf_lo(v[sc][i].w); at[8 * i + 7] += bf_hi(v[sc][i].w);
          }
      }
      TS(0, 1);
      float st[2][6];
#pragma unroll
      for (int h = 0; h < 2; h++)
#pragma unroll
        for (int i = 0; i < 6; i++) st[h][i] = 0.f;
      uint32_t ua[20];
#pragma unroll
      for (int nb = 0; nb < 10; nb++) {
        const float2 ga = lds_f2(pcol + (P_OGA + 8 * nb) * 4), a = lds_f2(pcol + (P_OA + 8 * nb) * 4), b = lds_f2(pcol + (P_OB + 8 * nb) * 4);
#pragma unroll
        for (int h = 0; h < 2; h++) {
          const uint32_t pk = pack_bf16(fmaf(ga.x, at[4 * nb + 2 * h], bf_lo(xu[2 * nb + h])), fmaf(ga.y, at[4 * nb + 2 * h + 1], bf_hi(xu[2 * nb + h])));
          ua[2 * nb + h] = pk;
          const float v0 = bf_lo(pk), v1 = bf_hi(pk);
          const float y0 = a.x * v0, y1 = a.y * v1;
          st[h][0] += v0 + v1; st[h][1] = fmaf(v0, v0, fmaf(v1, v1, st[h][1]));
          st[h][2] += y0 + y1; st[h][3] = fmaf(a.x, y0, fmaf(a.y, y1, st[h][3]));
          st[h][4] = fmaf(y0, y0, fmaf(y1, y1, st[h][4])); st[h][5] = fmaf(b.x, y0, fmaf(b.y, y1, st[h][5]));
        }
      }
      frag80_store(ua, g_xa + (size_t)(o_qt * 128 + rl) * D_ + o_col, D_, lane, 3);
#pragma unroll
      for (int h = 0; h < 2; h++)
#pragma unroll
        for (int i = 0; i < 6; i++) st[h][i] = quad_sum(st[h][i]);
      if ((lane & 3) < 2) {
        const int h = lane & 1;
        float* sp = g_st1 + (size_t)(o_qt * 128 + rl + 8 * h) * 8;
        const float s0 = h ? st[1][0] : st[0][0], s1 = h ? st[1][1] : st[0][1], s2 = h ? st[1][2] : st[0][2];
        const float s3 = h ? st[1][3] : st[0][3], s4 = h ? st[1][4] : st[0][4], s5 = h ? st[1][5] : st[0][5];
        asm volatile("red.global.add.v4.f32 [%0], {%1, %2, %3, %4};" :: "l"(sp), "f"(s0), "f"(s1), "f"(s2), "f"(s3) : "memory");
        asm volatile("red.global.add.v2.f32 [%0], {%1, %2};" :: "l"(sp + 4), "f"(s4), "f"(s5) : "memory");
      }
      SIGNAL();
      TS(0, 2);
    }
    Rings rr = to_rings(r);
#define T_WAIT(s_) mbar_wait(bar_full + 8 * (s_), rr.take(s_))

    const int grow = qt * 128 + rl;
#define T_GEMM80(ACC, NKB)                                                                                             \
    {                                                                                                                  \
      uint32_t pa = 0, pb = 0, sbq = 0;                                                                                \
      for (int kb = 0; kb < (NKB); kb++) {                                                                             \
        if (!(kb & 1)) { sbq = rr.nextB(); T_WAIT(sbq); }                                                               \
        const uint32_t sa = rr.nextA(); T_WAIT(sa);                                                                     \
        const uint64_t da = mkdesc(sb + sa * A_SLOT + w * 8192, 16, 1024);                                             \
        const uint64_t db = mkdesc(sb + sbq * A_SLOT + (kb & 1) * 10240, 16, 1024);                                    \
        wg_fence();                                                                                                    \
        _Pragma("unroll") for (int kk = 0; kk < 4; kk++) wgmma_ss_n80<0>(ACC, da + kk * 2, db + kk * 2, (kb | kk) != 0); \
        wg_commit();                                                                                                   \
        if (kb > 0) { wg_wait<1>(); A_RELEASE(pa); if (!(kb & 1)) A_RELEASE(pb); }                                     \
        pa = sa; pb = sbq;                                                                                             \
      }                                                                                                                \
      wg_wait<0>();                                                                                                    \
      fence_regs(ACC);                                                                                                 \
      A_RELEASE(pa); A_RELEASE(pb);                                                                                    \
    }

    float mu[2], rs[2];
    {
      float acc[40];
      T_GEMM80(acc, 10)
      TS(1, 0);
      float al[2], be[2], ga2[2], de[2];
#pragma unroll
      for (int h = 0; h < 2; h++) {
        const float4 s03 = __ldcg(reinterpret_cast<const float4*>(g_st1 + (size_t)(grow + 8 * h) * 8));
        const float2 s45 = __ldcg(reinterpret_cast<const float2*>(g_st1 + (size_t)(grow + 8 * h) * 8 + 4));
        const float m = s03.x * (1.f / D_);
        const float q1 = rsqrtf(fmaxf(s03.y * (1.f / D_) - m * m, 0.f) + LN_EPS);
        mu[h] = m; rs[h] = q1;
        const float sa = lds_f(par + P_SC * 4), saa = lds_f(par + (P_SC + 1) * 4), sab = lds_f(par + (P_SC + 2) * 4);
        const float sb1 = lds_f(par + (P_SC + 3) * 4), sbb = lds_f(par + (P_SC + 4) * 4);
        const float m2 = (q1 * (s03.z - m * sa) + sb1) * (1.f / D_);
        const float e2 = (q1 * q1 * (s45.x - 2.f * m * s03.w + m * m * saa) + 2.f * q1 * (s45.y - m * sab) + sbb) * (1.f / D_);
        const float r2 = rsqrtf(fmaxf(e2 - m2 * m2, 0.f) + LN_EPS);
        al[h] = r2 * q1; be[h] = -r2 * q1 * m; ga2[h] = r2; de[h] = -r2 * m2;
      }
      uint32_t u[20];
#pragma unroll
      for (int nb = 0; nb < 10; nb++) {
        const float2 va = lds_f2(pcol + (P_VA + 8 * nb) * 4), vb = lds_f2(pcol + (P_VB + 8 * nb) * 4), vc = lds_f2(pcol + (P_VC + 8 * nb) * 4);
#pragma unroll
        for (int h = 0; h < 2; h++) {
          const float z0 = fmaf(al[h], acc[4 * nb + 2 * h], fmaf(be[h], va.x, fmaf(ga2[h], vb.x, de[h] * vc.x)));
          const float z1 = fmaf(al[h], acc[4 * nb + 2 * h + 1], fmaf(be[h], va.y, fmaf(ga2[h], vb.y, de[h] * vc.y)));
          u[2 * nb + h] = pack_bf16(gelu_tanh(z0), gelu_tanh(z1));
        }
      }
      const int grp = js >> 1;
      const int sh = (grp == 0) ? 1 : (grp == 1) ? -1 : (grp == 2) ? 2 : -2;
      const int d0 = grow + sh, d1 = grow + 8 + sh;
      frag80_store(u, g_us + (ptrdiff_t)d0 * D_ + js * 80, D_, lane, (d0 >= 0 ? 1 : 0) | (d1 < S_ ? 2 : 0));
      if (sh > 0 ? (grow < sh) : (grow + 8 >= S_ + sh)) {
        bf16* zr = g_us + (size_t)(sh > 0 ? grow : grow + 8) * D_ + js * 80 + (lane & 3) * 8;
        *reinterpret_cast<uint4*>(zr) = make_uint4(0, 0, 0, 0);
        *reinterpret_cast<uint4*>(zr + 32) = make_uint4(0, 0, 0, 0);
        if ((lane & 3) < 2) *reinterpret_cast<uint4*>(zr + 64) = make_uint4(0, 0, 0, 0);
      }
      SIGNAL();
      TS(1, 1);
    }
    uint32_t xau[20], x1u[20];
    {
      uint4 xv[5];
      frag80_load(xv, g_xa + (size_t)grow * D_ + js * 80, D_, lane);
      float acc[40];
      T_GEMM80(acc, 10)
      TS(2, 0);
      frag80_unpack(xv, xau, lane);
      float s1[2] = {0.f, 0.f}, s2[2] = {0.f, 0.f};
#pragma unroll
      for (int nb = 0; nb < 10; nb++) {
        const float2 a = lds_f2(pcol + (P_A2 + 8 * nb) * 4), b = lds_f2(pcol + (P_B2 + 8 * nb) * 4);
#pragma unroll
        for (int h = 0; h < 2; h++) {
          const float h0 = fmaf(a.x * rs[h], bf_lo(xau[2 * nb + h]) - mu[h], b.x), h1 = fmaf(a.y * rs[h], bf_hi(xau[2 * nb + h]) - mu[h], b.y);
          const uint32_t pk = pack_bf16(h0 + acc[4 * nb + 2 * h], h1 + acc[4 * nb + 2 * h + 1]);
          x1u[2 * nb + h] = pk;
          const float v0 = bf_lo(pk), v1 = bf_hi(pk);
          s1[h] += v0 + v1; s2[h] = fmaf(v0, v0, fmaf(v1, v1, s2[h]));
        }
      }
      frag80_store(x1u, g_x1 + (size_t)grow * D_ + js * 80, D_, lane, 3);
      s1[0] = quad_sum(s1[0]); s1[1] = quad_sum(s1[1]); s2[0] = quad_sum(s2[0]); s2[1] = quad_sum(s2[1]);
      if ((lane & 3) < 2) {
        const int h = lane & 1;
        asm volatile("red.global.add.v2.f32 [%0], {%1, %2};" :: "l"(g_st2 + (size_t)(grow + 8 * h) * 2), "f"(h ? s1[1] : s1[0]), "f"(h ? s2[1] : s2[0]) : "memory");
      }
      SIGNAL();
      TS(2, 1);
    }
    {
      float acc[96];
      uint32_t pa = 0, pb = 0;
      for (int kb = 0; kb < 10; kb++) {
        const uint32_t s1 = rr.nextB(), sa = rr.nextA();
        T_WAIT(s1); T_WAIT(sa);
        const uint64_t da = mkdesc(sb + sa * A_SLOT + w * 8192, 16, 1024);
        const uint64_t d1 = mkdesc(sb + s1 * A_SLOT, 8192, 1024);
        wg_fence();
#pragma unroll
        for (int kk = 0; kk < 4; kk++) wgmma_ss_n192<1>(acc, da + kk * 2, d1 + kk * 128, (kb | kk) != 0);
        wg_commit();
        if (kb > 0) { wg_wait<1>(); A_RELEASE(pa); A_RELEASE(pb); }
        pa = sa; pb = s1;
      }
      const float2 q0 = __ldcg(reinterpret_cast<const float2*>(g_st2 + (size_t)grow * 2));
      const float2 q1 = __ldcg(reinterpret_cast<const float2*>(g_st2 + (size_t)(grow + 8) * 2));
      wg_wait<0>();
      fence_regs(acc);
      A_RELEASE(pa); A_RELEASE(pb);
      TS(3, 0);
      const float m0 = q0.x * (1.f / D_), m1 = q1.x * (1.f / D_);
      const float r0 = rsqrtf(fmaxf(q0.y * (1.f / D_) - m0 * m0, 0.f) + LN_EPS), r1 = rsqrtf(fmaxf(q1.y * (1.f / D_) - m1 * m1, 0.f) + LN_EPS);
      const float n0 = -r0 * m0, n1 = -r1 * m1;
      bf16* grow_p = g_g + (size_t)grow * F_ + js * 192 + (lane & 3) * 8;
#pragma unroll
      for (int gq = 0; gq < 6; gq++) {
        uint32_t u[4], v[4];
#pragma unroll
        for (int i = 0; i < 4; i++) {
          const int nb = gq * 4 + i;
          const float2 cs = lds_f2(pcol + (P_CS3 + 8 * nb) * 4);
          u[i] = pack_bf16(gelu_tanh(fmaf(r0, acc[4 * nb], n0 * cs.x)), gelu_tanh(fmaf(r0, acc[4 * nb + 1], n0 * cs.y)));
          v[i] = pack_bf16(gelu_tanh(fmaf(r1, acc[4 * nb + 2], n1 * cs.x)), gelu_tanh(fmaf(r1, acc[4 * nb + 3], n1 * cs.y)));
        }
        quad_transpose(u[0], u[1], u[2], u[3], lane);
        *reinterpret_cast<uint4*>(grow_p + gq * 32) = make_uint4(u[0], u[1], u[2], u[3]);
        quad_transpose(v[0], v[1], v[2], v[3], lane);
        *reinterpret_cast<uint4*>(grow_p + (size_t)8 * F_ + gq * 32) = make_uint4(v[0], v[1], v[2], v[3]);
      }
      SIGNAL();
      TS(3, 1);
    }
    {
      float acc[40];
      T_GEMM80(acc, 24)
      TS(1, 2);
      uint32_t u[20];
#pragma unroll
      for (int nb = 0; nb < 10; nb++) {
        const float2 gb = lds_f2(pcol + (P_GB + 8 * nb) * 4);
#pragma unroll
        for (int h = 0; h < 2; h++)
          u[2 * nb + h] = pack_bf16(fmaf(gb.x, bf_lo(x1u[2 * nb + h]) + acc[4 * nb + 2 * h], bf_lo(xau[2 * nb + h])),
                                    fmaf(gb.y, bf_hi(x1u[2 * nb + h]) + acc[4 * nb + 2 * h + 1], bf_hi(xau[2 * nb + h])));
      }
      frag80_store(u, out + (size_t)grow * D_ + js * 80, D_, lane, 3);
      TS(1, 3);
    }
    if ((threadIdx.x & 127) == 0) TL_END(2);
    cluster_sync();
  }
}

typedef CUresult (*EncFn)(CUtensorMap*, CUtensorMapDataType, cuuint32_t, void*, const cuuint64_t*, const cuuint64_t*,
                          const cuuint32_t*, const cuuint32_t*, CUtensorMapInterleave, CUtensorMapSwizzle,
                          CUtensorMapL2promotion, CUtensorMapFloatOOBfill);
static EncFn g_enc = nullptr;

static CUtensorMap map2d(const void* p, uint64_t rows, uint64_t cols, uint32_t box_rows) {
  CUtensorMap m;
  cuuint64_t gd[2] = {cols, rows}; cuuint64_t gs[1] = {cols * 2};
  cuuint32_t bx[2] = {64, box_rows}; cuuint32_t es[2] = {1, 1};
  g_enc(&m, CU_TENSOR_MAP_DATA_TYPE_BFLOAT16, 2, const_cast<void*>(p), gd, gs, bx, es, CU_TENSOR_MAP_INTERLEAVE_NONE,
        CU_TENSOR_MAP_SWIZZLE_128B, CU_TENSOR_MAP_L2_PROMOTION_L2_256B, CU_TENSOR_MAP_FLOAT_OOB_FILL_NONE);
  return m;
}
static CUtensorMap map3d(const void* p, uint64_t rows, uint64_t cols, uint32_t box_rows, uint32_t nblk) {
  CUtensorMap m;
  cuuint64_t gd[3] = {64, rows, cols / 64}; cuuint64_t gs[2] = {cols * 2, 128};
  cuuint32_t bx[3] = {64, box_rows, nblk}; cuuint32_t es[3] = {1, 1, 1};
  g_enc(&m, CU_TENSOR_MAP_DATA_TYPE_BFLOAT16, 3, const_cast<void*>(p), gd, gs, bx, es, CU_TENSOR_MAP_INTERLEAVE_NONE,
        CU_TENSOR_MAP_SWIZZLE_128B, CU_TENSOR_MAP_L2_PROMOTION_L2_256B, CU_TENSOR_MAP_FLOAT_OOB_FILL_NONE);
  return m;
}

template <typename... KArgs, typename... Args>
static void launch(void (*kern)(KArgs...), dim3 grid, dim3 block, int smem, bool pdl, Args... args) {
  cudaLaunchConfig_t cfg = {};
  cfg.gridDim = grid; cfg.blockDim = block; cfg.dynamicSmemBytes = smem; cfg.stream = cudaStreamPerThread;
  cudaLaunchAttribute at[1];
  at[0].id = cudaLaunchAttributeProgrammaticStreamSerialization;
  at[0].val.programmaticStreamSerializationAllowed = 1;
  cfg.attrs = at; cfg.numAttrs = pdl ? 1 : 0;
  cudaLaunchKernelEx(&cfg, kern, KArgs(args)...);
}

extern "C" void kernel_launch(void* const* d_in, const int* in_sizes, int n_in, void* d_out, int out_size) {
  const bf16* x = (const bf16*)d_in[0];
  const bf16* kc = (const bf16*)d_in[1];
  const bf16* vc = (const bf16*)d_in[2];
  const bf16* wq = (const bf16*)d_in[3];
  const bf16* wo = (const bf16*)d_in[4];
  const bf16* w1 = (const bf16*)d_in[6];
  const bf16* w2 = (const bf16*)d_in[7];
  const bf16* w3 = (const bf16*)d_in[8];
  const bf16* w4 = (const bf16*)d_in[9];
  const bf16* c = (const bf16*)d_in[10];
  const bf16* wmod = (const bf16*)d_in[11];
  bf16* out = (bf16*)d_out;

  static void *p_h, *p_o, *p_xa, *p_us, *p_x1, *p_g, *p_w1t, *p_w2t, *p_w4t;
  if (!g_enc) {
    void* fn = nullptr; cudaDriverEntryPointQueryResult qr;
    cudaGetDriverEntryPoint("cuTensorMapEncodeTiled", &fn, cudaEnableDefault, &qr);
    g_enc = (EncFn)fn;
    cudaGetSymbolAddress(&p_h, g_h); cudaGetSymbolAddress(&p_o, g_o); cudaGetSymbolAddress(&p_xa, g_xa);
    cudaGetSymbolAddress(&p_us, g_us); cudaGetSymbolAddress(&p_x1, g_x1); cudaGetSymbolAddress(&p_g, g_g);
    cudaGetSymbolAddress(&p_w1t, g_w1t); cudaGetSymbolAddress(&p_w2t, g_w2t); cudaGetSymbolAddress(&p_w4t, g_w4t);
    cudaFuncSetAttribute(fused_kernel, cudaFuncAttributeMaxDynamicSharedMemorySize, T_SMEM);
  }
  Maps tm;
  tm.h = map2d(p_h, S_, D_, 128);
  tm.wq = map3d(wq, D_, HD_, 64, 3);
  tm.k = map3d(kc, (uint64_t)H_ * S_, DH_, 64, 3);
  tm.v = map3d(vc, (uint64_t)H_ * S_, DH_, 64, 3);
  tm.o = map2d(p_o, S_, HD_, 128);
  tm.wo3 = map3d(wo, HD_, D_, 64, 3);
  tm.wo2 = map3d(wo, HD_, D_, 64, 2);
  tm.xa = map2d(p_xa, S_, D_, 64);
  tm.w1t = map3d(p_w1t, D_, D_, 80, 2);
  tm.us = map2d(p_us, S_, D_, 64);
  tm.w2t = map3d(p_w2t, D_, D_, 80, 2);
  tm.x1 = map2d(p_x1, S_, D_, 64);
  tm.w3 = map3d(w3, D_, F_, 64, 3);
  tm.g = map2d(p_g, S_, F_, 64);
  tm.w4t = map3d(p_w4t, D_, F_, 80, 2);
  PfList pf;
  pf.p[0] = (const uint8_t*)wo; pf.p[1] = (const uint8_t*)w3; pf.p[2] = (const uint8_t*)p_w4t;
  pf.p[3] = (const uint8_t*)x; pf.p[4] = (const uint8_t*)p_w1t; pf.p[5] = (const uint8_t*)p_w2t;

  launch(mod_kernel, dim3(120), dim3(256), 0, false, c, wmod);
  launch(ln1_kernel, dim3(256), dim3(256), 0, true, x);
  launch(fused_kernel, dim3(128), dim3(384), T_SMEM, true, tm, pf, PrepW{w1, w2, w3, w4}, x, out);
}
```

```cpp
#include <cuda_runtime.h>
#include <cuda.h>
#include <cuda_bf16.h>
#include <stdint.h>

typedef __nv_bfloat16 bf16;

constexpr int S_  = 2048;
constexpr int D_  = 640;
constexpr int H_  = 32;
constexpr int DH_ = 192;
constexpr int HD_ = H_ * DH_;
constexpr int F_  = 1536;
constexpr float LN_EPS = 1e-5f;

__device__ __forceinline__ uint32_t smem_u32(const void* p) { return (uint32_t)__cvta_generic_to_shared(p); }
__device__ __forceinline__ void mbar_init(uint32_t a, uint32_t c) { asm volatile("mbarrier.init.shared::cta.b64 [%0], %1;" :: "r"(a), "r"(c) : "memory"); }
__device__ __forceinline__ void mbar_expect(uint32_t a, uint32_t b) { asm volatile("mbarrier.arrive.expect_tx.shared::cta.b64 _, [%0], %1;" :: "r"(a), "r"(b) : "memory"); }
__device__ __forceinline__ void mbar_arrive(uint32_t a) { asm volatile("mbarrier.arrive.shared::cta.b64 _, [%0];" :: "r"(a) : "memory"); }
__device__ __forceinline__ void mbar_arrive_remote(uint32_t ra) { asm volatile("mbarrier.arrive.shared::cluster.b64 _, [%0];" :: "r"(ra) : "memory"); }
__device__ __forceinline__ uint32_t mapa(uint32_t a, uint32_t cta) { uint32_t r; asm volatile("mapa.shared::cluster.u32 %0, %1, %2;" : "=r"(r) : "r"(a), "r"(cta)); return r; }
__device__ __forceinline__ uint32_t mbar_try(uint32_t a, uint32_t ph) {
  uint32_t ok;
  asm volatile("{\n.reg .pred p;\nmbarrier.test_wait.parity.shared::cta.b64 p, [%1], %2;\nselp.u32 %0, 1, 0, p;\n}\n" : "=r"(ok) : "r"(a), "r"(ph) : "memory");
  return ok;
}
__device__ __forceinline__ void mbar_wait(uint32_t a, uint32_t ph) {
  asm volatile(
      "{\n.reg .pred p;\n.reg .u32 n;\n"
      "mov.u32 n, 0;\n"
      "SPIN:\n"
      "mbarrier.try_wait.parity.shared::cta.b64 p, [%0], %1;\n"
      "@p bra DONE;\n"
      "add.u32 n, n, 1;\n"
      "setp.le.u32 p, n, 16777216;\n"
      "@p bra SPIN;\n"
      "trap;\n"
      "DONE:\n}\n" :: "r"(a), "r"(ph) : "memory");
}
__device__ __forceinline__ void tma2d(uint32_t dst, const CUtensorMap* m, uint32_t bar, int c0, int c1) {
  asm volatile("cp.async.bulk.tensor.2d.shared::cluster.global.mbarrier::complete_tx::bytes [%0], [%1, {%3, %4}], [%2];"
               :: "r"(dst), "l"(m), "r"(bar), "r"(c0), "r"(c1) : "memory");
}
__device__ __forceinline__ void tma3d(uint32_t dst, const CUtensorMap* m, uint32_t bar, int c0, int c1, int c2) {
  asm volatile("cp.async.bulk.tensor.3d.shared::cluster.global.mbarrier::complete_tx::bytes [%0], [%1, {%3, %4, %5}], [%2];"
               :: "r"(dst), "l"(m), "r"(bar), "r"(c0), "r"(c1), "r"(c2) : "memory");
}
__device__ __forceinline__ void tma3d_mc(uint32_t dst, const CUtensorMap* m, uint32_t bar, int c0, int c1, int c2, uint16_t mask) {
  asm volatile("cp.async.bulk.tensor.3d.shared::cluster.global.mbarrier::complete_tx::bytes.multicast::cluster [%0], [%1, {%3, %4, %5}], [%2], %6;"
               :: "r"(dst), "l"(m), "r"(bar), "r"(c0), "r"(c1), "r"(c2), "h"(mask) : "memory");
}
__device__ __forceinline__ void prefetch_tmap(const CUtensorMap* m) { asm volatile("prefetch.tensormap [%0];" :: "l"(m) : "memory"); }
__device__ __forceinline__ void wg_fence() { asm volatile("wgmma.fence.sync.aligned;" ::: "memory"); }
__device__ __forceinline__ void wg_commit() { asm volatile("wgmma.commit_group.sync.aligned;" ::: "memory"); }
template <int N> __device__ __forceinline__ void wg_wait() { asm volatile("wgmma.wait_group.sync.aligned %0;" :: "n"(N) : "memory"); }
template <int N> __device__ __forceinline__ void fence_regs(float (&r)[N]) {
#pragma unroll
  for (int i = 0; i < N; i++) asm volatile("" : "+f"(r[i]) :: "memory");
}
template <int N> __device__ __forceinline__ void fence_regs(uint32_t (&r)[N]) {
#pragma unroll
  for (int i = 0; i < N; i++) asm volatile("" : "+r"(r[i]) :: "memory");
}
__device__ __forceinline__ uint64_t mkdesc(uint32_t addr, uint32_t lbo, uint32_t sbo) {
  return (uint64_t)((addr & 0x3FFFF) >> 4) | ((uint64_t)(lbo >> 4) << 16) | ((uint64_t)(sbo >> 4) << 32) | (1ull << 62);
}
__device__ __forceinline__ void bar_sync(int id, int n) { asm volatile("bar.sync %0, %1;" :: "r"(id), "r"(n) : "memory"); }
__device__ __forceinline__ void bar_arrive(int id, int n) { asm volatile("bar.arrive %0, %1;" :: "r"(id), "r"(n) : "memory"); }
__device__ __forceinline__ void cluster_sync() { asm volatile("barrier.cluster.arrive.aligned;\nbarrier.cluster.wait.aligned;" ::: "memory"); }
__device__ __forceinline__ void pdl_wait() { asm volatile("griddepcontrol.wait;" ::: "memory"); }
__device__ __forceinline__ void pdl_launch() { asm volatile("griddepcontrol.launch_dependents;" ::: "memory"); }
__device__ __forceinline__ float ex2(float x) { float y; asm("ex2.approx.ftz.f32 %0, %1;" : "=f"(y) : "f"(x)); return y; }
__device__ __forceinline__ uint32_t pack_bf16(float lo, float hi) { uint32_t r; asm("cvt.rn.bf16x2.f32 %0, %1, %2;" : "=r"(r) : "f"(hi), "f"(lo)); return r; }
__device__ __forceinline__ float bf_lo(uint32_t u) { return __uint_as_float(u << 16); }
__device__ __forceinline__ float bf_hi(uint32_t u) { return __uint_as_float(u & 0xffff0000u); }
__device__ __forceinline__ float bf_round(float x) { return __bfloat162float(__float2bfloat16_rn(x)); }
__device__ __forceinline__ float tanh_fast(float x) { float y; asm("tanh.approx.f32 %0, %1;" : "=f"(y) : "f"(x)); return y; }
__device__ __forceinline__ float gelu_tanh(float x) {
  float u = x * (0.7978845608028654f + 0.035677408136300125f * x * x);
  float hx = 0.5f * x;
  return fmaf(hx, tanh_fast(u), hx);
}
__device__ __forceinline__ float warp_sum(float v) {
#pragma unroll
  for (int o = 16; o > 0; o >>= 1) v += __shfl_xor_sync(0xffffffffu, v, o);
  return v;
}
__device__ __forceinline__ void quad_transpose(uint32_t& v0, uint32_t& v1, uint32_t& v2, uint32_t& v3, int lane) {
  const bool b0 = lane & 1, b1 = lane & 2;
  uint32_t s0 = b0 ? v0 : v1, s1 = b0 ? v2 : v3;
  s0 = __shfl_xor_sync(0xffffffffu, s0, 1); s1 = __shfl_xor_sync(0xffffffffu, s1, 1);
  if (b0) { v0 = s0; v2 = s1; } else { v1 = s0; v3 = s1; }
  uint32_t t0 = b1 ? v0 : v2, t1 = b1 ? v1 : v3;
  t0 = __shfl_xor_sync(0xffffffffu, t0, 2); t1 = __shfl_xor_sync(0xffffffffu, t1, 2);
  if (b1) { v0 = t0; v1 = t1; } else { v2 = t0; v3 = t1; }
}

#define TX(i)
#define TXC(i)
#define TSA(item, i)
#define TL_ENTRY(k)
#define TL_WAITED(k)
#define TL_END(k)
#define TS(item, i)
template<int TB> __device__ __forceinline__ void wgmma_rs_n64(float (&d)[32], uint32_t a0, uint32_t a1, uint32_t a2, uint32_t a3, uint64_t db, int scale_d) {
  asm volatile("{\n.reg .pred p;\nsetp.ne.b32 p, %37, 0;\n"
    "wgmma.mma_async.sync.aligned.m64n64k16.f32.bf16.bf16 {%0, %1, %2, %3, %4, %5, %6, %7, %8, %9, %10, %11, %12, %13, %14, %15, %16, %17, %18, %19, %20, %21, %22, %23, %24, %25, %26, %27, %28, %29, %30, %31}, {%32, %33, %34, %35}, %36, p, 1, 1, %38;\n}\n"
    : "+f"(d[0]), "+f"(d[1]), "+f"(d[2]), "+f"(d[3]), "+f"(d[4]), "+f"(d[5]), "+f"(d[6]), "+f"(d[7]), "+f"(d[8]), "+f"(d[9]), "+f"(d[10]), "+f"(d[11]), "+f"(d[12]), "+f"(d[13]), "+f"(d[14]), "+f"(d[15]), "+f"(d[16]), "+f"(d[17]), "+f"(d[18]), "+f"(d[19]), "+f"(d[20]), "+f"(d[21]), "+f"(d[22]), "+f"(d[23]), "+f"(d[24]), "+f"(d[25]), "+f"(d[26]), "+f"(d[27]), "+f"(d[28]), "+f"(d[29]), "+f"(d[30]), "+f"(d[31])
    : "r"(a0), "r"(a1), "r"(a2), "r"(a3), "l"(db), "r"(scale_d), "n"(TB));
}
template<int TB> __device__ __forceinline__ void wgmma_rs_n192(float (&d)[96], uint32_t a0, uint32_t a1, uint32_t a2, uint32_t a3, uint64_t db, int scale_d) {
  asm volatile("{\n.reg .pred p;\nsetp.ne.b32 p, %101, 0;\n"
    "wgmma.mma_async.sync.aligned.m64n192k16.f32.bf16.bf16 {%0, %1, %2, %3, %4, %5, %6, %7, %8, %9, %10, %11, %12, %13, %14, %15, %16, %17, %18, %19, %20, %21, %22, %23, %24, %25, %26, %27, %28, %29, %30, %31, %32, %33, %34, %35, %36, %37, %38, %39, %40, %41, %42, %43, %44, %45, %46, %47, %48, %49, %50, %51, %52, %53, %54, %55, %56, %57, %58, %59, %60, %61, %62, %63, %64, %65, %66, %67, %68, %69, %70, %71, %72, %73, %74, %75, %76, %77, %78, %79, %80, %81, %82, %83, %84, %85, %86, %87, %88, %89, %90, %91, %92, %93, %94, %95}, {%96, %97, %98, %99}, %100, p, 1, 1, %102;\n}\n"
    : "+f"(d[0]), "+f"(d[1]), "+f"(d[2]), "+f"(d[3]), "+f"(d[4]), "+f"(d[5]), "+f"(d[6]), "+f"(d[7]), "+f"(d[8]), "+f"(d[9]), "+f"(d[10]), "+f"(d[11]), "+f"(d[12]), "+f"(d[13]), "+f"(d[14]), "+f"(d[15]), "+f"(d[16]), "+f"(d[17]), "+f"(d[18]), "+f"(d[19]), "+f"(d[20]), "+f"(d[21]), "+f"(d[22]), "+f"(d[23]), "+f"(d[24]), "+f"(d[25]), "+f"(d[26]), "+f"(d[27]), "+f"(d[28]), "+f"(d[29]), "+f"(d[30]), "+f"(d[31]), "+f"(d[32]), "+f"(d[33]), "+f"(d[34]), "+f"(d[35]), "+f"(d[36]), "+f"(d[37]), "+f"(d[38]), "+f"(d[39]), "+f"(d[40]), "+f"(d[41]), "+f"(d[42]), "+f"(d[43]), "+f"(d[44]), "+f"(d[45]), "+f"(d[46]), "+f"(d[47]), "+f"(d[48]), "+f"(d[49]), "+f"(d[50]), "+f"(d[51]), "+f"(d[52]), "+f"(d[53]), "+f"(d[54]), "+f"(d[55]), "+f"(d[56]), "+f"(d[57]), "+f"(d[58]), "+f"(d[59]), "+f"(d[60]), "+f"(d[61]), "+f"(d[62]), "+f"(d[63]), "+f"(d[64]), "+f"(d[65]), "+f"(d[66]), "+f"(d[67]), "+f"(d[68]), "+f"(d[69]), "+f"(d[70]), "+f"(d[71]), "+f"(d[72]), "+f"(d[73]), "+f"(d[74]), "+f"(d[75]), "+f"(d[76]), "+f"(d[77]), "+f"(d[78]), "+f"(d[79]), "+f"(d[80]), "+f"(d[81]), "+f"(d[82]), "+f"(d[83]), "+f"(d[84]), "+f"(d[85]), "+f"(d[86]), "+f"(d[87]), "+f"(d[88]), "+f"(d[89]), "+f"(d[90]), "+f"(d[91]), "+f"(d[92]), "+f"(d[93]), "+f"(d[94]), "+f"(d[95])
    : "r"(a0), "r"(a1), "r"(a2), "r"(a3), "l"(db), "r"(scale_d), "n"(TB));
}
template<int TB> __device__ __forceinline__ void wgmma_ss_n128(float (&d)[64], uint64_t da, uint64_t db, int scale_d) {
  asm volatile("{\n.reg .pred p;\nsetp.ne.b32 p, %66, 0;\n"
    "wgmma.mma_async.sync.aligned.m64n128k16.f32.bf16.bf16 {%0, %1, %2, %3, %4, %5, %6, %7, %8, %9, %10, %11, %12, %13, %14, %15, %16, %17, %18, %19, %20, %21, %22, %23, %24, %25, %26, %27, %28, %29, %30, %31, %32, %33, %34, %35, %36, %37, %38, %39, %40, %41, %42, %43, %44, %45, %46, %47, %48, %49, %50, %51, %52, %53, %54, %55, %56, %57, %58, %59, %60, %61, %62, %63}, %64, %65, p, 1, 1, 0, %67;\n}\n"
    : "+f"(d[0]), "+f"(d[1]), "+f"(d[2]), "+f"(d[3]), "+f"(d[4]), "+f"(d[5]), "+f"(d[6]), "+f"(d[7]), "+f"(d[8]), "+f"(d[9]), "+f"(d[10]), "+f"(d[11]), "+f"(d[12]), "+f"(d[13]), "+f"(d[14]), "+f"(d[15]), "+f"(d[16]), "+f"(d[17]), "+f"(d[18]), "+f"(d[19]), "+f"(d[20]), "+f"(d[21]), "+f"(d[22]), "+f"(d[23]), "+f"(d[24]), "+f"(d[25]), "+f"(d[26]), "+f"(d[27]), "+f"(d[28]), "+f"(d[29]), "+f"(d[30]), "+f"(d[31]), "+f"(d[32]), "+f"(d[33]), "+f"(d[34]), "+f"(d[35]), "+f"(d[36]), "+f"(d[37]), "+f"(d[38]), "+f"(d[39]), "+f"(d[40]), "+f"(d[41]), "+f"(d[42]), "+f"(d[43]), "+f"(d[44]), "+f"(d[45]), "+f"(d[46]), "+f"(d[47]), "+f"(d[48]), "+f"(d[49]), "+f"(d[50]), "+f"(d[51]), "+f"(d[52]), "+f"(d[53]), "+f"(d[54]), "+f"(d[55]), "+f"(d[56]), "+f"(d[57]), "+f"(d[58]), "+f"(d[59]), "+f"(d[60]), "+f"(d[61]), "+f"(d[62]), "+f"(d[63])
    : "l"(da), "l"(db), "r"(scale_d), "n"(TB));
}
template<int TB> __device__ __forceinline__ void wgmma_ss_n192(float (&d)[96], uint64_t da, uint64_t db, int scale_d) {
  asm volatile("{\n.reg .pred p;\nsetp.ne.b32 p, %98, 0;\n"
    "wgmma.mma_async.sync.aligned.m64n192k16.f32.bf16.bf16 {%0, %1, %2, %3, %4, %5, %6, %7, %8, %9, %10, %11, %12, %13, %14, %15, %16, %17, %18, %19, %20, %21, %22, %23, %24, %25, %26, %27, %28, %29, %30, %31, %32, %33, %34, %35, %36, %37, %38, %39, %40, %41, %42, %43, %44, %45, %46, %47, %48, %49, %50, %51, %52, %53, %54, %55, %56, %57, %58, %59, %60, %61, %62, %63, %64, %65, %66, %67, %68, %69, %70, %71, %72, %73, %74, %75, %76, %77, %78, %79, %80, %81, %82, %83, %84, %85, %86, %87, %88, %89, %90, %91, %92, %93, %94, %95}, %96, %97, p, 1, 1, 0, %99;\n}\n"
    : "+f"(d[0]), "+f"(d[1]), "+f"(d[2]), "+f"(d[3]), "+f"(d[4]), "+f"(d[5]), "+f"(d[6]), "+f"(d[7]), "+f"(d[8]), "+f"(d[9]), "+f"(d[10]), "+f"(d[11]), "+f"(d[12]), "+f"(d[13]), "+f"(d[14]), "+f"(d[15]), "+f"(d[16]), "+f"(d[17]), "+f"(d[18]), "+f"(d[19]), "+f"(d[20]), "+f"(d[21]), "+f"(d[22]), "+f"(d[23]), "+f"(d[24]), "+f"(d[25]), "+f"(d[26]), "+f"(d[27]), "+f"(d[28]), "+f"(d[29]), "+f"(d[30]), "+f"(d[31]), "+f"(d[32]), "+f"(d[33]), "+f"(d[34]), "+f"(d[35]), "+f"(d[36]), "+f"(d[37]), "+f"(d[38]), "+f"(d[39]), "+f"(d[40]), "+f"(d[41]), "+f"(d[42]), "+f"(d[43]), "+f"(d[44]), "+f"(d[45]), "+f"(d[46]), "+f"(d[47]), "+f"(d[48]), "+f"(d[49]), "+f"(d[50]), "+f"(d[51]), "+f"(d[52]), "+f"(d[53]), "+f"(d[54]), "+f"(d[55]), "+f"(d[56]), "+f"(d[57]), "+f"(d[58]), "+f"(d[59]), "+f"(d[60]), "+f"(d[61]), "+f"(d[62]), "+f"(d[63]), "+f"(d[64]), "+f"(d[65]), "+f"(d[66]), "+f"(d[67]), "+f"(d[68]), "+f"(d[69]), "+f"(d[70]), "+f"(d[71]), "+f"(d[72]), "+f"(d[73]), "+f"(d[74]), "+f"(d[75]), "+f"(d[76]), "+f"(d[77]), "+f"(d[78]), "+f"(d[79]), "+f"(d[80]), "+f"(d[81]), "+f"(d[82]), "+f"(d[83]), "+f"(d[84]), "+f"(d[85]), "+f"(d[86]), "+f"(d[87]), "+f"(d[88]), "+f"(d[89]), "+f"(d[90]), "+f"(d[91]), "+f"(d[92]), "+f"(d[93]), "+f"(d[94]), "+f"(d[95])
    : "l"(da), "l"(db), "r"(scale_d), "n"(TB));
}
template<int TB> __device__ __forceinline__ void wgmma_ss_n80(float (&d)[40], uint64_t da, uint64_t db, int scale_d) {
  asm volatile("{\n.reg .pred p;\nsetp.ne.b32 p, %42, 0;\n"
    "wgmma.mma_async.sync.aligned.m64n80k16.f32.bf16.bf16 {%0, %1, %2, %3, %4, %5, %6, %7, %8, %9, %10, %11, %12, %13, %14, %15, %16, %17, %18, %19, %20, %21, %22, %23, %24, %25, %26, %27, %28, %29, %30, %31, %32, %33, %34, %35, %36, %37, %38, %39}, %40, %41, p, 1, 1, 0, %43;\n}\n"
    : "+f"(d[0]), "+f"(d[1]), "+f"(d[2]), "+f"(d[3]), "+f"(d[4]), "+f"(d[5]), "+f"(d[6]), "+f"(d[7]), "+f"(d[8]), "+f"(d[9]), "+f"(d[10]), "+f"(d[11]), "+f"(d[12]), "+f"(d[13]), "+f"(d[14]), "+f"(d[15]), "+f"(d[16]), "+f"(d[17]), "+f"(d[18]), "+f"(d[19]), "+f"(d[20]), "+f"(d[21]), "+f"(d[22]), "+f"(d[23]), "+f"(d[24]), "+f"(d[25]), "+f"(d[26]), "+f"(d[27]), "+f"(d[28]), "+f"(d[29]), "+f"(d[30]), "+f"(d[31]), "+f"(d[32]), "+f"(d[33]), "+f"(d[34]), "+f"(d[35]), "+f"(d[36]), "+f"(d[37]), "+f"(d[38]), "+f"(d[39])
    : "l"(da), "l"(db), "r"(scale_d), "n"(TB));
}

__device__ float g_mod[6 * D_];
__device__ __align__(1024) bf16 g_h[S_ * D_];
__device__ __align__(1024) bf16 g_o[S_ * HD_];
__device__ __align__(1024) bf16 g_xch[16 * 2 * 4 * 4 * 128 * 80];
__device__ __align__(1024) bf16 g_w1t[D_ * D_];
__device__ __align__(1024) bf16 g_w2t[D_ * D_];
__device__ __align__(1024) bf16 g_w4t[D_ * F_];
__device__ __align__(32) float g_st1[S_ * 8];
__device__ __align__(32) float g_st2[S_ * 2];
__device__ __align__(32) float g_vec[3 * D_ + F_ + 8];
__device__ unsigned g_flag[1024];
enum { F_XCH = 0, F_XA = 256, F_US = 272, F_X1 = 288, F_G = 304, F_PREP = 320, F_O = 512 };
__device__ __align__(1024) bf16 g_xa[S_ * D_];
__device__ __align__(1024) bf16 g_us[S_ * D_];
__device__ __align__(1024) bf16 g_x1[S_ * D_];
__device__ __align__(1024) bf16 g_g[S_ * F_];

__global__ void __launch_bounds__(256) mod_kernel(const bf16* __restrict__ c, const bf16* __restrict__ w_mod) {
  TL_ENTRY(0);
  pdl_launch();
  __shared__ float red[8][32];
  if (blockIdx.x < 14) { const int i = blockIdx.x * 256 + threadIdx.x; if (i < 3 * D_ + F_) g_vec[i] = 0.f; }
  else if (blockIdx.x < 18) g_flag[(blockIdx.x - 14) * 256 + threadIdx.x] = 0u;
  const int t = threadIdx.x, cg = t & 3, r0 = t >> 2;
  const int col0 = blockIdx.x * 32 + cg * 8;
  uint4 w[10];
#pragma unroll
  for (int i = 0; i < 10; i++) w[i] = __ldg(reinterpret_cast<const uint4*>(w_mod + (size_t)(r0 + 64 * i) * (6 * D_) + col0));
  float acc[8];
#pragma unroll
  for (int j = 0; j < 8; j++) acc[j] = 0.f;
#pragma unroll
  for (int i = 0; i < 10; i++) {
    float cv = __bfloat162float(c[r0 + 64 * i]);
    float s = bf_round(cv / (1.f + __expf(-cv)));
    acc[0] = fmaf(s, bf_lo(w[i].x), acc[0]); acc[1] = fmaf(s, bf_hi(w[i].x), acc[1]);
    acc[2] = fmaf(s, bf_lo(w[i].y), acc[2]); acc[3] = fmaf(s, bf_hi(w[i].y), acc[3]);
    acc[4] = fmaf(s, bf_lo(w[i].z), acc[4]); acc[5] = fmaf(s, bf_hi(w[i].z), acc[5]);
    acc[6] = fmaf(s, bf_lo(w[i].w), acc[6]); acc[7] = fmaf(s, bf_hi(w[i].w), acc[7]);
  }
#pragma unroll
  for (int j = 0; j < 8; j++) {
    acc[j] += __shfl_xor_sync(0xffffffffu, acc[j], 4);
    acc[j] += __shfl_xor_sync(0xffffffffu, acc[j], 8);
    acc[j] += __shfl_xor_sync(0xffffffffu, acc[j], 16);
  }
  if ((t & 31) < 4) {
#pragma unroll
    for (int j = 0; j < 8; j++) red[t >> 5][cg * 8 + j] = acc[j];
  }
  __syncthreads();
  if (t < 32) {
    float s = 0.f;
#pragma unroll
    for (int w8 = 0; w8 < 8; w8++) s += red[w8][t];
    const int col = blockIdx.x * 32 + t;
    s = bf_round(s);
    const int part = col / D_;
    if (part == 1 || part == 4) s = bf_round(1.f + s);
    g_mod[col] = s;
    if (t == 0) TL_END(0);
  }
}

__device__ __forceinline__ void row_stats(const float (&v)[20], float& mean, float& rstd) {
  float s = 0.f;
#pragma unroll
  for (int i = 0; i < 20; i++) s += v[i];
  mean = warp_sum(s) * (1.f / D_);
  float q = 0.f;
#pragma unroll
  for (int i = 0; i < 20; i++) { float d = v[i] - mean; q = fmaf(d, d, q); }
  rstd = rsqrtf(warp_sum(q) * (1.f / D_) + LN_EPS);
}
__device__ __forceinline__ void load_row_bf16(const bf16* p, int lane, float (&v)[20]) {
#pragma unroll
  for (int i = 0; i < 5; i++) {
    uint2 u = *reinterpret_cast<const uint2*>(p + (lane + 32 * i) * 4);
    v[4 * i] = bf_lo(u.x); v[4 * i + 1] = bf_hi(u.x); v[4 * i + 2] = bf_lo(u.y); v[4 * i + 3] = bf_hi(u.y);
  }
}
__device__ __forceinline__ void store_row_bf16(bf16* p, int lane, const float (&v)[20]) {
#pragma unroll
  for (int i = 0; i < 5; i++) {
    uint2 u; u.x = pack_bf16(v[4 * i], v[4 * i + 1]); u.y = pack_bf16(v[4 * i + 2], v[4 * i + 3]);
    *reinterpret_cast<uint2*>(p + (lane + 32 * i) * 4) = u;
  }
}
__device__ __forceinline__ void load_row_f32(const float* p, int lane, float (&v)[20]) {
#pragma unroll
  for (int i = 0; i < 5; i++) {
    float4 u = *reinterpret_cast<const float4*>(p + (lane + 32 * i) * 4);
    v[4 * i] = u.x; v[4 * i + 1] = u.y; v[4 * i + 2] = u.z; v[4 * i + 3] = u.w;
  }
}

__global__ void __launch_bounds__(256) ln1_kernel(const bf16* __restrict__ x) {
  TL_ENTRY(1);
  pdl_launch();
  const int lane = threadIdx.x & 31, row = blockIdx.x * 8 + (threadIdx.x >> 5);
  float v[20];
  load_row_bf16(x + (size_t)row * D_, lane, v);
  float mean, rstd;
  row_stats(v, mean, rstd);
  if (lane < 8) g_st1[row * 8 + lane] = 0.f;
  if (lane < 2) g_st2[row * 2 + lane] = 0.f;
  pdl_wait();
  if (threadIdx.x == 0) TL_WAITED(1);
  float sa[20], ca[20];
  load_row_f32(g_mod, lane, sa);
  load_row_f32(g_mod + D_, lane, ca);
#pragma unroll
  for (int i = 0; i < 20; i++) v[i] = fmaf((v[i] - mean) * rstd, ca[i], sa[i]);
  store_row_bf16(g_h + (size_t)row * D_, lane, v);
  if (threadIdx.x == 0) TL_END(1);
}

constexpr int PREP_JOBS = 200 + 200 + 480 + 480;
struct PrepW { const bf16 *w1, *w2, *w3, *w4; };
__device__ __forceinline__ void prep_warp(const PrepW& pw, bf16 (*tile)[72], int lane) {
#pragma unroll 1
  for (int job = blockIdx.x; job < PREP_JOBS; job += gridDim.x) {
    const bf16* src; bf16* dst; int ld = D_, ldd = D_, kt, nt, kind = 1;
    if (job < 200) { src = pw.w1; dst = g_w1t; kt = job / 10; nt = job % 10; kind = 0; }
    else if (job < 400) { src = pw.w2; dst = g_w2t; kt = (job - 200) / 10; nt = (job - 200) % 10; }
    else if (job < 880) { src = pw.w4; dst = g_w4t; ldd = F_; kt = (job - 400) / 10; nt = (job - 400) % 10; }
    else { src = pw.w3; dst = nullptr; ld = F_; kt = (job - 880) / 24; nt = (job - 880) % 24; kind = 2; }
    src += (size_t)(kt * 32 + (lane >> 3)) * ld + nt * 64 + (lane & 7) * 8;
    __syncwarp();
#pragma unroll
    for (int h = 0; h < 2; h++) {
      uint4 v[4];
#pragma unroll
      for (int i = 0; i < 4; i++) v[i] = __ldg(reinterpret_cast<const uint4*>(src + (size_t)(h * 16 + i * 4) * ld));
#pragma unroll
      for (int i = 0; i < 4; i++) *reinterpret_cast<uint4*>(&tile[h * 16 + i * 4 + (lane >> 3)][(lane & 7) * 8]) = v[i];
    }
    __syncwarp();
    const float* pa = g_mod + 4 * D_ + kt * 32;
    const float* pb = g_mod + 3 * D_ + kt * 32;
#pragma unroll 1
    for (int h = 0; h < 2; h++) {
      const int n = lane + 32 * h;
      float sa = 0.f, sb = 0.f, sc = 0.f;
#pragma unroll 1
      for (int c = 0; c < 4; c++) {
        uint32_t u[4];
#pragma unroll
        for (int e = 0; e < 4; e++) {
          const int k = c * 8 + 2 * e;
          float lo = __bfloat162float(tile[k][n]), hi = __bfloat162float(tile[k + 1][n]);
          sc += lo + hi;
          if (kind == 0) {
            const float2 a = __ldcg(reinterpret_cast<const float2*>(pa + k)), b = __ldcg(reinterpret_cast<const float2*>(pb + k));
            sb = fmaf(b.x, lo, fmaf(b.y, hi, sb));
            lo *= a.x; hi *= a.y;
          }
          u[e] = pack_bf16(lo, hi);
          sa += bf_lo(u[e]) + bf_hi(u[e]);
        }
        if (kind != 2) *reinterpret_cast<uint4*>(dst + (size_t)(nt * 64 + n) * ldd + kt * 32 + c * 8) = make_uint4(u[0], u[1], u[2], u[3]);
      }
      if (kind == 0) { atomicAdd(&g_vec[nt * 64 + n], sa); atomicAdd(&g_vec[D_ + nt * 64 + n], sb); atomicAdd(&g_vec[2 * D_ + nt * 64 + n], sc); }
      else if (kind == 2) atomicAdd(&g_vec[3 * D_ + nt * 64 + n], sc);
    }
  }
  __syncwarp();
  if (lane == 0) {
    asm volatile("fence.acq_rel.gpu;" ::: "memory");
    asm volatile("red.relaxed.gpu.global.add.u32 [%0], 1;" :: "l"(g_flag + F_PREP) : "memory");
  }
}

constexpr int A_NSLOT = 9;
constexpr int A_SLOT = 24576;
constexpr int A_NKV = S_ / 64;
constexpr int PREP_CTAS = 128;

struct Ring {
  uint32_t slot, phase;
  __device__ __forceinline__ void adv(int n) { if (++slot == (uint32_t)n) { slot = 0; phase ^= 1; } }
};
constexpr int T_PAR = A_NSLOT * A_SLOT + 256;
constexpr int T_PREP = T_PAR + 3712;
constexpr int T_SMEM = T_PREP + 32 * 72 * 2 + 1024;
enum { P_OGA = 0, P_OA = 80, P_OB = 160, P_VA = 240, P_VB = 320, P_VC = 400, P_A2 = 480, P_B2 = 560, P_GB = 640, P_CS3 = 720, P_SC = 912 };

__device__ __forceinline__ void flag_wait(const unsigned* p, unsigned target) {
  asm volatile(
      "{\n.reg .pred p;\n.reg .u32 n, v;\n"
      "mov.u32 n, 0;\n"
      "SPIN:\n"
      "ld.relaxed.gpu.global.u32 v, [%0];\n"
      "setp.ge.u32 p, v, %1;\n"
      "@p bra DONE;\n"
      "add.u32 n, n, 1;\n"
      "setp.gt.u32 p, n, 4194304;\n"
      "@p trap;\n"
      "bra SPIN;\n"
      "DONE:\n}\n" :: "l"(p), "r"(target) : "memory");
}
__device__ __forceinline__ void fence_async_global() { asm volatile("fence.proxy.async.global;" ::: "memory"); }
__device__ __forceinline__ float lds_f(uint32_t a) { float v; asm volatile("ld.shared.f32 %0, [%1];" : "=f"(v) : "r"(a)); return v; }
__device__ __forceinline__ float2 lds_f2(uint32_t a) { float2 v; asm volatile("ld.shared.v2.f32 {%0, %1}, [%2];" : "=f"(v.x), "=f"(v.y) : "r"(a)); return v; }
__device__ __forceinline__ uint4 ldcg4(const void* p) { return __ldcg(reinterpret_cast<const uint4*>(p)); }

__device__ __forceinline__ void sts_f2(uint32_t a, float x, float y) { asm volatile("st.shared.v2.f32 [%0], {%1, %2};" :: "r"(a), "f"(x), "f"(y) : "memory"); }
__device__ __forceinline__ float4 lds_f4(uint32_t a) { float4 v; asm volatile("ld.shared.v4.f32 {%0, %1, %2, %3}, [%4];" : "=f"(v.x), "=f"(v.y), "=f"(v.z), "=f"(v.w) : "r"(a) : "memory"); return v; }
__device__ __forceinline__ uint4 lds_u4(uint32_t a) { uint4 v; asm volatile("ld.shared.v4.u32 {%0, %1, %2, %3}, [%4];" : "=r"(v.x), "=r"(v.y), "=r"(v.z), "=r"(v.w) : "r"(a) : "memory"); return v; }
__device__ __forceinline__ void lds8(uint32_t a, float (&v)[8]) {
  const float4 p = lds_f4(a), q = lds_f4(a + 16);
  v[0] = p.x; v[1] = p.y; v[2] = p.z; v[3] = p.w; v[4] = q.x; v[5] = q.y; v[6] = q.z; v[7] = q.w;
}
__device__ __forceinline__ void lds8_bf(uint32_t a, float (&v)[8]) {
  const uint4 u = lds_u4(a);
  v[0] = bf_lo(u.x); v[1] = bf_hi(u.x); v[2] = bf_lo(u.y); v[3] = bf_hi(u.y); v[4] = bf_lo(u.z); v[5] = bf_hi(u.z); v[6] = bf_lo(u.w); v[7] = bf_hi(u.w);
}
__device__ __forceinline__ uint4 pack8(const float (&v)[8]) {
  return make_uint4(pack_bf16(v[0], v[1]), pack_bf16(v[2], v[3]), pack_bf16(v[4], v[5]), pack_bf16(v[6], v[7]));
}
__device__ __forceinline__ void mbar_wait_c(uint32_t a, uint32_t ph) {
  asm volatile("{\n.reg .pred p;\nSPIN:\nmbarrier.try_wait.parity.shared::cta.b64 p, [%0], %1;\n@!p bra SPIN;\n}\n" :: "r"(a), "r"(ph) : "memory");
}
constexpr int ST_P = 88;
constexpr int E_TILE = 128 * 80 * 2;

struct Maps { CUtensorMap h, wq, k, v, o, wo3, wo2, xa, w1t, us, w2t, x1, w3, g, w4t, ex, exa, ex1; };
struct PfList { const uint8_t* p[6]; };

struct Rings {
  uint32_t a, b, par;
  __device__ __forceinline__ uint32_t nextA() { uint32_t s = 5 + a; a = (a + 1) & 3; return s; }
  __device__ __forceinline__ uint32_t nextB() { uint32_t s = b; b = (b == 4) ? 0 : b + 1; return s; }
  __device__ __forceinline__ uint32_t take(uint32_t s) { uint32_t p = (par >> s) & 1; par ^= 1u << s; return p; }
};
__device__ __forceinline__ Rings to_rings(const Ring& r) {
  const uint32_t lo = (1u << r.slot) - 1u;
  return Rings{0, 0, r.phase ? (0x1ffu & ~lo) : lo};
}

__global__ void __cluster_dims__(2, 1, 1) __launch_bounds__(384, 1)
fused_kernel(const __grid_constant__ Maps tm, const __grid_constant__ PfList pf, const __grid_constant__ PrepW pw, const bf16* __restrict__ x, bf16* __restrict__ out) {
  extern __shared__ uint8_t smem_raw[];
  const uint32_t sb = (smem_u32(smem_raw) + 1023) & ~1023u;
  TL_ENTRY(2);
  const uint32_t bar_full = sb + A_NSLOT * A_SLOT;
  const uint32_t bar_empty = bar_full + 8 * A_NSLOT;
  const uint32_t bar_sig = bar_empty + 8 * A_NSLOT;
  const uint32_t par = sb + T_PAR;
  float* parf = reinterpret_cast<float*>(smem_raw + (par - smem_u32(smem_raw)));
  uint32_t rank;
  asm volatile("mov.u32 %0, %%cluster_ctarank;" : "=r"(rank));
  const int cid = blockIdx.x >> 1;
  const int wg = threadIdx.x >> 7;
  const int qtile = (cid & 7) * 2 + rank, hbase = cid >> 3;
  const int o_qt = qtile, o_nh = (cid >> 3) & 1, o_ks = cid >> 4;
  const int o_col = o_nh * 320 + o_ks * 80;
  const int qt = cid >> 2, js = (cid & 3) * 2 + rank;
  if (threadIdx.x == 0) {
    for (int i = 0; i < A_NSLOT; i++) { mbar_init(bar_full + 8 * i, 1); mbar_init(bar_empty + 8 * i, 16); }
    mbar_init(bar_sig, 4); mbar_init(bar_sig + 8, 4);
    asm volatile("fence.mbarrier_init.release.cluster;" ::: "memory");
    prefetch_tmap(&tm.h); prefetch_tmap(&tm.wq); prefetch_tmap(&tm.k); prefetch_tmap(&tm.v);
  }
  __syncthreads();
  cluster_sync();

  if (wg == 0) {
    asm volatile("setmaxnreg.dec.sync.aligned.u32 40;");
    if (threadIdx.x == 0) {
      Ring r{0, 1};
#define P_ACQ(bytes_) do { mbar_wait(bar_empty + 8 * r.slot, r.phase); mbar_expect(bar_full + 8 * r.slot, bytes_); } while (0)
#define P_DST (sb + r.slot * A_SLOT)
#define P_BAR (bar_full + 8 * r.slot)
      pdl_wait();
      TL_WAITED(2);
#pragma unroll 1
      for (int item = 0; item < 4; item++) {
        const int head = hbase + 8 * item;
#pragma unroll 1
        for (int kb = 0; kb < 10; kb++) {
          P_ACQ(16384);
          tma2d(P_DST, &tm.h, P_BAR, kb * 64, qtile * 128);
          r.adv(A_NSLOT);
          P_ACQ(A_SLOT);
          if ((uint32_t)(kb & 1) == rank) tma3d_mc(P_DST, &tm.wq, P_BAR, 0, kb * 64, head * 3, 3);
          r.adv(A_NSLOT);
        }
#pragma unroll 1
        for (int j = 0; j <= A_NKV; j++) {
          if (j < A_NKV) {
            P_ACQ(A_SLOT);
            if (rank == 0) tma3d_mc(P_DST, &tm.k, P_BAR, 0, head * S_ + j * 64, 0, 3);
            r.adv(A_NSLOT);
          }
          if (j > 0) {
            P_ACQ(A_SLOT);
            if (rank == 1) tma3d_mc(P_DST, &tm.v, P_BAR, 0, head * S_ + (j - 1) * 64, 0, 3);
            r.adv(A_NSLOT);
          }
          if (item == 3 && (j & 3) == 0) {
            const int c = (j >> 2) * 128 + blockIdx.x;
            if (c < 980) {
              const int li = c < 480 ? 0 : c < 600 ? 1 : c < 720 ? 2 : c < 880 ? 3 : c < 930 ? 4 : 5;
              const int c0 = c < 480 ? 0 : c < 600 ? 480 : c < 720 ? 600 : c < 880 ? 720 : c < 930 ? 880 : 930;
              asm volatile("cp.async.bulk.prefetch.L2.global [%0], 16384;" :: "l"(pf.p[li] + (size_t)(c - c0) * 16384) : "memory");
            }
            if (j == 0) {
              prefetch_tmap(&tm.o); prefetch_tmap(&tm.wo3); prefetch_tmap(&tm.wo2); prefetch_tmap(&tm.xa); prefetch_tmap(&tm.w1t); prefetch_tmap(&tm.us);
              prefetch_tmap(&tm.w2t); prefetch_tmap(&tm.x1); prefetch_tmap(&tm.w3); prefetch_tmap(&tm.g); prefetch_tmap(&tm.w4t);
              prefetch_tmap(&tm.ex); prefetch_tmap(&tm.exa); prefetch_tmap(&tm.ex1);
            }
          }
        }
      }
#pragma unroll 1
      for (int kb = 0; kb < 24; kb++) {
        const int head = (kb / 6) * 8 + 2 * o_ks + (kb % 6) / 3;
        const int kcol = head * DH_ + (kb % 3) * 64;
        P_ACQ(24576);
        if (rank == 0) tma3d_mc(P_DST, &tm.wo3, P_BAR, 0, kcol, o_nh * 5, 3);
        r.adv(A_NSLOT);
        P_ACQ(16384);
        if (rank == 1) tma3d_mc(P_DST, &tm.wo2, P_BAR, 0, kcol, o_nh * 5 + 3, 3);
        r.adv(A_NSLOT);
        if (kb % 3 == 0) { flag_wait(g_flag + F_O + o_qt * 32 + head, 2); fence_async_global(); }
        P_ACQ(16384);
        tma2d(P_DST, &tm.o, P_BAR, kcol, o_qt * 128);
        r.adv(A_NSLOT);
      }
      P_ACQ(E_TILE);
      tma2d(P_DST, &tm.ex, P_BAR, o_col, o_qt * 128);
      r.adv(A_NSLOT);
      flag_wait(g_flag + F_XCH + (o_qt * 2 + o_nh) * 4 + o_ks, 6);
      fence_async_global();
#pragma unroll 1
      for (int i = 0; i < 3; i++) {
        P_ACQ(E_TILE);
        asm volatile("cp.async.bulk.shared::cluster.global.mbarrier::complete_tx::bytes [%0], [%1], %2, [%3];"
                     :: "r"(P_DST), "l"(g_xch + (size_t)((((o_qt * 2 + o_nh) * 4 + o_ks) * 4) + ((o_ks + 1 + i) & 3)) * (E_TILE / 2)), "r"(E_TILE), "r"(P_BAR) : "memory");
        r.adv(A_NSLOT);
      }
      Rings rr = to_rings(r);
#define T_ACQ(s_, bytes_) do { mbar_wait(bar_empty + 8 * (s_), rr.take(s_)); mbar_expect(bar_full + 8 * (s_), bytes_); } while (0)
      flag_wait(g_flag + F_PREP, PREP_CTAS);
      fence_async_global();
#pragma unroll 1
      for (int ph = 0; ph < 4; ph++) {
        const CUtensorMap* ma = ph == 0 ? &tm.xa : ph == 1 ? &tm.us : ph == 2 ? &tm.x1 : &tm.g;
        const CUtensorMap* mb = ph == 0 ? &tm.w1t : ph == 1 ? &tm.w2t : ph == 2 ? &tm.w3 : &tm.w4t;
        const int nkb = ph == 3 ? 24 : 10;
        const int nbl = ph == 2 ? 10 : nkb / 2;
        const int nel = ph == 1 ? 1 : ph == 3 ? 2 : 0;
        int bl = 0;
#define T_LOADB() do { const uint32_t s_ = rr.nextB();                                                               \
                       T_ACQ(s_, (ph == 2) ? 24576 : 20480);                                                          \
                       if (bl < nbl) tma3d(sb + s_ * A_SLOT, mb, bar_full + 8 * s_, 0, ph == 2 ? bl * 64 : js * 80, ph == 2 ? js * 3 : bl * 2); \
                       else tma2d(sb + s_ * A_SLOT, bl == nbl ? &tm.exa : &tm.ex1, bar_full + 8 * s_, js * 80, qt * 128); \
                       bl++; } while (0)
#pragma unroll 1
        for (int i = 0; i < 5; i++) T_LOADB();
        TX(8 + ph * 4);
        const unsigned* fl = g_flag + F_XA + 16 * ph;
        flag_wait(fl + qt, 16);
        if (ph == 1) { flag_wait(fl + ((qt + 15) & 15), 16); flag_wait(fl + ((qt + 1) & 15), 16); }
        TX(9 + ph * 4);
        fence_async_global();
#pragma unroll 1
        for (int kb = 0; kb < nkb; kb++) {
          const uint32_t s = rr.nextA(); T_ACQ(s, 16384);
          asm volatile("cp.async.bulk.tensor.2d.shared::cluster.global.mbarrier::complete_tx::bytes.multicast::cluster [%0], [%1, {%3, %4}], [%2], %5;"
                       :: "r"(sb + s * A_SLOT + rank * 8192), "l"(ma), "r"(bar_full + 8 * s), "r"(kb * 64), "r"(qt * 128 + (int)rank * 64), "h"((uint16_t)3) : "memory");
          if (bl < nbl + nel && kb >= (ph == 2 ? bl - 2 : 2 * bl - 6)) T_LOADB();
        }
      }
    } else if (threadIdx.x >= 32 && threadIdx.x < 96) {
      const int w = (threadIdx.x >> 5) - 1, lane = threadIdx.x & 31;
#pragma unroll 1
      for (int sig = 0; sig < 9; sig++) {
        mbar_wait(bar_sig + 8 * w, sig & 1);
        if (threadIdx.x == 32) TX(32 + sig * 2);
        unsigned* f;
        bool act = lane == 0;
        if (sig < 4) f = g_flag + F_O + qtile * 32 + hbase + 8 * sig;
        else if (sig == 4) { f = g_flag + F_XCH + (o_qt * 2 + o_nh) * 4 + (lane & 3); act = lane < 4 && lane != o_ks; }
        else if (sig == 5) f = g_flag + F_XA + o_qt;
        else f = g_flag + F_XA + 16 * (sig - 5) + qt;
        if (act) {
          asm volatile("fence.acq_rel.gpu;" ::: "memory");
          asm volatile("red.relaxed.gpu.global.add.u32 [%0], 1;" :: "l"(f) : "memory");
        }
        if (threadIdx.x == 32) TX(33 + sig * 2);
        __syncwarp();
      }
    } else if (threadIdx.x >= 96) {
      pdl_wait();
      prep_warp(pw, reinterpret_cast<bf16(*)[72]>(smem_raw + (sb + T_PREP - smem_u32(smem_raw))), threadIdx.x & 31);
    }
    __syncwarp();
    cluster_sync();
  } else {
    asm volatile("setmaxnreg.inc.sync.aligned.u32 232;");
    const int w = wg - 1;
    const int lane = threadIdx.x & 31;
    const int warp = (threadIdx.x >> 5) & 3;
    const int tid = threadIdx.x - 128;
    const uint32_t rel_base = mapa(bar_empty, (lane == 0) ? rank : (rank ^ 1));
    Ring r{0, 0};
#define A_RELEASE(slot_) do { if (lane < 2) mbar_arrive_remote(rel_base + 8 * (slot_)); } while (0)
#define SIGNAL() do { __syncwarp(); if (lane == 0) mbar_arrive(bar_sig + 8 * w); } while (0)
    {
    const float SC = 0.07216878364870322f * 1.4426950408889634f;
    float o[96];
    uint32_t q[48];
    float s[32];
    uint32_t p[16], p2[16];
    if (w == 1) bar_arrive(1, 256);
    for (int item = 0; item < 4; item++) {
      const int head = hbase + 8 * item;
      TSA(item, 0);
      uint32_t prevA = 0, prevB = 0;
      for (int kb = 0; kb < 10; kb++) {
        const uint32_t sA = r.slot; mbar_wait_c(bar_full + 8 * sA, r.phase); r.adv(A_NSLOT);
        const uint32_t sB = r.slot; mbar_wait_c(bar_full + 8 * sB, r.phase); r.adv(A_NSLOT);
        const uint64_t da = mkdesc(sb + sA * A_SLOT + w * 8192, 16, 1024);
        const uint64_t db = mkdesc(sb + sB * A_SLOT, 8192, 1024);
        wg_fence();
#pragma unroll
        for (int kk = 0; kk < 4; kk++) wgmma_ss_n192<1>(o, da + kk * 2, db + kk * 128, (kb | kk) != 0);
        wg_commit();
        if (kb > 0) { wg_wait<1>(); A_RELEASE(prevA); A_RELEASE(prevB); }
        prevA = sA; prevB = sB;
      }
      wg_wait<0>();
      fence_regs(o);
      A_RELEASE(prevA); A_RELEASE(prevB);
#pragma unroll
      for (int i = 0; i < 48; i++) q[i] = pack_bf16(o[2 * i], o[2 * i + 1]);

      TSA(item, 1);
      float c0, c1, l0, l1;
      {
        const uint32_t sK = r.slot; mbar_wait_c(bar_full + 8 * sK, r.phase); r.adv(A_NSLOT);
        const uint64_t dk = mkdesc(sb + sK * A_SLOT, 16, 1024);
        bar_sync(1 + w, 256);
        wg_fence();
#pragma unroll
        for (int kk = 0; kk < 12; kk++)
          wgmma_rs_n64<0>(s, q[4 * kk], q[4 * kk + 1], q[4 * kk + 2], q[4 * kk + 3], dk + (kk >> 2) * 512 + (kk & 3) * 2, kk != 0);
        wg_commit();
        bar_arrive(1 + (w ^ 1), 256);
        wg_wait<0>();
        fence_regs(s);
        A_RELEASE(sK);
        float mx0 = fmaxf(s[0], s[1]), mx1 = fmaxf(s[2], s[3]);
#pragma unroll
        for (int i = 1; i < 8; i++) { mx0 = fmaxf(mx0, fmaxf(s[4 * i], s[4 * i + 1])); mx1 = fmaxf(mx1, fmaxf(s[4 * i + 2], s[4 * i + 3])); }
        mx0 = fmaxf(mx0, __shfl_xor_sync(0xffffffffu, mx0, 1)); mx1 = fmaxf(mx1, __shfl_xor_sync(0xffffffffu, mx1, 1));
        mx0 = fmaxf(mx0, __shfl_xor_sync(0xffffffffu, mx0, 2)); mx1 = fmaxf(mx1, __shfl_xor_sync(0xffffffffu, mx1, 2));
        c0 = mx0 * SC; c1 = mx1 * SC;
        l0 = 0.f; l1 = 0.f;
#pragma unroll
        for (int i = 0; i < 8; i++) {
          s[4 * i] = ex2(fmaf(s[4 * i], SC, -c0)); s[4 * i + 1] = ex2(fmaf(s[4 * i + 1], SC, -c0));
          s[4 * i + 2] = ex2(fmaf(s[4 * i + 2], SC, -c1)); s[4 * i + 3] = ex2(fmaf(s[4 * i + 3], SC, -c1));
          l0 += s[4 * i] + s[4 * i + 1]; l1 += s[4 * i + 2] + s[4 * i + 3];
        }
#pragma unroll
        for (int i = 0; i < 16; i++) p[i] = pack_bf16(s[2 * i], s[2 * i + 1]);
      }
      TSA(item, 2);
      uint32_t okn;
      {
        Ring r2 = r; r2.adv(A_NSLOT);
        okn = mbar_try(bar_full + 8 * r.slot, r.phase) & mbar_try(bar_full + 8 * r2.slot, r2.phase);
      }
#define A_STEP(PC, PN, FIRST)                                                                                          \
      {                                                                                                                \
        const uint32_t sK = r.slot, phK = r.phase; r.adv(A_NSLOT);                                                     \
        const uint32_t sV = r.slot, phV = r.phase; r.adv(A_NSLOT);                                                     \
        const uint64_t dk = mkdesc(sb + sK * A_SLOT, 16, 1024);                                                        \
        const uint64_t dv = mkdesc(sb + sV * A_SLOT, 8192, 1024);                                                      \
        if (!okn) { mbar_wait_c(bar_full + 8 * sK, phK); mbar_wait_c(bar_full + 8 * sV, phV); }                            \
        bar_sync(1 + w, 256);                                                                                          \
        wg_fence();                                                                                                    \
        _Pragma("unroll") for (int kk = 0; kk < 12; kk++)                                                              \
          wgmma_rs_n64<0>(s, q[4 * kk], q[4 * kk + 1], q[4 * kk + 2], q[4 * kk + 3], dk + (kk >> 2) * 512 + (kk & 3) * 2, kk != 0); \
        wg_commit();                                                                                                   \
        _Pragma("unroll") for (int kk = 0; kk < 4; kk++)                                                               \
          wgmma_rs_n192<1>(o, PC[4 * kk], PC[4 * kk + 1], PC[4 * kk + 2], PC[4 * kk + 3], dv + kk * 128, !(FIRST) || (kk != 0)); \
        wg_commit();                                                                                                   \
        bar_arrive(1 + (w ^ 1), 256);                                                                                  \
        {                                                                                                              \
          Ring r2 = r; r2.adv(A_NSLOT);                                                                                \
          okn = mbar_try(bar_full + 8 * r.slot, r.phase) & mbar_try(bar_full + 8 * r2.slot, r2.phase);                 \
        }                                                                                                              \
        wg_wait<1>();                                                                                                  \
        fence_regs(s);                                                                                                 \
        A_RELEASE(sK);                                                                                                 \
        float b0 = 0.f, b1 = 0.f;                                                                                      \
        _Pragma("unroll") for (int i = 0; i < 8; i++) {                                                                \
          const float e0 = ex2(fmaf(s[4 * i], SC, -c0)), e1 = ex2(fmaf(s[4 * i + 1], SC, -c0));                        \
          const float e2 = ex2(fmaf(s[4 * i + 2], SC, -c1)), e3 = ex2(fmaf(s[4 * i + 3], SC, -c1));                    \
          b0 += e0 + e1; b1 += e2 + e3;                                                                                \
          PN[2 * i] = pack_bf16(e0, e1); PN[2 * i + 1] = pack_bf16(e2, e3);                                            \
        }                                                                                                              \
        wg_wait<0>();                                                                                                  \
        fence_regs(o);                                                                                                 \
        fence_regs(PC);                                                                                                \
        A_RELEASE(sV);                                                                                                 \
        if (__any_sync(0xffffffffu, !(b0 <= 65536.f) || !(b1 <= 65536.f))) {                                           \
          float mx0 = fmaxf(s[0], s[1]), mx1 = fmaxf(s[2], s[3]);                                                      \
          _Pragma("unroll") for (int i = 1; i < 8; i++) {                                                              \
            mx0 = fmaxf(mx0, fmaxf(s[4 * i], s[4 * i + 1])); mx1 = fmaxf(mx1, fmaxf(s[4 * i + 2], s[4 * i + 3]));     \
          }                                                                                                            \
          mx0 = fmaxf(mx0, __shfl_xor_sync(0xffffffffu, mx0, 1)); mx1 = fmaxf(mx1, __shfl_xor_sync(0xffffffffu, mx1, 1)); \
          mx0 = fmaxf(mx0, __shfl_xor_sync(0xffffffffu, mx0, 2)); mx1 = fmaxf(mx1, __shfl_xor_sync(0xffffffffu, mx1, 2)); \
          const float n0 = fmaxf(c0, mx0 * SC), n1 = fmaxf(c1, mx1 * SC);                                              \
          const float a0 = ex2(c0 - n0), a1 = ex2(c1 - n1);                                                            \
          c0 = n0; c1 = n1;                                                                                            \
          l0 *= a0; l1 *= a1;                                                                                          \
          _Pragma("unroll") for (int i = 0; i < 24; i++) { o[4 * i] *= a0; o[4 * i + 1] *= a0; o[4 * i + 2] *= a1; o[4 * i + 3] *= a1; } \
          b0 = 0.f; b1 = 0.f;                                                                                          \
          _Pragma("unroll") for (int i = 0; i < 8; i++) {                                                              \
            const float e0 = ex2(fmaf(s[4 * i], SC, -c0)), e1 = ex2(fmaf(s[4 * i + 1], SC, -c0));                      \
            const float e2 = ex2(fmaf(s[4 * i + 2], SC, -c1)), e3 = ex2(fmaf(s[4 * i + 3], SC, -c1));                  \
            b0 += e0 + e1; b1 += e2 + e3;                                                                              \
            PN[2 * i] = pack_bf16(e0, e1); PN[2 * i + 1] = pack_bf16(e2, e3);                                          \
          }                                                                                                            \
        }                                                                                                              \
        l0 += b0; l1 += b1;                                                                                            \
      }
      for (int jj = 0; jj < 15; jj++) {
        A_STEP(p, p2, jj == 0)
        A_STEP(p2, p, false)
      }
      A_STEP(p, p2, false)
      TSA(item, 3);
      {
        const uint32_t sV = r.slot; mbar_wait_c(bar_full + 8 * sV, r.phase); r.adv(A_NSLOT);
        const uint64_t dv = mkdesc(sb + sV * A_SLOT, 8192, 1024);
        bar_sync(1 + w, 256);
        wg_fence();
#pragma unroll
        for (int kk = 0; kk < 4; kk++)
          wgmma_rs_n192<1>(o, p2[4 * kk], p2[4 * kk + 1], p2[4 * kk + 2], p2[4 * kk + 3], dv + kk * 128, 1);
        wg_commit();
        bar_arrive(1 + (w ^ 1), 256);
        wg_wait<0>();
        fence_regs(o);
        A_RELEASE(sV);
      }
      TSA(item, 4);
      l0 += __shfl_xor_sync(0xffffffffu, l0, 1); l1 += __shfl_xor_sync(0xffffffffu, l1, 1);
      l0 += __shfl_xor_sync(0xffffffffu, l0, 2); l1 += __shfl_xor_sync(0xffffffffu, l1, 2);
      const float i0 = 1.f / l0, i1 = 1.f / l1;
      bf16* orow = g_o + (size_t)(qtile * 128 + w * 64 + warp * 16 + (lane >> 2)) * HD_ + head * DH_ + (lane & 3) * 8;
#pragma unroll
      for (int g = 0; g < 6; g++) {
        uint32_t u0 = pack_bf16(o[16 * g + 0] * i0, o[16 * g + 1] * i0), u1 = pack_bf16(o[16 * g + 4] * i0, o[16 * g + 5] * i0);
        uint32_t u2 = pack_bf16(o[16 * g + 8] * i0, o[16 * g + 9] * i0), u3 = pack_bf16(o[16 * g + 12] * i0, o[16 * g + 13] * i0);
        quad_transpose(u0, u1, u2, u3, lane);
        *reinterpret_cast<uint4*>(orow + g * 32) = make_uint4(u0, u1, u2, u3);
        uint32_t v0 = pack_bf16(o[16 * g + 2] * i1, o[16 * g + 3] * i1), v1 = pack_bf16(o[16 * g + 6] * i1, o[16 * g + 7] * i1);
        uint32_t v2 = pack_bf16(o[16 * g + 10] * i1, o[16 * g + 11] * i1), v3 = pack_bf16(o[16 * g + 14] * i1, o[16 * g + 15] * i1);
        quad_transpose(v0, v1, v2, v3, lane);
        *reinterpret_cast<uint4*>(orow + (size_t)8 * HD_ + g * 32) = make_uint4(v0, v1, v2, v3);
      }
      SIGNAL();
      TSA(item, 5);
    }
    }
    TS(3, 2);
    const uint32_t st_w = (uint32_t)((warp * 16 + (lane >> 2)) * ST_P + (lane & 3) * 2) * 4;
    const int er = (tid & 127) >> 1, eh = tid & 1;
    const uint32_t st_r = (uint32_t)(er * ST_P + eh * 8) * 4;
    const uint32_t e_r = (uint32_t)((w * 64 + er) * 160 + eh * 16);
    const uint32_t p_r = par + eh * 32;
#define STAGE10(ACC, BASE)                                                                                             \
    _Pragma("unroll") for (int nb = 0; nb < 10; nb++) {                                                                \
      sts_f2(stg + st_w + nb * 32, ACC(BASE + 4 * nb), ACC(BASE + 4 * nb + 1));                                        \
      sts_f2(stg + st_w + nb * 32 + 8 * ST_P * 4, ACC(BASE + 4 * nb + 2), ACC(BASE + 4 * nb + 3));                     \
    }

    {
      float acc1[96], acc2[64];
      uint32_t p0 = 0, p1 = 0, p2 = 0;
#pragma unroll 1
      for (int kb = 0; kb < 24; kb++) {
        const uint32_t s1 = r.slot; mbar_wait_c(bar_full + 8 * s1, r.phase); r.adv(A_NSLOT);
        const uint32_t s2 = r.slot; mbar_wait_c(bar_full + 8 * s2, r.phase); r.adv(A_NSLOT);
        const uint32_t sa = r.slot; mbar_wait_c(bar_full + 8 * sa, r.phase); r.adv(A_NSLOT);
        const uint64_t da = mkdesc(sb + sa * A_SLOT + w * 8192, 16, 1024);
        const uint64_t d1 = mkdesc(sb + s1 * A_SLOT, 8192, 1024), d2 = mkdesc(sb + s2 * A_SLOT, 8192, 1024);
        wg_fence();
#pragma unroll
        for (int kk = 0; kk < 4; kk++) {
          wgmma_ss_n192<1>(acc1, da + kk * 2, d1 + kk * 128, (kb | kk) != 0);
          wgmma_ss_n128<1>(acc2, da + kk * 2, d2 + kk * 128, (kb | kk) != 0);
        }
        wg_commit();
        if (kb > 0) { wg_wait<1>(); A_RELEASE(p0); A_RELEASE(p1); A_RELEASE(p2); }
        p0 = s1; p1 = s2; p2 = sa;
        if (kb == 4) {
          if (tid == 255) flag_wait(g_flag + F_PREP, PREP_CTAS);
          bar_sync(5, 256);
#pragma unroll 1
          for (int i = tid; i < P_SC; i += 256) {
            const int v = i < P_CS3 ? i / 80 : 9, j = i - (i < P_CS3 ? v * 80 : P_CS3);
            const float* src = v == 0 ? g_mod + 2 * D_ + o_col : v == 1 ? g_mod + 4 * D_ + o_col : v == 2 ? g_mod + 3 * D_ + o_col
                             : v < 6 ? g_vec + (v - 3) * D_ + js * 80 : v == 6 ? g_mod + 4 * D_ + js * 80 : v == 7 ? g_mod + 3 * D_ + js * 80
                             : v == 8 ? g_mod + 5 * D_ + js * 80 : g_vec + 3 * D_ + js * 192;
            parf[i] = __ldcg(src + j);
          }
          if (tid >= 224) {
            float sv[5] = {0.f, 0.f, 0.f, 0.f, 0.f};
#pragma unroll 1
            for (int i = lane; i < D_; i += 32) {
              const float a = __ldcg(g_mod + 4 * D_ + i), b = __ldcg(g_mod + 3 * D_ + i);
              sv[0] += a; sv[1] = fmaf(a, a, sv[1]); sv[2] = fmaf(a, b, sv[2]); sv[3] += b; sv[4] = fmaf(b, b, sv[4]);
            }
#pragma unroll 1
            for (int o_ = 16; o_ > 0; o_ >>= 1) {
#pragma unroll
              for (int i = 0; i < 5; i++) sv[i] += __shfl_xor_sync(0xffffffffu, sv[i], o_);
            }
            if (lane == 0) {
#pragma unroll
              for (int i = 0; i < 5; i++) parf[P_SC + i] = sv[i];
            }
          }
        }
      }
      wg_wait<0>();
      fence_regs(acc1); fence_regs(acc2);
      A_RELEASE(p2);
      bar_sync(5, 256);
      TS(0, 0);
      const uint32_t stg = sb + (w ? p1 : p0) * A_SLOT;
#define OACC(e) (((e) < 96) ? acc1[(e) < 96 ? (e) : 0] : acc2[(e) >= 96 ? (e) - 96 : 0])
#pragma unroll 1
      for (int i = 0; i < 4; i++) {
        const int d = (o_ks + 1 + i) & 3;
        if (d == 0) { STAGE10(OACC, 0) } else if (d == 1) { STAGE10(OACC, 40) } else if (d == 2) { STAGE10(OACC, 80) } else { STAGE10(OACC, 120) }
        bar_sync(3 + w, 128);
        if (i < 3) {
          uint8_t* dst = reinterpret_cast<uint8_t*>(g_xch + (size_t)((((o_qt * 2 + o_nh) * 4 + d) * 4) + o_ks) * (E_TILE / 2)) + e_r;
#pragma unroll 1
          for (int c = 0; c < 5; c++) {
            float v[8];
            lds8(stg + st_r + c * 64, v);
            *reinterpret_cast<uint4*>(dst + c * 32) = pack8(v);
          }
          if (i == 2) SIGNAL();
          bar_sync(3 + w, 128);
        }
      }
      const uint32_t sx = r.slot; mbar_wait_c(bar_full + 8 * sx, r.phase); r.adv(A_NSLOT);
      const uint32_t q0 = r.slot; mbar_wait_c(bar_full + 8 * q0, r.phase); r.adv(A_NSLOT);
      const uint32_t q1 = r.slot; mbar_wait_c(bar_full + 8 * q1, r.phase); r.adv(A_NSLOT);
      const uint32_t q2 = r.slot; mbar_wait_c(bar_full + 8 * q2, r.phase); r.adv(A_NSLOT);
      TS(0, 1);
      float st[6] = {0.f, 0.f, 0.f, 0.f, 0.f, 0.f};
      bf16* dst = g_xa + (size_t)(o_qt * 128 + w * 64 + er) * D_ + o_col + eh * 8;
#pragma unroll 1
      for (int c = 0; c < 5; c++) {
        float v[8], t0[8], t1[8], t2[8];
        lds8(stg + st_r + c * 64, v);
        lds8_bf(sb + q0 * A_SLOT + e_r + c * 32, t0); lds8_bf(sb + q1 * A_SLOT + e_r + c * 32, t1); lds8_bf(sb + q2 * A_SLOT + e_r + c * 32, t2);
#pragma unroll
        for (int e = 0; e < 8; e++) v[e] += (t0[e] + t1[e]) + t2[e];
        lds8_bf(sb + sx * A_SLOT + e_r + c * 32, t0);
        lds8(p_r + P_OGA * 4 + c * 64, t1);
#pragma unroll
        for (int e = 0; e < 8; e++) v[e] = fmaf(t1[e], v[e], t0[e]);
        const uint4 pk = pack8(v);
        *reinterpret_cast<uint4*>(dst + c * 16) = pk;
        v[0] = bf_lo(pk.x); v[1] = bf_hi(pk.x); v[2] = bf_lo(pk.y); v[3] = bf_hi(pk.y); v[4] = bf_lo(pk.z); v[5] = bf_hi(pk.z); v[6] = bf_lo(pk.w); v[7] = bf_hi(pk.w);
        lds8(p_r + P_OA * 4 + c * 64, t1);
        lds8(p_r + P_OB * 4 + c * 64, t2);
#pragma unroll
        for (int e = 0; e < 8; e++) {
          const float y = t1[e] * v[e];
          st[0] += v[e]; st[1] = fmaf(v[e], v[e], st[1]); st[2] += y; st[3] = fmaf(t1[e], y, st[3]); st[4] = fmaf(y, y, st[4]); st[5] = fmaf(t2[e], y, st[5]);
        }
      }
#pragma unroll
      for (int i = 0; i < 6; i++) st[i] += __shfl_xor_sync(0xffffffffu, st[i], 1);
      if (eh == 0) {
        float* sp = g_st1 + (size_t)(o_qt * 128 + w * 64 + er) * 8;
        asm volatile("red.global.add.v4.f32 [%0], {%1, %2, %3, %4};" :: "l"(sp), "f"(st[0]), "f"(st[1]), "f"(st[2]), "f"(st[3]) : "memory");
        asm volatile("red.global.add.v2.f32 [%0], {%1, %2};" :: "l"(sp + 4), "f"(st[4]), "f"(st[5]) : "memory");
      }
      SIGNAL();
      bar_sync(5, 256);
      A_RELEASE(p0); A_RELEASE(p1); A_RELEASE(sx); A_RELEASE(q0); A_RELEASE(q1); A_RELEASE(q2);
      TS(0, 2);
    }

    Rings rr = to_rings(r);
#define T_WAIT(s_) mbar_wait_c(bar_full + 8 * (s_), rr.take(s_))
    const int grow = qt * 128 + w * 64 + er;
    float mu = 0.f, rs = 0.f;
#pragma unroll 1
    for (int ph = 0; ph < 4; ph++) {
      float acc[96];
      float (&acc80)[40] = *reinterpret_cast<float(*)[40]>(&acc[0]);
      uint32_t pa = 0, pb = 0, sbq = 0;
      float4 s03 = make_float4(0.f, 0.f, 0.f, 0.f);
      float2 s45 = make_float2(0.f, 0.f);
      const int nkb = ph == 3 ? 24 : 10;
#pragma unroll 1
      for (int kb = 0; kb < nkb; kb++) {
        if (ph == 2 || !(kb & 1)) { sbq = rr.nextB(); T_WAIT(sbq); }
        const uint32_t sa = rr.nextA(); T_WAIT(sa);
        const uint64_t da = mkdesc(sb + sa * A_SLOT + w * 8192, 16, 1024);
        if (ph == 2) {
          const uint64_t db = mkdesc(sb + sbq * A_SLOT, 8192, 1024);
          wg_fence();
#pragma unroll
          for (int kk = 0; kk < 4; kk++) wgmma_ss_n192<1>(acc, da + kk * 2, db + kk * 128, (kb | kk) != 0);
        } else {
          const uint64_t db = mkdesc(sb + sbq * A_SLOT + (kb & 1) * 10240, 16, 1024);
          wg_fence();
#pragma unroll
          for (int kk = 0; kk < 4; kk++) wgmma_ss_n80<0>(acc80, da + kk * 2, db + kk * 2, (kb | kk) != 0);
        }
        wg_commit();
        if (kb > 0) { wg_wait<1>(); A_RELEASE(pa); if (ph == 2 || !(kb & 1)) A_RELEASE(pb); }
        else {
          if (ph == 0) { s03 = __ldcg(reinterpret_cast<const float4*>(g_st1 + (size_t)grow * 8)); s45 = __ldcg(reinterpret_cast<const float2*>(g_st1 + (size_t)grow * 8 + 4)); }
          if (ph == 2) s45 = __ldcg(reinterpret_cast<const float2*>(g_st2 + (size_t)grow * 2));
        }
        pa = sa; pb = sbq;
      }
      wg_wait<0>();
      fence_regs(acc);
      bar_sync(5, 256);
      TS(1 + (ph == 3 ? 0 : ph), ph == 3 ? 2 : 0);
      const uint32_t stg = sb + (w ? pb : pa) * A_SLOT;
#define MACC(e) acc[e]
      if (!(ph & 1)) {
        float c0, c1, c2 = 0.f, c3 = 0.f;
        bf16* dst; bool ok = true;
        if (ph == 0) {
          const float4 sc = lds_f4(par + P_SC * 4);
          const float sbb = lds_f(par + (P_SC + 4) * 4);
          mu = s03.x * (1.f / D_);
          rs = rsqrtf(fmaxf(s03.y * (1.f / D_) - mu * mu, 0.f) + LN_EPS);
          const float m2 = (rs * (s03.z - mu * sc.x) + sc.w) * (1.f / D_);
          const float e2 = (rs * rs * (s45.x - 2.f * mu * s03.w + mu * mu * sc.y) + 2.f * rs * (s45.y - mu * sc.z) + sbb) * (1.f / D_);
          c2 = rsqrtf(fmaxf(e2 - m2 * m2, 0.f) + LN_EPS);
          c0 = c2 * rs; c1 = -c0 * mu; c3 = -c2 * m2;
          const int grp = js >> 1;
          const int sh = (grp & 2 ? 2 : 1) * (grp & 1 ? -1 : 1);
          ok = (unsigned)(grow + sh) < (unsigned)S_;
          dst = g_us + (size_t)(ok ? grow + sh : (sh > 0 ? grow + sh - S_ : grow + sh + S_)) * D_ + js * 80 + eh * 8;
        } else {
          const float m = s45.x * (1.f / D_);
          c0 = rsqrtf(fmaxf(s45.y * (1.f / D_) - m * m, 0.f) + LN_EPS);
          c1 = -c0 * m;
          dst = g_g + (size_t)grow * F_ + js * 192 + eh * 8;
        }
        const int npass = ph == 0 ? 1 : 3, nch = ph == 0 ? 5 : 4;
#pragma unroll 1
        for (int ps = 0; ps < npass; ps++) {
          if (ps == 0) { STAGE10(MACC, 0) }
          else {
            bar_sync(3 + w, 128);
            if (ps == 1) { STAGE10(MACC, 32) } else { STAGE10(MACC, 56) }
          }
          bar_sync(3 + w, 128);
          const uint32_t cofs = ps == 2 ? 64 : 0;
          const uint32_t pp = p_r + (ph == 0 ? P_VA : P_CS3 + ps * 64) * 4;
#pragma unroll 1
          for (int c = 0; c < nch; c++) {
            float v[8], t[8];
            lds8(stg + st_r + cofs + c * 64, v);
            lds8(pp + c * 64, t);
#pragma unroll
            for (int e = 0; e < 8; e++) v[e] = fmaf(c0, v[e], c1 * t[e]);
            if (ph == 0) {
              lds8(pp + 320 + c * 64, t);
#pragma unroll
              for (int e = 0; e < 8; e++) v[e] = fmaf(c2, t[e], v[e]);
              lds8(pp + 640 + c * 64, t);
#pragma unroll
              for (int e = 0; e < 8; e++) v[e] = fmaf(c3, t[e], v[e]);
            }
#pragma unroll
            for (int e = 0; e < 8; e++) v[e] = gelu_tanh(v[e]);
            const uint4 pk = pack8(v);
            *reinterpret_cast<uint4*>(dst + ps * 64 + c * 16) = ok ? pk : make_uint4(0, 0, 0, 0);
          }
        }
        SIGNAL();
        bar_sync(5, 256);
        A_RELEASE(pa); A_RELEASE(pb);
      } else {
        STAGE10(MACC, 0)
        const uint32_t e1 = rr.nextB(); T_WAIT(e1);
        uint32_t e2 = e1;
        if (ph == 3) { e2 = rr.nextB(); T_WAIT(e2); }
        bar_sync(3 + w, 128);
        float s1 = 0.f, s2 = 0.f;
        bf16* dst = (ph == 1 ? g_x1 : out) + (size_t)grow * D_ + js * 80 + eh * 8;
#pragma unroll 1
        for (int c = 0; c < 5; c++) {
          float v[8], xa[8], t[8];
          lds8(stg + st_r + c * 64, v);
          lds8_bf(sb + e1 * A_SLOT + e_r + c * 32, xa);
          if (ph == 1) {
            lds8(p_r + P_A2 * 4 + c * 64, t);
#pragma unroll
            for (int e = 0; e < 8; e++) v[e] = fmaf(t[e] * rs, xa[e] - mu, v[e]);
            lds8(p_r + P_B2 * 4 + c * 64, t);
#pragma unroll
            for (int e = 0; e < 8; e++) v[e] += t[e];
          } else {
            lds8_bf(sb + e2 * A_SLOT + e_r + c * 32, t);
#pragma unroll
            for (int e = 0; e < 8; e++) v[e] += t[e];
            lds8(p_r + P_GB * 4 + c * 64, t);
#pragma unroll
            for (int e = 0; e < 8; e++) v[e] = fmaf(t[e], v[e], xa[e]);
          }
          const uint4 pk = pack8(v);
          *reinterpret_cast<uint4*>(dst + c * 16) = pk;
          v[0] = bf_lo(pk.x); v[1] = bf_hi(pk.x); v[2] = bf_lo(pk.y); v[3] = bf_hi(pk.y); v[4] = bf_lo(pk.z); v[5] = bf_hi(pk.z); v[6] = bf_lo(pk.w); v[7] = bf_hi(pk.w);
#pragma unroll
          for (int e = 0; e < 8; e++) { s1 += v[e]; s2 = fmaf(v[e], v[e], s2); }
        }
        if (ph == 1) {
          s1 += __shfl_xor_sync(0xffffffffu, s1, 1); s2 += __shfl_xor_sync(0xffffffffu, s2, 1);
          if (eh == 0) asm volatile("red.global.add.v2.f32 [%0], {%1, %2};" :: "l"(g_st2 + (size_t)grow * 2), "f"(s1), "f"(s2) : "memory");
          SIGNAL();
          bar_sync(5, 256);
          A_RELEASE(pa); A_RELEASE(pb); A_RELEASE(e1);
        }
      }
      TS(1 + (ph == 3 ? 0 : ph), ph == 3 ? 3 : 1);
    }
    if ((threadIdx.x & 127) == 0) TL_END(2);
    cluster_sync();
  }
}

typedef CUresult (*EncFn)(CUtensorMap*, CUtensorMapDataType, cuuint32_t, void*, const cuuint64_t*, const cuuint64_t*,
                          const cuuint32_t*, const cuuint32_t*, CUtensorMapInterleave, CUtensorMapSwizzle,
                          CUtensorMapL2promotion, CUtensorMapFloatOOBfill);
static EncFn g_enc = nullptr;

static CUtensorMap map2d(const void* p, uint64_t rows, uint64_t cols, uint32_t box_rows) {
  CUtensorMap m;
  cuuint64_t gd[2] = {cols, rows}; cuuint64_t gs[1] = {cols * 2};
  cuuint32_t bx[2] = {64, box_rows}; cuuint32_t es[2] = {1, 1};
  g_enc(&m, CU_TENSOR_MAP_DATA_TYPE_BFLOAT16, 2, const_cast<void*>(p), gd, gs, bx, es, CU_TENSOR_MAP_INTERLEAVE_NONE,
        CU_TENSOR_MAP_SWIZZLE_128B, CU_TENSOR_MAP_L2_PROMOTION_L2_256B, CU_TENSOR_MAP_FLOAT_OOB_FILL_NONE);
  return m;
}
static CUtensorMap map3d(const void* p, uint64_t rows, uint64_t cols, uint32_t box_rows, uint32_t nblk) {
  CUtensorMap m;
  cuuint64_t gd[3] = {64, rows, cols / 64}; cuuint64_t gs[2] = {cols * 2, 128};
  cuuint32_t bx[3] = {64, box_rows, nblk}; cuuint32_t es[3] = {1, 1, 1};
  g_enc(&m, CU_TENSOR_MAP_DATA_TYPE_BFLOAT16, 3, const_cast<void*>(p), gd, gs, bx, es, CU_TENSOR_MAP_INTERLEAVE_NONE,
        CU_TENSOR_MAP_SWIZZLE_128B, CU_TENSOR_MAP_L2_PROMOTION_L2_256B, CU_TENSOR_MAP_FLOAT_OOB_FILL_NONE);
  return m;
}

static CUtensorMap map_e(const void* p) {
  CUtensorMap m;
  cuuint64_t gd[2] = {D_, S_}; cuuint64_t gs[1] = {D_ * 2};
  cuuint32_t bx[2] = {80, 128}; cuuint32_t es[2] = {1, 1};
  g_enc(&m, CU_TENSOR_MAP_DATA_TYPE_BFLOAT16, 2, const_cast<void*>(p), gd, gs, bx, es, CU_TENSOR_MAP_INTERLEAVE_NONE,
        CU_TENSOR_MAP_SWIZZLE_NONE, CU_TENSOR_MAP_L2_PROMOTION_L2_256B, CU_TENSOR_MAP_FLOAT_OOB_FILL_NONE);
  return m;
}

template <typename... KArgs, typename... Args>
static void launch(void (*kern)(KArgs...), dim3 grid, dim3 block, int smem, bool pdl, Args... args) {
  cudaLaunchConfig_t cfg = {};
  cfg.gridDim = grid; cfg.blockDim = block; cfg.dynamicSmemBytes = smem; cfg.stream = cudaStreamPerThread;
  cudaLaunchAttribute at[1];
  at[0].id = cudaLaunchAttributeProgrammaticStreamSerialization;
  at[0].val.programmaticStreamSerializationAllowed = 1;
  cfg.attrs = at; cfg.numAttrs = pdl ? 1 : 0;
  cudaLaunchKernelEx(&cfg, kern, KArgs(args)...);
}

extern "C" void kernel_launch(void* const* d_in, const int* in_sizes, int n_in, void* d_out, int out_size) {
  const bf16* x = (const bf16*)d_in[0];
  const bf16* kc = (const bf16*)d_in[1];
  const bf16* vc = (const bf16*)d_in[2];
  const bf16* wq = (const bf16*)d_in[3];
  const bf16* wo = (const bf16*)d_in[4];
  const bf16* w1 = (const bf16*)d_in[6];
  const bf16* w2 = (const bf16*)d_in[7];
  const bf16* w3 = (const bf16*)d_in[8];
  const bf16* w4 = (const bf16*)d_in[9];
  const bf16* c = (const bf16*)d_in[10];
  const bf16* wmod = (const bf16*)d_in[11];
  bf16* out = (bf16*)d_out;

  static void *p_h, *p_o, *p_xa, *p_us, *p_x1, *p_g, *p_w1t, *p_w2t, *p_w4t;
  if (!g_enc) {
    void* fn = nullptr; cudaDriverEntryPointQueryResult qr;
    cudaGetDriverEntryPoint("cuTensorMapEncodeTiled", &fn, cudaEnableDefault, &qr);
    g_enc = (EncFn)fn;
    cudaGetSymbolAddress(&p_h, g_h); cudaGetSymbolAddress(&p_o, g_o); cudaGetSymbolAddress(&p_xa, g_xa);
    cudaGetSymbolAddress(&p_us, g_us); cudaGetSymbolAddress(&p_x1, g_x1); cudaGetSymbolAddress(&p_g, g_g);
    cudaGetSymbolAddress(&p_w1t, g_w1t); cudaGetSymbolAddress(&p_w2t, g_w2t); cudaGetSymbolAddress(&p_w4t, g_w4t);
    cudaFuncSetAttribute(fused_kernel, cudaFuncAttributeMaxDynamicSharedMemorySize, T_SMEM);
  }
  Maps tm;
  tm.h = map2d(p_h, S_, D_, 128);
  tm.wq = map3d(wq, D_, HD_, 64, 3);
  tm.k = map3d(kc, (uint64_t)H_ * S_, DH_, 64, 3);
  tm.v = map3d(vc, (uint64_t)H_ * S_, DH_, 64, 3);
  tm.o = map2d(p_o, S_, HD_, 128);
  tm.wo3 = map3d(wo, HD_, D_, 64, 3);
  tm.wo2 = map3d(wo, HD_, D_, 64, 2);
  tm.xa = map2d(p_xa, S_, D_, 64);
  tm.w1t = map3d(p_w1t, D_, D_, 80, 2);
  tm.us = map2d(p_us, S_, D_, 64);
  tm.w2t = map3d(p_w2t, D_, D_, 80, 2);
  tm.x1 = map2d(p_x1, S_, D_, 64);
  tm.w3 = map3d(w3, D_, F_, 64, 3);
  tm.g = map2d(p_g, S_, F_, 64);
  tm.w4t = map3d(p_w4t, D_, F_, 80, 2);
  tm.ex = map_e(x); tm.exa = map_e(p_xa); tm.ex1 = map_e(p_x1);
  PfList pf;
  pf.p[0] = (const uint8_t*)wo; pf.p[1] = (const uint8_t*)w3; pf.p[2] = (const uint8_t*)p_w4t;
  pf.p[3] = (const uint8_t*)x; pf.p[4] = (const uint8_t*)p_w1t; pf.p[5] = (const uint8_t*)p_w2t;

  launch(mod_kernel, dim3(120), dim3(256), 0, false, c, wmod);
  launch(ln1_kernel, dim3(256), dim3(256), 0, true, x);
  launch(fused_kernel, dim3(128), dim3(384), T_SMEM, true, tm, pf, PrepW{w1, w2, w3, w4}, x, out);
}
```

```cpp
#include <cuda_runtime.h>
#include <cuda.h>
#include <cuda_bf16.h>
#include <stdint.h>

typedef __nv_bfloat16 bf16;

constexpr int S_  = 2048;
constexpr int D_  = 640;
constexpr int H_  = 32;
constexpr int DH_ = 192;
constexpr int HD_ = H_ * DH_;
constexpr int F_  = 1536;
constexpr float LN_EPS = 1e-5f;

__device__ __forceinline__ uint32_t smem_u32(const void* p) { return (uint32_t)__cvta_generic_to_shared(p); }
__device__ __forceinline__ void mbar_init(uint32_t a, uint32_t c) { asm volatile("mbarrier.init.shared::cta.b64 [%0], %1;" :: "r"(a), "r"(c) : "memory"); }
__device__ __forceinline__ void mbar_expect(uint32_t a, uint32_t b) { asm volatile("mbarrier.arrive.expect_tx.shared::cta.b64 _, [%0], %1;" :: "r"(a), "r"(b) : "memory"); }
__device__ __forceinline__ void mbar_arrive(uint32_t a) { asm volatile("mbarrier.arrive.shared::cta.b64 _, [%0];" :: "r"(a) : "memory"); }
__device__ __forceinline__ void mbar_arrive_remote(uint32_t ra) { asm volatile("mbarrier.arrive.shared::cluster.b64 _, [%0];" :: "r"(ra) : "memory"); }
__device__ __forceinline__ uint32_t mapa(uint32_t a, uint32_t cta) { uint32_t r; asm volatile("mapa.shared::cluster.u32 %0, %1, %2;" : "=r"(r) : "r"(a), "r"(cta)); return r; }
__device__ __forceinline__ uint32_t mbar_try(uint32_t a, uint32_t ph) {
  uint32_t ok;
  asm volatile("{\n.reg .pred p;\nmbarrier.test_wait.parity.shared::cta.b64 p, [%1], %2;\nselp.u32 %0, 1, 0, p;\n}\n" : "=r"(ok) : "r"(a), "r"(ph) : "memory");
  return ok;
}
__device__ __forceinline__ void mbar_wait(uint32_t a, uint32_t ph) {
  asm volatile(
      "{\n.reg .pred p;\n.reg .u32 n;\n"
      "mov.u32 n, 0;\n"
      "SPIN:\n"
      "mbarrier.try_wait.parity.shared::cta.b64 p, [%0], %1;\n"
      "@p bra DONE;\n"
      "add.u32 n, n, 1;\n"
      "setp.le.u32 p, n, 16777216;\n"
      "@p bra SPIN;\n"
      "trap;\n"
      "DONE:\n}\n" :: "r"(a), "r"(ph) : "memory");
}
__device__ __forceinline__ void tma2d(uint32_t dst, const CUtensorMap* m, uint32_t bar, int c0, int c1) {
  asm volatile("cp.async.bulk.tensor.2d.shared::cluster.global.mbarrier::complete_tx::bytes [%0], [%1, {%3, %4}], [%2];"
               :: "r"(dst), "l"(m), "r"(bar), "r"(c0), "r"(c1) : "memory");
}
__device__ __forceinline__ void tma3d(uint32_t dst, const CUtensorMap* m, uint32_t bar, int c0, int c1, int c2) {
  asm volatile("cp.async.bulk.tensor.3d.shared::cluster.global.mbarrier::complete_tx::bytes [%0], [%1, {%3, %4, %5}], [%2];"
               :: "r"(dst), "l"(m), "r"(bar), "r"(c0), "r"(c1), "r"(c2) : "memory");
}
__device__ __forceinline__ void tma3d_mc(uint32_t dst, const CUtensorMap* m, uint32_t bar, int c0, int c1, int c2, uint16_t mask) {
  asm volatile("cp.async.bulk.tensor.3d.shared::cluster.global.mbarrier::complete_tx::bytes.multicast::cluster [%0], [%1, {%3, %4, %5}], [%2], %6;"
               :: "r"(dst), "l"(m), "r"(bar), "r"(c0), "r"(c1), "r"(c2), "h"(mask) : "memory");
}
__device__ __forceinline__ void prefetch_tmap(const CUtensorMap* m) { asm volatile("prefetch.tensormap [%0];" :: "l"(m) : "memory"); }
__device__ __forceinline__ void wg_fence() { asm volatile("wgmma.fence.sync.aligned;" ::: "memory"); }
__device__ __forceinline__ void wg_commit() { asm volatile("wgmma.commit_group.sync.aligned;" ::: "memory"); }
template <int N> __device__ __forceinline__ void wg_wait() { asm volatile("wgmma.wait_group.sync.aligned %0;" :: "n"(N) : "memory"); }
template <int N> __device__ __forceinline__ void fence_regs(float (&r)[N]) {
#pragma unroll
  for (int i = 0; i < N; i++) asm volatile("" : "+f"(r[i]) :: "memory");
}
template <int N> __device__ __forceinline__ void fence_regs(uint32_t (&r)[N]) {
#pragma unroll
  for (int i = 0; i < N; i++) asm volatile("" : "+r"(r[i]) :: "memory");
}
__device__ __forceinline__ uint64_t mkdesc(uint32_t addr, uint32_t lbo, uint32_t sbo) {
  return (uint64_t)((addr & 0x3FFFF) >> 4) | ((uint64_t)(lbo >> 4) << 16) | ((uint64_t)(sbo >> 4) << 32) | (1ull << 62);
}
__device__ __forceinline__ void bar_sync(int id, int n) { asm volatile("bar.sync %0, %1;" :: "r"(id), "r"(n) : "memory"); }
__device__ __forceinline__ void bar_arrive(int id, int n) { asm volatile("bar.arrive %0, %1;" :: "r"(id), "r"(n) : "memory"); }
__device__ __forceinline__ void cluster_sync() { asm volatile("barrier.cluster.arrive.aligned;\nbarrier.cluster.wait.aligned;" ::: "memory"); }
__device__ __forceinline__ void pdl_wait() { asm volatile("griddepcontrol.wait;" ::: "memory"); }
__device__ __forceinline__ void pdl_launch() { asm volatile("griddepcontrol.launch_dependents;" ::: "memory"); }
__device__ __forceinline__ float ex2(float x) { float y; asm("ex2.approx.ftz.f32 %0, %1;" : "=f"(y) : "f"(x)); return y; }
__device__ __forceinline__ uint32_t pack_bf16(float lo, float hi) { uint32_t r; asm("cvt.rn.bf16x2.f32 %0, %1, %2;" : "=r"(r) : "f"(hi), "f"(lo)); return r; }
__device__ __forceinline__ float bf_lo(uint32_t u) { return __uint_as_float(u << 16); }
__device__ __forceinline__ float bf_hi(uint32_t u) { return __uint_as_float(u & 0xffff0000u); }
__device__ __forceinline__ float bf_round(float x) { return __bfloat162float(__float2bfloat16_rn(x)); }
__device__ __forceinline__ float tanh_fast(float x) { float y; asm("tanh.approx.f32 %0, %1;" : "=f"(y) : "f"(x)); return y; }
__device__ __forceinline__ float gelu_tanh(float x) {
  float u = x * (0.7978845608028654f + 0.035677408136300125f * x * x);
  float hx = 0.5f * x;
  return fmaf(hx, tanh_fast(u), hx);
}
__device__ __forceinline__ float warp_sum(float v) {
#pragma unroll
  for (int o = 16; o > 0; o >>= 1) v += __shfl_xor_sync(0xffffffffu, v, o);
  return v;
}
__device__ __forceinline__ void quad_transpose(uint32_t& v0, uint32_t& v1, uint32_t& v2, uint32_t& v3, int lane) {
  const bool b0 = lane & 1, b1 = lane & 2;
  uint32_t s0 = b0 ? v0 : v1, s1 = b0 ? v2 : v3;
  s0 = __shfl_xor_sync(0xffffffffu, s0, 1); s1 = __shfl_xor_sync(0xffffffffu, s1, 1);
  if (b0) { v0 = s0; v2 = s1; } else { v1 = s0; v3 = s1; }
  uint32_t t0 = b1 ? v0 : v2, t1 = b1 ? v1 : v3;
  t0 = __shfl_xor_sync(0xffffffffu, t0, 2); t1 = __shfl_xor_sync(0xffffffffu, t1, 2);
  if (b1) { v0 = t0; v1 = t1; } else { v2 = t0; v3 = t1; }
}

#define TX(i)
#define TXC(i)
#define TSA(item, i)
#define TL_ENTRY(k)
#define TL_WAITED(k)
#define TL_END(k)
#define TS(item, i)
template<int TB> __device__ __forceinline__ void wgmma_rs_n64(float (&d)[32], uint32_t a0, uint32_t a1, uint32_t a2, uint32_t a3, uint64_t db, int scale_d) {
  asm volatile("{\n.reg .pred p;\nsetp.ne.b32 p, %37, 0;\n"
    "wgmma.mma_async.sync.aligned.m64n64k16.f32.bf16.bf16 {%0, %1, %2, %3, %4, %5, %6, %7, %8, %9, %10, %11, %12, %13, %14, %15, %16, %17, %18, %19, %20, %21, %22, %23, %24, %25, %26, %27, %28, %29, %30, %31}, {%32, %33, %34, %35}, %36, p, 1, 1, %38;\n}\n"
    : "+f"(d[0]), "+f"(d[1]), "+f"(d[2]), "+f"(d[3]), "+f"(d[4]), "+f"(d[5]), "+f"(d[6]), "+f"(d[7]), "+f"(d[8]), "+f"(d[9]), "+f"(d[10]), "+f"(d[11]), "+f"(d[12]), "+f"(d[13]), "+f"(d[14]), "+f"(d[15]), "+f"(d[16]), "+f"(d[17]), "+f"(d[18]), "+f"(d[19]), "+f"(d[20]), "+f"(d[21]), "+f"(d[22]), "+f"(d[23]), "+f"(d[24]), "+f"(d[25]), "+f"(d[26]), "+f"(d[27]), "+f"(d[28]), "+f"(d[29]), "+f"(d[30]), "+f"(d[31])
    : "r"(a0), "r"(a1), "r"(a2), "r"(a3), "l"(db), "r"(scale_d), "n"(TB));
}
template<int TB> __device__ __forceinline__ void wgmma_rs_n192(float (&d)[96], uint32_t a0, uint32_t a1, uint32_t a2, uint32_t a3, uint64_t db, int scale_d) {
  asm volatile("{\n.reg .pred p;\nsetp.ne.b32 p, %101, 0;\n"
    "wgmma.mma_async.sync.aligned.m64n192k16.f32.bf16.bf16 {%0, %1, %2, %3, %4, %5, %6, %7, %8, %9, %10, %11, %12, %13, %14, %15, %16, %17, %18, %19, %20, %21, %22, %23, %24, %25, %26, %27, %28, %29, %30, %31, %32, %33, %34, %35, %36, %37, %38, %39, %40, %41, %42, %43, %44, %45, %46, %47, %48, %49, %50, %51, %52, %53, %54, %55, %56, %57, %58, %59, %60, %61, %62, %63, %64, %65, %66, %67, %68, %69, %70, %71, %72, %73, %74, %75, %76, %77, %78, %79, %80, %81, %82, %83, %84, %85, %86, %87, %88, %89, %90, %91, %92, %93, %94, %95}, {%96, %97, %98, %99}, %100, p, 1, 1, %102;\n}\n"
    : "+f"(d[0]), "+f"(d[1]), "+f"(d[2]), "+f"(d[3]), "+f"(d[4]), "+f"(d[5]), "+f"(d[6]), "+f"(d[7]), "+f"(d[8]), "+f"(d[9]), "+f"(d[10]), "+f"(d[11]), "+f"(d[12]), "+f"(d[13]), "+f"(d[14]), "+f"(d[15]), "+f"(d[16]), "+f"(d[17]), "+f"(d[18]), "+f"(d[19]), "+f"(d[20]), "+f"(d[21]), "+f"(d[22]), "+f"(d[23]), "+f"(d[24]), "+f"(d[25]), "+f"(d[26]), "+f"(d[27]), "+f"(d[28]), "+f"(d[29]), "+f"(d[30]), "+f"(d[31]), "+f"(d[32]), "+f"(d[33]), "+f"(d[34]), "+f"(d[35]), "+f"(d[36]), "+f"(d[37]), "+f"(d[38]), "+f"(d[39]), "+f"(d[40]), "+f"(d[41]), "+f"(d[42]), "+f"(d[43]), "+f"(d[44]), "+f"(d[45]), "+f"(d[46]), "+f"(d[47]), "+f"(d[48]), "+f"(d[49]), "+f"(d[50]), "+f"(d[51]), "+f"(d[52]), "+f"(d[53]), "+f"(d[54]), "+f"(d[55]), "+f"(d[56]), "+f"(d[57]), "+f"(d[58]), "+f"(d[59]), "+f"(d[60]), "+f"(d[61]), "+f"(d[62]), "+f"(d[63]), "+f"(d[64]), "+f"(d[65]), "+f"(d[66]), "+f"(d[67]), "+f"(d[68]), "+f"(d[69]), "+f"(d[70]), "+f"(d[71]), "+f"(d[72]), "+f"(d[73]), "+f"(d[74]), "+f"(d[75]), "+f"(d[76]), "+f"(d[77]), "+f"(d[78]), "+f"(d[79]), "+f"(d[80]), "+f"(d[81]), "+f"(d[82]), "+f"(d[83]), "+f"(d[84]), "+f"(d[85]), "+f"(d[86]), "+f"(d[87]), "+f"(d[88]), "+f"(d[89]), "+f"(d[90]), "+f"(d[91]), "+f"(d[92]), "+f"(d[93]), "+f"(d[94]), "+f"(d[95])
    : "r"(a0), "r"(a1), "r"(a2), "r"(a3), "l"(db), "r"(scale_d), "n"(TB));
}
template<int TB> __device__ __forceinline__ void wgmma_ss_n128(float (&d)[64], uint64_t da, uint64_t db, int scale_d) {
  asm volatile("{\n.reg .pred p;\nsetp.ne.b32 p, %66, 0;\n"
    "wgmma.mma_async.sync.aligned.m64n128k16.f32.bf16.bf16 {%0, %1, %2, %3, %4, %5, %6, %7, %8, %9, %10, %11, %12, %13, %14, %15, %16, %17, %18, %19, %20, %21, %22, %23, %24, %25, %26, %27, %28, %29, %30, %31, %32, %33, %34, %35, %36, %37, %38, %39, %40, %41, %42, %43, %44, %45, %46, %47, %48, %49, %50, %51, %52, %53, %54, %55, %56, %57, %58, %59, %60, %61, %62, %63}, %64, %65, p, 1, 1, 0, %67;\n}\n"
    : "+f"(d[0]), "+f"(d[1]), "+f"(d[2]), "+f"(d[3]), "+f"(d[4]), "+f"(d[5]), "+f"(d[6]), "+f"(d[7]), "+f"(d[8]), "+f"(d[9]), "+f"(d[10]), "+f"(d[11]), "+f"(d[12]), "+f"(d[13]), "+f"(d[14]), "+f"(d[15]), "+f"(d[16]), "+f"(d[17]), "+f"(d[18]), "+f"(d[19]), "+f"(d[20]), "+f"(d[21]), "+f"(d[22]), "+f"(d[23]), "+f"(d[24]), "+f"(d[25]), "+f"(d[26]), "+f"(d[27]), "+f"(d[28]), "+f"(d[29]), "+f"(d[30]), "+f"(d[31]), "+f"(d[32]), "+f"(d[33]), "+f"(d[34]), "+f"(d[35]), "+f"(d[36]), "+f"(d[37]), "+f"(d[38]), "+f"(d[39]), "+f"(d[40]), "+f"(d[41]), "+f"(d[42]), "+f"(d[43]), "+f"(d[44]), "+f"(d[45]), "+f"(d[46]), "+f"(d[47]), "+f"(d[48]), "+f"(d[49]), "+f"(d[50]), "+f"(d[51]), "+f"(d[52]), "+f"(d[53]), "+f"(d[54]), "+f"(d[55]), "+f"(d[56]), "+f"(d[57]), "+f"(d[58]), "+f"(d[59]), "+f"(d[60]), "+f"(d[61]), "+f"(d[62]), "+f"(d[63])
    : "l"(da), "l"(db), "r"(scale_d), "n"(TB));
}
template<int TB> __device__ __forceinline__ void wgmma_ss_n192(float (&d)[96], uint64_t da, uint64_t db, int scale_d) {
  asm volatile("{\n.reg .pred p;\nsetp.ne.b32 p, %98, 0;\n"
    "wgmma.mma_async.sync.aligned.m64n192k16.f32.bf16.bf16 {%0, %1, %2, %3, %4, %5, %6, %7, %8, %9, %10, %11, %12, %13, %14, %15, %16, %17, %18, %19, %20, %21, %22, %23, %24, %25, %26, %27, %28, %29, %30, %31, %32, %33, %34, %35, %36, %37, %38, %39, %40, %41, %42, %43, %44, %45, %46, %47, %48, %49, %50, %51, %52, %53, %54, %55, %56, %57, %58, %59, %60, %61, %62, %63, %64, %65, %66, %67, %68, %69, %70, %71, %72, %73, %74, %75, %76, %77, %78, %79, %80, %81, %82, %83, %84, %85, %86, %87, %88, %89, %90, %91, %92, %93, %94, %95}, %96, %97, p, 1, 1, 0, %99;\n}\n"
    : "+f"(d[0]), "+f"(d[1]), "+f"(d[2]), "+f"(d[3]), "+f"(d[4]), "+f"(d[5]), "+f"(d[6]), "+f"(d[7]), "+f"(d[8]), "+f"(d[9]), "+f"(d[10]), "+f"(d[11]), "+f"(d[12]), "+f"(d[13]), "+f"(d[14]), "+f"(d[15]), "+f"(d[16]), "+f"(d[17]), "+f"(d[18]), "+f"(d[19]), "+f"(d[20]), "+f"(d[21]), "+f"(d[22]), "+f"(d[23]), "+f"(d[24]), "+f"(d[25]), "+f"(d[26]), "+f"(d[27]), "+f"(d[28]), "+f"(d[29]), "+f"(d[30]), "+f"(d[31]), "+f"(d[32]), "+f"(d[33]), "+f"(d[34]), "+f"(d[35]), "+f"(d[36]), "+f"(d[37]), "+f"(d[38]), "+f"(d[39]), "+f"(d[40]), "+f"(d[41]), "+f"(d[42]), "+f"(d[43]), "+f"(d[44]), "+f"(d[45]), "+f"(d[46]), "+f"(d[47]), "+f"(d[48]), "+f"(d[49]), "+f"(d[50]), "+f"(d[51]), "+f"(d[52]), "+f"(d[53]), "+f"(d[54]), "+f"(d[55]), "+f"(d[56]), "+f"(d[57]), "+f"(d[58]), "+f"(d[59]), "+f"(d[60]), "+f"(d[61]), "+f"(d[62]), "+f"(d[63]), "+f"(d[64]), "+f"(d[65]), "+f"(d[66]), "+f"(d[67]), "+f"(d[68]), "+f"(d[69]), "+f"(d[70]), "+f"(d[71]), "+f"(d[72]), "+f"(d[73]), "+f"(d[74]), "+f"(d[75]), "+f"(d[76]), "+f"(d[77]), "+f"(d[78]), "+f"(d[79]), "+f"(d[80]), "+f"(d[81]), "+f"(d[82]), "+f"(d[83]), "+f"(d[84]), "+f"(d[85]), "+f"(d[86]), "+f"(d[87]), "+f"(d[88]), "+f"(d[89]), "+f"(d[90]), "+f"(d[91]), "+f"(d[92]), "+f"(d[93]), "+f"(d[94]), "+f"(d[95])
    : "l"(da), "l"(db), "r"(scale_d), "n"(TB));
}
template<int TB> __device__ __forceinline__ void wgmma_ss_n80(float (&d)[40], uint64_t da, uint64_t db, int scale_d) {
  asm volatile("{\n.reg .pred p;\nsetp.ne.b32 p, %42, 0;\n"
    "wgmma.mma_async.sync.aligned.m64n80k16.f32.bf16.bf16 {%0, %1, %2, %3, %4, %5, %6, %7, %8, %9, %10, %11, %12, %13, %14, %15, %16, %17, %18, %19, %20, %21, %22, %23, %24, %25, %26, %27, %28, %29, %30, %31, %32, %33, %34, %35, %36, %37, %38, %39}, %40, %41, p, 1, 1, 0, %43;\n}\n"
    : "+f"(d[0]), "+f"(d[1]), "+f"(d[2]), "+f"(d[3]), "+f"(d[4]), "+f"(d[5]), "+f"(d[6]), "+f"(d[7]), "+f"(d[8]), "+f"(d[9]), "+f"(d[10]), "+f"(d[11]), "+f"(d[12]), "+f"(d[13]), "+f"(d[14]), "+f"(d[15]), "+f"(d[16]), "+f"(d[17]), "+f"(d[18]), "+f"(d[19]), "+f"(d[20]), "+f"(d[21]), "+f"(d[22]), "+f"(d[23]), "+f"(d[24]), "+f"(d[25]), "+f"(d[26]), "+f"(d[27]), "+f"(d[28]), "+f"(d[29]), "+f"(d[30]), "+f"(d[31]), "+f"(d[32]), "+f"(d[33]), "+f"(d[34]), "+f"(d[35]), "+f"(d[36]), "+f"(d[37]), "+f"(d[38]), "+f"(d[39])
    : "l"(da), "l"(db), "r"(scale_d), "n"(TB));
}

__device__ float g_mod[6 * D_];
__device__ __align__(1024) bf16 g_h[S_ * D_];
__device__ __align__(1024) bf16 g_o[S_ * HD_];
__device__ __align__(1024) bf16 g_xch[16 * 2 * 4 * 4 * 128 * 80];
__device__ __align__(1024) bf16 g_w1t[D_ * D_];
__device__ __align__(1024) bf16 g_w2t[D_ * D_];
__device__ __align__(1024) bf16 g_w4t[D_ * F_];
__device__ __align__(32) float g_st1[S_ * 8];
__device__ __align__(32) float g_st2[S_ * 2];
__device__ __align__(32) float g_vec[3 * D_ + F_ + 8];
__device__ unsigned g_flag[1024];
enum { F_XCH = 0, F_XA = 256, F_US = 272, F_X1 = 288, F_G = 304, F_PREP = 320, F_O = 512 };
__device__ __align__(1024) bf16 g_xa[S_ * D_];
__device__ __align__(1024) bf16 g_us[S_ * D_];
__device__ __align__(1024) bf16 g_x1[S_ * D_];
__device__ __align__(1024) bf16 g_g[S_ * F_];

__global__ void __launch_bounds__(256) mod_kernel(const bf16* __restrict__ c, const bf16* __restrict__ w_mod) {
  TL_ENTRY(0);
  pdl_launch();
  __shared__ float red[8][32];
  if (blockIdx.x < 14) { const int i = blockIdx.x * 256 + threadIdx.x; if (i < 3 * D_ + F_) g_vec[i] = 0.f; }
  else if (blockIdx.x < 18) g_flag[(blockIdx.x - 14) * 256 + threadIdx.x] = 0u;
  const int t = threadIdx.x, cg = t & 3, r0 = t >> 2;
  const int col0 = blockIdx.x * 32 + cg * 8;
  uint4 w[10];
#pragma unroll
  for (int i = 0; i < 10; i++) w[i] = __ldg(reinterpret_cast<const uint4*>(w_mod + (size_t)(r0 + 64 * i) * (6 * D_) + col0));
  float acc[8];
#pragma unroll
  for (int j = 0; j < 8; j++) acc[j] = 0.f;
#pragma unroll
  for (int i = 0; i < 10; i++) {
    float cv = __bfloat162float(c[r0 + 64 * i]);
    float s = bf_round(cv / (1.f + __expf(-cv)));
    acc[0] = fmaf(s, bf_lo(w[i].x), acc[0]); acc[1] = fmaf(s, bf_hi(w[i].x), acc[1]);
    acc[2] = fmaf(s, bf_lo(w[i].y), acc[2]); acc[3] = fmaf(s, bf_hi(w[i].y), acc[3]);
    acc[4] = fmaf(s, bf_lo(w[i].z), acc[4]); acc[5] = fmaf(s, bf_hi(w[i].z), acc[5]);
    acc[6] = fmaf(s, bf_lo(w[i].w), acc[6]); acc[7] = fmaf(s, bf_hi(w[i].w), acc[7]);
  }
#pragma unroll
  for (int j = 0; j < 8; j++) {
    acc[j] += __shfl_xor_sync(0xffffffffu, acc[j], 4);
    acc[j] += __shfl_xor_sync(0xffffffffu, acc[j], 8);
    acc[j] += __shfl_xor_sync(0xffffffffu, acc[j], 16);
  }
  if ((t & 31) < 4) {
#pragma unroll
    for (int j = 0; j < 8; j++) red[t >> 5][cg * 8 + j] = acc[j];
  }
  __syncthreads();
  if (t < 32) {
    float s = 0.f;
#pragma unroll
    for (int w8 = 0; w8 < 8; w8++) s += red[w8][t];
    const int col = blockIdx.x * 32 + t;
    s = bf_round(s);
    const int part = col / D_;
    if (part == 1 || part == 4) s = bf_round(1.f + s);
    g_mod[col] = s;
    if (t == 0) TL_END(0);
  }
}

__device__ __forceinline__ void row_stats(const float (&v)[20], float& mean, float& rstd) {
  float s = 0.f;
#pragma unroll
  for (int i = 0; i < 20; i++) s += v[i];
  mean = warp_sum(s) * (1.f / D_);
  float q = 0.f;
#pragma unroll
  for (int i = 0; i < 20; i++) { float d = v[i] - mean; q = fmaf(d, d, q); }
  rstd = rsqrtf(warp_sum(q) * (1.f / D_) + LN_EPS);
}
__device__ __forceinline__ void load_row_bf16(const bf16* p, int lane, float (&v)[20]) {
#pragma unroll
  for (int i = 0; i < 5; i++) {
    uint2 u = *reinterpret_cast<const uint2*>(p + (lane + 32 * i) * 4);
    v[4 * i] = bf_lo(u.x); v[4 * i + 1] = bf_hi(u.x); v[4 * i + 2] = bf_lo(u.y); v[4 * i + 3] = bf_hi(u.y);
  }
}
__device__ __forceinline__ void store_row_bf16(bf16* p, int lane, const float (&v)[20]) {
#pragma unroll
  for (int i = 0; i < 5; i++) {
    uint2 u; u.x = pack_bf16(v[4 * i], v[4 * i + 1]); u.y = pack_bf16(v[4 * i + 2], v[4 * i + 3]);
    *reinterpret_cast<uint2*>(p + (lane + 32 * i) * 4) = u;
  }
}
__device__ __forceinline__ void load_row_f32(const float* p, int lane, float (&v)[20]) {
#pragma unroll
  for (int i = 0; i < 5; i++) {
    float4 u = *reinterpret_cast<const float4*>(p + (lane + 32 * i) * 4);
    v[4 * i] = u.x; v[4 * i + 1] = u.y; v[4 * i + 2] = u.z; v[4 * i + 3] = u.w;
  }
}

__global__ void __launch_bounds__(256) ln1_kernel(const bf16* __restrict__ x) {
  TL_ENTRY(1);
  pdl_launch();
  const int lane = threadIdx.x & 31, row = blockIdx.x * 8 + (threadIdx.x >> 5);
  float v[20];
  load_row_bf16(x + (size_t)row * D_, lane, v);
  float mean, rstd;
  row_stats(v, mean, rstd);
  if (lane < 8) g_st1[row * 8 + lane] = 0.f;
  if (lane < 2) g_st2[row * 2 + lane] = 0.f;
  pdl_wait();
  if (threadIdx.x == 0) TL_WAITED(1);
  float sa[20], ca[20];
  load_row_f32(g_mod, lane, sa);
  load_row_f32(g_mod + D_, lane, ca);
#pragma unroll
  for (int i = 0; i < 20; i++) v[i] = fmaf((v[i] - mean) * rstd, ca[i], sa[i]);
  store_row_bf16(g_h + (size_t)row * D_, lane, v);
  if (threadIdx.x == 0) TL_END(1);
}

constexpr int PREP_JOBS = 200 + 200 + 480 + 480;
struct PrepW { const bf16 *w1, *w2, *w3, *w4; };
__device__ __forceinline__ void prep_warp(const PrepW& pw, bf16 (*tile)[72], int lane) {
#pragma unroll 1
  for (int job = blockIdx.x; job < PREP_JOBS; job += gridDim.x) {
    const bf16* src; bf16* dst; int ld = D_, ldd = D_, kt, nt, kind = 1;
    if (job < 200) { src = pw.w1; dst = g_w1t; kt = job / 10; nt = job % 10; kind = 0; }
    else if (job < 400) { src = pw.w2; dst = g_w2t; kt = (job - 200) / 10; nt = (job - 200) % 10; }
    else if (job < 880) { src = pw.w4; dst = g_w4t; ldd = F_; kt = (job - 400) / 10; nt = (job - 400) % 10; }
    else { src = pw.w3; dst = nullptr; ld = F_; kt = (job - 880) / 24; nt = (job - 880) % 24; kind = 2; }
    src += (size_t)(kt * 32 + (lane >> 3)) * ld + nt * 64 + (lane & 7) * 8;
    __syncwarp();
#pragma unroll
    for (int h = 0; h < 2; h++) {
      uint4 v[4];
#pragma unroll
      for (int i = 0; i < 4; i++) v[i] = __ldg(reinterpret_cast<const uint4*>(src + (size_t)(h * 16 + i * 4) * ld));
#pragma unroll
      for (int i = 0; i < 4; i++) *reinterpret_cast<uint4*>(&tile[h * 16 + i * 4 + (lane >> 3)][(lane & 7) * 8]) = v[i];
    }
    __syncwarp();
    const float* pa = g_mod + 4 * D_ + kt * 32;
    const float* pb = g_mod + 3 * D_ + kt * 32;
#pragma unroll 1
    for (int h = 0; h < 2; h++) {
      const int n = lane + 32 * h;
      float sa = 0.f, sb = 0.f, sc = 0.f;
#pragma unroll 1
      for (int c = 0; c < 4; c++) {
        uint32_t u[4];
#pragma unroll
        for (int e = 0; e < 4; e++) {
          const int k = c * 8 + 2 * e;
          float lo = __bfloat162float(tile[k][n]), hi = __bfloat162float(tile[k + 1][n]);
          sc += lo + hi;
          if (kind == 0) {
            const float2 a = __ldcg(reinterpret_cast<const float2*>(pa + k)), b = __ldcg(reinterpret_cast<const float2*>(pb + k));
            sb = fmaf(b.x, lo, fmaf(b.y, hi, sb));
            lo *= a.x; hi *= a.y;
          }
          u[e] = pack_bf16(lo, hi);
          sa += bf_lo(u[e]) + bf_hi(u[e]);
        }
        if (kind != 2) *reinterpret_cast<uint4*>(dst + (size_t)(nt * 64 + n) * ldd + kt * 32 + c * 8) = make_uint4(u[0], u[1], u[2], u[3]);
      }
      if (kind == 0) { atomicAdd(&g_vec[nt * 64 + n], sa); atomicAdd(&g_vec[D_ + nt * 64 + n], sb); atomicAdd(&g_vec[2 * D_ + nt * 64 + n], sc); }
      else if (kind == 2) atomicAdd(&g_vec[3 * D_ + nt * 64 + n], sc);
    }
  }
  __syncwarp();
  if (lane == 0) {
    asm volatile("fence.acq_rel.gpu;" ::: "memory");
    asm volatile("red.relaxed.gpu.global.add.u32 [%0], 1;" :: "l"(g_flag + F_PREP) : "memory");
  }
}

constexpr int A_NSLOT = 9;
constexpr int A_SLOT = 24576;
constexpr int A_NKV = S_ / 64;
constexpr int PREP_CTAS = 128;

struct Ring {
  uint32_t slot, phase;
  __device__ __forceinline__ void adv(int n) { if (++slot == (uint32_t)n) { slot = 0; phase ^= 1; } }
};
constexpr int T_PAR = A_NSLOT * A_SLOT + 384;
constexpr int T_PREP = T_PAR + 3712;
constexpr int T_SMEM = T_PREP + 32 * 72 * 2 + 1024;
enum { P_OGA = 0, P_OA = 80, P_OB = 160, P_VA = 240, P_VB = 320, P_VC = 400, P_A2 = 480, P_B2 = 560, P_GB = 640, P_CS3 = 720, P_SC = 912 };

__device__ __forceinline__ void flag_wait(const unsigned* p, unsigned target) {
  asm volatile(
      "{\n.reg .pred p;\n.reg .u32 n, v;\n"
      "mov.u32 n, 0;\n"
      "SPIN:\n"
      "ld.relaxed.gpu.global.u32 v, [%0];\n"
      "setp.ge.u32 p, v, %1;\n"
      "@p bra DONE;\n"
      "add.u32 n, n, 1;\n"
      "setp.gt.u32 p, n, 4194304;\n"
      "@p trap;\n"
      "bra SPIN;\n"
      "DONE:\n}\n" :: "l"(p), "r"(target) : "memory");
}
__device__ __forceinline__ void fence_async_global() { asm volatile("fence.proxy.async.global;" ::: "memory"); }
__device__ __forceinline__ float lds_f(uint32_t a) { float v; asm volatile("ld.shared.f32 %0, [%1];" : "=f"(v) : "r"(a)); return v; }
__device__ __forceinline__ float2 lds_f2(uint32_t a) { float2 v; asm volatile("ld.shared.v2.f32 {%0, %1}, [%2];" : "=f"(v.x), "=f"(v.y) : "r"(a)); return v; }
__device__ __forceinline__ uint4 ldcg4(const void* p) { return __ldcg(reinterpret_cast<const uint4*>(p)); }

__device__ __forceinline__ void sts_f2(uint32_t a, float x, float y) { asm volatile("st.shared.v2.f32 [%0], {%1, %2};" :: "r"(a), "f"(x), "f"(y) : "memory"); }
__device__ __forceinline__ float4 lds_f4(uint32_t a) { float4 v; asm volatile("ld.shared.v4.f32 {%0, %1, %2, %3}, [%4];" : "=f"(v.x), "=f"(v.y), "=f"(v.z), "=f"(v.w) : "r"(a) : "memory"); return v; }
__device__ __forceinline__ uint4 lds_u4(uint32_t a) { uint4 v; asm volatile("ld.shared.v4.u32 {%0, %1, %2, %3}, [%4];" : "=r"(v.x), "=r"(v.y), "=r"(v.z), "=r"(v.w) : "r"(a) : "memory"); return v; }
__device__ __forceinline__ void lds8(uint32_t a, float (&v)[8]) {
  const float4 p = lds_f4(a), q = lds_f4(a + 16);
  v[0] = p.x; v[1] = p.y; v[2] = p.z; v[3] = p.w; v[4] = q.x; v[5] = q.y; v[6] = q.z; v[7] = q.w;
}
__device__ __forceinline__ void lds8_bf(uint32_t a, float (&v)[8]) {
  const uint4 u = lds_u4(a);
  v[0] = bf_lo(u.x); v[1] = bf_hi(u.x); v[2] = bf_lo(u.y); v[3] = bf_hi(u.y); v[4] = bf_lo(u.z); v[5] = bf_hi(u.z); v[6] = bf_lo(u.w); v[7] = bf_hi(u.w);
}
__device__ __forceinline__ uint4 pack8(const float (&v)[8]) {
  return make_uint4(pack_bf16(v[0], v[1]), pack_bf16(v[2], v[3]), pack_bf16(v[4], v[5]), pack_bf16(v[6], v[7]));
}
__device__ __forceinline__ void mbar_wait_c(uint32_t a, uint32_t ph) {
  asm volatile("{\n.reg .pred p;\nSPIN:\nmbarrier.try_wait.parity.shared::cta.b64 p, [%0], %1;\n@!p bra SPIN;\n}\n" :: "r"(a), "r"(ph) : "memory");
}
constexpr int ST_P = 80;
constexpr int E_TILE = 128 * 80 * 2;

struct Maps { CUtensorMap h, wq, k, v, o, wo3, wo2, xa, w1t, us, w2t, x1, w3, g, w4t, ex, exa, ex1; };
struct PfList { const uint8_t* p[6]; };

constexpr int M_AOFF = 102400, M_NA = 7;

__global__ void __cluster_dims__(2, 1, 1) __launch_bounds__(384, 1)
fused_kernel(const __grid_constant__ Maps tm, const __grid_constant__ PfList pf, const __grid_constant__ PrepW pw, const bf16* __restrict__ x, bf16* __restrict__ out) {
  extern __shared__ uint8_t smem_raw[];
  const uint32_t sb = (smem_u32(smem_raw) + 1023) & ~1023u;
  TL_ENTRY(2);
  const uint32_t bar_full = sb + A_NSLOT * A_SLOT;
  const uint32_t bar_empty = bar_full + 8 * A_NSLOT;
  const uint32_t bar_sig = bar_empty + 8 * A_NSLOT;
  const uint32_t mb_full = bar_sig + 16;
  const uint32_t mb_empty = mb_full + 96;
  const uint32_t par = sb + T_PAR;
  float* parf = reinterpret_cast<float*>(smem_raw + (par - smem_u32(smem_raw)));
  uint32_t rank;
  asm volatile("mov.u32 %0, %%cluster_ctarank;" : "=r"(rank));
  const int cid = blockIdx.x >> 1;
  const int wg = threadIdx.x >> 7;
  const int qtile = (cid & 7) * 2 + rank, hbase = cid >> 3;
  const int o_qt = qtile, o_nh = (cid >> 3) & 1, o_ks = cid >> 4;
  const int o_col = o_nh * 320 + o_ks * 80;
  const int qt = cid >> 2, js = (cid & 3) * 2 + rank;
  if (threadIdx.x == 0) {
    for (int i = 0; i < A_NSLOT; i++) { mbar_init(bar_full + 8 * i, 1); mbar_init(bar_empty + 8 * i, 16); }
    mbar_init(bar_sig, 4); mbar_init(bar_sig + 8, 4);
    for (int i = 0; i < 12; i++) { mbar_init(mb_full + 8 * i, 1); mbar_init(mb_empty + 8 * i, i < 5 ? 8 : 16); }
    asm volatile("fence.mbarrier_init.release.cluster;" ::: "memory");
    prefetch_tmap(&tm.h); prefetch_tmap(&tm.wq); prefetch_tmap(&tm.k); prefetch_tmap(&tm.v);
  }
  __syncthreads();
  cluster_sync();

  if (wg == 0) {
    asm volatile("setmaxnreg.dec.sync.aligned.u32 40;");
    if (threadIdx.x == 0) {
      Ring r{0, 1};
#define P_ACQ(bytes_) do { mbar_wait(bar_empty + 8 * r.slot, r.phase); mbar_expect(bar_full + 8 * r.slot, bytes_); } while (0)
#define P_DST (sb + r.slot * A_SLOT)
#define P_BAR (bar_full + 8 * r.slot)
      pdl_wait();
      TL_WAITED(2);
#pragma unroll 1
      for (int item = 0; item < 4; item++) {
        const int head = hbase + 8 * item;
#pragma unroll 1
        for (int kb = 0; kb < 10; kb++) {
          P_ACQ(16384);
          tma2d(P_DST, &tm.h, P_BAR, kb * 64, qtile * 128);
          r.adv(A_NSLOT);
          P_ACQ(A_SLOT);
          if ((uint32_t)(kb & 1) == rank) tma3d_mc(P_DST, &tm.wq, P_BAR, 0, kb * 64, head * 3, 3);
          r.adv(A_NSLOT);
        }
#pragma unroll 1
        for (int j = 0; j <= A_NKV; j++) {
          if (j < A_NKV) {
            P_ACQ(A_SLOT);
            if (rank == 0) tma3d_mc(P_DST, &tm.k, P_BAR, 0, head * S_ + j * 64, 0, 3);
            r.adv(A_NSLOT);
          }
          if (j > 0) {
            P_ACQ(A_SLOT);
            if (rank == 1) tma3d_mc(P_DST, &tm.v, P_BAR, 0, head * S_ + (j - 1) * 64, 0, 3);
            r.adv(A_NSLOT);
          }
          if (item == 3 && (j & 3) == 0) {
            const int c = (j >> 2) * 128 + blockIdx.x;
            if (c < 980) {
              const int li = c < 480 ? 0 : c < 600 ? 1 : c < 720 ? 2 : c < 880 ? 3 : c < 930 ? 4 : 5;
              const int c0 = c < 480 ? 0 : c < 600 ? 480 : c < 720 ? 600 : c < 880 ? 720 : c < 930 ? 880 : 930;
              asm volatile("cp.async.bulk.prefetch.L2.global [%0], 16384;" :: "l"(pf.p[li] + (size_t)(c - c0) * 16384) : "memory");
            }
          }
          if (item == 3) {
            if (j >= 6 && j < 24) {
              const int kb = j - 6;
              asm volatile("cp.async.bulk.prefetch.tensor.2d.L2.global [%0, {%1, %2}];"
                           :: "l"(&tm.o), "r"(((kb / 6) * 8 + 2 * o_ks + (kb % 6) / 3) * DH_ + (kb % 3) * 64), "r"(o_qt * 128) : "memory");
            }
            if (j >= 24 && j < 30) flag_wait(g_flag + F_O + o_qt * 32 + ((j - 24) >> 1) * 8 + 2 * o_ks + (j & 1), 2);
            if (j == 0) {
              prefetch_tmap(&tm.o); prefetch_tmap(&tm.wo3); prefetch_tmap(&tm.wo2); prefetch_tmap(&tm.xa); prefetch_tmap(&tm.w1t); prefetch_tmap(&tm.us);
              prefetch_tmap(&tm.w2t); prefetch_tmap(&tm.x1); prefetch_tmap(&tm.w3); prefetch_tmap(&tm.g); prefetch_tmap(&tm.w4t);
              prefetch_tmap(&tm.ex); prefetch_tmap(&tm.exa); prefetch_tmap(&tm.ex1);
            }
          }
        }
      }
#pragma unroll 1
      for (int kb = 0; kb < 24; kb++) {
        const int head = (kb / 6) * 8 + 2 * o_ks + (kb % 6) / 3;
        const int kcol = head * DH_ + (kb % 3) * 64;
        P_ACQ(24576);
        if (rank == 0) tma3d_mc(P_DST, &tm.wo3, P_BAR, 0, kcol, o_nh * 5, 3);
        r.adv(A_NSLOT);
        P_ACQ(16384);
        if (rank == 1) tma3d_mc(P_DST, &tm.wo2, P_BAR, 0, kcol, o_nh * 5 + 3, 3);
        r.adv(A_NSLOT);
        if (kb == 18 || kb == 21) flag_wait(g_flag + F_O + o_qt * 32 + head, 2);
        if (kb % 3 == 0) fence_async_global();
        P_ACQ(16384);
        tma2d(P_DST, &tm.o, P_BAR, kcol, o_qt * 128);
        r.adv(A_NSLOT);
      }
      P_ACQ(E_TILE);
      tma2d(P_DST, &tm.ex, P_BAR, o_col, o_qt * 128);
      r.adv(A_NSLOT);
      flag_wait(g_flag + F_XCH + (o_qt * 2 + o_nh) * 4 + o_ks, 6);
      fence_async_global();
#pragma unroll 1
      for (int i = 0; i < 3; i++) {
        P_ACQ(E_TILE);
        asm volatile("cp.async.bulk.shared::cluster.global.mbarrier::complete_tx::bytes [%0], [%1], %2, [%3];"
                     :: "r"(P_DST), "l"(g_xch + (size_t)((((o_qt * 2 + o_nh) * 4 + o_ks) * 4) + ((o_ks + 1 + i) & 3)) * (E_TILE / 2)), "r"(E_TILE), "r"(P_BAR) : "memory");
        r.adv(A_NSLOT);
      }
      flag_wait(g_flag + F_PREP, PREP_CTAS);
      fence_async_global();
#pragma unroll 1
      for (int i = 0; i < A_NSLOT; i++) { mbar_wait(bar_empty + 8 * r.slot, r.phase); r.adv(A_NSLOT); }
      Ring ra{0, 1};
      uint32_t bpar = 0x1f;
#pragma unroll 1
      for (int ph = 0; ph < 4; ph++) {
        const CUtensorMap* ma = ph == 0 ? &tm.xa : ph == 1 ? &tm.us : ph == 2 ? &tm.x1 : &tm.g;
        const CUtensorMap* mb = ph == 0 ? &tm.w1t : ph == 1 ? &tm.w2t : ph == 2 ? &tm.w3 : &tm.w4t;
        const int nkb = ph == 3 ? 24 : 10;
        const int nbl = ph == 2 ? 10 : nkb / 2;
        const int nel = ph == 1 ? 1 : ph == 3 ? 2 : 0;
        const uint32_t nbs = ph == 2 ? 4 : 5, bsz = ph == 2 ? 24576 : 20480;
        int bl = 0; uint32_t bs = 0;
#pragma unroll 1
        for (int i = 0; i < 5; i++) mbar_wait(mb_empty + 8 * i, (bpar >> i) & 1);
#define T_LOADB() do { mbar_wait(mb_empty + 8 * bs, (bpar >> bs) & 1); bpar ^= 1u << bs; mbar_expect(mb_full + 8 * bs, bsz);    \
                       if (bl < nbl) tma3d(sb + bs * bsz, mb, mb_full + 8 * bs, 0, ph == 2 ? bl * 64 : js * 80, ph == 2 ? js * 3 : bl * 2); \
                       else tma2d(sb + bs * bsz, bl == nbl ? &tm.exa : &tm.ex1, mb_full + 8 * bs, js * 80, qt * 128); \
                       bl++; if (++bs == nbs) bs = 0; } while (0)
#pragma unroll 1
        for (uint32_t i = 0; i < nbs; i++) T_LOADB();
        TX(8 + ph * 4);
        const unsigned* fl = g_flag + F_XA + 16 * ph;
        flag_wait(fl + qt, 16);
        if (ph == 1) { flag_wait(fl + ((qt + 15) & 15), 16); flag_wait(fl + ((qt + 1) & 15), 16); }
        TX(9 + ph * 4);
        fence_async_global();
#pragma unroll 1
        for (int kb = 0; kb < nkb; kb++) {
          mbar_wait(mb_empty + 40 + 8 * ra.slot, ra.phase);
          mbar_expect(mb_full + 40 + 8 * ra.slot, 16384);
          asm volatile("cp.async.bulk.tensor.2d.shared::cluster.global.mbarrier::complete_tx::bytes.multicast::cluster [%0], [%1, {%3, %4}], [%2], %5;"
                       :: "r"(sb + M_AOFF + ra.slot * 16384 + rank * 8192), "l"(ma), "r"(mb_full + 40 + 8 * ra.slot), "r"(kb * 64), "r"(qt * 128 + (int)rank * 64), "h"((uint16_t)3) : "memory");
          ra.adv(M_NA);
          while (bl < nbl + nel && (kb == nkb - 1 || kb >= (ph == 2 ? bl + 2 : 2 * bl - 3))) T_LOADB();
        }
      }
    } else if (threadIdx.x >= 32 && threadIdx.x < 96) {
      const int w = (threadIdx.x >> 5) - 1, lane = threadIdx.x & 31;
#pragma unroll 1
      for (int sig = 0; sig < 9; sig++) {
        mbar_wait(bar_sig + 8 * w, sig & 1);
        if (threadIdx.x == 32) TX(32 + sig * 2);
        unsigned* f;
        bool act = lane == 0;
        if (sig < 4) f = g_flag + F_O + qtile * 32 + hbase + 8 * sig;
        else if (sig == 4) { f = g_flag + F_XCH + (o_qt * 2 + o_nh) * 4 + (lane & 3); act = lane < 4 && lane != o_ks; }
        else if (sig == 5) f = g_flag + F_XA + o_qt;
        else f = g_flag + F_XA + 16 * (sig - 5) + qt;
        if (act) {
          asm volatile("fence.acq_rel.gpu;" ::: "memory");
          asm volatile("red.relaxed.gpu.global.add.u32 [%0], 1;" :: "l"(f) : "memory");
        }
        if (threadIdx.x == 32) TX(33 + sig * 2);
        __syncwarp();
      }
    } else if (threadIdx.x >= 96) {
      pdl_wait();
      prep_warp(pw, reinterpret_cast<bf16(*)[72]>(smem_raw + (sb + T_PREP - smem_u32(smem_raw))), threadIdx.x & 31);
    }
    __syncwarp();
    cluster_sync();
  } else {
    asm volatile("setmaxnreg.inc.sync.aligned.u32 232;");
    const int w = wg - 1;
    const int lane = threadIdx.x & 31;
    const int warp = (threadIdx.x >> 5) & 3;
    const int tid = threadIdx.x - 128;
    const uint32_t rel_base = mapa(bar_empty, (lane == 0) ? rank : (rank ^ 1));
    Ring r{0, 0};
#define A_RELEASE(slot_) do { if (lane < 2) mbar_arrive_remote(rel_base + 8 * (slot_)); } while (0)
#define SIGNAL() do { __syncwarp(); if (lane == 0) mbar_arrive(bar_sig + 8 * w); } while (0)
    {
    const float SC = 0.07216878364870322f * 1.4426950408889634f;
    float o[96];
    uint32_t q[48];
    float s[32];
    uint32_t p[16], p2[16];
    if (w == 1) bar_arrive(1, 256);
    for (int item = 0; item < 4; item++) {
      const int head = hbase + 8 * item;
      TSA(item, 0);
      uint32_t prevA = 0, prevB = 0;
      for (int kb = 0; kb < 10; kb++) {
        const uint32_t sA = r.slot; mbar_wait_c(bar_full + 8 * sA, r.phase); r.adv(A_NSLOT);
        const uint32_t sB = r.slot; mbar_wait_c(bar_full + 8 * sB, r.phase); r.adv(A_NSLOT);
        const uint64_t da = mkdesc(sb + sA * A_SLOT + w * 8192, 16, 1024);
        const uint64_t db = mkdesc(sb + sB * A_SLOT, 8192, 1024);
        wg_fence();
#pragma unroll
        for (int kk = 0; kk < 4; kk++) wgmma_ss_n192<1>(o, da + kk * 2, db + kk * 128, (kb | kk) != 0);
        wg_commit();
        if (kb > 0) { wg_wait<1>(); A_RELEASE(prevA); A_RELEASE(prevB); }
        prevA = sA; prevB = sB;
      }
      wg_wait<0>();
      fence_regs(o);
      A_RELEASE(prevA); A_RELEASE(prevB);
#pragma unroll
      for (int i = 0; i < 48; i++) q[i] = pack_bf16(o[2 * i], o[2 * i + 1]);

      TSA(item, 1);
      float c0, c1, l0, l1;
      {
        const uint32_t sK = r.slot; mbar_wait_c(bar_full + 8 * sK, r.phase); r.adv(A_NSLOT);
        const uint64_t dk = mkdesc(sb + sK * A_SLOT, 16, 1024);
        bar_sync(1 + w, 256);
        wg_fence();
#pragma unroll
        for (int kk = 0; kk < 12; kk++)
          wgmma_rs_n64<0>(s, q[4 * kk], q[4 * kk + 1], q[4 * kk + 2], q[4 * kk + 3], dk + (kk >> 2) * 512 + (kk & 3) * 2, kk != 0);
        wg_commit();
        bar_arrive(1 + (w ^ 1), 256);
        wg_wait<0>();
        fence_regs(s);
        A_RELEASE(sK);
        float mx0 = fmaxf(s[0], s[1]), mx1 = fmaxf(s[2], s[3]);
#pragma unroll
        for (int i = 1; i < 8; i++) { mx0 = fmaxf(mx0, fmaxf(s[4 * i], s[4 * i + 1])); mx1 = fmaxf(mx1, fmaxf(s[4 * i + 2], s[4 * i + 3])); }
        mx0 = fmaxf(mx0, __shfl_xor_sync(0xffffffffu, mx0, 1)); mx1 = fmaxf(mx1, __shfl_xor_sync(0xffffffffu, mx1, 1));
        mx0 = fmaxf(mx0, __shfl_xor_sync(0xffffffffu, mx0, 2)); mx1 = fmaxf(mx1, __shfl_xor_sync(0xffffffffu, mx1, 2));
        c0 = mx0 * SC; c1 = mx1 * SC;
        l0 = 0.f; l1 = 0.f;
#pragma unroll
        for (int i = 0; i < 8; i++) {
          s[4 * i] = ex2(fmaf(s[4 * i], SC, -c0)); s[4 * i + 1] = ex2(fmaf(s[4 * i + 1], SC, -c0));
          s[4 * i + 2] = ex2(fmaf(s[4 * i + 2], SC, -c1)); s[4 * i + 3] = ex2(fmaf(s[4 * i + 3], SC, -c1));
          l0 += s[4 * i] + s[4 * i + 1]; l1 += s[4 * i + 2] + s[4 * i + 3];
        }
#pragma unroll
        for (int i = 0; i < 16; i++) p[i] = pack_bf16(s[2 * i], s[2 * i + 1]);
      }
      TSA(item, 2);
      uint32_t okn;
      {
        Ring r2 = r; r2.adv(A_NSLOT);
        okn = mbar_try(bar_full + 8 * r.slot, r.phase) & mbar_try(bar_full + 8 * r2.slot, r2.phase);
      }
#define A_STEP(PC, PN, FIRST)                                                                                          \
      {                                                                                                                \
        const uint32_t sK = r.slot, phK = r.phase; r.adv(A_NSLOT);                                                     \
        const uint32_t sV = r.slot, phV = r.phase; r.adv(A_NSLOT);                                                     \
        const uint64_t dk = mkdesc(sb + sK * A_SLOT, 16, 1024);                                                        \
        const uint64_t dv = mkdesc(sb + sV * A_SLOT, 8192, 1024);                                                      \
        if (!okn) { mbar_wait_c(bar_full + 8 * sK, phK); mbar_wait_c(bar_full + 8 * sV, phV); }                            \
        bar_sync(1 + w, 256);                                                                                          \
        wg_fence();                                                                                                    \
        _Pragma("unroll") for (int kk = 0; kk < 12; kk++)                                                              \
          wgmma_rs_n64<0>(s, q[4 * kk], q[4 * kk + 1], q[4 * kk + 2], q[4 * kk + 3], dk + (kk >> 2) * 512 + (kk & 3) * 2, kk != 0); \
        wg_commit();                                                                                                   \
        _Pragma("unroll") for (int kk = 0; kk < 4; kk++)                                                               \
          wgmma_rs_n192<1>(o, PC[4 * kk], PC[4 * kk + 1], PC[4 * kk + 2], PC[4 * kk + 3], dv + kk * 128, !(FIRST) || (kk != 0)); \
        wg_commit();                                                                                                   \
        bar_arrive(1 + (w ^ 1), 256);                                                                                  \
        {                                                                                                              \
          Ring r2 = r; r2.adv(A_NSLOT);                                                                                \
          okn = mbar_try(bar_full + 8 * r.slot, r.phase) & mbar_try(bar_full + 8 * r2.slot, r2.phase);                 \
        }                                                                                                              \
        wg_wait<1>();                                                                                                  \
        fence_regs(s);                                                                                                 \
        A_RELEASE(sK);                                                                                                 \
        float b0 = 0.f, b1 = 0.f;                                                                                      \
        _Pragma("unroll") for (int i = 0; i < 8; i++) {                                                                \
          const float e0 = ex2(fmaf(s[4 * i], SC, -c0)), e1 = ex2(fmaf(s[4 * i + 1], SC, -c0));                        \
          const float e2 = ex2(fmaf(s[4 * i + 2], SC, -c1)), e3 = ex2(fmaf(s[4 * i + 3], SC, -c1));                    \
          b0 += e0 + e1; b1 += e2 + e3;                                                                                \
          PN[2 * i] = pack_bf16(e0, e1); PN[2 * i + 1] = pack_bf16(e2, e3);                                            \
        }                                                                                                              \
        wg_wait<0>();                                                                                                  \
        fence_regs(o);                                                                                                 \
        fence_regs(PC);                                                                                                \
        A_RELEASE(sV);                                                                                                 \
        if (__any_sync(0xffffffffu, !(b0 <= 65536.f) || !(b1 <= 65536.f))) {                                           \
          float mx0 = fmaxf(s[0], s[1]), mx1 = fmaxf(s[2], s[3]);                                                      \
          _Pragma("unroll") for (int i = 1; i < 8; i++) {                                                              \
            mx0 = fmaxf(mx0, fmaxf(s[4 * i], s[4 * i + 1])); mx1 = fmaxf(mx1, fmaxf(s[4 * i + 2], s[4 * i + 3]));     \
          }                                                                                                            \
          mx0 = fmaxf(mx0, __shfl_xor_sync(0xffffffffu, mx0, 1)); mx1 = fmaxf(mx1, __shfl_xor_sync(0xffffffffu, mx1, 1)); \
          mx0 = fmaxf(mx0, __shfl_xor_sync(0xffffffffu, mx0, 2)); mx1 = fmaxf(mx1, __shfl_xor_sync(0xffffffffu, mx1, 2)); \
          const float n0 = fmaxf(c0, mx0 * SC), n1 = fmaxf(c1, mx1 * SC);                                              \
          const float a0 = ex2(c0 - n0), a1 = ex2(c1 - n1);                                                            \
          c0 = n0; c1 = n1;                                                                                            \
          l0 *= a0; l1 *= a1;                                                                                          \
          _Pragma("unroll") for (int i = 0; i < 24; i++) { o[4 * i] *= a0; o[4 * i + 1] *= a0; o[4 * i + 2] *= a1; o[4 * i + 3] *= a1; } \
          b0 = 0.f; b1 = 0.f;                                                                                          \
          _Pragma("unroll") for (int i = 0; i < 8; i++) {                                                              \
            const float e0 = ex2(fmaf(s[4 * i], SC, -c0)), e1 = ex2(fmaf(s[4 * i + 1], SC, -c0));                      \
            const float e2 = ex2(fmaf(s[4 * i + 2], SC, -c1)), e3 = ex2(fmaf(s[4 * i + 3], SC, -c1));                  \
            b0 += e0 + e1; b1 += e2 + e3;                                                                              \
            PN[2 * i] = pack_bf16(e0, e1); PN[2 * i + 1] = pack_bf16(e2, e3);                                          \
          }                                                                                                            \
        }                                                                                                              \
        l0 += b0; l1 += b1;                                                                                            \
      }
      for (int jj = 0; jj < 15; jj++) {
        A_STEP(p, p2, jj == 0)
        A_STEP(p2, p, false)
      }
      A_STEP(p, p2, false)
      TSA(item, 3);
      {
        const uint32_t sV = r.slot; mbar_wait_c(bar_full + 8 * sV, r.phase); r.adv(A_NSLOT);
        const uint64_t dv = mkdesc(sb + sV * A_SLOT, 8192, 1024);
        bar_sync(1 + w, 256);
        wg_fence();
#pragma unroll
        for (int kk = 0; kk < 4; kk++)
          wgmma_rs_n192<1>(o, p2[4 * kk], p2[4 * kk + 1], p2[4 * kk + 2], p2[4 * kk + 3], dv + kk * 128, 1);
        wg_commit();
        bar_arrive(1 + (w ^ 1), 256);
        wg_wait<0>();
        fence_regs(o);
        A_RELEASE(sV);
      }
      TSA(item, 4);
      l0 += __shfl_xor_sync(0xffffffffu, l0, 1); l1 += __shfl_xor_sync(0xffffffffu, l1, 1);
      l0 += __shfl_xor_sync(0xffffffffu, l0, 2); l1 += __shfl_xor_sync(0xffffffffu, l1, 2);
      const float i0 = 1.f / l0, i1 = 1.f / l1;
      bf16* orow = g_o + (size_t)(qtile * 128 + w * 64 + warp * 16 + (lane >> 2)) * HD_ + head * DH_ + (lane & 3) * 8;
#pragma unroll
      for (int g = 0; g < 6; g++) {
        uint32_t u0 = pack_bf16(o[16 * g + 0] * i0, o[16 * g + 1] * i0), u1 = pack_bf16(o[16 * g + 4] * i0, o[16 * g + 5] * i0);
        uint32_t u2 = pack_bf16(o[16 * g + 8] * i0, o[16 * g + 9] * i0), u3 = pack_bf16(o[16 * g + 12] * i0, o[16 * g + 13] * i0);
        quad_transpose(u0, u1, u2, u3, lane);
        *reinterpret_cast<uint4*>(orow + g * 32) = make_uint4(u0, u1, u2, u3);
        uint32_t v0 = pack_bf16(o[16 * g + 2] * i1, o[16 * g + 3] * i1), v1 = pack_bf16(o[16 * g + 6] * i1, o[16 * g + 7] * i1);
        uint32_t v2 = pack_bf16(o[16 * g + 10] * i1, o[16 * g + 11] * i1), v3 = pack_bf16(o[16 * g + 14] * i1, o[16 * g + 15] * i1);
        quad_transpose(v0, v1, v2, v3, lane);
        *reinterpret_cast<uint4*>(orow + (size_t)8 * HD_ + g * 32) = make_uint4(v0, v1, v2, v3);
      }
      SIGNAL();
      TSA(item, 5);
    }
    }
    TS(3, 2);
    const uint32_t st_w = (uint32_t)((warp * 16 + (lane >> 2)) * ST_P + (lane & 3) * 2) * 4;
    const uint32_t st_x = (lane & 8) << 2;
    const int er = (tid & 127) >> 1, eh = tid & 1;
    const uint32_t st_r = (uint32_t)(er * ST_P + (eh ^ ((er >> 1) & 1)) * 8) * 4;
    const uint32_t e_r = (uint32_t)((w * 64 + er) * 160 + eh * 16);
    const uint32_t p_r = par + eh * 32;
#define STAGE10(ACC, BASE)                                                                                             \
    _Pragma("unroll") for (int nb = 0; nb < 10; nb++) {                                                                \
      sts_f2(stg + st_w + ((nb * 32) ^ st_x), ACC(BASE + 4 * nb), ACC(BASE + 4 * nb + 1));                                       \
      sts_f2(stg + st_w + ((nb * 32) ^ st_x) + 8 * ST_P * 4, ACC(BASE + 4 * nb + 2), ACC(BASE + 4 * nb + 3));                    \
    }

    {
      float acc1[96], acc2[64];
      uint32_t p0 = 0, p1 = 0, p2 = 0;
#pragma unroll 1
      for (int kb = 0; kb < 24; kb++) {
        const uint32_t s1 = r.slot; mbar_wait_c(bar_full + 8 * s1, r.phase); r.adv(A_NSLOT);
        const uint32_t s2 = r.slot; mbar_wait_c(bar_full + 8 * s2, r.phase); r.adv(A_NSLOT);
        const uint32_t sa = r.slot; mbar_wait_c(bar_full + 8 * sa, r.phase); r.adv(A_NSLOT);
        const uint64_t da = mkdesc(sb + sa * A_SLOT + w * 8192, 16, 1024);
        const uint64_t d1 = mkdesc(sb + s1 * A_SLOT, 8192, 1024), d2 = mkdesc(sb + s2 * A_SLOT, 8192, 1024);
        wg_fence();
#pragma unroll
        for (int kk = 0; kk < 4; kk++) {
          wgmma_ss_n192<1>(acc1, da + kk * 2, d1 + kk * 128, (kb | kk) != 0);
          wgmma_ss_n128<1>(acc2, da + kk * 2, d2 + kk * 128, (kb | kk) != 0);
        }
        wg_commit();
        if (kb > 0) { wg_wait<1>(); A_RELEASE(p0); A_RELEASE(p1); A_RELEASE(p2); }
        p0 = s1; p1 = s2; p2 = sa;
        if (kb == 4) {
          if (tid == 255) flag_wait(g_flag + F_PREP, PREP_CTAS);
          bar_sync(5, 256);
#pragma unroll 1
          for (int i = tid; i < P_SC; i += 256) {
            const int v = i < P_CS3 ? i / 80 : 9, j = i - (i < P_CS3 ? v * 80 : P_CS3);
            const float* src = v == 0 ? g_mod + 2 * D_ + o_col : v == 1 ? g_mod + 4 * D_ + o_col : v == 2 ? g_mod + 3 * D_ + o_col
                             : v < 6 ? g_vec + (v - 3) * D_ + js * 80 : v == 6 ? g_mod + 4 * D_ + js * 80 : v == 7 ? g_mod + 3 * D_ + js * 80
                             : v == 8 ? g_mod + 5 * D_ + js * 80 : g_vec + 3 * D_ + js * 192;
            parf[i] = __ldcg(src + j);
          }
          if (tid >= 224) {
            float sv[5] = {0.f, 0.f, 0.f, 0.f, 0.f};
#pragma unroll 1
            for (int i = lane; i < D_; i += 32) {
              const float a = __ldcg(g_mod + 4 * D_ + i), b = __ldcg(g_mod + 3 * D_ + i);
              sv[0] += a; sv[1] = fmaf(a, a, sv[1]); sv[2] = fmaf(a, b, sv[2]); sv[3] += b; sv[4] = fmaf(b, b, sv[4]);
            }
#pragma unroll 1
            for (int o_ = 16; o_ > 0; o_ >>= 1) {
#pragma unroll
              for (int i = 0; i < 5; i++) sv[i] += __shfl_xor_sync(0xffffffffu, sv[i], o_);
            }
            if (lane == 0) {
#pragma unroll
              for (int i = 0; i < 5; i++) parf[P_SC + i] = sv[i];
            }
          }
        }
      }
      wg_wait<0>();
      fence_regs(acc1); fence_regs(acc2);
      A_RELEASE(p2);
      bar_sync(5, 256);
      TS(0, 0);
      const uint32_t stg = sb + (w ? p1 : p0) * A_SLOT;
#define OACC(e) (((e) < 96) ? acc1[(e) < 96 ? (e) : 0] : acc2[(e) >= 96 ? (e) - 96 : 0])
#pragma unroll 1
      for (int i = 0; i < 4; i++) {
        const int d = (o_ks + 1 + i) & 3;
        if (d == 0) { STAGE10(OACC, 0) } else if (d == 1) { STAGE10(OACC, 40) } else if (d == 2) { STAGE10(OACC, 80) } else { STAGE10(OACC, 120) }
        bar_sync(3 + w, 128);
        if (i < 3) {
          uint8_t* dst = reinterpret_cast<uint8_t*>(g_xch + (size_t)((((o_qt * 2 + o_nh) * 4 + d) * 4) + o_ks) * (E_TILE / 2)) + e_r;
#pragma unroll 1
          for (int c = 0; c < 5; c++) {
            float v[8];
            lds8(stg + st_r + c * 64, v);
            *reinterpret_cast<uint4*>(dst + c * 32) = pack8(v);
          }
          if (i == 2) SIGNAL();
          bar_sync(3 + w, 128);
        }
      }
      const uint32_t sx = r.slot; mbar_wait_c(bar_full + 8 * sx, r.phase); r.adv(A_NSLOT);
      const uint32_t q0 = r.slot; mbar_wait_c(bar_full + 8 * q0, r.phase); r.adv(A_NSLOT);
      const uint32_t q1 = r.slot; mbar_wait_c(bar_full + 8 * q1, r.phase); r.adv(A_NSLOT);
      const uint32_t q2 = r.slot; mbar_wait_c(bar_full + 8 * q2, r.phase); r.adv(A_NSLOT);
      TS(0, 1);
      float st[6] = {0.f, 0.f, 0.f, 0.f, 0.f, 0.f};
      bf16* dst = g_xa + (size_t)(o_qt * 128 + w * 64 + er) * D_ + o_col + eh * 8;
#pragma unroll 1
      for (int c = 0; c < 5; c++) {
        float v[8], t0[8], t1[8], t2[8];
        lds8(stg + st_r + c * 64, v);
        lds8_bf(sb + q0 * A_SLOT + e_r + c * 32, t0); lds8_bf(sb + q1 * A_SLOT + e_r + c * 32, t1); lds8_bf(sb + q2 * A_SLOT + e_r + c * 32, t2);
#pragma unroll
        for (int e = 0; e < 8; e++) v[e] += (t0[e] + t1[e]) + t2[e];
        lds8_bf(sb + sx * A_SLOT + e_r + c * 32, t0);
        lds8(p_r + P_OGA * 4 + c * 64, t1);
#pragma unroll
        for (int e = 0; e < 8; e++) v[e] = fmaf(t1[e], v[e], t0[e]);
        const uint4 pk = pack8(v);
        *reinterpret_cast<uint4*>(dst + c * 16) = pk;
        v[0] = bf_lo(pk.x); v[1] = bf_hi(pk.x); v[2] = bf_lo(pk.y); v[3] = bf_hi(pk.y); v[4] = bf_lo(pk.z); v[5] = bf_hi(pk.z); v[6] = bf_lo(pk.w); v[7] = bf_hi(pk.w);
        lds8(p_r + P_OA * 4 + c * 64, t1);
        lds8(p_r + P_OB * 4 + c * 64, t2);
#pragma unroll
        for (int e = 0; e < 8; e++) {
          const float y = t1[e] * v[e];
          st[0] += v[e]; st[1] = fmaf(v[e], v[e], st[1]); st[2] += y; st[3] = fmaf(t1[e], y, st[3]); st[4] = fmaf(y, y, st[4]); st[5] = fmaf(t2[e], y, st[5]);
        }
      }
#pragma unroll
      for (int i = 0; i < 6; i++) st[i] += __shfl_xor_sync(0xffffffffu, st[i], 1);
      if (eh == 0) {
        float* sp = g_st1 + (size_t)(o_qt * 128 + w * 64 + er) * 8;
        asm volatile("red.global.add.v4.f32 [%0], {%1, %2, %3, %4};" :: "l"(sp), "f"(st[0]), "f"(st[1]), "f"(st[2]), "f"(st[3]) : "memory");
        asm volatile("red.global.add.v2.f32 [%0], {%1, %2};" :: "l"(sp + 4), "f"(st[4]), "f"(st[5]) : "memory");
      }
      SIGNAL();
      bar_sync(5, 256);
      A_RELEASE(p0); A_RELEASE(p1); A_RELEASE(sx); A_RELEASE(q0); A_RELEASE(q1); A_RELEASE(q2);
      TS(0, 2);
    }

    Ring ra{0, 0};
    uint32_t bpar = 0;
    const uint32_t rel_a = mapa(mb_empty + 40, (lane == 0) ? rank : (rank ^ 1));
#define B_NEXT(s_) do { s_ = bs; mbar_wait_c(mb_full + 8 * bs, (bpar >> bs) & 1); bpar ^= 1u << bs; if (++bs == nbs) bs = 0; } while (0)
#define B_RELEASE(s_) do { if (lane == 0) mbar_arrive(mb_empty + 8 * (s_)); } while (0)
#define MA_RELEASE(s_) do { if (lane < 2) mbar_arrive_remote(rel_a + 8 * (s_)); } while (0)
    const int grow = qt * 128 + w * 64 + er;
    float mu = 0.f, rs = 0.f;
#pragma unroll 1
    for (int ph = 0; ph < 4; ph++) {
      float acc[96];
      float (&acc80)[40] = *reinterpret_cast<float(*)[40]>(&acc[0]);
      uint32_t pa = 0, pb = 0, sbq = 0;
      float4 s03 = make_float4(0.f, 0.f, 0.f, 0.f);
      float2 s45 = make_float2(0.f, 0.f);
      const int nkb = ph == 3 ? 24 : 10;
      const uint32_t nbs = ph == 2 ? 4 : 5, bsz = ph == 2 ? 24576 : 20480;
      uint32_t bs = 0;
#pragma unroll 1
      for (int kb = 0; kb < nkb; kb++) {
        if (ph == 2 || !(kb & 1)) B_NEXT(sbq);
        const uint32_t sa = ra.slot; mbar_wait_c(mb_full + 40 + 8 * sa, ra.phase); ra.adv(M_NA);
        if (kb == 0) TXC(ph);
        const uint64_t da = mkdesc(sb + M_AOFF + sa * 16384 + w * 8192, 16, 1024);
        if (ph == 2) {
          const uint64_t db = mkdesc(sb + sbq * 24576, 8192, 1024);
          wg_fence();
#pragma unroll
          for (int kk = 0; kk < 4; kk++) wgmma_ss_n192<1>(acc, da + kk * 2, db + kk * 128, (kb | kk) != 0);
        } else {
          const uint64_t db = mkdesc(sb + sbq * 20480 + (kb & 1) * 10240, 16, 1024);
          wg_fence();
#pragma unroll
          for (int kk = 0; kk < 4; kk++) wgmma_ss_n80<0>(acc80, da + kk * 2, db + kk * 2, (kb | kk) != 0);
        }
        wg_commit();
        if (kb > 0) { wg_wait<1>(); MA_RELEASE(pa); if (ph == 2 || !(kb & 1)) B_RELEASE(pb); }
        else {
          if (ph == 0) { s03 = __ldcg(reinterpret_cast<const float4*>(g_st1 + (size_t)grow * 8)); s45 = __ldcg(reinterpret_cast<const float2*>(g_st1 + (size_t)grow * 8 + 4)); }
          if (ph == 2) s45 = __ldcg(reinterpret_cast<const float2*>(g_st2 + (size_t)grow * 2));
        }
        pa = sa; pb = sbq;
      }
      wg_wait<0>();
      fence_regs(acc);
      MA_RELEASE(pa);
      bar_sync(5, 256);
      TS(1 + (ph == 3 ? 0 : ph), ph == 3 ? 2 : 0);
      const uint32_t stg = sb + (w ? pb : (pb == 0 ? nbs - 1 : pb - 1)) * bsz;
#define MACC(e) acc[e]
      if (!(ph & 1)) {
        float c0, c1, c2 = 0.f, c3 = 0.f;
        bf16* dst; bool ok = true;
        if (ph == 0) {
          const float4 sc = lds_f4(par + P_SC * 4);
          const float sbb = lds_f(par + (P_SC + 4) * 4);
          mu = s03.x * (1.f / D_);
          rs = rsqrtf(fmaxf(s03.y * (1.f / D_) - mu * mu, 0.f) + LN_EPS);
          const float m2 = (rs * (s03.z - mu * sc.x) + sc.w) * (1.f / D_);
          const float e2 = (rs * rs * (s45.x - 2.f * mu * s03.w + mu * mu * sc.y) + 2.f * rs * (s45.y - mu * sc.z) + sbb) * (1.f / D_);
          c2 = rsqrtf(fmaxf(e2 - m2 * m2, 0.f) + LN_EPS);
          c0 = c2 * rs; c1 = -c0 * mu; c3 = -c2 * m2;
          const int grp = js >> 1;
          const int sh = (grp & 2 ? 2 : 1) * (grp & 1 ? -1 : 1);
          ok = (unsigned)(grow + sh) < (unsigned)S_;
          dst = g_us + (size_t)(ok ? grow + sh : (sh > 0 ? grow + sh - S_ : grow + sh + S_)) * D_ + js * 80 + eh * 8;
        } else {
          const float m = s45.x * (1.f / D_);
          c0 = rsqrtf(fmaxf(s45.y * (1.f / D_) - m * m, 0.f) + LN_EPS);
          c1 = -c0 * m;
          dst = g_g + (size_t)grow * F_ + js * 192 + eh * 8;
        }
        const int npass = ph == 0 ? 1 : 3, nch = ph == 0 ? 5 : 4;
#pragma unroll 1
        for (int ps = 0; ps < npass; ps++) {
          if (ps == 0) { STAGE10(MACC, 0) }
          else {
            bar_sync(3 + w, 128);
            if (ps == 1) { STAGE10(MACC, 32) } else { STAGE10(MACC, 56) }
          }
          bar_sync(3 + w, 128);
          const uint32_t cofs = ps == 2 ? 64 : 0;
          const uint32_t pp = p_r + (ph == 0 ? P_VA : P_CS3 + ps * 64) * 4;
#pragma unroll 1
          for (int c = 0; c < nch; c++) {
            float v[8], t[8];
            lds8(stg + st_r + cofs + c * 64, v);
            lds8(pp + c * 64, t);
#pragma unroll
            for (int e = 0; e < 8; e++) v[e] = fmaf(c0, v[e], c1 * t[e]);
            if (ph == 0) {
              lds8(pp + 320 + c * 64, t);
#pragma unroll
              for (int e = 0; e < 8; e++) v[e] = fmaf(c2, t[e], v[e]);
              lds8(pp + 640 + c * 64, t);
#pragma unroll
              for (int e = 0; e < 8; e++) v[e] = fmaf(c3, t[e], v[e]);
            }
#pragma unroll
            for (int e = 0; e < 8; e++) v[e] = gelu_tanh(v[e]);
            const uint4 pk = pack8(v);
            *reinterpret_cast<uint4*>(dst + ps * 64 + c * 16) = ok ? pk : make_uint4(0, 0, 0, 0);
          }
        }
        SIGNAL();
        bar_sync(5, 256);
        B_RELEASE(pb);
      } else {
        STAGE10(MACC, 0)
        uint32_t e1, e2;
        B_NEXT(e1);
        e2 = e1;
        if (ph == 3) B_NEXT(e2);
        bar_sync(3 + w, 128);
        TXC(4 + (ph >> 1));
        float s1 = 0.f, s2 = 0.f;
        bf16* dst = (ph == 1 ? g_x1 : out) + (size_t)grow * D_ + js * 80 + eh * 8;
#pragma unroll 1
        for (int c = 0; c < 5; c++) {
          float v[8], xa[8], t[8];
          lds8(stg + st_r + c * 64, v);
          lds8_bf(sb + e1 * 20480 + e_r + c * 32, xa);
          if (ph == 1) {
            lds8(p_r + P_A2 * 4 + c * 64, t);
#pragma unroll
            for (int e = 0; e < 8; e++) v[e] = fmaf(t[e] * rs, xa[e] - mu, v[e]);
            lds8(p_r + P_B2 * 4 + c * 64, t);
#pragma unroll
            for (int e = 0; e < 8; e++) v[e] += t[e];
          } else {
            lds8_bf(sb + e2 * 20480 + e_r + c * 32, t);
#pragma unroll
            for (int e = 0; e < 8; e++) v[e] += t[e];
            lds8(p_r + P_GB * 4 + c * 64, t);
#pragma unroll
            for (int e = 0; e < 8; e++) v[e] = fmaf(t[e], v[e], xa[e]);
          }
          const uint4 pk = pack8(v);
          *reinterpret_cast<uint4*>(dst + c * 16) = pk;
          v[0] = bf_lo(pk.x); v[1] = bf_hi(pk.x); v[2] = bf_lo(pk.y); v[3] = bf_hi(pk.y); v[4] = bf_lo(pk.z); v[5] = bf_hi(pk.z); v[6] = bf_lo(pk.w); v[7] = bf_hi(pk.w);
#pragma unroll
          for (int e = 0; e < 8; e++) { s1 += v[e]; s2 = fmaf(v[e], v[e], s2); }
        }
        if (ph == 1) {
          s1 += __shfl_xor_sync(0xffffffffu, s1, 1); s2 += __shfl_xor_sync(0xffffffffu, s2, 1);
          if (eh == 0) asm volatile("red.global.add.v2.f32 [%0], {%1, %2};" :: "l"(g_st2 + (size_t)grow * 2), "f"(s1), "f"(s2) : "memory");
          SIGNAL();
          bar_sync(5, 256);
          B_RELEASE(pb); B_RELEASE(e1);
        }
      }
      TS(1 + (ph == 3 ? 0 : ph), ph == 3 ? 3 : 1);
    }
    if ((threadIdx.x & 127) == 0) TL_END(2);
    cluster_sync();
  }
}

typedef CUresult (*EncFn)(CUtensorMap*, CUtensorMapDataType, cuuint32_t, void*, const cuuint64_t*, const cuuint64_t*,
                          const cuuint32_t*, const cuuint32_t*, CUtensorMapInterleave, CUtensorMapSwizzle,
                          CUtensorMapL2promotion, CUtensorMapFloatOOBfill);
static EncFn g_enc = nullptr;

static CUtensorMap map2d(const void* p, uint64_t rows, uint64_t cols, uint32_t box_rows) {
  CUtensorMap m;
  cuuint64_t gd[2] = {cols, rows}; cuuint64_t gs[1] = {cols * 2};
  cuuint32_t bx[2] = {64, box_rows}; cuuint32_t es[2] = {1, 1};
  g_enc(&m, CU_TENSOR_MAP_DATA_TYPE_BFLOAT16, 2, const_cast<void*>(p), gd, gs, bx, es, CU_TENSOR_MAP_INTERLEAVE_NONE,
        CU_TENSOR_MAP_SWIZZLE_128B, CU_TENSOR_MAP_L2_PROMOTION_L2_256B, CU_TENSOR_MAP_FLOAT_OOB_FILL_NONE);
  return m;
}
static CUtensorMap map3d(const void* p, uint64_t rows, uint64_t cols, uint32_t box_rows, uint32_t nblk) {
  CUtensorMap m;
  cuuint64_t gd[3] = {64, rows, cols / 64}; cuuint64_t gs[2] = {cols * 2, 128};
  cuuint32_t bx[3] = {64, box_rows, nblk}; cuuint32_t es[3] = {1, 1, 1};
  g_enc(&m, CU_TENSOR_MAP_DATA_TYPE_BFLOAT16, 3, const_cast<void*>(p), gd, gs, bx, es, CU_TENSOR_MAP_INTERLEAVE_NONE,
        CU_TENSOR_MAP_SWIZZLE_128B, CU_TENSOR_MAP_L2_PROMOTION_L2_256B, CU_TENSOR_MAP_FLOAT_OOB_FILL_NONE);
  return m;
}

static CUtensorMap map_e(const void* p) {
  CUtensorMap m;
  cuuint64_t gd[2] = {D_, S_}; cuuint64_t gs[1] = {D_ * 2};
  cuuint32_t bx[2] = {80, 128}; cuuint32_t es[2] = {1, 1};
  g_enc(&m, CU_TENSOR_MAP_DATA_TYPE_BFLOAT16, 2, const_cast<void*>(p), gd, gs, bx, es, CU_TENSOR_MAP_INTERLEAVE_NONE,
        CU_TENSOR_MAP_SWIZZLE_NONE, CU_TENSOR_MAP_L2_PROMOTION_L2_256B, CU_TENSOR_MAP_FLOAT_OOB_FILL_NONE);
  return m;
}

template <typename... KArgs, typename... Args>
static void launch(void (*kern)(KArgs...), dim3 grid, dim3 block, int smem, bool pdl, Args... args) {
  cudaLaunchConfig_t cfg = {};
  cfg.gridDim = grid; cfg.blockDim = block; cfg.dynamicSmemBytes = smem; cfg.stream = cudaStreamPerThread;
  cudaLaunchAttribute at[1];
  at[0].id = cudaLaunchAttributeProgrammaticStreamSerialization;
  at[0].val.programmaticStreamSerializationAllowed = 1;
  cfg.attrs = at; cfg.numAttrs = pdl ? 1 : 0;
  cudaLaunchKernelEx(&cfg, kern, KArgs(args)...);
}

extern "C" void kernel_launch(void* const* d_in, const int* in_sizes, int n_in, void* d_out, int out_size) {
  const bf16* x = (const bf16*)d_in[0];
  const bf16* kc = (const bf16*)d_in[1];
  const bf16* vc = (const bf16*)d_in[2];
  const bf16* wq = (const bf16*)d_in[3];
  const bf16* wo = (const bf16*)d_in[4];
  const bf16* w1 = (const bf16*)d_in[6];
  const bf16* w2 = (const bf16*)d_in[7];
  const bf16* w3 = (const bf16*)d_in[8];
  const bf16* w4 = (const bf16*)d_in[9];
  const bf16* c = (const bf16*)d_in[10];
  const bf16* wmod = (const bf16*)d_in[11];
  bf16* out = (bf16*)d_out;

  static void *p_h, *p_o, *p_xa, *p_us, *p_x1, *p_g, *p_w1t, *p_w2t, *p_w4t;
  if (!g_enc) {
    void* fn = nullptr; cudaDriverEntryPointQueryResult qr;
    cudaGetDriverEntryPoint("cuTensorMapEncodeTiled", &fn, cudaEnableDefault, &qr);
    g_enc = (EncFn)fn;
    cudaGetSymbolAddress(&p_h, g_h); cudaGetSymbolAddress(&p_o, g_o); cudaGetSymbolAddress(&p_xa, g_xa);
    cudaGetSymbolAddress(&p_us, g_us); cudaGetSymbolAddress(&p_x1, g_x1); cudaGetSymbolAddress(&p_g, g_g);
    cudaGetSymbolAddress(&p_w1t, g_w1t); cudaGetSymbolAddress(&p_w2t, g_w2t); cudaGetSymbolAddress(&p_w4t, g_w4t);
    cudaFuncSetAttribute(fused_kernel, cudaFuncAttributeMaxDynamicSharedMemorySize, T_SMEM);
  }
  Maps tm;
  tm.h = map2d(p_h, S_, D_, 128);
  tm.wq = map3d(wq, D_, HD_, 64, 3);
  tm.k = map3d(kc, (uint64_t)H_ * S_, DH_, 64, 3);
  tm.v = map3d(vc, (uint64_t)H_ * S_, DH_, 64, 3);
  tm.o = map2d(p_o, S_, HD_, 128);
  tm.wo3 = map3d(wo, HD_, D_, 64, 3);
  tm.wo2 = map3d(wo, HD_, D_, 64, 2);
  tm.xa = map2d(p_xa, S_, D_, 64);
  tm.w1t = map3d(p_w1t, D_, D_, 80, 2);
  tm.us = map2d(p_us, S_, D_, 64);
  tm.w2t = map3d(p_w2t, D_, D_, 80, 2);
  tm.x1 = map2d(p_x1, S_, D_, 64);
  tm.w3 = map3d(w3, D_, F_, 64, 3);
  tm.g = map2d(p_g, S_, F_, 64);
  tm.w4t = map3d(p_w4t, D_, F_, 80, 2);
  tm.ex = map_e(x); tm.exa = map_e(p_xa); tm.ex1 = map_e(p_x1);
  PfList pf;
  pf.p[0] = (const uint8_t*)wo; pf.p[1] = (const uint8_t*)w3; pf.p[2] = (const uint8_t*)p_w4t;
  pf.p[3] = (const uint8_t*)x; pf.p[4] = (const uint8_t*)p_w1t; pf.p[5] = (const uint8_t*)p_w2t;

  launch(mod_kernel, dim3(120), dim3(256), 0, false, c, wmod);
  launch(ln1_kernel, dim3(256), dim3(256), 0, true, x);
  launch(fused_kernel, dim3(128), dim3(384), T_SMEM, true, tm, pf, PrepW{w1, w2, w3, w4}, x, out);
}
```

```cpp
#include <cuda_runtime.h>
#include <cuda.h>
#include <cuda_bf16.h>
#include <stdint.h>

typedef __nv_bfloat16 bf16;

constexpr int S_  = 2048;
constexpr int D_  = 640;
constexpr int H_  = 32;
constexpr int DH_ = 192;
constexpr int HD_ = H_ * DH_;
constexpr int F_  = 1536;
constexpr float LN_EPS = 1e-5f;

__device__ __forceinline__ uint32_t smem_u32(const void* p) { return (uint32_t)__cvta_generic_to_shared(p); }
__device__ __forceinline__ void mbar_init(uint32_t a, uint32_t c) { asm volatile("mbarrier.init.shared::cta.b64 [%0], %1;" :: "r"(a), "r"(c) : "memory"); }
__device__ __forceinline__ void mbar_expect(uint32_t a, uint32_t b) { asm volatile("mbarrier.arrive.expect_tx.shared::cta.b64 _, [%0], %1;" :: "r"(a), "r"(b) : "memory"); }
__device__ __forceinline__ void mbar_arrive(uint32_t a) { asm volatile("mbarrier.arrive.shared::cta.b64 _, [%0];" :: "r"(a) : "memory"); }
__device__ __forceinline__ void mbar_arrive_remote(uint32_t ra) { asm volatile("mbarrier.arrive.shared::cluster.b64 _, [%0];" :: "r"(ra) : "memory"); }
__device__ __forceinline__ uint32_t mapa(uint32_t a, uint32_t cta) { uint32_t r; asm volatile("mapa.shared::cluster.u32 %0, %1, %2;" : "=r"(r) : "r"(a), "r"(cta)); return r; }
__device__ __forceinline__ uint32_t mbar_try(uint32_t a, uint32_t ph) {
  uint32_t ok;
  asm volatile("{\n.reg .pred p;\nmbarrier.test_wait.parity.shared::cta.b64 p, [%1], %2;\nselp.u32 %0, 1, 0, p;\n}\n" : "=r"(ok) : "r"(a), "r"(ph) : "memory");
  return ok;
}
__device__ __forceinline__ void mbar_wait(uint32_t a, uint32_t ph) {
  asm volatile(
      "{\n.reg .pred p;\n.reg .u32 n;\n"
      "mov.u32 n, 0;\n"
      "SPIN:\n"
      "mbarrier.try_wait.parity.shared::cta.b64 p, [%0], %1;\n"
      "@p bra DONE;\n"
      "add.u32 n, n, 1;\n"
      "setp.le.u32 p, n, 16777216;\n"
      "@p bra SPIN;\n"
      "trap;\n"
      "DONE:\n}\n" :: "r"(a), "r"(ph) : "memory");
}
__device__ __forceinline__ void tma2d(uint32_t dst, const CUtensorMap* m, uint32_t bar, int c0, int c1) {
  asm volatile("cp.async.bulk.tensor.2d.shared::cluster.global.mbarrier::complete_tx::bytes [%0], [%1, {%3, %4}], [%2];"
               :: "r"(dst), "l"(m), "r"(bar), "r"(c0), "r"(c1) : "memory");
}
__device__ __forceinline__ void tma3d(uint32_t dst, const CUtensorMap* m, uint32_t bar, int c0, int c1, int c2) {
  asm volatile("cp.async.bulk.tensor.3d.shared::cluster.global.mbarrier::complete_tx::bytes [%0], [%1, {%3, %4, %5}], [%2];"
               :: "r"(dst), "l"(m), "r"(bar), "r"(c0), "r"(c1), "r"(c2) : "memory");
}
__device__ __forceinline__ void tma3d_mc(uint32_t dst, const CUtensorMap* m, uint32_t bar, int c0, int c1, int c2, uint16_t mask) {
  asm volatile("cp.async.bulk.tensor.3d.shared::cluster.global.mbarrier::complete_tx::bytes.multicast::cluster [%0], [%1, {%3, %4, %5}], [%2], %6;"
               :: "r"(dst), "l"(m), "r"(bar), "r"(c0), "r"(c1), "r"(c2), "h"(mask) : "memory");
}
__device__ __forceinline__ void tma3d_mc_hint(uint32_t dst, const CUtensorMap* m, uint32_t bar, int c0, int c1, int c2, uint16_t mask, uint64_t pol) {
  asm volatile("cp.async.bulk.tensor.3d.shared::cluster.global.mbarrier::complete_tx::bytes.multicast::cluster.L2::cache_hint [%0], [%1, {%3, %4, %5}], [%2], %6, %7;"
               :: "r"(dst), "l"(m), "r"(bar), "r"(c0), "r"(c1), "r"(c2), "h"(mask), "l"(pol) : "memory");
}
__device__ __forceinline__ void stg128(void* p, uint4 v) {
  asm volatile("st.global.v4.u32 [%0], {%1, %2, %3, %4};" :: "l"(p), "r"(v.x), "r"(v.y), "r"(v.z), "r"(v.w) : "memory");
}
__device__ __forceinline__ void prefetch_tmap(const CUtensorMap* m) { asm volatile("prefetch.tensormap [%0];" :: "l"(m) : "memory"); }
__device__ __forceinline__ void wg_fence() { asm volatile("wgmma.fence.sync.aligned;" ::: "memory"); }
__device__ __forceinline__ void wg_commit() { asm volatile("wgmma.commit_group.sync.aligned;" ::: "memory"); }
template <int N> __device__ __forceinline__ void wg_wait() { asm volatile("wgmma.wait_group.sync.aligned %0;" :: "n"(N) : "memory"); }
template <int N> __device__ __forceinline__ void fence_regs(float (&r)[N]) {
#pragma unroll
  for (int i = 0; i < N; i++) asm volatile("" : "+f"(r[i]) :: "memory");
}
template <int N> __device__ __forceinline__ void fence_regs(uint32_t (&r)[N]) {
#pragma unroll
  for (int i = 0; i < N; i++) asm volatile("" : "+r"(r[i]) :: "memory");
}
__device__ __forceinline__ uint64_t mkdesc(uint32_t addr, uint32_t lbo, uint32_t sbo) {
  return (uint64_t)((addr & 0x3FFFF) >> 4) | ((uint64_t)(lbo >> 4) << 16) | ((uint64_t)(sbo >> 4) << 32) | (1ull << 62);
}
__device__ __forceinline__ void bar_sync(int id, int n) { asm volatile("bar.sync %0, %1;" :: "r"(id), "r"(n) : "memory"); }
__device__ __forceinline__ void bar_arrive(int id, int n) { asm volatile("bar.arrive %0, %1;" :: "r"(id), "r"(n) : "memory"); }
__device__ __forceinline__ void cluster_sync() { asm volatile("barrier.cluster.arrive.aligned;\nbarrier.cluster.wait.aligned;" ::: "memory"); }
__device__ __forceinline__ void pdl_wait() { asm volatile("griddepcontrol.wait;" ::: "memory"); }
__device__ __forceinline__ void pdl_launch() { asm volatile("griddepcontrol.launch_dependents;" ::: "memory"); }
__device__ __forceinline__ float ex2(float x) { float y; asm("ex2.approx.ftz.f32 %0, %1;" : "=f"(y) : "f"(x)); return y; }
__device__ __forceinline__ uint32_t pack_bf16(float lo, float hi) { uint32_t r; asm("cvt.rn.bf16x2.f32 %0, %1, %2;" : "=r"(r) : "f"(hi), "f"(lo)); return r; }
__device__ __forceinline__ float bf_lo(uint32_t u) { return __uint_as_float(u << 16); }
__device__ __forceinline__ float bf_hi(uint32_t u) { return __uint_as_float(u & 0xffff0000u); }
__device__ __forceinline__ float bf_round(float x) { return __bfloat162float(__float2bfloat16_rn(x)); }
__device__ __forceinline__ float tanh_fast(float x) { float y; asm("tanh.approx.f32 %0, %1;" : "=f"(y) : "f"(x)); return y; }
__device__ __forceinline__ float gelu_tanh(float x) {
  float u = x * (0.7978845608028654f + 0.035677408136300125f * x * x);
  float hx = 0.5f * x;
  return fmaf(hx, tanh_fast(u), hx);
}
__device__ __forceinline__ float warp_sum(float v) {
#pragma unroll
  for (int o = 16; o > 0; o >>= 1) v += __shfl_xor_sync(0xffffffffu, v, o);
  return v;
}
__device__ __forceinline__ void quad_transpose(uint32_t& v0, uint32_t& v1, uint32_t& v2, uint32_t& v3, int lane) {
  const bool b0 = lane & 1, b1 = lane & 2;
  uint32_t s0 = b0 ? v0 : v1, s1 = b0 ? v2 : v3;
  s0 = __shfl_xor_sync(0xffffffffu, s0, 1); s1 = __shfl_xor_sync(0xffffffffu, s1, 1);
  if (b0) { v0 = s0; v2 = s1; } else { v1 = s0; v3 = s1; }
  uint32_t t0 = b1 ? v0 : v2, t1 = b1 ? v1 : v3;
  t0 = __shfl_xor_sync(0xffffffffu, t0, 2); t1 = __shfl_xor_sync(0xffffffffu, t1, 2);
  if (b1) { v0 = t0; v1 = t1; } else { v2 = t0; v3 = t1; }
}

#define TX(i)
#define TXC(i)
#define TSA(item, i)
#define TL_ENTRY(k)
#define TL_WAITED(k)
#define TL_END(k)
#define TS(item, i)
template<int TB> __device__ __forceinline__ void wgmma_rs_n64(float (&d)[32], uint32_t a0, uint32_t a1, uint32_t a2, uint32_t a3, uint64_t db, int scale_d) {
  asm volatile("{\n.reg .pred p;\nsetp.ne.b32 p, %37, 0;\n"
    "wgmma.mma_async.sync.aligned.m64n64k16.f32.bf16.bf16 {%0, %1, %2, %3, %4, %5, %6, %7, %8, %9, %10, %11, %12, %13, %14, %15, %16, %17, %18, %19, %20, %21, %22, %23, %24, %25, %26, %27, %28, %29, %30, %31}, {%32, %33, %34, %35}, %36, p, 1, 1, %38;\n}\n"
    : "+f"(d[0]), "+f"(d[1]), "+f"(d[2]), "+f"(d[3]), "+f"(d[4]), "+f"(d[5]), "+f"(d[6]), "+f"(d[7]), "+f"(d[8]), "+f"(d[9]), "+f"(d[10]), "+f"(d[11]), "+f"(d[12]), "+f"(d[13]), "+f"(d[14]), "+f"(d[15]), "+f"(d[16]), "+f"(d[17]), "+f"(d[18]), "+f"(d[19]), "+f"(d[20]), "+f"(d[21]), "+f"(d[22]), "+f"(d[23]), "+f"(d[24]), "+f"(d[25]), "+f"(d[26]), "+f"(d[27]), "+f"(d[28]), "+f"(d[29]), "+f"(d[30]), "+f"(d[31])
    : "r"(a0), "r"(a1), "r"(a2), "r"(a3), "l"(db), "r"(scale_d), "n"(TB));
}
template<int TB> __device__ __forceinline__ void wgmma_rs_n192(float (&d)[96], uint32_t a0, uint32_t a1, uint32_t a2, uint32_t a3, uint64_t db, int scale_d) {
  asm volatile("{\n.reg .pred p;\nsetp.ne.b32 p, %101, 0;\n"
    "wgmma.mma_async.sync.aligned.m64n192k16.f32.bf16.bf16 {%0, %1, %2, %3, %4, %5, %6, %7, %8, %9, %10, %11, %12, %13, %14, %15, %16, %17, %18, %19, %20, %21, %22, %23, %24, %25, %26, %27, %28, %29, %30, %31, %32, %33, %34, %35, %36, %37, %38, %39, %40, %41, %42, %43, %44, %45, %46, %47, %48, %49, %50, %51, %52, %53, %54, %55, %56, %57, %58, %59, %60, %61, %62, %63, %64, %65, %66, %67, %68, %69, %70, %71, %72, %73, %74, %75, %76, %77, %78, %79, %80, %81, %82, %83, %84, %85, %86, %87, %88, %89, %90, %91, %92, %93, %94, %95}, {%96, %97, %98, %99}, %100, p, 1, 1, %102;\n}\n"
    : "+f"(d[0]), "+f"(d[1]), "+f"(d[2]), "+f"(d[3]), "+f"(d[4]), "+f"(d[5]), "+f"(d[6]), "+f"(d[7]), "+f"(d[8]), "+f"(d[9]), "+f"(d[10]), "+f"(d[11]), "+f"(d[12]), "+f"(d[13]), "+f"(d[14]), "+f"(d[15]), "+f"(d[16]), "+f"(d[17]), "+f"(d[18]), "+f"(d[19]), "+f"(d[20]), "+f"(d[21]), "+f"(d[22]), "+f"(d[23]), "+f"(d[24]), "+f"(d[25]), "+f"(d[26]), "+f"(d[27]), "+f"(d[28]), "+f"(d[29]), "+f"(d[30]), "+f"(d[31]), "+f"(d[32]), "+f"(d[33]), "+f"(d[34]), "+f"(d[35]), "+f"(d[36]), "+f"(d[37]), "+f"(d[38]), "+f"(d[39]), "+f"(d[40]), "+f"(d[41]), "+f"(d[42]), "+f"(d[43]), "+f"(d[44]), "+f"(d[45]), "+f"(d[46]), "+f"(d[47]), "+f"(d[48]), "+f"(d[49]), "+f"(d[50]), "+f"(d[51]), "+f"(d[52]), "+f"(d[53]), "+f"(d[54]), "+f"(d[55]), "+f"(d[56]), "+f"(d[57]), "+f"(d[58]), "+f"(d[59]), "+f"(d[60]), "+f"(d[61]), "+f"(d[62]), "+f"(d[63]), "+f"(d[64]), "+f"(d[65]), "+f"(d[66]), "+f"(d[67]), "+f"(d[68]), "+f"(d[69]), "+f"(d[70]), "+f"(d[71]), "+f"(d[72]), "+f"(d[73]), "+f"(d[74]), "+f"(d[75]), "+f"(d[76]), "+f"(d[77]), "+f"(d[78]), "+f"(d[79]), "+f"(d[80]), "+f"(d[81]), "+f"(d[82]), "+f"(d[83]), "+f"(d[84]), "+f"(d[85]), "+f"(d[86]), "+f"(d[87]), "+f"(d[88]), "+f"(d[89]), "+f"(d[90]), "+f"(d[91]), "+f"(d[92]), "+f"(d[93]), "+f"(d[94]), "+f"(d[95])
    : "r"(a0), "r"(a1), "r"(a2), "r"(a3), "l"(db), "r"(scale_d), "n"(TB));
}
template<int TB> __device__ __forceinline__ void wgmma_ss_n128(float (&d)[64], uint64_t da, uint64_t db, int scale_d) {
  asm volatile("{\n.reg .pred p;\nsetp.ne.b32 p, %66, 0;\n"
    "wgmma.mma_async.sync.aligned.m64n128k16.f32.bf16.bf16 {%0, %1, %2, %3, %4, %5, %6, %7, %8, %9, %10, %11, %12, %13, %14, %15, %16, %17, %18, %19, %20, %21, %22, %23, %24, %25, %26, %27, %28, %29, %30, %31, %32, %33, %34, %35, %36, %37, %38, %39, %40, %41, %42, %43, %44, %45, %46, %47, %48, %49, %50, %51, %52, %53, %54, %55, %56, %57, %58, %59, %60, %61, %62, %63}, %64, %65, p, 1, 1, 0, %67;\n}\n"
    : "+f"(d[0]), "+f"(d[1]), "+f"(d[2]), "+f"(d[3]), "+f"(d[4]), "+f"(d[5]), "+f"(d[6]), "+f"(d[7]), "+f"(d[8]), "+f"(d[9]), "+f"(d[10]), "+f"(d[11]), "+f"(d[12]), "+f"(d[13]), "+f"(d[14]), "+f"(d[15]), "+f"(d[16]), "+f"(d[17]), "+f"(d[18]), "+f"(d[19]), "+f"(d[20]), "+f"(d[21]), "+f"(d[22]), "+f"(d[23]), "+f"(d[24]), "+f"(d[25]), "+f"(d[26]), "+f"(d[27]), "+f"(d[28]), "+f"(d[29]), "+f"(d[30]), "+f"(d[31]), "+f"(d[32]), "+f"(d[33]), "+f"(d[34]), "+f"(d[35]), "+f"(d[36]), "+f"(d[37]), "+f"(d[38]), "+f"(d[39]), "+f"(d[40]), "+f"(d[41]), "+f"(d[42]), "+f"(d[43]), "+f"(d[44]), "+f"(d[45]), "+f"(d[46]), "+f"(d[47]), "+f"(d[48]), "+f"(d[49]), "+f"(d[50]), "+f"(d[51]), "+f"(d[52]), "+f"(d[53]), "+f"(d[54]), "+f"(d[55]), "+f"(d[56]), "+f"(d[57]), "+f"(d[58]), "+f"(d[59]), "+f"(d[60]), "+f"(d[61]), "+f"(d[62]), "+f"(d[63])
    : "l"(da), "l"(db), "r"(scale_d), "n"(TB));
}
template<int TB> __device__ __forceinline__ void wgmma_ss_n192(float (&d)[96], uint64_t da, uint64_t db, int scale_d) {
  asm volatile("{\n.reg .pred p;\nsetp.ne.b32 p, %98, 0;\n"
    "wgmma.mma_async.sync.aligned.m64n192k16.f32.bf16.bf16 {%0, %1, %2, %3, %4, %5, %6, %7, %8, %9, %10, %11, %12, %13, %14, %15, %16, %17, %18, %19, %20, %21, %22, %23, %24, %25, %26, %27, %28, %29, %30, %31, %32, %33, %34, %35, %36, %37, %38, %39, %40, %41, %42, %43, %44, %45, %46, %47, %48, %49, %50, %51, %52, %53, %54, %55, %56, %57, %58, %59, %60, %61, %62, %63, %64, %65, %66, %67, %68, %69, %70, %71, %72, %73, %74, %75, %76, %77, %78, %79, %80, %81, %82, %83, %84, %85, %86, %87, %88, %89, %90, %91, %92, %93, %94, %95}, %96, %97, p, 1, 1, 0, %99;\n}\n"
    : "+f"(d[0]), "+f"(d[1]), "+f"(d[2]), "+f"(d[3]), "+f"(d[4]), "+f"(d[5]), "+f"(d[6]), "+f"(d[7]), "+f"(d[8]), "+f"(d[9]), "+f"(d[10]), "+f"(d[11]), "+f"(d[12]), "+f"(d[13]), "+f"(d[14]), "+f"(d[15]), "+f"(d[16]), "+f"(d[17]), "+f"(d[18]), "+f"(d[19]), "+f"(d[20]), "+f"(d[21]), "+f"(d[22]), "+f"(d[23]), "+f"(d[24]), "+f"(d[25]), "+f"(d[26]), "+f"(d[27]), "+f"(d[28]), "+f"(d[29]), "+f"(d[30]), "+f"(d[31]), "+f"(d[32]), "+f"(d[33]), "+f"(d[34]), "+f"(d[35]), "+f"(d[36]), "+f"(d[37]), "+f"(d[38]), "+f"(d[39]), "+f"(d[40]), "+f"(d[41]), "+f"(d[42]), "+f"(d[43]), "+f"(d[44]), "+f"(d[45]), "+f"(d[46]), "+f"(d[47]), "+f"(d[48]), "+f"(d[49]), "+f"(d[50]), "+f"(d[51]), "+f"(d[52]), "+f"(d[53]), "+f"(d[54]), "+f"(d[55]), "+f"(d[56]), "+f"(d[57]), "+f"(d[58]), "+f"(d[59]), "+f"(d[60]), "+f"(d[61]), "+f"(d[62]), "+f"(d[63]), "+f"(d[64]), "+f"(d[65]), "+f"(d[66]), "+f"(d[67]), "+f"(d[68]), "+f"(d[69]), "+f"(d[70]), "+f"(d[71]), "+f"(d[72]), "+f"(d[73]), "+f"(d[74]), "+f"(d[75]), "+f"(d[76]), "+f"(d[77]), "+f"(d[78]), "+f"(d[79]), "+f"(d[80]), "+f"(d[81]), "+f"(d[82]), "+f"(d[83]), "+f"(d[84]), "+f"(d[85]), "+f"(d[86]), "+f"(d[87]), "+f"(d[88]), "+f"(d[89]), "+f"(d[90]), "+f"(d[91]), "+f"(d[92]), "+f"(d[93]), "+f"(d[94]), "+f"(d[95])
    : "l"(da), "l"(db), "r"(scale_d), "n"(TB));
}
template<int TB> __device__ __forceinline__ void wgmma_ss_n80(float (&d)[40], uint64_t da, uint64_t db, int scale_d) {
  asm volatile("{\n.reg .pred p;\nsetp.ne.b32 p, %42, 0;\n"
    "wgmma.mma_async.sync.aligned.m64n80k16.f32.bf16.bf16 {%0, %1, %2, %3, %4, %5, %6, %7, %8, %9, %10, %11, %12, %13, %14, %15, %16, %17, %18, %19, %20, %21, %22, %23, %24, %25, %26, %27, %28, %29, %30, %31, %32, %33, %34, %35, %36, %37, %38, %39}, %40, %41, p, 1, 1, 0, %43;\n}\n"
    : "+f"(d[0]), "+f"(d[1]), "+f"(d[2]), "+f"(d[3]), "+f"(d[4]), "+f"(d[5]), "+f"(d[6]), "+f"(d[7]), "+f"(d[8]), "+f"(d[9]), "+f"(d[10]), "+f"(d[11]), "+f"(d[12]), "+f"(d[13]), "+f"(d[14]), "+f"(d[15]), "+f"(d[16]), "+f"(d[17]), "+f"(d[18]), "+f"(d[19]), "+f"(d[20]), "+f"(d[21]), "+f"(d[22]), "+f"(d[23]), "+f"(d[24]), "+f"(d[25]), "+f"(d[26]), "+f"(d[27]), "+f"(d[28]), "+f"(d[29]), "+f"(d[30]), "+f"(d[31]), "+f"(d[32]), "+f"(d[33]), "+f"(d[34]), "+f"(d[35]), "+f"(d[36]), "+f"(d[37]), "+f"(d[38]), "+f"(d[39])
    : "l"(da), "l"(db), "r"(scale_d), "n"(TB));
}

__device__ float g_mod[6 * D_];
__device__ __align__(1024) bf16 g_h[S_ * D_];
__device__ __align__(1024) bf16 g_o[S_ * HD_];
__device__ __align__(1024) bf16 g_xch[16 * 2 * 4 * 4 * 128 * 80];
__device__ __align__(1024) bf16 g_w1t[D_ * D_];
__device__ __align__(1024) bf16 g_w2t[D_ * D_];
__device__ __align__(1024) bf16 g_w4t[D_ * F_];
__device__ __align__(32) float g_st1[S_ * 8];
__device__ __align__(32) float g_st2[S_ * 2];
__device__ __align__(32) float g_vec[3 * D_ + F_ + 8];
__device__ unsigned g_flag[1024];
enum { F_XCH = 0, F_XA = 256, F_US = 272, F_X1 = 288, F_G = 304, F_PREP = 320, F_O = 512 };
__device__ __align__(1024) bf16 g_xa[S_ * D_];
__device__ __align__(1024) bf16 g_us[S_ * D_];
__device__ __align__(1024) bf16 g_x1[S_ * D_];
__device__ __align__(1024) bf16 g_g[S_ * F_];

__global__ void __launch_bounds__(256) mod_kernel(const bf16* __restrict__ c, const bf16* __restrict__ w_mod) {
  TL_ENTRY(0);
  pdl_launch();
  __shared__ float red[8][32];
  if (blockIdx.x < 14) { const int i = blockIdx.x * 256 + threadIdx.x; if (i < 3 * D_ + F_) g_vec[i] = 0.f; }
  else if (blockIdx.x < 18) g_flag[(blockIdx.x - 14) * 256 + threadIdx.x] = 0u;
  const int t = threadIdx.x, cg = t & 3, r0 = t >> 2;
  const int col0 = blockIdx.x * 32 + cg * 8;
  uint4 w[10];
#pragma unroll
  for (int i = 0; i < 10; i++) w[i] = __ldg(reinterpret_cast<const uint4*>(w_mod + (size_t)(r0 + 64 * i) * (6 * D_) + col0));
  float acc[8];
#pragma unroll
  for (int j = 0; j < 8; j++) acc[j] = 0.f;
#pragma unroll
  for (int i = 0; i < 10; i++) {
    float cv = __bfloat162float(c[r0 + 64 * i]);
    float s = bf_round(cv / (1.f + __expf(-cv)));
    acc[0] = fmaf(s, bf_lo(w[i].x), acc[0]); acc[1] = fmaf(s, bf_hi(w[i].x), acc[1]);
    acc[2] = fmaf(s, bf_lo(w[i].y), acc[2]); acc[3] = fmaf(s, bf_hi(w[i].y), acc[3]);
    acc[4] = fmaf(s, bf_lo(w[i].z), acc[4]); acc[5] = fmaf(s, bf_hi(w[i].z), acc[5]);
    acc[6] = fmaf(s, bf_lo(w[i].w), acc[6]); acc[7] = fmaf(s, bf_hi(w[i].w), acc[7]);
  }
#pragma unroll
  for (int j = 0; j < 8; j++) {
    acc[j] += __shfl_xor_sync(0xffffffffu, acc[j], 4);
    acc[j] += __shfl_xor_sync(0xffffffffu, acc[j], 8);
    acc[j] += __shfl_xor_sync(0xffffffffu, acc[j], 16);
  }
  if ((t & 31) < 4) {
#pragma unroll
    for (int j = 0; j < 8; j++) red[t >> 5][cg * 8 + j] = acc[j];
  }
  __syncthreads();
  if (t < 32) {
    float s = 0.f;
#pragma unroll
    for (int w8 = 0; w8 < 8; w8++) s += red[w8][t];
    const int col = blockIdx.x * 32 + t;
    s = bf_round(s);
    const int part = col / D_;
    if (part == 1 || part == 4) s = bf_round(1.f + s);
    g_mod[col] = s;
    if (t == 0) TL_END(0);
  }
}

__device__ __forceinline__ void row_stats(const float (&v)[20], float& mean, float& rstd) {
  float s = 0.f;
#pragma unroll
  for (int i = 0; i < 20; i++) s += v[i];
  mean = warp_sum(s) * (1.f / D_);
  float q = 0.f;
#pragma unroll
  for (int i = 0; i < 20; i++) { float d = v[i] - mean; q = fmaf(d, d, q); }
  rstd = rsqrtf(warp_sum(q) * (1.f / D_) + LN_EPS);
}
__device__ __forceinline__ void load_row_bf16(const bf16* p, int lane, float (&v)[20]) {
#pragma unroll
  for (int i = 0; i < 5; i++) {
    uint2 u = *reinterpret_cast<const uint2*>(p + (lane + 32 * i) * 4);
    v[4 * i] = bf_lo(u.x); v[4 * i + 1] = bf_hi(u.x); v[4 * i + 2] = bf_lo(u.y); v[4 * i + 3] = bf_hi(u.y);
  }
}
__device__ __forceinline__ void store_row_bf16(bf16* p, int lane, const float (&v)[20]) {
#pragma unroll
  for (int i = 0; i < 5; i++) {
    uint2 u; u.x = pack_bf16(v[4 * i], v[4 * i + 1]); u.y = pack_bf16(v[4 * i + 2], v[4 * i + 3]);
    *reinterpret_cast<uint2*>(p + (lane + 32 * i) * 4) = u;
  }
}
__device__ __forceinline__ void load_row_f32(const float* p, int lane, float (&v)[20]) {
#pragma unroll
  for (int i = 0; i < 5; i++) {
    float4 u = *reinterpret_cast<const float4*>(p + (lane + 32 * i) * 4);
    v[4 * i] = u.x; v[4 * i + 1] = u.y; v[4 * i + 2] = u.z; v[4 * i + 3] = u.w;
  }
}

__global__ void __launch_bounds__(256) ln1_kernel(const bf16* __restrict__ x) {
  TL_ENTRY(1);
  pdl_launch();
  const int lane = threadIdx.x & 31, row = blockIdx.x * 8 + (threadIdx.x >> 5);
  float v[20];
  load_row_bf16(x + (size_t)row * D_, lane, v);
  float mean, rstd;
  row_stats(v, mean, rstd);
  if (lane < 8) g_st1[row * 8 + lane] = 0.f;
  if (lane < 2) g_st2[row * 2 + lane] = 0.f;
  pdl_wait();
  if (threadIdx.x == 0) TL_WAITED(1);
  float sa[20], ca[20];
  load_row_f32(g_mod, lane, sa);
  load_row_f32(g_mod + D_, lane, ca);
#pragma unroll
  for (int i = 0; i < 20; i++) v[i] = fmaf((v[i] - mean) * rstd, ca[i], sa[i]);
  store_row_bf16(g_h + (size_t)row * D_, lane, v);
  if (threadIdx.x == 0) TL_END(1);
}

constexpr int PREP_JOBS = 200 + 200 + 480 + 480;
struct PrepW { const bf16 *w1, *w2, *w3, *w4; };
__device__ __forceinline__ void prep_warp(const PrepW& pw, bf16 (*tile)[72], int lane) {
#pragma unroll 1
  for (int job = blockIdx.x; job < PREP_JOBS; job += gridDim.x) {
    const bf16* src; bf16* dst; int ld = D_, ldd = D_, kt, nt, kind = 1;
    if (job < 200) { src = pw.w1; dst = g_w1t; kt = job / 10; nt = job % 10; kind = 0; }
    else if (job < 400) { src = pw.w2; dst = g_w2t; kt = (job - 200) / 10; nt = (job - 200) % 10; }
    else if (job < 880) { src = pw.w4; dst = g_w4t; ldd = F_; kt = (job - 400) / 10; nt = (job - 400) % 10; }
    else { src = pw.w3; dst = nullptr; ld = F_; kt = (job - 880) / 24; nt = (job - 880) % 24; kind = 2; }
    src += (size_t)(kt * 32 + (lane >> 3)) * ld + nt * 64 + (lane & 7) * 8;
    __syncwarp();
#pragma unroll
    for (int h = 0; h < 2; h++) {
      uint4 v[4];
#pragma unroll
      for (int i = 0; i < 4; i++) v[i] = __ldg(reinterpret_cast<const uint4*>(src + (size_t)(h * 16 + i * 4) * ld));
#pragma unroll
      for (int i = 0; i < 4; i++) *reinterpret_cast<uint4*>(&tile[h * 16 + i * 4 + (lane >> 3)][(lane & 7) * 8]) = v[i];
    }
    __syncwarp();
    const float* pa = g_mod + 4 * D_ + kt * 32;
    const float* pb = g_mod + 3 * D_ + kt * 32;
#pragma unroll 1
    for (int h = 0; h < 2; h++) {
      const int n = lane + 32 * h;
      float sa = 0.f, sb = 0.f, sc = 0.f;
#pragma unroll 1
      for (int c = 0; c < 4; c++) {
        uint32_t u[4];
#pragma unroll
        for (int e = 0; e < 4; e++) {
          const int k = c * 8 + 2 * e;
          float lo = __bfloat162float(tile[k][n]), hi = __bfloat162float(tile[k + 1][n]);
          sc += lo + hi;
          if (kind == 0) {
            const float2 a = __ldcg(reinterpret_cast<const float2*>(pa + k)), b = __ldcg(reinterpret_cast<const float2*>(pb + k));
            sb = fmaf(b.x, lo, fmaf(b.y, hi, sb));
            lo *= a.x; hi *= a.y;
          }
          u[e] = pack_bf16(lo, hi);
          sa += bf_lo(u[e]) + bf_hi(u[e]);
        }
        if (kind != 2) *reinterpret_cast<uint4*>(dst + (size_t)(nt * 64 + n) * ldd + kt * 32 + c * 8) = make_uint4(u[0], u[1], u[2], u[3]);
      }
      if (kind == 0) { atomicAdd(&g_vec[nt * 64 + n], sa); atomicAdd(&g_vec[D_ + nt * 64 + n], sb); atomicAdd(&g_vec[2 * D_ + nt * 64 + n], sc); }
      else if (kind == 2) atomicAdd(&g_vec[3 * D_ + nt * 64 + n], sc);
    }
  }
  __syncwarp();
  if (lane == 0) {
    asm volatile("fence.acq_rel.gpu;" ::: "memory");
    asm volatile("red.relaxed.gpu.global.add.u32 [%0], 1;" :: "l"(g_flag + F_PREP) : "memory");
  }
}

constexpr int A_NSLOT = 9;
constexpr int A_SLOT = 24576;
constexpr int A_NKV = S_ / 64;
constexpr int PREP_CTAS = 128;

struct Ring {
  uint32_t slot, phase;
  __device__ __forceinline__ void adv(int n) { if (++slot == (uint32_t)n) { slot = 0; phase ^= 1; } }
};
constexpr int T_PAR = A_NSLOT * A_SLOT + 384;
constexpr int T_PREP = T_PAR + 3712;
constexpr int T_SMEM = T_PREP + 32 * 72 * 2 + 1024;
enum { P_OGA = 0, P_OA = 80, P_OB = 160, P_VA = 240, P_VB = 320, P_VC = 400, P_A2 = 480, P_B2 = 560, P_GB = 640, P_CS3 = 720, P_SC = 912 };

__device__ __forceinline__ void flag_wait(const unsigned* p, unsigned target) {
  asm volatile(
      "{\n.reg .pred p;\n.reg .u32 n, v;\n"
      "mov.u32 n, 0;\n"
      "SPIN:\n"
      "ld.relaxed.gpu.global.u32 v, [%0];\n"
      "setp.ge.u32 p, v, %1;\n"
      "@p bra DONE;\n"
      "add.u32 n, n, 1;\n"
      "setp.gt.u32 p, n, 4194304;\n"
      "@p trap;\n"
      "bra SPIN;\n"
      "DONE:\n}\n" :: "l"(p), "r"(target) : "memory");
}
__device__ __forceinline__ void fence_async_global() { asm volatile("fence.proxy.async.global;" ::: "memory"); }
__device__ __forceinline__ float lds_f(uint32_t a) { float v; asm volatile("ld.shared.f32 %0, [%1];" : "=f"(v) : "r"(a)); return v; }
__device__ __forceinline__ float2 lds_f2(uint32_t a) { float2 v; asm volatile("ld.shared.v2.f32 {%0, %1}, [%2];" : "=f"(v.x), "=f"(v.y) : "r"(a)); return v; }
__device__ __forceinline__ uint4 ldcg4(const void* p) { return __ldcg(reinterpret_cast<const uint4*>(p)); }

__device__ __forceinline__ void sts_f2(uint32_t a, float x, float y) { asm volatile("st.shared.v2.f32 [%0], {%1, %2};" :: "r"(a), "f"(x), "f"(y) : "memory"); }
__device__ __forceinline__ float4 lds_f4(uint32_t a) { float4 v; asm volatile("ld.shared.v4.f32 {%0, %1, %2, %3}, [%4];" : "=f"(v.x), "=f"(v.y), "=f"(v.z), "=f"(v.w) : "r"(a) : "memory"); return v; }
__device__ __forceinline__ uint4 lds_u4(uint32_t a) { uint4 v; asm volatile("ld.shared.v4.u32 {%0, %1, %2, %3}, [%4];" : "=r"(v.x), "=r"(v.y), "=r"(v.z), "=r"(v.w) : "r"(a) : "memory"); return v; }
__device__ __forceinline__ void lds8(uint32_t a, float (&v)[8]) {
  const float4 p = lds_f4(a), q = lds_f4(a + 16);
  v[0] = p.x; v[1] = p.y; v[2] = p.z; v[3] = p.w; v[4] = q.x; v[5] = q.y; v[6] = q.z; v[7] = q.w;
}
__device__ __forceinline__ void lds8_bf(uint32_t a, float (&v)[8]) {
  const uint4 u = lds_u4(a);
  v[0] = bf_lo(u.x); v[1] = bf_hi(u.x); v[2] = bf_lo(u.y); v[3] = bf_hi(u.y); v[4] = bf_lo(u.z); v[5] = bf_hi(u.z); v[6] = bf_lo(u.w); v[7] = bf_hi(u.w);
}
__device__ __forceinline__ uint4 pack8(const float (&v)[8]) {
  return make_uint4(pack_bf16(v[0], v[1]), pack_bf16(v[2], v[3]), pack_bf16(v[4], v[5]), pack_bf16(v[6], v[7]));
}
__device__ __forceinline__ void mbar_wait_c(uint32_t a, uint32_t ph) {
  asm volatile("{\n.reg .pred p;\nSPIN:\nmbarrier.try_wait.parity.shared::cta.b64 p, [%0], %1;\n@!p bra SPIN;\n}\n" :: "r"(a), "r"(ph) : "memory");
}
constexpr int ST_P = 80;
constexpr int E_TILE = 128 * 80 * 2;

struct Maps { CUtensorMap h, wq, k, v, o, wo3, wo2, xa, w1t, us, w2t, x1, w3, g, w4t, ex, exa, ex1; };
struct PfList { const uint8_t* p[6]; };

constexpr int M_AOFF = 102400, M_NA = 7;

__global__ void __cluster_dims__(2, 1, 1) __launch_bounds__(384, 1)
fused_kernel(const __grid_constant__ Maps tm, const __grid_constant__ PfList pf, const __grid_constant__ PrepW pw, const bf16* __restrict__ x, bf16* __restrict__ out) {
  extern __shared__ uint8_t smem_raw[];
  const uint32_t sb = (smem_u32(smem_raw) + 1023) & ~1023u;
  TL_ENTRY(2);
  const uint32_t bar_full = sb + A_NSLOT * A_SLOT;
  const uint32_t bar_empty = bar_full + 8 * A_NSLOT;
  const uint32_t bar_sig = bar_empty + 8 * A_NSLOT;
  const uint32_t mb_full = bar_sig + 16;
  const uint32_t mb_empty = mb_full + 96;
  const uint32_t par = sb + T_PAR;
  float* parf = reinterpret_cast<float*>(smem_raw + (par - smem_u32(smem_raw)));
  uint32_t rank;
  asm volatile("mov.u32 %0, %%cluster_ctarank;" : "=r"(rank));
  const int cid = blockIdx.x >> 1;
  const int wg = threadIdx.x >> 7;
  const int qtile = (cid & 7) * 2 + rank, hbase = cid >> 3;
  const int o_qt = qtile, o_nh = (cid >> 3) & 1, o_ks = cid >> 4;
  const int o_col = o_nh * 320 + o_ks * 80;
  const int qt = cid >> 2, js = (cid & 3) * 2 + rank;
  if (threadIdx.x == 0) {
    for (int i = 0; i < A_NSLOT; i++) { mbar_init(bar_full + 8 * i, 1); mbar_init(bar_empty + 8 * i, 16); }
    mbar_init(bar_sig, 4); mbar_init(bar_sig + 8, 4);
    for (int i = 0; i < 12; i++) { mbar_init(mb_full + 8 * i, 1); mbar_init(mb_empty + 8 * i, i < 5 ? 8 : 16); }
    asm volatile("fence.mbarrier_init.release.cluster;" ::: "memory");
    prefetch_tmap(&tm.h); prefetch_tmap(&tm.wq); prefetch_tmap(&tm.k); prefetch_tmap(&tm.v);
  }
  __syncthreads();
  cluster_sync();

  if (wg == 0) {
    asm volatile("setmaxnreg.dec.sync.aligned.u32 40;");
    if (threadIdx.x == 0) {
      Ring r{0, 1};
#define P_ACQ(bytes_) do { mbar_wait(bar_empty + 8 * r.slot, r.phase); mbar_expect(bar_full + 8 * r.slot, bytes_); } while (0)
#define P_DST (sb + r.slot * A_SLOT)
#define P_BAR (bar_full + 8 * r.slot)
      uint64_t pol_ef;
      asm volatile("createpolicy.fractional.L2::evict_first.b64 %0, 1.0;" : "=l"(pol_ef));
      pdl_wait();
      TL_WAITED(2);
#pragma unroll 1
      for (int item = 0; item < 4; item++) {
        const int head = hbase + 8 * item;
#pragma unroll 1
        for (int kb = 0; kb < 10; kb++) {
          P_ACQ(16384);
          tma2d(P_DST, &tm.h, P_BAR, kb * 64, qtile * 128);
          r.adv(A_NSLOT);
          P_ACQ(A_SLOT);
          if ((uint32_t)(kb & 1) == rank) tma3d_mc_hint(P_DST, &tm.wq, P_BAR, 0, kb * 64, head * 3, 3, pol_ef);
          r.adv(A_NSLOT);
        }
#pragma unroll 1
        for (int j = 0; j <= A_NKV; j++) {
          if (j < A_NKV) {
            P_ACQ(A_SLOT);
            if (rank == 0) tma3d_mc_hint(P_DST, &tm.k, P_BAR, 0, head * S_ + j * 64, 0, 3, pol_ef);
            r.adv(A_NSLOT);
          }
          if (j > 0) {
            P_ACQ(A_SLOT);
            if (rank == 1) tma3d_mc_hint(P_DST, &tm.v, P_BAR, 0, head * S_ + (j - 1) * 64, 0, 3, pol_ef);
            r.adv(A_NSLOT);
          }
          if (item == 3 && (j & 3) == 0) {
            const int c = (j >> 2) * 128 + blockIdx.x;
            if (c < 980) {
              const int li = c < 480 ? 0 : c < 600 ? 1 : c < 720 ? 2 : c < 880 ? 3 : c < 930 ? 4 : 5;
              const int c0 = c < 480 ? 0 : c < 600 ? 480 : c < 720 ? 600 : c < 880 ? 720 : c < 930 ? 880 : 930;
              asm volatile("cp.async.bulk.prefetch.L2.global [%0], 16384;" :: "l"(pf.p[li] + (size_t)(c - c0) * 16384) : "memory");
            }
          }
          if (item == 3) {
            if (j >= 6 && j < 24) {
              const int kb = j - 6;
              asm volatile("cp.async.bulk.prefetch.tensor.2d.L2.global [%0, {%1, %2}];"
                           :: "l"(&tm.o), "r"(((kb / 6) * 8 + 2 * o_ks + (kb % 6) / 3) * DH_ + (kb % 3) * 64), "r"(o_qt * 128) : "memory");
            }
            if (j >= 24 && j < 30) flag_wait(g_flag + F_O + o_qt * 32 + ((j - 24) >> 1) * 8 + 2 * o_ks + (j & 1), 2);
            if (j == 0) {
              prefetch_tmap(&tm.o); prefetch_tmap(&tm.wo3); prefetch_tmap(&tm.wo2); prefetch_tmap(&tm.xa); prefetch_tmap(&tm.w1t); prefetch_tmap(&tm.us);
              prefetch_tmap(&tm.w2t); prefetch_tmap(&tm.x1); prefetch_tmap(&tm.w3); prefetch_tmap(&tm.g); prefetch_tmap(&tm.w4t);
              prefetch_tmap(&tm.ex); prefetch_tmap(&tm.exa); prefetch_tmap(&tm.ex1);
            }
          }
        }
      }
#pragma unroll 1
      for (int kb = 0; kb < 24; kb++) {
        const int head = (kb / 6) * 8 + 2 * o_ks + (kb % 6) / 3;
        const int kcol = head * DH_ + (kb % 3) * 64;
        P_ACQ(24576);
        if (rank == 0) tma3d_mc(P_DST, &tm.wo3, P_BAR, 0, kcol, o_nh * 5, 3);
        r.adv(A_NSLOT);
        P_ACQ(16384);
        if (rank == 1) tma3d_mc(P_DST, &tm.wo2, P_BAR, 0, kcol, o_nh * 5 + 3, 3);
        r.adv(A_NSLOT);
        if (kb == 18 || kb == 21) flag_wait(g_flag + F_O + o_qt * 32 + head, 2);
        if (kb % 3 == 0) fence_async_global();
        P_ACQ(16384);
        tma2d(P_DST, &tm.o, P_BAR, kcol, o_qt * 128);
        r.adv(A_NSLOT);
      }
      P_ACQ(E_TILE);
      tma2d(P_DST, &tm.ex, P_BAR, o_col, o_qt * 128);
      r.adv(A_NSLOT);
      flag_wait(g_flag + F_XCH + (o_qt * 2 + o_nh) * 4 + o_ks, 6);
      fence_async_global();
#pragma unroll 1
      for (int i = 0; i < 3; i++) {
        P_ACQ(E_TILE);
        asm volatile("cp.async.bulk.shared::cluster.global.mbarrier::complete_tx::bytes [%0], [%1], %2, [%3];"
                     :: "r"(P_DST), "l"(g_xch + (size_t)((((o_qt * 2 + o_nh) * 4 + o_ks) * 4) + ((o_ks + 1 + i) & 3)) * (E_TILE / 2)), "r"(E_TILE), "r"(P_BAR) : "memory");
        r.adv(A_NSLOT);
      }
      flag_wait(g_flag + F_PREP, PREP_CTAS);
      fence_async_global();
#pragma unroll 1
      for (int i = 0; i < A_NSLOT; i++) { mbar_wait(bar_empty + 8 * r.slot, r.phase); r.adv(A_NSLOT); }
      Ring ra{0, 1};
      uint32_t bpar = 0x1f;
#pragma unroll 1
      for (int ph = 0; ph < 4; ph++) {
        const CUtensorMap* ma = ph == 0 ? &tm.xa : ph == 1 ? &tm.us : ph == 2 ? &tm.x1 : &tm.g;
        const CUtensorMap* mb = ph == 0 ? &tm.w1t : ph == 1 ? &tm.w2t : ph == 2 ? &tm.w3 : &tm.w4t;
        const int nkb = ph == 3 ? 24 : 10;
        const int nbl = ph == 2 ? 10 : nkb / 2;
        const int nel = ph == 1 ? 1 : ph == 3 ? 2 : 0;
        const uint32_t nbs = ph == 2 ? 4 : 5, bsz = ph == 2 ? 24576 : 20480;
        int bl = 0; uint32_t bs = 0;
#pragma unroll 1
        for (int i = 0; i < 5; i++) mbar_wait(mb_empty + 8 * i, (bpar >> i) & 1);
#define T_LOADB() do { mbar_wait(mb_empty + 8 * bs, (bpar >> bs) & 1); bpar ^= 1u << bs; mbar_expect(mb_full + 8 * bs, bsz);    \
                       if (bl < nbl) tma3d(sb + bs * bsz, mb, mb_full + 8 * bs, 0, ph == 2 ? bl * 64 : js * 80, ph == 2 ? js * 3 : bl * 2); \
                       else tma2d(sb + bs * bsz, bl == nbl ? &tm.exa : &tm.ex1, mb_full + 8 * bs, js * 80, qt * 128); \
                       bl++; if (++bs == nbs) bs = 0; } while (0)
#pragma unroll 1
        for (uint32_t i = 0; i < nbs; i++) T_LOADB();
        TX(8 + ph * 4);
        const unsigned* fl = g_flag + F_XA + 16 * ph;
        flag_wait(fl + qt, 16);
        if (ph == 1) { flag_wait(fl + ((qt + 15) & 15), 16); flag_wait(fl + ((qt + 1) & 15), 16); }
        TX(9 + ph * 4);
        fence_async_global();
#pragma unroll 1
        for (int kb = 0; kb < nkb; kb++) {
          mbar_wait(mb_empty + 40 + 8 * ra.slot, ra.phase);
          mbar_expect(mb_full + 40 + 8 * ra.slot, 16384);
          asm volatile("cp.async.bulk.tensor.2d.shared::cluster.global.mbarrier::complete_tx::bytes.multicast::cluster [%0], [%1, {%3, %4}], [%2], %5;"
                       :: "r"(sb + M_AOFF + ra.slot * 16384 + rank * 8192), "l"(ma), "r"(mb_full + 40 + 8 * ra.slot), "r"(kb * 64), "r"(qt * 128 + (int)rank * 64), "h"((uint16_t)3) : "memory");
          ra.adv(M_NA);
          while (bl < nbl + nel && (kb == nkb - 1 || kb >= (ph == 2 ? bl + 2 : 2 * bl - 3))) T_LOADB();
        }
      }
    } else if (threadIdx.x >= 32 && threadIdx.x < 96) {
      const int w = (threadIdx.x >> 5) - 1, lane = threadIdx.x & 31;
#pragma unroll 1
      for (int sig = 0; sig < 9; sig++) {
        mbar_wait(bar_sig + 8 * w, sig & 1);
        if (threadIdx.x == 32) TX(32 + sig * 2);
        unsigned* f;
        bool act = lane == 0;
        if (sig < 4) f = g_flag + F_O + qtile * 32 + hbase + 8 * sig;
        else if (sig == 4) { f = g_flag + F_XCH + (o_qt * 2 + o_nh) * 4 + (lane & 3); act = lane < 4 && lane != o_ks; }
        else if (sig == 5) f = g_flag + F_XA + o_qt;
        else f = g_flag + F_XA + 16 * (sig - 5) + qt;
        if (act) {
          asm volatile("fence.acq_rel.gpu;" ::: "memory");
          asm volatile("red.relaxed.gpu.global.add.u32 [%0], 1;" :: "l"(f) : "memory");
        }
        if (threadIdx.x == 32) TX(33 + sig * 2);
        __syncwarp();
      }
    } else if (threadIdx.x >= 96) {
      pdl_wait();
      prep_warp(pw, reinterpret_cast<bf16(*)[72]>(smem_raw + (sb + T_PREP - smem_u32(smem_raw))), threadIdx.x & 31);
    }
    __syncwarp();
    cluster_sync();
  } else {
    asm volatile("setmaxnreg.inc.sync.aligned.u32 232;");
    const int w = wg - 1;
    const int lane = threadIdx.x & 31;
    const int warp = (threadIdx.x >> 5) & 3;
    const int tid = threadIdx.x - 128;
    const uint32_t rel_base = mapa(bar_empty, (lane == 0) ? rank : (rank ^ 1));
    Ring r{0, 0};
#define A_RELEASE(slot_) do { if (lane < 2) mbar_arrive_remote(rel_base + 8 * (slot_)); } while (0)
#define SIGNAL() do { __syncwarp(); if (lane == 0) mbar_arrive(bar_sig + 8 * w); } while (0)
    {
    const float SC = 0.07216878364870322f * 1.4426950408889634f;
    float o[96];
    uint32_t q[48];
    float s[32];
    uint32_t p[16], p2[16];
    if (w == 1) bar_arrive(1, 256);
    for (int item = 0; item < 4; item++) {
      const int head = hbase + 8 * item;
      TSA(item, 0);
      uint32_t prevA = 0, prevB = 0;
      for (int kb = 0; kb < 10; kb++) {
        const uint32_t sA = r.slot; mbar_wait_c(bar_full + 8 * sA, r.phase); r.adv(A_NSLOT);
        const uint32_t sB = r.slot; mbar_wait_c(bar_full + 8 * sB, r.phase); r.adv(A_NSLOT);
        const uint64_t da = mkdesc(sb + sA * A_SLOT + w * 8192, 16, 1024);
        const uint64_t db = mkdesc(sb + sB * A_SLOT, 8192, 1024);
        wg_fence();
#pragma unroll
        for (int kk = 0; kk < 4; kk++) wgmma_ss_n192<1>(o, da + kk * 2, db + kk * 128, (kb | kk) != 0);
        wg_commit();
        if (kb > 0) { wg_wait<1>(); A_RELEASE(prevA); A_RELEASE(prevB); }
        prevA = sA; prevB = sB;
      }
      wg_wait<0>();
      fence_regs(o);
      A_RELEASE(prevA); A_RELEASE(prevB);
#pragma unroll
      for (int i = 0; i < 48; i++) q[i] = pack_bf16(o[2 * i], o[2 * i + 1]);

      TSA(item, 1);
      float c0, c1, l0, l1;
      {
        const uint32_t sK = r.slot; mbar_wait_c(bar_full + 8 * sK, r.phase); r.adv(A_NSLOT);
        const uint64_t dk = mkdesc(sb + sK * A_SLOT, 16, 1024);
        bar_sync(1 + w, 256);
        wg_fence();
#pragma unroll
        for (int kk = 0; kk < 12; kk++)
          wgmma_rs_n64<0>(s, q[4 * kk], q[4 * kk + 1], q[4 * kk + 2], q[4 * kk + 3], dk + (kk >> 2) * 512 + (kk & 3) * 2, kk != 0);
        wg_commit();
        bar_arrive(1 + (w ^ 1), 256);
        wg_wait<0>();
        fence_regs(s);
        A_RELEASE(sK);
        float mx0 = fmaxf(s[0], s[1]), mx1 = fmaxf(s[2], s[3]);
#pragma unroll
        for (int i = 1; i < 8; i++) { mx0 = fmaxf(mx0, fmaxf(s[4 * i], s[4 * i + 1])); mx1 = fmaxf(mx1, fmaxf(s[4 * i + 2], s[4 * i + 3])); }
        mx0 = fmaxf(mx0, __shfl_xor_sync(0xffffffffu, mx0, 1)); mx1 = fmaxf(mx1, __shfl_xor_sync(0xffffffffu, mx1, 1));
        mx0 = fmaxf(mx0, __shfl_xor_sync(0xffffffffu, mx0, 2)); mx1 = fmaxf(mx1, __shfl_xor_sync(0xffffffffu, mx1, 2));
        c0 = mx0 * SC; c1 = mx1 * SC;
        l0 = 0.f; l1 = 0.f;
#pragma unroll
        for (int i = 0; i < 8; i++) {
          s[4 * i] = ex2(fmaf(s[4 * i], SC, -c0)); s[4 * i + 1] = ex2(fmaf(s[4 * i + 1], SC, -c0));
          s[4 * i + 2] = ex2(fmaf(s[4 * i + 2], SC, -c1)); s[4 * i + 3] = ex2(fmaf(s[4 * i + 3], SC, -c1));
          l0 += s[4 * i] + s[4 * i + 1]; l1 += s[4 * i + 2] + s[4 * i + 3];
        }
#pragma unroll
        for (int i = 0; i < 16; i++) p[i] = pack_bf16(s[2 * i], s[2 * i + 1]);
      }
      TSA(item, 2);
      uint32_t okn;
      {
        Ring r2 = r; r2.adv(A_NSLOT);
        okn = mbar_try(bar_full + 8 * r.slot, r.phase) & mbar_try(bar_full + 8 * r2.slot, r2.phase);
      }
#define A_STEP(PC, PN, FIRST)                                                                                          \
      {                                                                                                                \
        const uint32_t sK = r.slot, phK = r.phase; r.adv(A_NSLOT);                                                     \
        const uint32_t sV = r.slot, phV = r.phase; r.adv(A_NSLOT);                                                     \
        const uint64_t dk = mkdesc(sb + sK * A_SLOT, 16, 1024);                                                        \
        const uint64_t dv = mkdesc(sb + sV * A_SLOT, 8192, 1024);                                                      \
        if (!okn) { mbar_wait_c(bar_full + 8 * sK, phK); mbar_wait_c(bar_full + 8 * sV, phV); }                            \
        bar_sync(1 + w, 256);                                                                                          \
        wg_fence();                                                                                                    \
        _Pragma("unroll") for (int kk = 0; kk < 12; kk++)                                                              \
          wgmma_rs_n64<0>(s, q[4 * kk], q[4 * kk + 1], q[4 * kk + 2], q[4 * kk + 3], dk + (kk >> 2) * 512 + (kk & 3) * 2, kk != 0); \
        wg_commit();                                                                                                   \
        _Pragma("unroll") for (int kk = 0; kk < 4; kk++)                                                               \
          wgmma_rs_n192<1>(o, PC[4 * kk], PC[4 * kk + 1], PC[4 * kk + 2], PC[4 * kk + 3], dv + kk * 128, !(FIRST) || (kk != 0)); \
        wg_commit();                                                                                                   \
        bar_arrive(1 + (w ^ 1), 256);                                                                                  \
        {                                                                                                              \
          Ring r2 = r; r2.adv(A_NSLOT);                                                                                \
          okn = mbar_try(bar_full + 8 * r.slot, r.phase) & mbar_try(bar_full + 8 * r2.slot, r2.phase);                 \
        }                                                                                                              \
        wg_wait<1>();                                                                                                  \
        fence_regs(s);                                                                                                 \
        A_RELEASE(sK);                                                                                                 \
        float b0 = 0.f, b1 = 0.f;                                                                                      \
        _Pragma("unroll") for (int i = 0; i < 8; i++) {                                                                \
          const float e0 = ex2(fmaf(s[4 * i], SC, -c0)), e1 = ex2(fmaf(s[4 * i + 1], SC, -c0));                        \
          const float e2 = ex2(fmaf(s[4 * i + 2], SC, -c1)), e3 = ex2(fmaf(s[4 * i + 3], SC, -c1));                    \
          b0 += e0 + e1; b1 += e2 + e3;                                                                                \
          PN[2 * i] = pack_bf16(e0, e1); PN[2 * i + 1] = pack_bf16(e2, e3);                                            \
        }                                                                                                              \
        wg_wait<0>();                                                                                                  \
        fence_regs(o);                                                                                                 \
        fence_regs(PC);                                                                                                \
        A_RELEASE(sV);                                                                                                 \
        if (__any_sync(0xffffffffu, !(b0 <= 65536.f) || !(b1 <= 65536.f))) {                                           \
          float mx0 = fmaxf(s[0], s[1]), mx1 = fmaxf(s[2], s[3]);                                                      \
          _Pragma("unroll") for (int i = 1; i < 8; i++) {                                                              \
            mx0 = fmaxf(mx0, fmaxf(s[4 * i], s[4 * i + 1])); mx1 = fmaxf(mx1, fmaxf(s[4 * i + 2], s[4 * i + 3]));     \
          }                                                                                                            \
          mx0 = fmaxf(mx0, __shfl_xor_sync(0xffffffffu, mx0, 1)); mx1 = fmaxf(mx1, __shfl_xor_sync(0xffffffffu, mx1, 1)); \
          mx0 = fmaxf(mx0, __shfl_xor_sync(0xffffffffu, mx0, 2)); mx1 = fmaxf(mx1, __shfl_xor_sync(0xffffffffu, mx1, 2)); \
          const float n0 = fmaxf(c0, mx0 * SC), n1 = fmaxf(c1, mx1 * SC);                                              \
          const float a0 = ex2(c0 - n0), a1 = ex2(c1 - n1);                                                            \
          c0 = n0; c1 = n1;                                                                                            \
          l0 *= a0; l1 *= a1;                                                                                          \
          _Pragma("unroll") for (int i = 0; i < 24; i++) { o[4 * i] *= a0; o[4 * i + 1] *= a0; o[4 * i + 2] *= a1; o[4 * i + 3] *= a1; } \
          b0 = 0.f; b1 = 0.f;                                                                                          \
          _Pragma("unroll") for (int i = 0; i < 8; i++) {                                                              \
            const float e0 = ex2(fmaf(s[4 * i], SC, -c0)), e1 = ex2(fmaf(s[4 * i + 1], SC, -c0));                      \
            const float e2 = ex2(fmaf(s[4 * i + 2], SC, -c1)), e3 = ex2(fmaf(s[4 * i + 3], SC, -c1));                  \
            b0 += e0 + e1; b1 += e2 + e3;                                                                              \
            PN[2 * i] = pack_bf16(e0, e1); PN[2 * i + 1] = pack_bf16(e2, e3);                                          \
          }                                                                                                            \
        }                                                                                                              \
        l0 += b0; l1 += b1;                                                                                            \
      }
      for (int jj = 0; jj < 15; jj++) {
        A_STEP(p, p2, jj == 0)
        A_STEP(p2, p, false)
      }
      A_STEP(p, p2, false)
      TSA(item, 3);
      {
        const uint32_t sV = r.slot; mbar_wait_c(bar_full + 8 * sV, r.phase); r.adv(A_NSLOT);
        const uint64_t dv = mkdesc(sb + sV * A_SLOT, 8192, 1024);
        bar_sync(1 + w, 256);
        wg_fence();
#pragma unroll
        for (int kk = 0; kk < 4; kk++)
          wgmma_rs_n192<1>(o, p2[4 * kk], p2[4 * kk + 1], p2[4 * kk + 2], p2[4 * kk + 3], dv + kk * 128, 1);
        wg_commit();
        bar_arrive(1 + (w ^ 1), 256);
        wg_wait<0>();
        fence_regs(o);
        A_RELEASE(sV);
      }
      TSA(item, 4);
      l0 += __shfl_xor_sync(0xffffffffu, l0, 1); l1 += __shfl_xor_sync(0xffffffffu, l1, 1);
      l0 += __shfl_xor_sync(0xffffffffu, l0, 2); l1 += __shfl_xor_sync(0xffffffffu, l1, 2);
      const float i0 = 1.f / l0, i1 = 1.f / l1;
      bf16* orow = g_o + (size_t)(qtile * 128 + w * 64 + warp * 16 + (lane >> 2)) * HD_ + head * DH_ + (lane & 3) * 8;
#pragma unroll
      for (int g = 0; g < 6; g++) {
        uint32_t u0 = pack_bf16(o[16 * g + 0] * i0, o[16 * g + 1] * i0), u1 = pack_bf16(o[16 * g + 4] * i0, o[16 * g + 5] * i0);
        uint32_t u2 = pack_bf16(o[16 * g + 8] * i0, o[16 * g + 9] * i0), u3 = pack_bf16(o[16 * g + 12] * i0, o[16 * g + 13] * i0);
        quad_transpose(u0, u1, u2, u3, lane);
        *reinterpret_cast<uint4*>(orow + g * 32) = make_uint4(u0, u1, u2, u3);
        uint32_t v0 = pack_bf16(o[16 * g + 2] * i1, o[16 * g + 3] * i1), v1 = pack_bf16(o[16 * g + 6] * i1, o[16 * g + 7] * i1);
        uint32_t v2 = pack_bf16(o[16 * g + 10] * i1, o[16 * g + 11] * i1), v3 = pack_bf16(o[16 * g + 14] * i1, o[16 * g + 15] * i1);
        quad_transpose(v0, v1, v2, v3, lane);
        *reinterpret_cast<uint4*>(orow + (size_t)8 * HD_ + g * 32) = make_uint4(v0, v1, v2, v3);
      }
      SIGNAL();
      TSA(item, 5);
    }
    }
    TS(3, 2);
    const uint32_t st_w = (uint32_t)((warp * 16 + (lane >> 2)) * ST_P + (lane & 3) * 2) * 4;
    const uint32_t st_x = (lane & 8) << 2;
    const int er = (tid & 127) >> 1, eh = tid & 1;
    const uint32_t st_r = (uint32_t)(er * ST_P + (eh ^ ((er >> 1) & 1)) * 8) * 4;
    const uint32_t e_r = (uint32_t)((w * 64 + er) * 160 + eh * 16);
    const uint32_t p_r = par + eh * 32;
#define STAGE10(ACC, BASE)                                                                                             \
    _Pragma("unroll") for (int nb = 0; nb < 10; nb++) {                                                                \
      sts_f2(stg + st_w + ((nb * 32) ^ st_x), ACC(BASE + 4 * nb), ACC(BASE + 4 * nb + 1));                                       \
      sts_f2(stg + st_w + ((nb * 32) ^ st_x) + 8 * ST_P * 4, ACC(BASE + 4 * nb + 2), ACC(BASE + 4 * nb + 3));                    \
    }

    {
      float acc1[96], acc2[64];
      uint32_t p0 = 0, p1 = 0, p2 = 0;
#pragma unroll 1
      for (int kb = 0; kb < 24; kb++) {
        const uint32_t s1 = r.slot; mbar_wait_c(bar_full + 8 * s1, r.phase); r.adv(A_NSLOT);
        const uint32_t s2 = r.slot; mbar_wait_c(bar_full + 8 * s2, r.phase); r.adv(A_NSLOT);
        const uint32_t sa = r.slot; mbar_wait_c(bar_full + 8 * sa, r.phase); r.adv(A_NSLOT);
        const uint64_t da = mkdesc(sb + sa * A_SLOT + w * 8192, 16, 1024);
        const uint64_t d1 = mkdesc(sb + s1 * A_SLOT, 8192, 1024), d2 = mkdesc(sb + s2 * A_SLOT, 8192, 1024);
        wg_fence();
#pragma unroll
        for (int kk = 0; kk < 4; kk++) {
          wgmma_ss_n192<1>(acc1, da + kk * 2, d1 + kk * 128, (kb | kk) != 0);
          wgmma_ss_n128<1>(acc2, da + kk * 2, d2 + kk * 128, (kb | kk) != 0);
        }
        wg_commit();
        if (kb > 0) { wg_wait<1>(); A_RELEASE(p0); A_RELEASE(p1); A_RELEASE(p2); }
        p0 = s1; p1 = s2; p2 = sa;
        if (kb == 4) {
          if (tid == 255) flag_wait(g_flag + F_PREP, PREP_CTAS);
          bar_sync(5, 256);
#pragma unroll 1
          for (int i = tid; i < P_SC; i += 256) {
            const int v = i < P_CS3 ? i / 80 : 9, j = i - (i < P_CS3 ? v * 80 : P_CS3);
            const float* src = v == 0 ? g_mod + 2 * D_ + o_col : v == 1 ? g_mod + 4 * D_ + o_col : v == 2 ? g_mod + 3 * D_ + o_col
                             : v < 6 ? g_vec + (v - 3) * D_ + js * 80 : v == 6 ? g_mod + 4 * D_ + js * 80 : v == 7 ? g_mod + 3 * D_ + js * 80
                             : v == 8 ? g_mod + 5 * D_ + js * 80 : g_vec + 3 * D_ + js * 192;
            parf[i] = __ldcg(src + j);
          }
          if (tid >= 224) {
            float sv[5] = {0.f, 0.f, 0.f, 0.f, 0.f};
#pragma unroll 1
            for (int i = lane; i < D_; i += 32) {
              const float a = __ldcg(g_mod + 4 * D_ + i), b = __ldcg(g_mod + 3 * D_ + i);
              sv[0] += a; sv[1] = fmaf(a, a, sv[1]); sv[2] = fmaf(a, b, sv[2]); sv[3] += b; sv[4] = fmaf(b, b, sv[4]);
            }
#pragma unroll 1
            for (int o_ = 16; o_ > 0; o_ >>= 1) {
#pragma unroll
              for (int i = 0; i < 5; i++) sv[i] += __shfl_xor_sync(0xffffffffu, sv[i], o_);
            }
            if (lane == 0) {
#pragma unroll
              for (int i = 0; i < 5; i++) parf[P_SC + i] = sv[i];
            }
          }
        }
      }
      wg_wait<0>();
      fence_regs(acc1); fence_regs(acc2);
      A_RELEASE(p2);
      bar_sync(5, 256);
      TS(0, 0);
      const uint32_t stg = sb + (w ? p1 : p0) * A_SLOT;
#define OACC(e) (((e) < 96) ? acc1[(e) < 96 ? (e) : 0] : acc2[(e) >= 96 ? (e) - 96 : 0])
#pragma unroll 1
      for (int i = 0; i < 4; i++) {
        const int d = (o_ks + 1 + i) & 3;
        if (d == 0) { STAGE10(OACC, 0) } else if (d == 1) { STAGE10(OACC, 40) } else if (d == 2) { STAGE10(OACC, 80) } else { STAGE10(OACC, 120) }
        bar_sync(3 + w, 128);
        if (i < 3) {
          uint8_t* dst = reinterpret_cast<uint8_t*>(g_xch + (size_t)((((o_qt * 2 + o_nh) * 4 + d) * 4) + o_ks) * (E_TILE / 2)) + e_r;
#pragma unroll 1
          for (int c = 0; c < 5; c++) {
            float v[8];
            lds8(stg + st_r + c * 64, v);
            stg128(dst + c * 32, pack8(v));
          }
          if (i == 2) SIGNAL();
          bar_sync(3 + w, 128);
        }
      }
      const uint32_t sx = r.slot; mbar_wait_c(bar_full + 8 * sx, r.phase); r.adv(A_NSLOT);
      const uint32_t q0 = r.slot; mbar_wait_c(bar_full + 8 * q0, r.phase); r.adv(A_NSLOT);
      const uint32_t q1 = r.slot; mbar_wait_c(bar_full + 8 * q1, r.phase); r.adv(A_NSLOT);
      const uint32_t q2 = r.slot; mbar_wait_c(bar_full + 8 * q2, r.phase); r.adv(A_NSLOT);
      TS(0, 1);
      float st[6] = {0.f, 0.f, 0.f, 0.f, 0.f, 0.f};
      bf16* dst = g_xa + (size_t)(o_qt * 128 + w * 64 + er) * D_ + o_col + eh * 8;
#pragma unroll 1
      for (int c = 0; c < 5; c++) {
        float v[8], t0[8], t1[8], t2[8];
        lds8(stg + st_r + c * 64, v);
        lds8_bf(sb + q0 * A_SLOT + e_r + c * 32, t0); lds8_bf(sb + q1 * A_SLOT + e_r + c * 32, t1); lds8_bf(sb + q2 * A_SLOT + e_r + c * 32, t2);
#pragma unroll
        for (int e = 0; e < 8; e++) v[e] += (t0[e] + t1[e]) + t2[e];
        lds8_bf(sb + sx * A_SLOT + e_r + c * 32, t0);
        lds8(p_r + P_OGA * 4 + c * 64, t1);
#pragma unroll
        for (int e = 0; e < 8; e++) v[e] = fmaf(t1[e], v[e], t0[e]);
        const uint4 pk = pack8(v);
        stg128(dst + c * 16, pk);
        v[0] = bf_lo(pk.x); v[1] = bf_hi(pk.x); v[2] = bf_lo(pk.y); v[3] = bf_hi(pk.y); v[4] = bf_lo(pk.z); v[5] = bf_hi(pk.z); v[6] = bf_lo(pk.w); v[7] = bf_hi(pk.w);
        lds8(p_r + P_OA * 4 + c * 64, t1);
        lds8(p_r + P_OB * 4 + c * 64, t2);
#pragma unroll
        for (int e = 0; e < 8; e++) {
          const float y = t1[e] * v[e];
          st[0] += v[e]; st[1] = fmaf(v[e], v[e], st[1]); st[2] += y; st[3] = fmaf(t1[e], y, st[3]); st[4] = fmaf(y, y, st[4]); st[5] = fmaf(t2[e], y, st[5]);
        }
      }
#pragma unroll
      for (int i = 0; i < 6; i++) st[i] += __shfl_xor_sync(0xffffffffu, st[i], 1);
      if (eh == 0) {
        float* sp = g_st1 + (size_t)(o_qt * 128 + w * 64 + er) * 8;
        asm volatile("red.global.add.v4.f32 [%0], {%1, %2, %3, %4};" :: "l"(sp), "f"(st[0]), "f"(st[1]), "f"(st[2]), "f"(st[3]) : "memory");
        asm volatile("red.global.add.v2.f32 [%0], {%1, %2};" :: "l"(sp + 4), "f"(st[4]), "f"(st[5]) : "memory");
      }
      SIGNAL();
      bar_sync(5, 256);
      A_RELEASE(p0); A_RELEASE(p1); A_RELEASE(sx); A_RELEASE(q0); A_RELEASE(q1); A_RELEASE(q2);
      TS(0, 2);
    }

    Ring ra{0, 0};
    uint32_t bpar = 0;
    const uint32_t rel_a = mapa(mb_empty + 40, (lane == 0) ? rank : (rank ^ 1));
#define B_NEXT(s_) do { s_ = bs; mbar_wait_c(mb_full + 8 * bs, (bpar >> bs) & 1); bpar ^= 1u << bs; if (++bs == nbs) bs = 0; } while (0)
#define B_RELEASE(s_) do { if (lane == 0) mbar_arrive(mb_empty + 8 * (s_)); } while (0)
#define MA_RELEASE(s_) do { if (lane < 2) mbar_arrive_remote(rel_a + 8 * (s_)); } while (0)
    const int grow = qt * 128 + w * 64 + er;
    float mu = 0.f, rs = 0.f;
#pragma unroll 1
    for (int ph = 0; ph < 4; ph++) {
      float acc[96];
      float (&acc80)[40] = *reinterpret_cast<float(*)[40]>(&acc[0]);
      uint32_t pa = 0, pb = 0, sbq = 0;
      float4 s03 = make_float4(0.f, 0.f, 0.f, 0.f);
      float2 s45 = make_float2(0.f, 0.f);
      const int nkb = ph == 3 ? 24 : 10;
      const uint32_t nbs = ph == 2 ? 4 : 5, bsz = ph == 2 ? 24576 : 20480;
      uint32_t bs = 0;
#pragma unroll 1
      for (int kb = 0; kb < nkb; kb++) {
        if (ph == 2 || !(kb & 1)) B_NEXT(sbq);
        const uint32_t sa = ra.slot; mbar_wait_c(mb_full + 40 + 8 * sa, ra.phase); ra.adv(M_NA);
        if (kb == 0) TXC(ph);
        const uint64_t da = mkdesc(sb + M_AOFF + sa * 16384 + w * 8192, 16, 1024);
        if (ph == 2) {
          const uint64_t db = mkdesc(sb + sbq * 24576, 8192, 1024);
          wg_fence();
#pragma unroll
          for (int kk = 0; kk < 4; kk++) wgmma_ss_n192<1>(acc, da + kk * 2, db + kk * 128, (kb | kk) != 0);
          wg_commit();
        } else {
          const uint64_t db = mkdesc(sb + sbq * 20480 + (kb & 1) * 10240, 16, 1024);
          wg_fence();
#pragma unroll
          for (int kk = 0; kk < 4; kk++) wgmma_ss_n80<0>(acc80, da + kk * 2, db + kk * 2, (kb | kk) != 0);
          wg_commit();
        }
        if (kb > 0) { wg_wait<1>(); MA_RELEASE(pa); if (ph == 2 || !(kb & 1)) B_RELEASE(pb); }
        else {
          if (ph == 0) { s03 = __ldcg(reinterpret_cast<const float4*>(g_st1 + (size_t)grow * 8)); s45 = __ldcg(reinterpret_cast<const float2*>(g_st1 + (size_t)grow * 8 + 4)); }
          if (ph == 2) s45 = __ldcg(reinterpret_cast<const float2*>(g_st2 + (size_t)grow * 2));
        }
        pa = sa; pb = sbq;
      }
      wg_wait<0>();
      fence_regs(acc);
      MA_RELEASE(pa);
      bar_sync(5, 256);
      TS(1 + (ph == 3 ? 0 : ph), ph == 3 ? 2 : 0);
      const uint32_t stg = sb + (w ? pb : (pb == 0 ? nbs - 1 : pb - 1)) * bsz;
#define MACC(e) acc[e]
      if (!(ph & 1)) {
        float c0, c1, c2 = 0.f, c3 = 0.f;
        bf16* dst; bool ok = true;
        if (ph == 0) {
          const float4 sc = lds_f4(par + P_SC * 4);
          const float sbb = lds_f(par + (P_SC + 4) * 4);
          mu = s03.x * (1.f / D_);
          rs = rsqrtf(fmaxf(s03.y * (1.f / D_) - mu * mu, 0.f) + LN_EPS);
          const float m2 = (rs * (s03.z - mu * sc.x) + sc.w) * (1.f / D_);
          const float e2 = (rs * rs * (s45.x - 2.f * mu * s03.w + mu * mu * sc.y) + 2.f * rs * (s45.y - mu * sc.z) + sbb) * (1.f / D_);
          c2 = rsqrtf(fmaxf(e2 - m2 * m2, 0.f) + LN_EPS);
          c0 = c2 * rs; c1 = -c0 * mu; c3 = -c2 * m2;
          const int grp = js >> 1;
          const int sh = (grp & 2 ? 2 : 1) * (grp & 1 ? -1 : 1);
          ok = (unsigned)(grow + sh) < (unsigned)S_;
          dst = g_us + (size_t)(ok ? grow + sh : (sh > 0 ? grow + sh - S_ : grow + sh + S_)) * D_ + js * 80 + eh * 8;
        } else {
          const float m = s45.x * (1.f / D_);
          c0 = rsqrtf(fmaxf(s45.y * (1.f / D_) - m * m, 0.f) + LN_EPS);
          c1 = -c0 * m;
          dst = g_g + (size_t)grow * F_ + js * 192 + eh * 8;
        }
        const int npass = ph == 0 ? 1 : 3, nch = ph == 0 ? 5 : 4;
#pragma unroll 1
        for (int ps = 0; ps < npass; ps++) {
          if (ps == 0) { STAGE10(MACC, 0) }
          else {
            bar_sync(3 + w, 128);
            if (ps == 1) { STAGE10(MACC, 32) } else { STAGE10(MACC, 56) }
          }
          bar_sync(3 + w, 128);
          const uint32_t cofs = ps == 2 ? 64 : 0;
          const uint32_t pp = p_r + (ph == 0 ? P_VA : P_CS3 + ps * 64) * 4;
#pragma unroll 1
          for (int c = 0; c < nch; c++) {
            float v[8], t[8];
            lds8(stg + st_r + cofs + c * 64, v);
            lds8(pp + c * 64, t);
#pragma unroll
            for (int e = 0; e < 8; e++) v[e] = fmaf(c0, v[e], c1 * t[e]);
            if (ph == 0) {
              lds8(pp + 320 + c * 64, t);
#pragma unroll
              for (int e = 0; e < 8; e++) v[e] = fmaf(c2, t[e], v[e]);
              lds8(pp + 640 + c * 64, t);
#pragma unroll
              for (int e = 0; e < 8; e++) v[e] = fmaf(c3, t[e], v[e]);
            }
#pragma unroll
            for (int e = 0; e < 8; e++) v[e] = gelu_tanh(v[e]);
            const uint4 pk = pack8(v);
            stg128(dst + ps * 64 + c * 16, ok ? pk : make_uint4(0, 0, 0, 0));
          }
        }
        SIGNAL();
        bar_sync(5, 256);
        B_RELEASE(pb);
      } else {
        STAGE10(MACC, 0)
        uint32_t e1, e2;
        B_NEXT(e1);
        e2 = e1;
        if (ph == 3) B_NEXT(e2);
        bar_sync(3 + w, 128);
        TXC(4 + (ph >> 1));
        float s1 = 0.f, s2 = 0.f;
        bf16* dst = (ph == 1 ? g_x1 : out) + (size_t)grow * D_ + js * 80 + eh * 8;
#pragma unroll 1
        for (int c = 0; c < 5; c++) {
          float v[8], xa[8], t[8];
          lds8(stg + st_r + c * 64, v);
          lds8_bf(sb + e1 * 20480 + e_r + c * 32, xa);
          if (ph == 1) {
            lds8(p_r + P_A2 * 4 + c * 64, t);
#pragma unroll
            for (int e = 0; e < 8; e++) v[e] = fmaf(t[e] * rs, xa[e] - mu, v[e]);
            lds8(p_r + P_B2 * 4 + c * 64, t);
#pragma unroll
            for (int e = 0; e < 8; e++) v[e] += t[e];
          } else {
            lds8_bf(sb + e2 * 20480 + e_r + c * 32, t);
#pragma unroll
            for (int e = 0; e < 8; e++) v[e] += t[e];
            lds8(p_r + P_GB * 4 + c * 64, t);
#pragma unroll
            for (int e = 0; e < 8; e++) v[e] = fmaf(t[e], v[e], xa[e]);
          }
          const uint4 pk = pack8(v);
          stg128(dst + c * 16, pk);
          v[0] = bf_lo(pk.x); v[1] = bf_hi(pk.x); v[2] = bf_lo(pk.y); v[3] = bf_hi(pk.y); v[4] = bf_lo(pk.z); v[5] = bf_hi(pk.z); v[6] = bf_lo(pk.w); v[7] = bf_hi(pk.w);
#pragma unroll
          for (int e = 0; e < 8; e++) { s1 += v[e]; s2 = fmaf(v[e], v[e], s2); }
        }
        if (ph == 1) {
          s1 += __shfl_xor_sync(0xffffffffu, s1, 1); s2 += __shfl_xor_sync(0xffffffffu, s2, 1);
          if (eh == 0) asm volatile("red.global.add.v2.f32 [%0], {%1, %2};" :: "l"(g_st2 + (size_t)grow * 2), "f"(s1), "f"(s2) : "memory");
          SIGNAL();
          bar_sync(5, 256);
          B_RELEASE(pb); B_RELEASE(e1);
        }
      }
      TS(1 + (ph == 3 ? 0 : ph), ph == 3 ? 3 : 1);
    }
    if ((threadIdx.x & 127) == 0) TL_END(2);
    cluster_sync();
  }
}

typedef CUresult (*EncFn)(CUtensorMap*, CUtensorMapDataType, cuuint32_t, void*, const cuuint64_t*, const cuuint64_t*,
                          const cuuint32_t*, const cuuint32_t*, CUtensorMapInterleave, CUtensorMapSwizzle,
                          CUtensorMapL2promotion, CUtensorMapFloatOOBfill);
static EncFn g_enc = nullptr;

static CUtensorMap map2d(const void* p, uint64_t rows, uint64_t cols, uint32_t box_rows) {
  CUtensorMap m;
  cuuint64_t gd[2] = {cols, rows}; cuuint64_t gs[1] = {cols * 2};
  cuuint32_t bx[2] = {64, box_rows}; cuuint32_t es[2] = {1, 1};
  g_enc(&m, CU_TENSOR_MAP_DATA_TYPE_BFLOAT16, 2, const_cast<void*>(p), gd, gs, bx, es, CU_TENSOR_MAP_INTERLEAVE_NONE,
        CU_TENSOR_MAP_SWIZZLE_128B, CU_TENSOR_MAP_L2_PROMOTION_L2_256B, CU_TENSOR_MAP_FLOAT_OOB_FILL_NONE);
  return m;
}
static CUtensorMap map3d(const void* p, uint64_t rows, uint64_t cols, uint32_t box_rows, uint32_t nblk) {
  CUtensorMap m;
  cuuint64_t gd[3] = {64, rows, cols / 64}; cuuint64_t gs[2] = {cols * 2, 128};
  cuuint32_t bx[3] = {64, box_rows, nblk}; cuuint32_t es[3] = {1, 1, 1};
  g_enc(&m, CU_TENSOR_MAP_DATA_TYPE_BFLOAT16, 3, const_cast<void*>(p), gd, gs, bx, es, CU_TENSOR_MAP_INTERLEAVE_NONE,
        CU_TENSOR_MAP_SWIZZLE_128B, CU_TENSOR_MAP_L2_PROMOTION_L2_256B, CU_TENSOR_MAP_FLOAT_OOB_FILL_NONE);
  return m;
}

static CUtensorMap map_e(const void* p) {
  CUtensorMap m;
  cuuint64_t gd[2] = {D_, S_}; cuuint64_t gs[1] = {D_ * 2};
  cuuint32_t bx[2] = {80, 128}; cuuint32_t es[2] = {1, 1};
  g_enc(&m, CU_TENSOR_MAP_DATA_TYPE_BFLOAT16, 2, const_cast<void*>(p), gd, gs, bx, es, CU_TENSOR_MAP_INTERLEAVE_NONE,
        CU_TENSOR_MAP_SWIZZLE_NONE, CU_TENSOR_MAP_L2_PROMOTION_L2_256B, CU_TENSOR_MAP_FLOAT_OOB_FILL_NONE);
  return m;
}

template <typename... KArgs, typename... Args>
static void launch(void (*kern)(KArgs...), dim3 grid, dim3 block, int smem, bool pdl, Args... args) {
  cudaLaunchConfig_t cfg = {};
  cfg.gridDim = grid; cfg.blockDim = block; cfg.dynamicSmemBytes = smem; cfg.stream = cudaStreamPerThread;
  cudaLaunchAttribute at[1];
  at[0].id = cudaLaunchAttributeProgrammaticStreamSerialization;
  at[0].val.programmaticStreamSerializationAllowed = 1;
  cfg.attrs = at; cfg.numAttrs = pdl ? 1 : 0;
  cudaLaunchKernelEx(&cfg, kern, KArgs(args)...);
}

extern "C" void kernel_launch(void* const* d_in, const int* in_sizes, int n_in, void* d_out, int out_size) {
  const bf16* x = (const bf16*)d_in[0];
  const bf16* kc = (const bf16*)d_in[1];
  const bf16* vc = (const bf16*)d_in[2];
  const bf16* wq = (const bf16*)d_in[3];
  const bf16* wo = (const bf16*)d_in[4];
  const bf16* w1 = (const bf16*)d_in[6];
  const bf16* w2 = (const bf16*)d_in[7];
  const bf16* w3 = (const bf16*)d_in[8];
  const bf16* w4 = (const bf16*)d_in[9];
  const bf16* c = (const bf16*)d_in[10];
  const bf16* wmod = (const bf16*)d_in[11];
  bf16* out = (bf16*)d_out;

  static void *p_h, *p_o, *p_xa, *p_us, *p_x1, *p_g, *p_w1t, *p_w2t, *p_w4t;
  if (!g_enc) {
    void* fn = nullptr; cudaDriverEntryPointQueryResult qr;
    cudaGetDriverEntryPoint("cuTensorMapEncodeTiled", &fn, cudaEnableDefault, &qr);
    g_enc = (EncFn)fn;
    cudaGetSymbolAddress(&p_h, g_h); cudaGetSymbolAddress(&p_o, g_o); cudaGetSymbolAddress(&p_xa, g_xa);
    cudaGetSymbolAddress(&p_us, g_us); cudaGetSymbolAddress(&p_x1, g_x1); cudaGetSymbolAddress(&p_g, g_g);
    cudaGetSymbolAddress(&p_w1t, g_w1t); cudaGetSymbolAddress(&p_w2t, g_w2t); cudaGetSymbolAddress(&p_w4t, g_w4t);
    cudaFuncSetAttribute(fused_kernel, cudaFuncAttributeMaxDynamicSharedMemorySize, T_SMEM);
  }
  Maps tm;
  tm.h = map2d(p_h, S_, D_, 128);
  tm.wq = map3d(wq, D_, HD_, 64, 3);
  tm.k = map3d(kc, (uint64_t)H_ * S_, DH_, 64, 3);
  tm.v = map3d(vc, (uint64_t)H_ * S_, DH_, 64, 3);
  tm.o = map2d(p_o, S_, HD_, 128);
  tm.wo3 = map3d(wo, HD_, D_, 64, 3);
  tm.wo2 = map3d(wo, HD_, D_, 64, 2);
  tm.xa = map2d(p_xa, S_, D_, 64);
  tm.w1t = map3d(p_w1t, D_, D_, 80, 2);
  tm.us = map2d(p_us, S_, D_, 64);
  tm.w2t = map3d(p_w2t, D_, D_, 80, 2);
  tm.x1 = map2d(p_x1, S_, D_, 64);
  tm.w3 = map3d(w3, D_, F_, 64, 3);
  tm.g = map2d(p_g, S_, F_, 64);
  tm.w4t = map3d(p_w4t, D_, F_, 80, 2);
  tm.ex = map_e(x); tm.exa = map_e(p_xa); tm.ex1 = map_e(p_x1);
  PfList pf;
  pf.p[0] = (const uint8_t*)wo; pf.p[1] = (const uint8_t*)w3; pf.p[2] = (const uint8_t*)p_w4t;
  pf.p[3] = (const uint8_t*)x; pf.p[4] = (const uint8_t*)p_w1t; pf.p[5] = (const uint8_t*)p_w2t;

  launch(mod_kernel, dim3(120), dim3(256), 0, false, c, wmod);
  launch(ln1_kernel, dim3(256), dim3(256), 0, true, x);
  launch(fused_kernel, dim3(128), dim3(384), T_SMEM, true, tm, pf, PrepW{w1, w2, w3, w4}, x, out);
}
```

```cpp
#include <cuda_runtime.h>
#include <cuda.h>
#include <cuda_bf16.h>
#include <stdint.h>

typedef __nv_bfloat16 bf16;

constexpr int S_  = 2048;
constexpr int D_  = 640;
constexpr int H_  = 32;
constexpr int DH_ = 192;
constexpr int HD_ = H_ * DH_;
constexpr int F_  = 1536;
constexpr float LN_EPS = 1e-5f;

__device__ __forceinline__ uint32_t smem_u32(const void* p) { return (uint32_t)__cvta_generic_to_shared(p); }
__device__ __forceinline__ void mbar_init(uint32_t a, uint32_t c) { asm volatile("mbarrier.init.shared::cta.b64 [%0], %1;" :: "r"(a), "r"(c) : "memory"); }
__device__ __forceinline__ void mbar_expect(uint32_t a, uint32_t b) { asm volatile("mbarrier.arrive.expect_tx.shared::cta.b64 _, [%0], %1;" :: "r"(a), "r"(b) : "memory"); }
__device__ __forceinline__ void mbar_arrive(uint32_t a) { asm volatile("mbarrier.arrive.shared::cta.b64 _, [%0];" :: "r"(a) : "memory"); }
__device__ __forceinline__ void mbar_arrive_remote(uint32_t ra) { asm volatile("mbarrier.arrive.shared::cluster.b64 _, [%0];" :: "r"(ra) : "memory"); }
__device__ __forceinline__ uint32_t mapa(uint32_t a, uint32_t cta) { uint32_t r; asm volatile("mapa.shared::cluster.u32 %0, %1, %2;" : "=r"(r) : "r"(a), "r"(cta)); return r; }
__device__ __forceinline__ uint32_t mbar_try(uint32_t a, uint32_t ph) {
  uint32_t ok;
  asm volatile("{\n.reg .pred p;\nmbarrier.test_wait.parity.shared::cta.b64 p, [%1], %2;\nselp.u32 %0, 1, 0, p;\n}\n" : "=r"(ok) : "r"(a), "r"(ph) : "memory");
  return ok;
}
__device__ __forceinline__ void mbar_wait(uint32_t a, uint32_t ph) {
  asm volatile(
      "{\n.reg .pred p;\n.reg .u32 n;\n"
      "mov.u32 n, 0;\n"
      "SPIN:\n"
      "mbarrier.try_wait.parity.shared::cta.b64 p, [%0], %1;\n"
      "@p bra DONE;\n"
      "add.u32 n, n, 1;\n"
      "setp.le.u32 p, n, 16777216;\n"
      "@p bra SPIN;\n"
      "trap;\n"
      "DONE:\n}\n" :: "r"(a), "r"(ph) : "memory");
}
#define ELECT_ "{\n.reg .pred p;\nelect.sync _|p, 0xffffffff;\n@p "
__device__ __forceinline__ void mbar_expect_e(uint32_t a, uint32_t b) { asm volatile(ELECT_ "mbarrier.arrive.expect_tx.shared::cta.b64 _, [%0], %1;\n}\n" :: "r"(a), "r"(b) : "memory"); }
__device__ __forceinline__ void tma2d(uint32_t dst, const CUtensorMap* m, uint32_t bar, int c0, int c1) {
  asm volatile(ELECT_ "cp.async.bulk.tensor.2d.shared::cluster.global.mbarrier::complete_tx::bytes [%0], [%1, {%3, %4}], [%2];\n}\n"
               :: "r"(dst), "l"(m), "r"(bar), "r"(c0), "r"(c1) : "memory");
}
__device__ __forceinline__ void tma2d_mc(uint32_t dst, const CUtensorMap* m, uint32_t bar, int c0, int c1, uint16_t mask) {
  asm volatile(ELECT_ "cp.async.bulk.tensor.2d.shared::cluster.global.mbarrier::complete_tx::bytes.multicast::cluster [%0], [%1, {%3, %4}], [%2], %5;\n}\n"
               :: "r"(dst), "l"(m), "r"(bar), "r"(c0), "r"(c1), "h"(mask) : "memory");
}
__device__ __forceinline__ void tma3d(uint32_t dst, const CUtensorMap* m, uint32_t bar, int c0, int c1, int c2) {
  asm volatile(ELECT_ "cp.async.bulk.tensor.3d.shared::cluster.global.mbarrier::complete_tx::bytes [%0], [%1, {%3, %4, %5}], [%2];\n}\n"
               :: "r"(dst), "l"(m), "r"(bar), "r"(c0), "r"(c1), "r"(c2) : "memory");
}
__device__ __forceinline__ void tma3d_mc(uint32_t dst, const CUtensorMap* m, uint32_t bar, int c0, int c1, int c2, uint16_t mask) {
  asm volatile(ELECT_ "cp.async.bulk.tensor.3d.shared::cluster.global.mbarrier::complete_tx::bytes.multicast::cluster [%0], [%1, {%3, %4, %5}], [%2], %6;\n}\n"
               :: "r"(dst), "l"(m), "r"(bar), "r"(c0), "r"(c1), "r"(c2), "h"(mask) : "memory");
}
__device__ __forceinline__ void tma3d_mc_hint(uint32_t dst, const CUtensorMap* m, uint32_t bar, int c0, int c1, int c2, uint16_t mask, uint64_t pol) {
  asm volatile(ELECT_ "cp.async.bulk.tensor.3d.shared::cluster.global.mbarrier::complete_tx::bytes.multicast::cluster.L2::cache_hint [%0], [%1, {%3, %4, %5}], [%2], %6, %7;\n}\n"
               :: "r"(dst), "l"(m), "r"(bar), "r"(c0), "r"(c1), "r"(c2), "h"(mask), "l"(pol) : "memory");
}
__device__ __forceinline__ void bulk_load(uint32_t dst, const void* src, uint32_t bytes, uint32_t bar) {
  asm volatile(ELECT_ "cp.async.bulk.shared::cluster.global.mbarrier::complete_tx::bytes [%0], [%1], %2, [%3];\n}\n"
               :: "r"(dst), "l"(src), "r"(bytes), "r"(bar) : "memory");
}
__device__ __forceinline__ void l2_prefetch16k(const void* p) { asm volatile(ELECT_ "cp.async.bulk.prefetch.L2.global [%0], 16384;\n}\n" :: "l"(p) : "memory"); }
__device__ __forceinline__ void l2_prefetch_t2d(const CUtensorMap* m, int c0, int c1) {
  asm volatile(ELECT_ "cp.async.bulk.prefetch.tensor.2d.L2.global [%0, {%1, %2}];\n}\n" :: "l"(m), "r"(c0), "r"(c1) : "memory");
}
__device__ __forceinline__ void stg128(void* p, uint4 v) {
  asm volatile("st.global.v4.u32 [%0], {%1, %2, %3, %4};" :: "l"(p), "r"(v.x), "r"(v.y), "r"(v.z), "r"(v.w) : "memory");
}
__device__ __forceinline__ void prefetch_tmap(const CUtensorMap* m) { asm volatile("prefetch.tensormap [%0];" :: "l"(m) : "memory"); }
__device__ __forceinline__ void wg_fence() { asm volatile("wgmma.fence.sync.aligned;" ::: "memory"); }
__device__ __forceinline__ void wg_commit() { asm volatile("wgmma.commit_group.sync.aligned;" ::: "memory"); }
template <int N> __device__ __forceinline__ void wg_wait() { asm volatile("wgmma.wait_group.sync.aligned %0;" :: "n"(N) : "memory"); }
template <int N> __device__ __forceinline__ void fence_regs(float (&r)[N]) {
#pragma unroll
  for (int i = 0; i < N; i++) asm volatile("" : "+f"(r[i]) :: "memory");
}
template <int N> __device__ __forceinline__ void fence_regs(uint32_t (&r)[N]) {
#pragma unroll
  for (int i = 0; i < N; i++) asm volatile("" : "+r"(r[i]) :: "memory");
}
__device__ __forceinline__ uint64_t mkdesc(uint32_t addr, uint32_t lbo, uint32_t sbo) {
  return (uint64_t)((addr & 0x3FFFF) >> 4) | ((uint64_t)(lbo >> 4) << 16) | ((uint64_t)(sbo >> 4) << 32) | (1ull << 62);
}
__device__ __forceinline__ void bar_sync(int id, int n) { asm volatile("bar.sync %0, %1;" :: "r"(id), "r"(n) : "memory"); }
__device__ __forceinline__ void bar_arrive(int id, int n) { asm volatile("bar.arrive %0, %1;" :: "r"(id), "r"(n) : "memory"); }
__device__ __forceinline__ void cluster_sync() { asm volatile("barrier.cluster.arrive.aligned;\nbarrier.cluster.wait.aligned;" ::: "memory"); }
__device__ __forceinline__ void pdl_wait() { asm volatile("griddepcontrol.wait;" ::: "memory"); }
__device__ __forceinline__ void pdl_launch() { asm volatile("griddepcontrol.launch_dependents;" ::: "memory"); }
__device__ __forceinline__ float ex2(float x) { float y; asm("ex2.approx.ftz.f32 %0, %1;" : "=f"(y) : "f"(x)); return y; }
__device__ __forceinline__ uint32_t pack_bf16(float lo, float hi) { uint32_t r; asm("cvt.rn.bf16x2.f32 %0, %1, %2;" : "=r"(r) : "f"(hi), "f"(lo)); return r; }
__device__ __forceinline__ float bf_lo(uint32_t u) { return __uint_as_float(u << 16); }
__device__ __forceinline__ float bf_hi(uint32_t u) { return __uint_as_float(u & 0xffff0000u); }
__device__ __forceinline__ float bf_round(float x) { return __bfloat162float(__float2bfloat16_rn(x)); }
__device__ __forceinline__ float tanh_fast(float x) { float y; asm("tanh.approx.f32 %0, %1;" : "=f"(y) : "f"(x)); return y; }
__device__ __forceinline__ float gelu_tanh(float x) {
  float u = x * (0.7978845608028654f + 0.035677408136300125f * x * x);
  float hx = 0.5f * x;
  return fmaf(hx, tanh_fast(u), hx);
}
__device__ __forceinline__ float warp_sum(float v) {
#pragma unroll
  for (int o = 16; o > 0; o >>= 1) v += __shfl_xor_sync(0xffffffffu, v, o);
  return v;
}
__device__ __forceinline__ void quad_transpose(uint32_t& v0, uint32_t& v1, uint32_t& v2, uint32_t& v3, int lane) {
  const bool b0 = lane & 1, b1 = lane & 2;
  uint32_t s0 = b0 ? v0 : v1, s1 = b0 ? v2 : v3;
  s0 = __shfl_xor_sync(0xffffffffu, s0, 1); s1 = __shfl_xor_sync(0xffffffffu, s1, 1);
  if (b0) { v0 = s0; v2 = s1; } else { v1 = s0; v3 = s1; }
  uint32_t t0 = b1 ? v0 : v2, t1 = b1 ? v1 : v3;
  t0 = __shfl_xor_sync(0xffffffffu, t0, 2); t1 = __shfl_xor_sync(0xffffffffu, t1, 2);
  if (b1) { v0 = t0; v1 = t1; } else { v2 = t0; v3 = t1; }
}

#define TX(i)
#define TXC(i)
#define TSA(item, i)
#define TL_ENTRY(k)
#define TL_WAITED(k)
#define TL_END(k)
#define TS(item, i)
template<int TB> __device__ __forceinline__ void wgmma_rs_n64(float (&d)[32], uint32_t a0, uint32_t a1, uint32_t a2, uint32_t a3, uint64_t db, int scale_d) {
  asm volatile("{\n.reg .pred p;\nsetp.ne.b32 p, %37, 0;\n"
    "wgmma.mma_async.sync.aligned.m64n64k16.f32.bf16.bf16 {%0, %1, %2, %3, %4, %5, %6, %7, %8, %9, %10, %11, %12, %13, %14, %15, %16, %17, %18, %19, %20, %21, %22, %23, %24, %25, %26, %27, %28, %29, %30, %31}, {%32, %33, %34, %35}, %36, p, 1, 1, %38;\n}\n"
    : "+f"(d[0]), "+f"(d[1]), "+f"(d[2]), "+f"(d[3]), "+f"(d[4]), "+f"(d[5]), "+f"(d[6]), "+f"(d[7]), "+f"(d[8]), "+f"(d[9]), "+f"(d[10]), "+f"(d[11]), "+f"(d[12]), "+f"(d[13]), "+f"(d[14]), "+f"(d[15]), "+f"(d[16]), "+f"(d[17]), "+f"(d[18]), "+f"(d[19]), "+f"(d[20]), "+f"(d[21]), "+f"(d[22]), "+f"(d[23]), "+f"(d[24]), "+f"(d[25]), "+f"(d[26]), "+f"(d[27]), "+f"(d[28]), "+f"(d[29]), "+f"(d[30]), "+f"(d[31])
    : "r"(a0), "r"(a1), "r"(a2), "r"(a3), "l"(db), "r"(scale_d), "n"(TB));
}
template<int TB> __device__ __forceinline__ void wgmma_rs_n192(float (&d)[96], uint32_t a0, uint32_t a1, uint32_t a2, uint32_t a3, uint64_t db, int scale_d) {
  asm volatile("{\n.reg .pred p;\nsetp.ne.b32 p, %101, 0;\n"
    "wgmma.mma_async.sync.aligned.m64n192k16.f32.bf16.bf16 {%0, %1, %2, %3, %4, %5, %6, %7, %8, %9, %10, %11, %12, %13, %14, %15, %16, %17, %18, %19, %20, %21, %22, %23, %24, %25, %26, %27, %28, %29, %30, %31, %32, %33, %34, %35, %36, %37, %38, %39, %40, %41, %42, %43, %44, %45, %46, %47, %48, %49, %50, %51, %52, %53, %54, %55, %56, %57, %58, %59, %60, %61, %62, %63, %64, %65, %66, %67, %68, %69, %70, %71, %72, %73, %74, %75, %76, %77, %78, %79, %80, %81, %82, %83, %84, %85, %86, %87, %88, %89, %90, %91, %92, %93, %94, %95}, {%96, %97, %98, %99}, %100, p, 1, 1, %102;\n}\n"
    : "+f"(d[0]), "+f"(d[1]), "+f"(d[2]), "+f"(d[3]), "+f"(d[4]), "+f"(d[5]), "+f"(d[6]), "+f"(d[7]), "+f"(d[8]), "+f"(d[9]), "+f"(d[10]), "+f"(d[11]), "+f"(d[12]), "+f"(d[13]), "+f"(d[14]), "+f"(d[15]), "+f"(d[16]), "+f"(d[17]), "+f"(d[18]), "+f"(d[19]), "+f"(d[20]), "+f"(d[21]), "+f"(d[22]), "+f"(d[23]), "+f"(d[24]), "+f"(d[25]), "+f"(d[26]), "+f"(d[27]), "+f"(d[28]), "+f"(d[29]), "+f"(d[30]), "+f"(d[31]), "+f"(d[32]), "+f"(d[33]), "+f"(d[34]), "+f"(d[35]), "+f"(d[36]), "+f"(d[37]), "+f"(d[38]), "+f"(d[39]), "+f"(d[40]), "+f"(d[41]), "+f"(d[42]), "+f"(d[43]), "+f"(d[44]), "+f"(d[45]), "+f"(d[46]), "+f"(d[47]), "+f"(d[48]), "+f"(d[49]), "+f"(d[50]), "+f"(d[51]), "+f"(d[52]), "+f"(d[53]), "+f"(d[54]), "+f"(d[55]), "+f"(d[56]), "+f"(d[57]), "+f"(d[58]), "+f"(d[59]), "+f"(d[60]), "+f"(d[61]), "+f"(d[62]), "+f"(d[63]), "+f"(d[64]), "+f"(d[65]), "+f"(d[66]), "+f"(d[67]), "+f"(d[68]), "+f"(d[69]), "+f"(d[70]), "+f"(d[71]), "+f"(d[72]), "+f"(d[73]), "+f"(d[74]), "+f"(d[75]), "+f"(d[76]), "+f"(d[77]), "+f"(d[78]), "+f"(d[79]), "+f"(d[80]), "+f"(d[81]), "+f"(d[82]), "+f"(d[83]), "+f"(d[84]), "+f"(d[85]), "+f"(d[86]), "+f"(d[87]), "+f"(d[88]), "+f"(d[89]), "+f"(d[90]), "+f"(d[91]), "+f"(d[92]), "+f"(d[93]), "+f"(d[94]), "+f"(d[95])
    : "r"(a0), "r"(a1), "r"(a2), "r"(a3), "l"(db), "r"(scale_d), "n"(TB));
}
template<int TB> __device__ __forceinline__ void wgmma_ss_n128(float (&d)[64], uint64_t da, uint64_t db, int scale_d) {
  asm volatile("{\n.reg .pred p;\nsetp.ne.b32 p, %66, 0;\n"
    "wgmma.mma_async.sync.aligned.m64n128k16.f32.bf16.bf16 {%0, %1, %2, %3, %4, %5, %6, %7, %8, %9, %10, %11, %12, %13, %14, %15, %16, %17, %18, %19, %20, %21, %22, %23, %24, %25, %26, %27, %28, %29, %30, %31, %32, %33, %34, %35, %36, %37, %38, %39, %40, %41, %42, %43, %44, %45, %46, %47, %48, %49, %50, %51, %52, %53, %54, %55, %56, %57, %58, %59, %60, %61, %62, %63}, %64, %65, p, 1, 1, 0, %67;\n}\n"
    : "+f"(d[0]), "+f"(d[1]), "+f"(d[2]), "+f"(d[3]), "+f"(d[4]), "+f"(d[5]), "+f"(d[6]), "+f"(d[7]), "+f"(d[8]), "+f"(d[9]), "+f"(d[10]), "+f"(d[11]), "+f"(d[12]), "+f"(d[13]), "+f"(d[14]), "+f"(d[15]), "+f"(d[16]), "+f"(d[17]), "+f"(d[18]), "+f"(d[19]), "+f"(d[20]), "+f"(d[21]), "+f"(d[22]), "+f"(d[23]), "+f"(d[24]), "+f"(d[25]), "+f"(d[26]), "+f"(d[27]), "+f"(d[28]), "+f"(d[29]), "+f"(d[30]), "+f"(d[31]), "+f"(d[32]), "+f"(d[33]), "+f"(d[34]), "+f"(d[35]), "+f"(d[36]), "+f"(d[37]), "+f"(d[38]), "+f"(d[39]), "+f"(d[40]), "+f"(d[41]), "+f"(d[42]), "+f"(d[43]), "+f"(d[44]), "+f"(d[45]), "+f"(d[46]), "+f"(d[47]), "+f"(d[48]), "+f"(d[49]), "+f"(d[50]), "+f"(d[51]), "+f"(d[52]), "+f"(d[53]), "+f"(d[54]), "+f"(d[55]), "+f"(d[56]), "+f"(d[57]), "+f"(d[58]), "+f"(d[59]), "+f"(d[60]), "+f"(d[61]), "+f"(d[62]), "+f"(d[63])
    : "l"(da), "l"(db), "r"(scale_d), "n"(TB));
}
template<int TB> __device__ __forceinline__ void wgmma_ss_n192(float (&d)[96], uint64_t da, uint64_t db, int scale_d) {
  asm volatile("{\n.reg .pred p;\nsetp.ne.b32 p, %98, 0;\n"
    "wgmma.mma_async.sync.aligned.m64n192k16.f32.bf16.bf16 {%0, %1, %2, %3, %4, %5, %6, %7, %8, %9, %10, %11, %12, %13, %14, %15, %16, %17, %18, %19, %20, %21, %22, %23, %24, %25, %26, %27, %28, %29, %30, %31, %32, %33, %34, %35, %36, %37, %38, %39, %40, %41, %42, %43, %44, %45, %46, %47, %48, %49, %50, %51, %52, %53, %54, %55, %56, %57, %58, %59, %60, %61, %62, %63, %64, %65, %66, %67, %68, %69, %70, %71, %72, %73, %74, %75, %76, %77, %78, %79, %80, %81, %82, %83, %84, %85, %86, %87, %88, %89, %90, %91, %92, %93, %94, %95}, %96, %97, p, 1, 1, 0, %99;\n}\n"
    : "+f"(d[0]), "+f"(d[1]), "+f"(d[2]), "+f"(d[3]), "+f"(d[4]), "+f"(d[5]), "+f"(d[6]), "+f"(d[7]), "+f"(d[8]), "+f"(d[9]), "+f"(d[10]), "+f"(d[11]), "+f"(d[12]), "+f"(d[13]), "+f"(d[14]), "+f"(d[15]), "+f"(d[16]), "+f"(d[17]), "+f"(d[18]), "+f"(d[19]), "+f"(d[20]), "+f"(d[21]), "+f"(d[22]), "+f"(d[23]), "+f"(d[24]), "+f"(d[25]), "+f"(d[26]), "+f"(d[27]), "+f"(d[28]), "+f"(d[29]), "+f"(d[30]), "+f"(d[31]), "+f"(d[32]), "+f"(d[33]), "+f"(d[34]), "+f"(d[35]), "+f"(d[36]), "+f"(d[37]), "+f"(d[38]), "+f"(d[39]), "+f"(d[40]), "+f"(d[41]), "+f"(d[42]), "+f"(d[43]), "+f"(d[44]), "+f"(d[45]), "+f"(d[46]), "+f"(d[47]), "+f"(d[48]), "+f"(d[49]), "+f"(d[50]), "+f"(d[51]), "+f"(d[52]), "+f"(d[53]), "+f"(d[54]), "+f"(d[55]), "+f"(d[56]), "+f"(d[57]), "+f"(d[58]), "+f"(d[59]), "+f"(d[60]), "+f"(d[61]), "+f"(d[62]), "+f"(d[63]), "+f"(d[64]), "+f"(d[65]), "+f"(d[66]), "+f"(d[67]), "+f"(d[68]), "+f"(d[69]), "+f"(d[70]), "+f"(d[71]), "+f"(d[72]), "+f"(d[73]), "+f"(d[74]), "+f"(d[75]), "+f"(d[76]), "+f"(d[77]), "+f"(d[78]), "+f"(d[79]), "+f"(d[80]), "+f"(d[81]), "+f"(d[82]), "+f"(d[83]), "+f"(d[84]), "+f"(d[85]), "+f"(d[86]), "+f"(d[87]), "+f"(d[88]), "+f"(d[89]), "+f"(d[90]), "+f"(d[91]), "+f"(d[92]), "+f"(d[93]), "+f"(d[94]), "+f"(d[95])
    : "l"(da), "l"(db), "r"(scale_d), "n"(TB));
}
template<int TB> __device__ __forceinline__ void wgmma_ss_n80(float (&d)[40], uint64_t da, uint64_t db, int scale_d) {
  asm volatile("{\n.reg .pred p;\nsetp.ne.b32 p, %42, 0;\n"
    "wgmma.mma_async.sync.aligned.m64n80k16.f32.bf16.bf16 {%0, %1, %2, %3, %4, %5, %6, %7, %8, %9, %10, %11, %12, %13, %14, %15, %16, %17, %18, %19, %20, %21, %22, %23, %24, %25, %26, %27, %28, %29, %30, %31, %32, %33, %34, %35, %36, %37, %38, %39}, %40, %41, p, 1, 1, 0, %43;\n}\n"
    : "+f"(d[0]), "+f"(d[1]), "+f"(d[2]), "+f"(d[3]), "+f"(d[4]), "+f"(d[5]), "+f"(d[6]), "+f"(d[7]), "+f"(d[8]), "+f"(d[9]), "+f"(d[10]), "+f"(d[11]), "+f"(d[12]), "+f"(d[13]), "+f"(d[14]), "+f"(d[15]), "+f"(d[16]), "+f"(d[17]), "+f"(d[18]), "+f"(d[19]), "+f"(d[20]), "+f"(d[21]), "+f"(d[22]), "+f"(d[23]), "+f"(d[24]), "+f"(d[25]), "+f"(d[26]), "+f"(d[27]), "+f"(d[28]), "+f"(d[29]), "+f"(d[30]), "+f"(d[31]), "+f"(d[32]), "+f"(d[33]), "+f"(d[34]), "+f"(d[35]), "+f"(d[36]), "+f"(d[37]), "+f"(d[38]), "+f"(d[39])
    : "l"(da), "l"(db), "r"(scale_d), "n"(TB));
}

__device__ float g_mod[6 * D_];
__device__ __align__(1024) bf16 g_h[S_ * D_];
__device__ __align__(1024) bf16 g_o[S_ * HD_];
__device__ __align__(1024) bf16 g_xch[16 * 2 * 4 * 4 * 128 * 80];
__device__ __align__(1024) bf16 g_w1t[D_ * D_];
__device__ __align__(1024) bf16 g_w2t[D_ * D_];
__device__ __align__(1024) bf16 g_w4t[D_ * F_];
__device__ __align__(32) float g_st1[S_ * 8];
__device__ __align__(32) float g_st2[S_ * 2];
__device__ __align__(32) float g_vec[3 * D_ + F_ + 8];
__device__ unsigned g_flag[1024];
enum { F_XCH = 0, F_XA = 256, F_US = 272, F_X1 = 288, F_G = 304, F_PREP = 320, F_O = 512 };
__device__ __align__(1024) bf16 g_xa[S_ * D_];
__device__ __align__(1024) bf16 g_us[S_ * D_];
__device__ __align__(1024) bf16 g_x1[S_ * D_];
__device__ __align__(1024) bf16 g_g[S_ * F_];

__global__ void __launch_bounds__(256) mod_kernel(const bf16* __restrict__ c, const bf16* __restrict__ w_mod) {
  TL_ENTRY(0);
  pdl_launch();
  __shared__ float red[8][32];
  if (blockIdx.x < 14) { const int i = blockIdx.x * 256 + threadIdx.x; if (i < 3 * D_ + F_) g_vec[i] = 0.f; }
  else if (blockIdx.x < 18) g_flag[(blockIdx.x - 14) * 256 + threadIdx.x] = 0u;
  const int t = threadIdx.x, cg = t & 3, r0 = t >> 2;
  const int col0 = blockIdx.x * 32 + cg * 8;
  uint4 w[10];
#pragma unroll
  for (int i = 0; i < 10; i++) w[i] = __ldg(reinterpret_cast<const uint4*>(w_mod + (size_t)(r0 + 64 * i) * (6 * D_) + col0));
  float acc[8];
#pragma unroll
  for (int j = 0; j < 8; j++) acc[j] = 0.f;
#pragma unroll
  for (int i = 0; i < 10; i++) {
    float cv = __bfloat162float(c[r0 + 64 * i]);
    float s = bf_round(cv / (1.f + __expf(-cv)));
    acc[0] = fmaf(s, bf_lo(w[i].x), acc[0]); acc[1] = fmaf(s, bf_hi(w[i].x), acc[1]);
    acc[2] = fmaf(s, bf_lo(w[i].y), acc[2]); acc[3] = fmaf(s, bf_hi(w[i].y), acc[3]);
    acc[4] = fmaf(s, bf_lo(w[i].z), acc[4]); acc[5] = fmaf(s, bf_hi(w[i].z), acc[5]);
    acc[6] = fmaf(s, bf_lo(w[i].w), acc[6]); acc[7] = fmaf(s, bf_hi(w[i].w), acc[7]);
  }
#pragma unroll
  for (int j = 0; j < 8; j++) {
    acc[j] += __shfl_xor_sync(0xffffffffu, acc[j], 4);
    acc[j] += __shfl_xor_sync(0xffffffffu, acc[j], 8);
    acc[j] += __shfl_xor_sync(0xffffffffu, acc[j], 16);
  }
  if ((t & 31) < 4) {
#pragma unroll
    for (int j = 0; j < 8; j++) red[t >> 5][cg * 8 + j] = acc[j];
  }
  __syncthreads();
  if (t < 32) {
    float s = 0.f;
#pragma unroll
    for (int w8 = 0; w8 < 8; w8++) s += red[w8][t];
    const int col = blockIdx.x * 32 + t;
    s = bf_round(s);
    const int part = col / D_;
    if (part == 1 || part == 4) s = bf_round(1.f + s);
    g_mod[col] = s;
    if (t == 0) TL_END(0);
  }
}

__device__ __forceinline__ void row_stats(const float (&v)[20], float& mean, float& rstd) {
  float s = 0.f;
#pragma unroll
  for (int i = 0; i < 20; i++) s += v[i];
  mean = warp_sum(s) * (1.f / D_);
  float q = 0.f;
#pragma unroll
  for (int i = 0; i < 20; i++) { float d = v[i] - mean; q = fmaf(d, d, q); }
  rstd = rsqrtf(warp_sum(q) * (1.f / D_) + LN_EPS);
}
__device__ __forceinline__ void load_row_bf16(const bf16* p, int lane, float (&v)[20]) {
#pragma unroll
  for (int i = 0; i < 5; i++) {
    uint2 u = *reinterpret_cast<const uint2*>(p + (lane + 32 * i) * 4);
    v[4 * i] = bf_lo(u.x); v[4 * i + 1] = bf_hi(u.x); v[4 * i + 2] = bf_lo(u.y); v[4 * i + 3] = bf_hi(u.y);
  }
}
__device__ __forceinline__ void store_row_bf16(bf16* p, int lane, const float (&v)[20]) {
#pragma unroll
  for (int i = 0; i < 5; i++) {
    uint2 u; u.x = pack_bf16(v[4 * i], v[4 * i + 1]); u.y = pack_bf16(v[4 * i + 2], v[4 * i + 3]);
    *reinterpret_cast<uint2*>(p + (lane + 32 * i) * 4) = u;
  }
}
__device__ __forceinline__ void load_row_f32(const float* p, int lane, float (&v)[20]) {
#pragma unroll
  for (int i = 0; i < 5; i++) {
    float4 u = *reinterpret_cast<const float4*>(p + (lane + 32 * i) * 4);
    v[4 * i] = u.x; v[4 * i + 1] = u.y; v[4 * i + 2] = u.z; v[4 * i + 3] = u.w;
  }
}

__global__ void __launch_bounds__(256) ln1_kernel(const bf16* __restrict__ x) {
  TL_ENTRY(1);
  pdl_launch();
  const int lane = threadIdx.x & 31, row = blockIdx.x * 8 + (threadIdx.x >> 5);
  float v[20];
  load_row_bf16(x + (size_t)row * D_, lane, v);
  float mean, rstd;
  row_stats(v, mean, rstd);
  if (lane < 8) g_st1[row * 8 + lane] = 0.f;
  if (lane < 2) g_st2[row * 2 + lane] = 0.f;
  pdl_wait();
  if (threadIdx.x == 0) TL_WAITED(1);
  float sa[20], ca[20];
  load_row_f32(g_mod, lane, sa);
  load_row_f32(g_mod + D_, lane, ca);
#pragma unroll
  for (int i = 0; i < 20; i++) v[i] = fmaf((v[i] - mean) * rstd, ca[i], sa[i]);
  store_row_bf16(g_h + (size_t)row * D_, lane, v);
  if (threadIdx.x == 0) TL_END(1);
}

constexpr int PREP_JOBS = 200 + 200 + 480 + 480;
struct PrepW { const bf16 *w1, *w2, *w3, *w4; };
__device__ __forceinline__ void prep_warp(const PrepW& pw, bf16 (*tile)[72], int lane) {
#pragma unroll 1
  for (int job = blockIdx.x; job < PREP_JOBS; job += gridDim.x) {
    const bf16* src; bf16* dst; int ld = D_, ldd = D_, kt, nt, kind = 1;
    if (job < 200) { src = pw.w1; dst = g_w1t; kt = job / 10; nt = job % 10; kind = 0; }
    else if (job < 400) { src = pw.w2; dst = g_w2t; kt = (job - 200) / 10; nt = (job - 200) % 10; }
    else if (job < 880) { src = pw.w4; dst = g_w4t; ldd = F_; kt = (job - 400) / 10; nt = (job - 400) % 10; }
    else { src = pw.w3; dst = nullptr; ld = F_; kt = (job - 880) / 24; nt = (job - 880) % 24; kind = 2; }
    src += (size_t)(kt * 32 + (lane >> 3)) * ld + nt * 64 + (lane & 7) * 8;
    __syncwarp();
#pragma unroll
    for (int h = 0; h < 2; h++) {
      uint4 v[4];
#pragma unroll
      for (int i = 0; i < 4; i++) v[i] = __ldg(reinterpret_cast<const uint4*>(src + (size_t)(h * 16 + i * 4) * ld));
#pragma unroll
      for (int i = 0; i < 4; i++) *reinterpret_cast<uint4*>(&tile[h * 16 + i * 4 + (lane >> 3)][(lane & 7) * 8]) = v[i];
    }
    __syncwarp();
    const float* pa = g_mod + 4 * D_ + kt * 32;
    const float* pb = g_mod + 3 * D_ + kt * 32;
#pragma unroll 1
    for (int h = 0; h < 2; h++) {
      const int n = lane + 32 * h;
      float sa = 0.f, sb = 0.f, sc = 0.f;
#pragma unroll 1
      for (int c = 0; c < 4; c++) {
        uint32_t u[4];
#pragma unroll
        for (int e = 0; e < 4; e++) {
          const int k = c * 8 + 2 * e;
          float lo = __bfloat162float(tile[k][n]), hi = __bfloat162float(tile[k + 1][n]);
          sc += lo + hi;
          if (kind == 0) {
            const float2 a = __ldcg(reinterpret_cast<const float2*>(pa + k)), b = __ldcg(reinterpret_cast<const float2*>(pb + k));
            sb = fmaf(b.x, lo, fmaf(b.y, hi, sb));
            lo *= a.x; hi *= a.y;
          }
          u[e] = pack_bf16(lo, hi);
          sa += bf_lo(u[e]) + bf_hi(u[e]);
        }
        if (kind != 2) *reinterpret_cast<uint4*>(dst + (size_t)(nt * 64 + n) * ldd + kt * 32 + c * 8) = make_uint4(u[0], u[1], u[2], u[3]);
      }
      if (kind == 0) { atomicAdd(&g_vec[nt * 64 + n], sa); atomicAdd(&g_vec[D_ + nt * 64 + n], sb); atomicAdd(&g_vec[2 * D_ + nt * 64 + n], sc); }
      else if (kind == 2) atomicAdd(&g_vec[3 * D_ + nt * 64 + n], sc);
    }
  }
  __syncwarp();
  if (lane == 0) {
    asm volatile("fence.acq_rel.gpu;" ::: "memory");
    asm volatile("red.relaxed.gpu.global.add.u32 [%0], 1;" :: "l"(g_flag + F_PREP) : "memory");
  }
}

constexpr int A_NSLOT = 9;
constexpr int A_SLOT = 24576;
constexpr int A_NKV = S_ / 64;
constexpr int PREP_CTAS = 128;

struct Ring {
  uint32_t slot, phase;
  __device__ __forceinline__ void adv(int n) { if (++slot == (uint32_t)n) { slot = 0; phase ^= 1; } }
};
constexpr int T_PAR = A_NSLOT * A_SLOT + 384;
constexpr int T_PREP = T_PAR + 3712;
constexpr int T_SMEM = T_PREP + 32 * 72 * 2 + 1024;
enum { P_OGA = 0, P_OA = 80, P_OB = 160, P_VA = 240, P_VB = 320, P_VC = 400, P_A2 = 480, P_B2 = 560, P_GB = 640, P_CS3 = 720, P_SC = 912 };

__device__ __forceinline__ void flag_wait(const unsigned* p, unsigned target) {
  asm volatile(
      "{\n.reg .pred p;\n.reg .u32 n, v;\n"
      "mov.u32 n, 0;\n"
      "SPIN:\n"
      "ld.relaxed.gpu.global.u32 v, [%0];\n"
      "setp.ge.u32 p, v, %1;\n"
      "@p bra DONE;\n"
      "add.u32 n, n, 1;\n"
      "setp.gt.u32 p, n, 4194304;\n"
      "@p trap;\n"
      "bra SPIN;\n"
      "DONE:\n}\n" :: "l"(p), "r"(target) : "memory");
}
__device__ __forceinline__ void fence_async_global() { asm volatile("fence.proxy.async.global;" ::: "memory"); }
__device__ __forceinline__ float lds_f(uint32_t a) { float v; asm volatile("ld.shared.f32 %0, [%1];" : "=f"(v) : "r"(a)); return v; }
__device__ __forceinline__ float2 lds_f2(uint32_t a) { float2 v; asm volatile("ld.shared.v2.f32 {%0, %1}, [%2];" : "=f"(v.x), "=f"(v.y) : "r"(a)); return v; }
__device__ __forceinline__ uint4 ldcg4(const void* p) { return __ldcg(reinterpret_cast<const uint4*>(p)); }

__device__ __forceinline__ void sts_f2(uint32_t a, float x, float y) { asm volatile("st.shared.v2.f32 [%0], {%1, %2};" :: "r"(a), "f"(x), "f"(y) : "memory"); }
__device__ __forceinline__ float4 lds_f4(uint32_t a) { float4 v; asm volatile("ld.shared.v4.f32 {%0, %1, %2, %3}, [%4];" : "=f"(v.x), "=f"(v.y), "=f"(v.z), "=f"(v.w) : "r"(a) : "memory"); return v; }
__device__ __forceinline__ uint4 lds_u4(uint32_t a) { uint4 v; asm volatile("ld.shared.v4.u32 {%0, %1, %2, %3}, [%4];" : "=r"(v.x), "=r"(v.y), "=r"(v.z), "=r"(v.w) : "r"(a) : "memory"); return v; }
__device__ __forceinline__ void lds8(uint32_t a, float (&v)[8]) {
  const float4 p = lds_f4(a), q = lds_f4(a + 16);
  v[0] = p.x; v[1] = p.y; v[2] = p.z; v[3] = p.w; v[4] = q.x; v[5] = q.y; v[6] = q.z; v[7] = q.w;
}
__device__ __forceinline__ void lds8_bf(uint32_t a, float (&v)[8]) {
  const uint4 u = lds_u4(a);
  v[0] = bf_lo(u.x); v[1] = bf_hi(u.x); v[2] = bf_lo(u.y); v[3] = bf_hi(u.y); v[4] = bf_lo(u.z); v[5] = bf_hi(u.z); v[6] = bf_lo(u.w); v[7] = bf_hi(u.w);
}
__device__ __forceinline__ uint4 pack8(const float (&v)[8]) {
  return make_uint4(pack_bf16(v[0], v[1]), pack_bf16(v[2], v[3]), pack_bf16(v[4], v[5]), pack_bf16(v[6], v[7]));
}
__device__ __forceinline__ void mbar_wait_c(uint32_t a, uint32_t ph) {
  asm volatile("{\n.reg .pred p;\nSPIN:\nmbarrier.try_wait.parity.shared::cta.b64 p, [%0], %1;\n@!p bra SPIN;\n}\n" :: "r"(a), "r"(ph) : "memory");
}
constexpr int ST_P = 80;
constexpr int E_TILE = 128 * 80 * 2;

struct Maps { CUtensorMap h, wq, k, v, o, wo3, wo2, xa, w1t, us, w2t, x1, w3, g, w4t, ex, exa, ex1; };
struct PfList { const uint8_t* p[6]; };

constexpr int M_AOFF = 102400, M_NA = 7;

__global__ void __cluster_dims__(2, 1, 1) __launch_bounds__(384, 1)
fused_kernel(const __grid_constant__ Maps tm, const __grid_constant__ PfList pf, const __grid_constant__ PrepW pw, const bf16* __restrict__ x, bf16* __restrict__ out) {
  extern __shared__ uint8_t smem_raw[];
  const uint32_t sb = (smem_u32(smem_raw) + 1023) & ~1023u;
  TL_ENTRY(2);
  const uint32_t bar_full = sb + A_NSLOT * A_SLOT;
  const uint32_t bar_empty = bar_full + 8 * A_NSLOT;
  const uint32_t bar_sig = bar_empty + 8 * A_NSLOT;
  const uint32_t mb_full = bar_sig + 16;
  const uint32_t mb_empty = mb_full + 96;
  const uint32_t par = sb + T_PAR;
  float* parf = reinterpret_cast<float*>(smem_raw + (par - smem_u32(smem_raw)));
  uint32_t rank;
  asm volatile("mov.u32 %0, %%cluster_ctarank;" : "=r"(rank));
  const int cid = blockIdx.x >> 1;
  const int wid = __shfl_sync(0xffffffffu, threadIdx.x >> 5, 0);
  const int wg = wid >> 2;
  const int qtile = (cid & 7) * 2 + rank, hbase = cid >> 3;
  const int o_qt = qtile, o_nh = (cid >> 3) & 1, o_ks = cid >> 4;
  const int o_col = o_nh * 320 + o_ks * 80;
  const int qt = cid >> 2, js = (cid & 3) * 2 + rank;
  if (threadIdx.x == 0) {
    for (int i = 0; i < A_NSLOT; i++) { mbar_init(bar_full + 8 * i, 1); mbar_init(bar_empty + 8 * i, 16); }
    mbar_init(bar_sig, 4); mbar_init(bar_sig + 8, 4);
    for (int i = 0; i < 12; i++) { mbar_init(mb_full + 8 * i, 1); mbar_init(mb_empty + 8 * i, i < 5 ? 8 : 16); }
    asm volatile("fence.mbarrier_init.release.cluster;" ::: "memory");
    prefetch_tmap(&tm.h); prefetch_tmap(&tm.wq); prefetch_tmap(&tm.k); prefetch_tmap(&tm.v);
  }
  __syncthreads();
  cluster_sync();

  if (wg == 0) {
    asm volatile("setmaxnreg.dec.sync.aligned.u32 40;");
    if (wid == 0) {
      Ring r{0, 1};
#define P_ACQ(bytes_) do { mbar_wait(bar_empty + 8 * r.slot, r.phase); mbar_expect_e(bar_full + 8 * r.slot, bytes_); } while (0)
#define P_DST (sb + r.slot * A_SLOT)
#define P_BAR (bar_full + 8 * r.slot)
      uint64_t pol_ef;
      asm volatile("createpolicy.fractional.L2::evict_first.b64 %0, 1.0;" : "=l"(pol_ef));
      pdl_wait();
      TL_WAITED(2);
#pragma unroll 1
      for (int item = 0; item < 4; item++) {
        const int head = hbase + 8 * item;
#pragma unroll 1
        for (int kb = 0; kb < 10; kb++) {
          P_ACQ(16384);
          tma2d(P_DST, &tm.h, P_BAR, kb * 64, qtile * 128);
          r.adv(A_NSLOT);
          P_ACQ(A_SLOT);
          if ((uint32_t)(kb & 1) == rank) tma3d_mc_hint(P_DST, &tm.wq, P_BAR, 0, kb * 64, head * 3, 3, pol_ef);
          r.adv(A_NSLOT);
        }
#pragma unroll 1
        for (int j = 0; j <= A_NKV; j++) {
          if (j < A_NKV) {
            P_ACQ(A_SLOT);
            if (rank == 0) tma3d_mc_hint(P_DST, &tm.k, P_BAR, 0, head * S_ + j * 64, 0, 3, pol_ef);
            r.adv(A_NSLOT);
          }
          if (j > 0) {
            P_ACQ(A_SLOT);
            if (rank == 1) tma3d_mc_hint(P_DST, &tm.v, P_BAR, 0, head * S_ + (j - 1) * 64, 0, 3, pol_ef);
            r.adv(A_NSLOT);
          }
          if (item == 3 && (j & 3) == 0) {
            const int c = (j >> 2) * 128 + blockIdx.x;
            if (c < 980) {
              const int li = c < 480 ? 0 : c < 600 ? 1 : c < 720 ? 2 : c < 880 ? 3 : c < 930 ? 4 : 5;
              const int c0 = c < 480 ? 0 : c < 600 ? 480 : c < 720 ? 600 : c < 880 ? 720 : c < 930 ? 880 : 930;
              l2_prefetch16k(pf.p[li] + (size_t)(c - c0) * 16384);
            }
          }
          if (item == 3) {
            if (j >= 6 && j < 24) {
              const int kb = j - 6;
              l2_prefetch_t2d(&tm.o, ((kb / 6) * 8 + 2 * o_ks + (kb % 6) / 3) * DH_ + (kb % 3) * 64, o_qt * 128);
            }
            if (j >= 24 && j < 30) flag_wait(g_flag + F_O + o_qt * 32 + ((j - 24) >> 1) * 8 + 2 * o_ks + (j & 1), 2);
            if (j == 0 && threadIdx.x == 0) {
              prefetch_tmap(&tm.o); prefetch_tmap(&tm.wo3); prefetch_tmap(&tm.wo2); prefetch_tmap(&tm.xa); prefetch_tmap(&tm.w1t); prefetch_tmap(&tm.us);
              prefetch_tmap(&tm.w2t); prefetch_tmap(&tm.x1); prefetch_tmap(&tm.w3); prefetch_tmap(&tm.g); prefetch_tmap(&tm.w4t);
              prefetch_tmap(&tm.ex); prefetch_tmap(&tm.exa); prefetch_tmap(&tm.ex1);
            }
          }
        }
      }
#pragma unroll 1
      for (int kb = 0; kb < 24; kb++) {
        const int head = (kb / 6) * 8 + 2 * o_ks + (kb % 6) / 3;
        const int kcol = head * DH_ + (kb % 3) * 64;
        P_ACQ(24576);
        if (rank == 0) tma3d_mc(P_DST, &tm.wo3, P_BAR, 0, kcol, o_nh * 5, 3);
        r.adv(A_NSLOT);
        P_ACQ(16384);
        if (rank == 1) tma3d_mc(P_DST, &tm.wo2, P_BAR, 0, kcol, o_nh * 5 + 3, 3);
        r.adv(A_NSLOT);
        if (kb == 18 || kb == 21) flag_wait(g_flag + F_O + o_qt * 32 + head, 2);
        if (kb % 3 == 0) fence_async_global();
        P_ACQ(16384);
        tma2d(P_DST, &tm.o, P_BAR, kcol, o_qt * 128);
        r.adv(A_NSLOT);
        if (kb < 12) TX(144 + kb);
      }
      P_ACQ(E_TILE);
      tma2d(P_DST, &tm.ex, P_BAR, o_col, o_qt * 128);
      r.adv(A_NSLOT);
      flag_wait(g_flag + F_XCH + (o_qt * 2 + o_nh) * 4 + o_ks, 6);
      fence_async_global();
#pragma unroll 1
      for (int i = 0; i < 3; i++) {
        P_ACQ(E_TILE);
        bulk_load(P_DST, g_xch + (size_t)((((o_qt * 2 + o_nh) * 4 + o_ks) * 4) + ((o_ks + 1 + i) & 3)) * (E_TILE / 2), E_TILE, P_BAR);
        r.adv(A_NSLOT);
      }
      flag_wait(g_flag + F_PREP, PREP_CTAS);
      fence_async_global();
#pragma unroll 1
      for (int i = 0; i < A_NSLOT; i++) { mbar_wait(bar_empty + 8 * r.slot, r.phase); r.adv(A_NSLOT); }
      Ring ra{0, 1};
      uint32_t bpar = 0x1f;
#pragma unroll 1
      for (int ph = 0; ph < 4; ph++) {
        const CUtensorMap* ma = ph == 0 ? &tm.xa : ph == 1 ? &tm.us : ph == 2 ? &tm.x1 : &tm.g;
        const CUtensorMap* mb = ph == 0 ? &tm.w1t : ph == 1 ? &tm.w2t : ph == 2 ? &tm.w3 : &tm.w4t;
        const int nkb = ph == 3 ? 24 : 10;
        const int nbl = ph == 2 ? 10 : nkb / 2;
        const int nel = ph == 1 ? 1 : ph == 3 ? 2 : 0;
        const uint32_t nbs = ph == 2 ? 4 : 5, bsz = ph == 2 ? 24576 : 20480;
        int bl = 0; uint32_t bs = 0;
#pragma unroll 1
        for (int i = 0; i < 5; i++) mbar_wait(mb_empty + 8 * i, (bpar >> i) & 1);
#define T_LOADB() do { mbar_wait(mb_empty + 8 * bs, (bpar >> bs) & 1); bpar ^= 1u << bs; mbar_expect_e(mb_full + 8 * bs, bsz);    \
                       if (bl < nbl) tma3d(sb + bs * bsz, mb, mb_full + 8 * bs, 0, ph == 2 ? bl * 64 : js * 80, ph == 2 ? js * 3 : bl * 2); \
                       else tma2d(sb + bs * bsz, bl == nbl ? &tm.exa : &tm.ex1, mb_full + 8 * bs, js * 80, qt * 128); \
                       bl++; if (++bs == nbs) bs = 0; } while (0)
#pragma unroll 1
        for (uint32_t i = 0; i < nbs; i++) T_LOADB();
        TX(8 + ph * 4);
        const unsigned* fl = g_flag + F_XA + 16 * ph;
        flag_wait(fl + qt, 16);
        if (ph == 1) { flag_wait(fl + ((qt + 15) & 15), 16); flag_wait(fl + ((qt + 1) & 15), 16); }
        TX(9 + ph * 4);
        fence_async_global();
#pragma unroll 1
        for (int kb = 0; kb < nkb; kb++) {
          mbar_wait(mb_empty + 40 + 8 * ra.slot, ra.phase);
          mbar_expect_e(mb_full + 40 + 8 * ra.slot, 16384);
          tma2d_mc(sb + M_AOFF + ra.slot * 16384 + rank * 8192, ma, mb_full + 40 + 8 * ra.slot, kb * 64, qt * 128 + (int)rank * 64, 3);
          ra.adv(M_NA);
          if (ph == 0) TX(64 + kb); if (ph == 3) TX(80 + kb);
          while (bl < nbl + nel && (kb == nkb - 1 || kb >= (ph == 2 ? bl + 2 : 2 * bl - 3))) T_LOADB();
        }
      }
    } else if (wid < 3) {
      const int w = wid - 1, lane = threadIdx.x & 31;
#pragma unroll 1
      for (int sig = 0; sig < 9; sig++) {
        mbar_wait(bar_sig + 8 * w, sig & 1);
        if (wid == 1) TX(32 + sig * 2);
        unsigned* f;
        bool act = lane == 0;
        if (sig < 4) f = g_flag + F_O + qtile * 32 + hbase + 8 * sig;
        else if (sig == 4) { f = g_flag + F_XCH + (o_qt * 2 + o_nh) * 4 + (lane & 3); act = lane < 4 && lane != o_ks; }
        else if (sig == 5) f = g_flag + F_XA + o_qt;
        else f = g_flag + F_XA + 16 * (sig - 5) + qt;
        if (act) {
          asm volatile("fence.acq_rel.gpu;" ::: "memory");
          asm volatile("red.relaxed.gpu.global.add.u32 [%0], 1;" :: "l"(f) : "memory");
        }
        if (wid == 1) TX(33 + sig * 2);
        __syncwarp();
      }
    } else {
      const int lane = threadIdx.x & 31;
      pdl_wait();
      prep_warp(pw, reinterpret_cast<bf16(*)[72]>(smem_raw + (sb + T_PREP - smem_u32(smem_raw))), lane);
      flag_wait(g_flag + F_PREP, PREP_CTAS);
#pragma unroll 1
      for (int i = lane; i < P_SC; i += 32) {
        const int v = i < P_CS3 ? i / 80 : 9, j = i - (i < P_CS3 ? v * 80 : P_CS3);
        const float* src = v == 0 ? g_mod + 2 * D_ + o_col : v == 1 ? g_mod + 4 * D_ + o_col : v == 2 ? g_mod + 3 * D_ + o_col
                         : v < 6 ? g_vec + (v - 3) * D_ + js * 80 : v == 6 ? g_mod + 4 * D_ + js * 80 : v == 7 ? g_mod + 3 * D_ + js * 80
                         : v == 8 ? g_mod + 5 * D_ + js * 80 : g_vec + 3 * D_ + js * 192;
        parf[i] = __ldcg(src + j);
      }
      float sv[5] = {0.f, 0.f, 0.f, 0.f, 0.f};
#pragma unroll 1
      for (int i = lane; i < D_; i += 32) {
        const float a = __ldcg(g_mod + 4 * D_ + i), b = __ldcg(g_mod + 3 * D_ + i);
        sv[0] += a; sv[1] = fmaf(a, a, sv[1]); sv[2] = fmaf(a, b, sv[2]); sv[3] += b; sv[4] = fmaf(b, b, sv[4]);
      }
#pragma unroll 1
      for (int o_ = 16; o_ > 0; o_ >>= 1) {
#pragma unroll
        for (int i = 0; i < 5; i++) sv[i] += __shfl_xor_sync(0xffffffffu, sv[i], o_);
      }
      if (lane == 0) {
#pragma unroll
        for (int i = 0; i < 5; i++) parf[P_SC + i] = sv[i];
      }
      bar_arrive(6, 288);
    }
    __syncwarp();
    cluster_sync();
  } else {
    asm volatile("setmaxnreg.inc.sync.aligned.u32 232;");
    const int w = wg - 1;
    const int lane = threadIdx.x & 31;
    const int warp = wid & 3;
    const int tid = threadIdx.x - 128;
    const uint32_t rel_base = mapa(bar_empty, (lane == 0) ? rank : (rank ^ 1));
    Ring r{0, 0};
#define A_RELEASE(slot_) do { if (lane < 2) mbar_arrive_remote(rel_base + 8 * (slot_)); } while (0)
#define SIGNAL() do { __syncwarp(); if (lane == 0) mbar_arrive(bar_sig + 8 * w); } while (0)
    {
    const float SC = 0.07216878364870322f * 1.4426950408889634f;
    float o[96];
    uint32_t q[48];
    float s[32];
    uint32_t p[16], p2[16];
    if (w == 1) bar_arrive(1, 256);
    for (int item = 0; item < 4; item++) {
      const int head = hbase + 8 * item;
      TSA(item, 0);
      uint32_t prevA = 0, prevB = 0;
      for (int kb = 0; kb < 10; kb++) {
        const uint32_t sA = r.slot; mbar_wait_c(bar_full + 8 * sA, r.phase); r.adv(A_NSLOT);
        const uint32_t sB = r.slot; mbar_wait_c(bar_full + 8 * sB, r.phase); r.adv(A_NSLOT);
        const uint64_t da = mkdesc(sb + sA * A_SLOT + w * 8192, 16, 1024);
        const uint64_t db = mkdesc(sb + sB * A_SLOT, 8192, 1024);
        wg_fence();
#pragma unroll
        for (int kk = 0; kk < 4; kk++) wgmma_ss_n192<1>(o, da + kk * 2, db + kk * 128, (kb | kk) != 0);
        wg_commit();
        if (kb > 0) { wg_wait<1>(); A_RELEASE(prevA); A_RELEASE(prevB); }
        prevA = sA; prevB = sB;
      }
      wg_wait<0>();
      fence_regs(o);
      A_RELEASE(prevA); A_RELEASE(prevB);
#pragma unroll
      for (int i = 0; i < 48; i++) q[i] = pack_bf16(o[2 * i], o[2 * i + 1]);

      TSA(item, 1);
      float c0, c1, l0, l1;
      {
        const uint32_t sK = r.slot; mbar_wait_c(bar_full + 8 * sK, r.phase); r.adv(A_NSLOT);
        const uint64_t dk = mkdesc(sb + sK * A_SLOT, 16, 1024);
        bar_sync(1 + w, 256);
        wg_fence();
#pragma unroll
        for (int kk = 0; kk < 12; kk++)
          wgmma_rs_n64<0>(s, q[4 * kk], q[4 * kk + 1], q[4 * kk + 2], q[4 * kk + 3], dk + (kk >> 2) * 512 + (kk & 3) * 2, kk != 0);
        wg_commit();
        bar_arrive(1 + (w ^ 1), 256);
        wg_wait<0>();
        fence_regs(s);
        A_RELEASE(sK);
        float mx0 = fmaxf(s[0], s[1]), mx1 = fmaxf(s[2], s[3]);
#pragma unroll
        for (int i = 1; i < 8; i++) { mx0 = fmaxf(mx0, fmaxf(s[4 * i], s[4 * i + 1])); mx1 = fmaxf(mx1, fmaxf(s[4 * i + 2], s[4 * i + 3])); }
        mx0 = fmaxf(mx0, __shfl_xor_sync(0xffffffffu, mx0, 1)); mx1 = fmaxf(mx1, __shfl_xor_sync(0xffffffffu, mx1, 1));
        mx0 = fmaxf(mx0, __shfl_xor_sync(0xffffffffu, mx0, 2)); mx1 = fmaxf(mx1, __shfl_xor_sync(0xffffffffu, mx1, 2));
        c0 = mx0 * SC; c1 = mx1 * SC;
        l0 = 0.f; l1 = 0.f;
#pragma unroll
        for (int i = 0; i < 8; i++) {
          s[4 * i] = ex2(fmaf(s[4 * i], SC, -c0)); s[4 * i + 1] = ex2(fmaf(s[4 * i + 1], SC, -c0));
          s[4 * i + 2] = ex2(fmaf(s[4 * i + 2], SC, -c1)); s[4 * i + 3] = ex2(fmaf(s[4 * i + 3], SC, -c1));
          l0 += s[4 * i] + s[4 * i + 1]; l1 += s[4 * i + 2] + s[4 * i + 3];
        }
#pragma unroll
        for (int i = 0; i < 16; i++) p[i] = pack_bf16(s[2 * i], s[2 * i + 1]);
      }
      TSA(item, 2);
      uint32_t okn;
      {
        Ring r2 = r; r2.adv(A_NSLOT);
        okn = mbar_try(bar_full + 8 * r.slot, r.phase) & mbar_try(bar_full + 8 * r2.slot, r2.phase);
      }
#define A_STEP(PC, PN, FIRST)                                                                                          \
      {                                                                                                                \
        const uint32_t sK = r.slot, phK = r.phase; r.adv(A_NSLOT);                                                     \
        const uint32_t sV = r.slot, phV = r.phase; r.adv(A_NSLOT);                                                     \
        const uint64_t dk = mkdesc(sb + sK * A_SLOT, 16, 1024);                                                        \
        const uint64_t dv = mkdesc(sb + sV * A_SLOT, 8192, 1024);                                                      \
        if (!okn) { mbar_wait_c(bar_full + 8 * sK, phK); mbar_wait_c(bar_full + 8 * sV, phV); }                            \
        bar_sync(1 + w, 256);                                                                                          \
        wg_fence();                                                                                                    \
        _Pragma("unroll") for (int kk = 0; kk < 12; kk++)                                                              \
          wgmma_rs_n64<0>(s, q[4 * kk], q[4 * kk + 1], q[4 * kk + 2], q[4 * kk + 3], dk + (kk >> 2) * 512 + (kk & 3) * 2, kk != 0); \
        wg_commit();                                                                                                   \
        _Pragma("unroll") for (int kk = 0; kk < 4; kk++)                                                               \
          wgmma_rs_n192<1>(o, PC[4 * kk], PC[4 * kk + 1], PC[4 * kk + 2], PC[4 * kk + 3], dv + kk * 128, !(FIRST) || (kk != 0)); \
        wg_commit();                                                                                                   \
        bar_arrive(1 + (w ^ 1), 256);                                                                                  \
        {                                                                                                              \
          Ring r2 = r; r2.adv(A_NSLOT);                                                                                \
          okn = mbar_try(bar_full + 8 * r.slot, r.phase) & mbar_try(bar_full + 8 * r2.slot, r2.phase);                 \
        }                                                                                                              \
        wg_wait<1>();                                                                                                  \
        fence_regs(s);                                                                                                 \
        A_RELEASE(sK);                                                                                                 \
        float b0 = 0.f, b1 = 0.f;                                                                                      \
        _Pragma("unroll") for (int i = 0; i < 8; i++) {                                                                \
          const float e0 = ex2(fmaf(s[4 * i], SC, -c0)), e1 = ex2(fmaf(s[4 * i + 1], SC, -c0));                        \
          const float e2 = ex2(fmaf(s[4 * i + 2], SC, -c1)), e3 = ex2(fmaf(s[4 * i + 3], SC, -c1));                    \
          b0 += e0 + e1; b1 += e2 + e3;                                                                                \
          PN[2 * i] = pack_bf16(e0, e1); PN[2 * i + 1] = pack_bf16(e2, e3);                                            \
        }                                                                                                              \
        wg_wait<0>();                                                                                                  \
        fence_regs(o);                                                                                                 \
        fence_regs(PC);                                                                                                \
        A_RELEASE(sV);                                                                                                 \
        if (__any_sync(0xffffffffu, !(b0 <= 65536.f) || !(b1 <= 65536.f))) {                                           \
          float mx0 = fmaxf(s[0], s[1]), mx1 = fmaxf(s[2], s[3]);                                                      \
          _Pragma("unroll") for (int i = 1; i < 8; i++) {                                                              \
            mx0 = fmaxf(mx0, fmaxf(s[4 * i], s[4 * i + 1])); mx1 = fmaxf(mx1, fmaxf(s[4 * i + 2], s[4 * i + 3]));     \
          }                                                                                                            \
          mx0 = fmaxf(mx0, __shfl_xor_sync(0xffffffffu, mx0, 1)); mx1 = fmaxf(mx1, __shfl_xor_sync(0xffffffffu, mx1, 1)); \
          mx0 = fmaxf(mx0, __shfl_xor_sync(0xffffffffu, mx0, 2)); mx1 = fmaxf(mx1, __shfl_xor_sync(0xffffffffu, mx1, 2)); \
          const float n0 = fmaxf(c0, mx0 * SC), n1 = fmaxf(c1, mx1 * SC);                                              \
          const float a0 = ex2(c0 - n0), a1 = ex2(c1 - n1);                                                            \
          c0 = n0; c1 = n1;                                                                                            \
          l0 *= a0; l1 *= a1;                                                                                          \
          _Pragma("unroll") for (int i = 0; i < 24; i++) { o[4 * i] *= a0; o[4 * i + 1] *= a0; o[4 * i + 2] *= a1; o[4 * i + 3] *= a1; } \
          b0 = 0.f; b1 = 0.f;                                                                                          \
          _Pragma("unroll") for (int i = 0; i < 8; i++) {                                                              \
            const float e0 = ex2(fmaf(s[4 * i], SC, -c0)), e1 = ex2(fmaf(s[4 * i + 1], SC, -c0));                      \
            const float e2 = ex2(fmaf(s[4 * i + 2], SC, -c1)), e3 = ex2(fmaf(s[4 * i + 3], SC, -c1));                  \
            b0 += e0 + e1; b1 += e2 + e3;                                                                              \
            PN[2 * i] = pack_bf16(e0, e1); PN[2 * i + 1] = pack_bf16(e2, e3);                                          \
          }                                                                                                            \
        }                                                                                                              \
        l0 += b0; l1 += b1;                                                                                            \
      }
      for (int jj = 0; jj < 15; jj++) {
        A_STEP(p, p2, jj == 0)
        A_STEP(p2, p, false)
      }
      A_STEP(p, p2, false)
      TSA(item, 3);
      {
        const uint32_t sV = r.slot; mbar_wait_c(bar_full + 8 * sV, r.phase); r.adv(A_NSLOT);
        const uint64_t dv = mkdesc(sb + sV * A_SLOT, 8192, 1024);
        bar_sync(1 + w, 256);
        wg_fence();
#pragma unroll
        for (int kk = 0; kk < 4; kk++)
          wgmma_rs_n192<1>(o, p2[4 * kk], p2[4 * kk + 1], p2[4 * kk + 2], p2[4 * kk + 3], dv + kk * 128, 1);
        wg_commit();
        bar_arrive(1 + (w ^ 1), 256);
        wg_wait<0>();
        fence_regs(o);
        A_RELEASE(sV);
      }
      TSA(item, 4);
      l0 += __shfl_xor_sync(0xffffffffu, l0, 1); l1 += __shfl_xor_sync(0xffffffffu, l1, 1);
      l0 += __shfl_xor_sync(0xffffffffu, l0, 2); l1 += __shfl_xor_sync(0xffffffffu, l1, 2);
      const float i0 = 1.f / l0, i1 = 1.f / l1;
      bf16* orow = g_o + (size_t)(qtile * 128 + w * 64 + warp * 16 + (lane >> 2)) * HD_ + head * DH_ + (lane & 3) * 8;
#pragma unroll
      for (int g = 0; g < 6; g++) {
        uint32_t u0 = pack_bf16(o[16 * g + 0] * i0, o[16 * g + 1] * i0), u1 = pack_bf16(o[16 * g + 4] * i0, o[16 * g + 5] * i0);
        uint32_t u2 = pack_bf16(o[16 * g + 8] * i0, o[16 * g + 9] * i0), u3 = pack_bf16(o[16 * g + 12] * i0, o[16 * g + 13] * i0);
        quad_transpose(u0, u1, u2, u3, lane);
        *reinterpret_cast<uint4*>(orow + g * 32) = make_uint4(u0, u1, u2, u3);
        uint32_t v0 = pack_bf16(o[16 * g + 2] * i1, o[16 * g + 3] * i1), v1 = pack_bf16(o[16 * g + 6] * i1, o[16 * g + 7] * i1);
        uint32_t v2 = pack_bf16(o[16 * g + 10] * i1, o[16 * g + 11] * i1), v3 = pack_bf16(o[16 * g + 14] * i1, o[16 * g + 15] * i1);
        quad_transpose(v0, v1, v2, v3, lane);
        *reinterpret_cast<uint4*>(orow + (size_t)8 * HD_ + g * 32) = make_uint4(v0, v1, v2, v3);
      }
      SIGNAL();
      TSA(item, 5);
    }
    }
    TS(3, 2);
    const uint32_t st_w = (uint32_t)((warp * 16 + (lane >> 2)) * ST_P + (lane & 3) * 2) * 4;
    const uint32_t st_x = (lane & 8) << 2;
    const int er = (tid & 127) >> 1, eh = tid & 1;
    const uint32_t st_r = (uint32_t)(er * ST_P + (eh ^ ((er >> 1) & 1)) * 8) * 4;
    const uint32_t e_r = (uint32_t)((w * 64 + er) * 160 + eh * 16);
    const uint32_t p_r = par + eh * 32;
#define STAGE10(ACC, BASE)                                                                                             \
    _Pragma("unroll") for (int nb = 0; nb < 10; nb++) {                                                                \
      sts_f2(stg + st_w + ((nb * 32) ^ st_x), ACC(BASE + 4 * nb), ACC(BASE + 4 * nb + 1));                                       \
      sts_f2(stg + st_w + ((nb * 32) ^ st_x) + 8 * ST_P * 4, ACC(BASE + 4 * nb + 2), ACC(BASE + 4 * nb + 3));                    \
    }

    {
      float acc1[96], acc2[64];
      uint32_t p0 = 0, p1 = 0, p2 = 0;
#pragma unroll 1
      for (int kb = 0; kb < 24; kb++) {
        const uint32_t s1 = r.slot; mbar_wait_c(bar_full + 8 * s1, r.phase); r.adv(A_NSLOT);
        const uint32_t s2 = r.slot; mbar_wait_c(bar_full + 8 * s2, r.phase); r.adv(A_NSLOT);
        const uint32_t sa = r.slot; mbar_wait_c(bar_full + 8 * sa, r.phase); r.adv(A_NSLOT);
        const uint64_t da = mkdesc(sb + sa * A_SLOT + w * 8192, 16, 1024);
        const uint64_t d1 = mkdesc(sb + s1 * A_SLOT, 8192, 1024), d2 = mkdesc(sb + s2 * A_SLOT, 8192, 1024);
        wg_fence();
#pragma unroll
        for (int kk = 0; kk < 4; kk++) {
          wgmma_ss_n192<1>(acc1, da + kk * 2, d1 + kk * 128, (kb | kk) != 0);
          wgmma_ss_n128<1>(acc2, da + kk * 2, d2 + kk * 128, (kb | kk) != 0);
        }
        wg_commit();
        if (kb > 0) { wg_wait<1>(); A_RELEASE(p0); A_RELEASE(p1); A_RELEASE(p2); }
        p0 = s1; p1 = s2; p2 = sa;
      }
      wg_wait<0>();
      fence_regs(acc1); fence_regs(acc2);
      A_RELEASE(p2);
      bar_sync(6, 288);
      TS(0, 0);
      const uint32_t stg = sb + (w ? p1 : p0) * A_SLOT;
#define OACC(e) (((e) < 96) ? acc1[(e) < 96 ? (e) : 0] : acc2[(e) >= 96 ? (e) - 96 : 0])
#pragma unroll 1
      for (int i = 0; i < 4; i++) {
        const int d = (o_ks + 1 + i) & 3;
        if (d == 0) { STAGE10(OACC, 0) } else if (d == 1) { STAGE10(OACC, 40) } else if (d == 2) { STAGE10(OACC, 80) } else { STAGE10(OACC, 120) }
        bar_sync(3 + w, 128);
        if (i < 3) {
          uint8_t* dst = reinterpret_cast<uint8_t*>(g_xch + (size_t)((((o_qt * 2 + o_nh) * 4 + d) * 4) + o_ks) * (E_TILE / 2)) + e_r;
#pragma unroll 1
          for (int c = 0; c < 5; c++) {
            float v[8];
            lds8(stg + st_r + c * 64, v);
            stg128(dst + c * 32, pack8(v));
          }
          if (i == 2) SIGNAL();
          bar_sync(3 + w, 128);
        }
      }
      const uint32_t sx = r.slot; mbar_wait_c(bar_full + 8 * sx, r.phase); r.adv(A_NSLOT);
      const uint32_t q0 = r.slot; mbar_wait_c(bar_full + 8 * q0, r.phase); r.adv(A_NSLOT);
      const uint32_t q1 = r.slot; mbar_wait_c(bar_full + 8 * q1, r.phase); r.adv(A_NSLOT);
      const uint32_t q2 = r.slot; mbar_wait_c(bar_full + 8 * q2, r.phase); r.adv(A_NSLOT);
      TS(0, 1);
      float st[6] = {0.f, 0.f, 0.f, 0.f, 0.f, 0.f};
      bf16* dst = g_xa + (size_t)(o_qt * 128 + w * 64 + er) * D_ + o_col + eh * 8;
#pragma unroll 1
      for (int c = 0; c < 5; c++) {
        float v[8], t0[8], t1[8], t2[8];
        lds8(stg + st_r + c * 64, v);
        lds8_bf(sb + q0 * A_SLOT + e_r + c * 32, t0); lds8_bf(sb + q1 * A_SLOT + e_r + c * 32, t1); lds8_bf(sb + q2 * A_SLOT + e_r + c * 32, t2);
#pragma unroll
        for (int e = 0; e < 8; e++) v[e] += (t0[e] + t1[e]) + t2[e];
        lds8_bf(sb + sx * A_SLOT + e_r + c * 32, t0);
        lds8(p_r + P_OGA * 4 + c * 64, t1);
#pragma unroll
        for (int e = 0; e < 8; e++) v[e] = fmaf(t1[e], v[e], t0[e]);
        const uint4 pk = pack8(v);
        stg128(dst + c * 16, pk);
        v[0] = bf_lo(pk.x); v[1] = bf_hi(pk.x); v[2] = bf_lo(pk.y); v[3] = bf_hi(pk.y); v[4] = bf_lo(pk.z); v[5] = bf_hi(pk.z); v[6] = bf_lo(pk.w); v[7] = bf_hi(pk.w);
        lds8(p_r + P_OA * 4 + c * 64, t1);
        lds8(p_r + P_OB * 4 + c * 64, t2);
#pragma unroll
        for (int e = 0; e < 8; e++) {
          const float y = t1[e] * v[e];
          st[0] += v[e]; st[1] = fmaf(v[e], v[e], st[1]); st[2] += y; st[3] = fmaf(t1[e], y, st[3]); st[4] = fmaf(y, y, st[4]); st[5] = fmaf(t2[e], y, st[5]);
        }
      }
#pragma unroll
      for (int i = 0; i < 6; i++) st[i] += __shfl_xor_sync(0xffffffffu, st[i], 1);
      if (eh == 0) {
        float* sp = g_st1 + (size_t)(o_qt * 128 + w * 64 + er) * 8;
        asm volatile("red.global.add.v4.f32 [%0], {%1, %2, %3, %4};" :: "l"(sp), "f"(st[0]), "f"(st[1]), "f"(st[2]), "f"(st[3]) : "memory");
        asm volatile("red.global.add.v2.f32 [%0], {%1, %2};" :: "l"(sp + 4), "f"(st[4]), "f"(st[5]) : "memory");
      }
      SIGNAL();
      bar_sync(5, 256);
      A_RELEASE(p0); A_RELEASE(p1); A_RELEASE(sx); A_RELEASE(q0); A_RELEASE(q1); A_RELEASE(q2);
      TS(0, 2);
    }

    Ring ra{0, 0};
    uint32_t bpar = 0;
    const uint32_t rel_a = mapa(mb_empty + 40, (lane == 0) ? rank : (rank ^ 1));
#define B_NEXT(s_) do { s_ = bs; mbar_wait_c(mb_full + 8 * bs, (bpar >> bs) & 1); bpar ^= 1u << bs; if (++bs == nbs) bs = 0; } while (0)
#define B_RELEASE(s_) do { if (lane == 0) mbar_arrive(mb_empty + 8 * (s_)); } while (0)
#define MA_RELEASE(s_) do { if (lane < 2) mbar_arrive_remote(rel_a + 8 * (s_)); } while (0)
    const int grow = qt * 128 + w * 64 + er;
    float mu = 0.f, rs = 0.f;
#pragma unroll 1
    for (int ph = 0; ph < 4; ph++) {
      float acc[96];
      float (&acc80)[40] = *reinterpret_cast<float(*)[40]>(&acc[0]);
      uint32_t pa = 0, pb = 0, sbq = 0;
      float4 s03 = make_float4(0.f, 0.f, 0.f, 0.f);
      float2 s45 = make_float2(0.f, 0.f);
      const int nkb = ph == 3 ? 24 : 10;
      const uint32_t nbs = ph == 2 ? 4 : 5, bsz = ph == 2 ? 24576 : 20480;
      uint32_t bs = 0;
#pragma unroll 1
      for (int kb = 0; kb < nkb; kb++) {
        if (ph == 2 || !(kb & 1)) B_NEXT(sbq);
        const uint32_t sa = ra.slot; mbar_wait_c(mb_full + 40 + 8 * sa, ra.phase); ra.adv(M_NA);
        if (kb == 0) TXC(ph);
        if (ph == 0) TXC(104 + kb); if (ph == 3) TXC(120 + kb);
        const uint64_t da = mkdesc(sb + M_AOFF + sa * 16384 + w * 8192, 16, 1024);
        if (ph == 2) {
          const uint64_t db = mkdesc(sb + sbq * 24576, 8192, 1024);
          wg_fence();
#pragma unroll
          for (int kk = 0; kk < 4; kk++) wgmma_ss_n192<1>(acc, da + kk * 2, db + kk * 128, (kb | kk) != 0);
          wg_commit();
        } else {
          const uint64_t db = mkdesc(sb + sbq * 20480 + (kb & 1) * 10240, 16, 1024);
          wg_fence();
#pragma unroll
          for (int kk = 0; kk < 4; kk++) wgmma_ss_n80<0>(acc80, da + kk * 2, db + kk * 2, (kb | kk) != 0);
          wg_commit();
        }
        if (kb > 0) { wg_wait<1>(); MA_RELEASE(pa); if (ph == 2 || !(kb & 1)) B_RELEASE(pb); }
        else {
          if (ph == 0) { s03 = __ldcg(reinterpret_cast<const float4*>(g_st1 + (size_t)grow * 8)); s45 = __ldcg(reinterpret_cast<const float2*>(g_st1 + (size_t)grow * 8 + 4)); }
          if (ph == 2) s45 = __ldcg(reinterpret_cast<const float2*>(g_st2 + (size_t)grow * 2));
        }
        pa = sa; pb = sbq;
      }
      wg_wait<0>();
      fence_regs(acc);
      MA_RELEASE(pa);
      bar_sync(5, 256);
      TS(1 + (ph == 3 ? 0 : ph), ph == 3 ? 2 : 0);
      const uint32_t stg = sb + (w ? pb : (pb == 0 ? nbs - 1 : pb - 1)) * bsz;
#define MACC(e) acc[e]
      if (!(ph & 1)) {
        float c0, c1, c2 = 0.f, c3 = 0.f;
        bf16* dst; bool ok = true;
        if (ph == 0) {
          const float4 sc = lds_f4(par + P_SC * 4);
          const float sbb = lds_f(par + (P_SC + 4) * 4);
          mu = s03.x * (1.f / D_);
          rs = rsqrtf(fmaxf(s03.y * (1.f / D_) - mu * mu, 0.f) + LN_EPS);
          const float m2 = (rs * (s03.z - mu * sc.x) + sc.w) * (1.f / D_);
          const float e2 = (rs * rs * (s45.x - 2.f * mu * s03.w + mu * mu * sc.y) + 2.f * rs * (s45.y - mu * sc.z) + sbb) * (1.f / D_);
          c2 = rsqrtf(fmaxf(e2 - m2 * m2, 0.f) + LN_EPS);
          c0 = c2 * rs; c1 = -c0 * mu; c3 = -c2 * m2;
          const int grp = js >> 1;
          const int sh = (grp & 2 ? 2 : 1) * (grp & 1 ? -1 : 1);
          ok = (unsigned)(grow + sh) < (unsigned)S_;
          dst = g_us + (size_t)(ok ? grow + sh : (sh > 0 ? grow + sh - S_ : grow + sh + S_)) * D_ + js * 80 + eh * 8;
        } else {
          const float m = s45.x * (1.f / D_);
          c0 = rsqrtf(fmaxf(s45.y * (1.f / D_) - m * m, 0.f) + LN_EPS);
          c1 = -c0 * m;
          dst = g_g + (size_t)grow * F_ + js * 192 + eh * 8;
        }
        const int npass = ph == 0 ? 1 : 3, nch = ph == 0 ? 5 : 4;
#pragma unroll 1
        for (int ps = 0; ps < npass; ps++) {
          if (ps == 0) { STAGE10(MACC, 0) }
          else {
            bar_sync(3 + w, 128);
            if (ps == 1) { STAGE10(MACC, 32) } else { STAGE10(MACC, 56) }
          }
          bar_sync(3 + w, 128);
          const uint32_t cofs = ps == 2 ? 64 : 0;
          const uint32_t pp = p_r + (ph == 0 ? P_VA : P_CS3 + ps * 64) * 4;
#pragma unroll 1
          for (int c = 0; c < nch; c++) {
            float v[8], t[8];
            lds8(stg + st_r + cofs + c * 64, v);
            lds8(pp + c * 64, t);
#pragma unroll
            for (int e = 0; e < 8; e++) v[e] = fmaf(c0, v[e], c1 * t[e]);
            if (ph == 0) {
              lds8(pp + 320 + c * 64, t);
#pragma unroll
              for (int e = 0; e < 8; e++) v[e] = fmaf(c2, t[e], v[e]);
              lds8(pp + 640 + c * 64, t);
#pragma unroll
              for (int e = 0; e < 8; e++) v[e] = fmaf(c3, t[e], v[e]);
            }
#pragma unroll
            for (int e = 0; e < 8; e++) v[e] = gelu_tanh(v[e]);
            const uint4 pk = pack8(v);
            stg128(dst + ps * 64 + c * 16, ok ? pk : make_uint4(0, 0, 0, 0));
          }
        }
        SIGNAL();
        bar_sync(5, 256);
        B_RELEASE(pb);
      } else {
        STAGE10(MACC, 0)
        uint32_t e1, e2;
        B_NEXT(e1);
        e2 = e1;
        if (ph == 3) B_NEXT(e2);
        bar_sync(3 + w, 128);
        TXC(4 + (ph >> 1));
        float s1 = 0.f, s2 = 0.f;
        bf16* dst = (ph == 1 ? g_x1 : out) + (size_t)grow * D_ + js * 80 + eh * 8;
#pragma unroll 1
        for (int c = 0; c < 5; c++) {
          float v[8], xa[8], t[8];
          lds8(stg + st_r + c * 64, v);
          lds8_bf(sb + e1 * 20480 + e_r + c * 32, xa);
          if (ph == 1) {
            lds8(p_r + P_A2 * 4 + c * 64, t);
#pragma unroll
            for (int e = 0; e < 8; e++) v[e] = fmaf(t[e] * rs, xa[e] - mu, v[e]);
            lds8(p_r + P_B2 * 4 + c * 64, t);
#pragma unroll
            for (int e = 0; e < 8; e++) v[e] += t[e];
          } else {
            lds8_bf(sb + e2 * 20480 + e_r + c * 32, t);
#pragma unroll
            for (int e = 0; e < 8; e++) v[e] += t[e];
            lds8(p_r + P_GB * 4 + c * 64, t);
#pragma unroll
            for (int e = 0; e < 8; e++) v[e] = fmaf(t[e], v[e], xa[e]);
          }
          const uint4 pk = pack8(v);
          stg128(dst + c * 16, pk);
          v[0] = bf_lo(pk.x); v[1] = bf_hi(pk.x); v[2] = bf_lo(pk.y); v[3] = bf_hi(pk.y); v[4] = bf_lo(pk.z); v[5] = bf_hi(pk.z); v[6] = bf_lo(pk.w); v[7] = bf_hi(pk.w);
#pragma unroll
          for (int e = 0; e < 8; e++) { s1 += v[e]; s2 = fmaf(v[e], v[e], s2); }
        }
        if (ph == 1) {
          s1 += __shfl_xor_sync(0xffffffffu, s1, 1); s2 += __shfl_xor_sync(0xffffffffu, s2, 1);
          if (eh == 0) asm volatile("red.global.add.v2.f32 [%0], {%1, %2};" :: "l"(g_st2 + (size_t)grow * 2), "f"(s1), "f"(s2) : "memory");
          SIGNAL();
          bar_sync(5, 256);
          B_RELEASE(pb); B_RELEASE(e1);
        }
      }
      TS(1 + (ph == 3 ? 0 : ph), ph == 3 ? 3 : 1);
    }
    if ((threadIdx.x & 127) == 0) TL_END(2);
    cluster_sync();
  }
}

typedef CUresult (*EncFn)(CUtensorMap*, CUtensorMapDataType, cuuint32_t, void*, const cuuint64_t*, const cuuint64_t*,
                          const cuuint32_t*, const cuuint32_t*, CUtensorMapInterleave, CUtensorMapSwizzle,
                          CUtensorMapL2promotion, CUtensorMapFloatOOBfill);
static EncFn g_enc = nullptr;

static CUtensorMap map2d(const void* p, uint64_t rows, uint64_t cols, uint32_t box_rows) {
  CUtensorMap m;
  cuuint64_t gd[2] = {cols, rows}; cuuint64_t gs[1] = {cols * 2};
  cuuint32_t bx[2] = {64, box_rows}; cuuint32_t es[2] = {1, 1};
  g_enc(&m, CU_TENSOR_MAP_DATA_TYPE_BFLOAT16, 2, const_cast<void*>(p), gd, gs, bx, es, CU_TENSOR_MAP_INTERLEAVE_NONE,
        CU_TENSOR_MAP_SWIZZLE_128B, CU_TENSOR_MAP_L2_PROMOTION_L2_256B, CU_TENSOR_MAP_FLOAT_OOB_FILL_NONE);
  return m;
}
static CUtensorMap map3d(const void* p, uint64_t rows, uint64_t cols, uint32_t box_rows, uint32_t nblk) {
  CUtensorMap m;
  cuuint64_t gd[3] = {64, rows, cols / 64}; cuuint64_t gs[2] = {cols * 2, 128};
  cuuint32_t bx[3] = {64, box_rows, nblk}; cuuint32_t es[3] = {1, 1, 1};
  g_enc(&m, CU_TENSOR_MAP_DATA_TYPE_BFLOAT16, 3, const_cast<void*>(p), gd, gs, bx, es, CU_TENSOR_MAP_INTERLEAVE_NONE,
        CU_TENSOR_MAP_SWIZZLE_128B, CU_TENSOR_MAP_L2_PROMOTION_L2_256B, CU_TENSOR_MAP_FLOAT_OOB_FILL_NONE);
  return m;
}

static CUtensorMap map_e(const void* p) {
  CUtensorMap m;
  cuuint64_t gd[2] = {D_, S_}; cuuint64_t gs[1] = {D_ * 2};
  cuuint32_t bx[2] = {80, 128}; cuuint32_t es[2] = {1, 1};
  g_enc(&m, CU_TENSOR_MAP_DATA_TYPE_BFLOAT16, 2, const_cast<void*>(p), gd, gs, bx, es, CU_TENSOR_MAP_INTERLEAVE_NONE,
        CU_TENSOR_MAP_SWIZZLE_NONE, CU_TENSOR_MAP_L2_PROMOTION_L2_256B, CU_TENSOR_MAP_FLOAT_OOB_FILL_NONE);
  return m;
}

template <typename... KArgs, typename... Args>
static void launch(void (*kern)(KArgs...), dim3 grid, dim3 block, int smem, bool pdl, Args... args) {
  cudaLaunchConfig_t cfg = {};
  cfg.gridDim = grid; cfg.blockDim = block; cfg.dynamicSmemBytes = smem; cfg.stream = cudaStreamPerThread;
  cudaLaunchAttribute at[1];
  at[0].id = cudaLaunchAttributeProgrammaticStreamSerialization;
  at[0].val.programmaticStreamSerializationAllowed = 1;
  cfg.attrs = at; cfg.numAttrs = pdl ? 1 : 0;
  cudaLaunchKernelEx(&cfg, kern, KArgs(args)...);
}

extern "C" void kernel_launch(void* const* d_in, const int* in_sizes, int n_in, void* d_out, int out_size) {
  const bf16* x = (const bf16*)d_in[0];
  const bf16* kc = (const bf16*)d_in[1];
  const bf16* vc = (const bf16*)d_in[2];
  const bf16* wq = (const bf16*)d_in[3];
  const bf16* wo = (const bf16*)d_in[4];
  const bf16* w1 = (const bf16*)d_in[6];
  const bf16* w2 = (const bf16*)d_in[7];
  const bf16* w3 = (const bf16*)d_in[8];
  const bf16* w4 = (const bf16*)d_in[9];
  const bf16* c = (const bf16*)d_in[10];
  const bf16* wmod = (const bf16*)d_in[11];
  bf16* out = (bf16*)d_out;

  static void *p_h, *p_o, *p_xa, *p_us, *p_x1, *p_g, *p_w1t, *p_w2t, *p_w4t;
  if (!g_enc) {
    void* fn = nullptr; cudaDriverEntryPointQueryResult qr;
    cudaGetDriverEntryPoint("cuTensorMapEncodeTiled", &fn, cudaEnableDefault, &qr);
    g_enc = (EncFn)fn;
    cudaGetSymbolAddress(&p_h, g_h); cudaGetSymbolAddress(&p_o, g_o); cudaGetSymbolAddress(&p_xa, g_xa);
    cudaGetSymbolAddress(&p_us, g_us); cudaGetSymbolAddress(&p_x1, g_x1); cudaGetSymbolAddress(&p_g, g_g);
    cudaGetSymbolAddress(&p_w1t, g_w1t); cudaGetSymbolAddress(&p_w2t, g_w2t); cudaGetSymbolAddress(&p_w4t, g_w4t);
    cudaFuncSetAttribute(fused_kernel, cudaFuncAttributeMaxDynamicSharedMemorySize, T_SMEM);
  }
  Maps tm;
  tm.h = map2d(p_h, S_, D_, 128);
  tm.wq = map3d(wq, D_, HD_, 64, 3);
  tm.k = map3d(kc, (uint64_t)H_ * S_, DH_, 64, 3);
  tm.v = map3d(vc, (uint64_t)H_ * S_, DH_, 64, 3);
  tm.o = map2d(p_o, S_, HD_, 128);
  tm.wo3 = map3d(wo, HD_, D_, 64, 3);
  tm.wo2 = map3d(wo, HD_, D_, 64, 2);
  tm.xa = map2d(p_xa, S_, D_, 64);
  tm.w1t = map3d(p_w1t, D_, D_, 80, 2);
  tm.us = map2d(p_us, S_, D_, 64);
  tm.w2t = map3d(p_w2t, D_, D_, 80, 2);
  tm.x1 = map2d(p_x1, S_, D_, 64);
  tm.w3 = map3d(w3, D_, F_, 64, 3);
  tm.g = map2d(p_g, S_, F_, 64);
  tm.w4t = map3d(p_w4t, D_, F_, 80, 2);
  tm.ex = map_e(x); tm.exa = map_e(p_xa); tm.ex1 = map_e(p_x1);
  PfList pf;
  pf.p[0] = (const uint8_t*)wo; pf.p[1] = (const uint8_t*)w3; pf.p[2] = (const uint8_t*)p_w4t;
  pf.p[3] = (const uint8_t*)x; pf.p[4] = (const uint8_t*)p_w1t; pf.p[5] = (const uint8_t*)p_w2t;

  launch(mod_kernel, dim3(120), dim3(256), 0, false, c, wmod);
  launch(ln1_kernel, dim3(256), dim3(256), 0, true, x);
  launch(fused_kernel, dim3(128), dim3(384), T_SMEM, true, tm, pf, PrepW{w1, w2, w3, w4}, x, out);
}
```

```cpp
#include <cuda_runtime.h>
#include <cuda.h>
#include <cuda_bf16.h>
#include <stdint.h>

typedef __nv_bfloat16 bf16;

constexpr int S_  = 2048;
constexpr int D_  = 640;
constexpr int H_  = 32;
constexpr int DH_ = 192;
constexpr int HD_ = H_ * DH_;
constexpr int F_  = 1536;
constexpr float LN_EPS = 1e-5f;

__device__ __forceinline__ uint32_t smem_u32(const void* p) { return (uint32_t)__cvta_generic_to_shared(p); }
__device__ __forceinline__ void mbar_init(uint32_t a, uint32_t c) { asm volatile("mbarrier.init.shared::cta.b64 [%0], %1;" :: "r"(a), "r"(c) : "memory"); }
__device__ __forceinline__ void mbar_expect(uint32_t a, uint32_t b) { asm volatile("mbarrier.arrive.expect_tx.shared::cta.b64 _, [%0], %1;" :: "r"(a), "r"(b) : "memory"); }
__device__ __forceinline__ void mbar_arrive(uint32_t a) { asm volatile("mbarrier.arrive.shared::cta.b64 _, [%0];" :: "r"(a) : "memory"); }
__device__ __forceinline__ void mbar_arrive_remote(uint32_t ra) { asm volatile("mbarrier.arrive.shared::cluster.b64 _, [%0];" :: "r"(ra) : "memory"); }
__device__ __forceinline__ uint32_t mapa(uint32_t a, uint32_t cta) { uint32_t r; asm volatile("mapa.shared::cluster.u32 %0, %1, %2;" : "=r"(r) : "r"(a), "r"(cta)); return r; }
__device__ __forceinline__ uint32_t mbar_try(uint32_t a, uint32_t ph) {
  uint32_t ok;
  asm volatile("{\n.reg .pred p;\nmbarrier.test_wait.parity.shared::cta.b64 p, [%1], %2;\nselp.u32 %0, 1, 0, p;\n}\n" : "=r"(ok) : "r"(a), "r"(ph) : "memory");
  return ok;
}
__device__ __forceinline__ void mbar_wait(uint32_t a, uint32_t ph) {
  asm volatile(
      "{\n.reg .pred p;\n.reg .u32 n;\n"
      "mov.u32 n, 0;\n"
      "SPIN:\n"
      "mbarrier.try_wait.parity.shared::cta.b64 p, [%0], %1;\n"
      "@p bra DONE;\n"
      "add.u32 n, n, 1;\n"
      "setp.le.u32 p, n, 16777216;\n"
      "@p bra SPIN;\n"
      "trap;\n"
      "DONE:\n}\n" :: "r"(a), "r"(ph) : "memory");
}
#define ELECT_ "{\n.reg .pred p;\nelect.sync _|p, 0xffffffff;\n@p "
__device__ __forceinline__ void mbar_expect_e(uint32_t a, uint32_t b) { asm volatile(ELECT_ "mbarrier.arrive.expect_tx.shared::cta.b64 _, [%0], %1;\n}\n" :: "r"(a), "r"(b) : "memory"); }
__device__ __forceinline__ void tma2d(uint32_t dst, const CUtensorMap* m, uint32_t bar, int c0, int c1) {
  asm volatile(ELECT_ "cp.async.bulk.tensor.2d.shared::cluster.global.mbarrier::complete_tx::bytes [%0], [%1, {%3, %4}], [%2];\n}\n"
               :: "r"(dst), "l"(m), "r"(bar), "r"(c0), "r"(c1) : "memory");
}
__device__ __forceinline__ void tma2d_mc(uint32_t dst, const CUtensorMap* m, uint32_t bar, int c0, int c1, uint16_t mask) {
  asm volatile(ELECT_ "cp.async.bulk.tensor.2d.shared::cluster.global.mbarrier::complete_tx::bytes.multicast::cluster [%0], [%1, {%3, %4}], [%2], %5;\n}\n"
               :: "r"(dst), "l"(m), "r"(bar), "r"(c0), "r"(c1), "h"(mask) : "memory");
}
__device__ __forceinline__ void tma3d(uint32_t dst, const CUtensorMap* m, uint32_t bar, int c0, int c1, int c2) {
  asm volatile(ELECT_ "cp.async.bulk.tensor.3d.shared::cluster.global.mbarrier::complete_tx::bytes [%0], [%1, {%3, %4, %5}], [%2];\n}\n"
               :: "r"(dst), "l"(m), "r"(bar), "r"(c0), "r"(c1), "r"(c2) : "memory");
}
__device__ __forceinline__ void tma3d_mc(uint32_t dst, const CUtensorMap* m, uint32_t bar, int c0, int c1, int c2, uint16_t mask) {
  asm volatile(ELECT_ "cp.async.bulk.tensor.3d.shared::cluster.global.mbarrier::complete_tx::bytes.multicast::cluster [%0], [%1, {%3, %4, %5}], [%2], %6;\n}\n"
               :: "r"(dst), "l"(m), "r"(bar), "r"(c0), "r"(c1), "r"(c2), "h"(mask) : "memory");
}
__device__ __forceinline__ void tma3d_mc_hint(uint32_t dst, const CUtensorMap* m, uint32_t bar, int c0, int c1, int c2, uint16_t mask, uint64_t pol) {
  asm volatile(ELECT_ "cp.async.bulk.tensor.3d.shared::cluster.global.mbarrier::complete_tx::bytes.multicast::cluster.L2::cache_hint [%0], [%1, {%3, %4, %5}], [%2], %6, %7;\n}\n"
               :: "r"(dst), "l"(m), "r"(bar), "r"(c0), "r"(c1), "r"(c2), "h"(mask), "l"(pol) : "memory");
}
__device__ __forceinline__ void bulk_load(uint32_t dst, const void* src, uint32_t bytes, uint32_t bar) {
  asm volatile(ELECT_ "cp.async.bulk.shared::cluster.global.mbarrier::complete_tx::bytes [%0], [%1], %2, [%3];\n}\n"
               :: "r"(dst), "l"(src), "r"(bytes), "r"(bar) : "memory");
}
__device__ __forceinline__ void l2_prefetch16k(const void* p) { asm volatile(ELECT_ "cp.async.bulk.prefetch.L2.global [%0], 16384;\n}\n" :: "l"(p) : "memory"); }
__device__ __forceinline__ void l2_prefetch_t2d(const CUtensorMap* m, int c0, int c1) {
  asm volatile(ELECT_ "cp.async.bulk.prefetch.tensor.2d.L2.global [%0, {%1, %2}];\n}\n" :: "l"(m), "r"(c0), "r"(c1) : "memory");
}
__device__ __forceinline__ void stg128(void* p, uint4 v) {
  asm volatile("st.global.v4.u32 [%0], {%1, %2, %3, %4};" :: "l"(p), "r"(v.x), "r"(v.y), "r"(v.z), "r"(v.w) : "memory");
}
__device__ __forceinline__ void prefetch_tmap(const CUtensorMap* m) { asm volatile("prefetch.tensormap [%0];" :: "l"(m) : "memory"); }
__device__ __forceinline__ void wg_fence() { asm volatile("wgmma.fence.sync.aligned;" ::: "memory"); }
__device__ __forceinline__ void wg_commit() { asm volatile("wgmma.commit_group.sync.aligned;" ::: "memory"); }
template <int N> __device__ __forceinline__ void wg_wait() { asm volatile("wgmma.wait_group.sync.aligned %0;" :: "n"(N) : "memory"); }
template <int N> __device__ __forceinline__ void fence_regs(float (&r)[N]) {
#pragma unroll
  for (int i = 0; i < N; i++) asm volatile("" : "+f"(r[i]) :: "memory");
}
template <int N> __device__ __forceinline__ void fence_regs(uint32_t (&r)[N]) {
#pragma unroll
  for (int i = 0; i < N; i++) asm volatile("" : "+r"(r[i]) :: "memory");
}
__device__ __forceinline__ uint64_t mkdesc(uint32_t addr, uint32_t lbo, uint32_t sbo) {
  return (uint64_t)((addr & 0x3FFFF) >> 4) | ((uint64_t)(lbo >> 4) << 16) | ((uint64_t)(sbo >> 4) << 32) | (1ull << 62);
}
__device__ __forceinline__ void bar_sync(int id, int n) { asm volatile("bar.sync %0, %1;" :: "r"(id), "r"(n) : "memory"); }
__device__ __forceinline__ void bar_arrive(int id, int n) { asm volatile("bar.arrive %0, %1;" :: "r"(id), "r"(n) : "memory"); }
__device__ __forceinline__ void cluster_sync() { asm volatile("barrier.cluster.arrive.aligned;\nbarrier.cluster.wait.aligned;" ::: "memory"); }
__device__ __forceinline__ void pdl_wait() { asm volatile("griddepcontrol.wait;" ::: "memory"); }
__device__ __forceinline__ void pdl_launch() { asm volatile("griddepcontrol.launch_dependents;" ::: "memory"); }
__device__ __forceinline__ float ex2(float x) { float y; asm("ex2.approx.ftz.f32 %0, %1;" : "=f"(y) : "f"(x)); return y; }
__device__ __forceinline__ uint32_t pack_bf16(float lo, float hi) { uint32_t r; asm("cvt.rn.bf16x2.f32 %0, %1, %2;" : "=r"(r) : "f"(hi), "f"(lo)); return r; }
__device__ __forceinline__ float bf_lo(uint32_t u) { return __uint_as_float(u << 16); }
__device__ __forceinline__ float bf_hi(uint32_t u) { return __uint_as_float(u & 0xffff0000u); }
__device__ __forceinline__ float bf_round(float x) { return __bfloat162float(__float2bfloat16_rn(x)); }
__device__ __forceinline__ float tanh_fast(float x) { float y; asm("tanh.approx.f32 %0, %1;" : "=f"(y) : "f"(x)); return y; }
__device__ __forceinline__ float gelu_tanh(float x) {
  float u = x * (0.7978845608028654f + 0.035677408136300125f * x * x);
  float hx = 0.5f * x;
  return fmaf(hx, tanh_fast(u), hx);
}
__device__ __forceinline__ float warp_sum(float v) {
#pragma unroll
  for (int o = 16; o > 0; o >>= 1) v += __shfl_xor_sync(0xffffffffu, v, o);
  return v;
}
__device__ __forceinline__ void quad_transpose(uint32_t& v0, uint32_t& v1, uint32_t& v2, uint32_t& v3, int lane) {
  const bool b0 = lane & 1, b1 = lane & 2;
  uint32_t s0 = b0 ? v0 : v1, s1 = b0 ? v2 : v3;
  s0 = __shfl_xor_sync(0xffffffffu, s0, 1); s1 = __shfl_xor_sync(0xffffffffu, s1, 1);
  if (b0) { v0 = s0; v2 = s1; } else { v1 = s0; v3 = s1; }
  uint32_t t0 = b1 ? v0 : v2, t1 = b1 ? v1 : v3;
  t0 = __shfl_xor_sync(0xffffffffu, t0, 2); t1 = __shfl_xor_sync(0xffffffffu, t1, 2);
  if (b1) { v0 = t0; v1 = t1; } else { v2 = t0; v3 = t1; }
}

#define TX(i)
#define TXC(i)
#define TSA(item, i)
#define TL_ENTRY(k)
#define TL_WAITED(k)
#define TL_END(k)
#define TS(item, i)
template<int TB> __device__ __forceinline__ void wgmma_rs_n64(float (&d)[32], uint32_t a0, uint32_t a1, uint32_t a2, uint32_t a3, uint64_t db, int scale_d) {
  asm volatile("{\n.reg .pred p;\nsetp.ne.b32 p, %37, 0;\n"
    "wgmma.mma_async.sync.aligned.m64n64k16.f32.bf16.bf16 {%0, %1, %2, %3, %4, %5, %6, %7, %8, %9, %10, %11, %12, %13, %14, %15, %16, %17, %18, %19, %20, %21, %22, %23, %24, %25, %26, %27, %28, %29, %30, %31}, {%32, %33, %34, %35}, %36, p, 1, 1, %38;\n}\n"
    : "+f"(d[0]), "+f"(d[1]), "+f"(d[2]), "+f"(d[3]), "+f"(d[4]), "+f"(d[5]), "+f"(d[6]), "+f"(d[7]), "+f"(d[8]), "+f"(d[9]), "+f"(d[10]), "+f"(d[11]), "+f"(d[12]), "+f"(d[13]), "+f"(d[14]), "+f"(d[15]), "+f"(d[16]), "+f"(d[17]), "+f"(d[18]), "+f"(d[19]), "+f"(d[20]), "+f"(d[21]), "+f"(d[22]), "+f"(d[23]), "+f"(d[24]), "+f"(d[25]), "+f"(d[26]), "+f"(d[27]), "+f"(d[28]), "+f"(d[29]), "+f"(d[30]), "+f"(d[31])
    : "r"(a0), "r"(a1), "r"(a2), "r"(a3), "l"(db), "r"(scale_d), "n"(TB));
}
template<int TB> __device__ __forceinline__ void wgmma_rs_n192(float (&d)[96], uint32_t a0, uint32_t a1, uint32_t a2, uint32_t a3, uint64_t db, int scale_d) {
  asm volatile("{\n.reg .pred p;\nsetp.ne.b32 p, %101, 0;\n"
    "wgmma.mma_async.sync.aligned.m64n192k16.f32.bf16.bf16 {%0, %1, %2, %3, %4, %5, %6, %7, %8, %9, %10, %11, %12, %13, %14, %15, %16, %17, %18, %19, %20, %21, %22, %23, %24, %25, %26, %27, %28, %29, %30, %31, %32, %33, %34, %35, %36, %37, %38, %39, %40, %41, %42, %43, %44, %45, %46, %47, %48, %49, %50, %51, %52, %53, %54, %55, %56, %57, %58, %59, %60, %61, %62, %63, %64, %65, %66, %67, %68, %69, %70, %71, %72, %73, %74, %75, %76, %77, %78, %79, %80, %81, %82, %83, %84, %85, %86, %87, %88, %89, %90, %91, %92, %93, %94, %95}, {%96, %97, %98, %99}, %100, p, 1, 1, %102;\n}\n"
    : "+f"(d[0]), "+f"(d[1]), "+f"(d[2]), "+f"(d[3]), "+f"(d[4]), "+f"(d[5]), "+f"(d[6]), "+f"(d[7]), "+f"(d[8]), "+f"(d[9]), "+f"(d[10]), "+f"(d[11]), "+f"(d[12]), "+f"(d[13]), "+f"(d[14]), "+f"(d[15]), "+f"(d[16]), "+f"(d[17]), "+f"(d[18]), "+f"(d[19]), "+f"(d[20]), "+f"(d[21]), "+f"(d[22]), "+f"(d[23]), "+f"(d[24]), "+f"(d[25]), "+f"(d[26]), "+f"(d[27]), "+f"(d[28]), "+f"(d[29]), "+f"(d[30]), "+f"(d[31]), "+f"(d[32]), "+f"(d[33]), "+f"(d[34]), "+f"(d[35]), "+f"(d[36]), "+f"(d[37]), "+f"(d[38]), "+f"(d[39]), "+f"(d[40]), "+f"(d[41]), "+f"(d[42]), "+f"(d[43]), "+f"(d[44]), "+f"(d[45]), "+f"(d[46]), "+f"(d[47]), "+f"(d[48]), "+f"(d[49]), "+f"(d[50]), "+f"(d[51]), "+f"(d[52]), "+f"(d[53]), "+f"(d[54]), "+f"(d[55]), "+f"(d[56]), "+f"(d[57]), "+f"(d[58]), "+f"(d[59]), "+f"(d[60]), "+f"(d[61]), "+f"(d[62]), "+f"(d[63]), "+f"(d[64]), "+f"(d[65]), "+f"(d[66]), "+f"(d[67]), "+f"(d[68]), "+f"(d[69]), "+f"(d[70]), "+f"(d[71]), "+f"(d[72]), "+f"(d[73]), "+f"(d[74]), "+f"(d[75]), "+f"(d[76]), "+f"(d[77]), "+f"(d[78]), "+f"(d[79]), "+f"(d[80]), "+f"(d[81]), "+f"(d[82]), "+f"(d[83]), "+f"(d[84]), "+f"(d[85]), "+f"(d[86]), "+f"(d[87]), "+f"(d[88]), "+f"(d[89]), "+f"(d[90]), "+f"(d[91]), "+f"(d[92]), "+f"(d[93]), "+f"(d[94]), "+f"(d[95])
    : "r"(a0), "r"(a1), "r"(a2), "r"(a3), "l"(db), "r"(scale_d), "n"(TB));
}
template<int TB> __device__ __forceinline__ void wgmma_ss_n128(float (&d)[64], uint64_t da, uint64_t db, int scale_d) {
  asm volatile("{\n.reg .pred p;\nsetp.ne.b32 p, %66, 0;\n"
    "wgmma.mma_async.sync.aligned.m64n128k16.f32.bf16.bf16 {%0, %1, %2, %3, %4, %5, %6, %7, %8, %9, %10, %11, %12, %13, %14, %15, %16, %17, %18, %19, %20, %21, %22, %23, %24, %25, %26, %27, %28, %29, %30, %31, %32, %33, %34, %35, %36, %37, %38, %39, %40, %41, %42, %43, %44, %45, %46, %47, %48, %49, %50, %51, %52, %53, %54, %55, %56, %57, %58, %59, %60, %61, %62, %63}, %64, %65, p, 1, 1, 0, %67;\n}\n"
    : "+f"(d[0]), "+f"(d[1]), "+f"(d[2]), "+f"(d[3]), "+f"(d[4]), "+f"(d[5]), "+f"(d[6]), "+f"(d[7]), "+f"(d[8]), "+f"(d[9]), "+f"(d[10]), "+f"(d[11]), "+f"(d[12]), "+f"(d[13]), "+f"(d[14]), "+f"(d[15]), "+f"(d[16]), "+f"(d[17]), "+f"(d[18]), "+f"(d[19]), "+f"(d[20]), "+f"(d[21]), "+f"(d[22]), "+f"(d[23]), "+f"(d[24]), "+f"(d[25]), "+f"(d[26]), "+f"(d[27]), "+f"(d[28]), "+f"(d[29]), "+f"(d[30]), "+f"(d[31]), "+f"(d[32]), "+f"(d[33]), "+f"(d[34]), "+f"(d[35]), "+f"(d[36]), "+f"(d[37]), "+f"(d[38]), "+f"(d[39]), "+f"(d[40]), "+f"(d[41]), "+f"(d[42]), "+f"(d[43]), "+f"(d[44]), "+f"(d[45]), "+f"(d[46]), "+f"(d[47]), "+f"(d[48]), "+f"(d[49]), "+f"(d[50]), "+f"(d[51]), "+f"(d[52]), "+f"(d[53]), "+f"(d[54]), "+f"(d[55]), "+f"(d[56]), "+f"(d[57]), "+f"(d[58]), "+f"(d[59]), "+f"(d[60]), "+f"(d[61]), "+f"(d[62]), "+f"(d[63])
    : "l"(da), "l"(db), "r"(scale_d), "n"(TB));
}
template<int TB> __device__ __forceinline__ void wgmma_ss_n192(float (&d)[96], uint64_t da, uint64_t db, int scale_d) {
  asm volatile("{\n.reg .pred p;\nsetp.ne.b32 p, %98, 0;\n"
    "wgmma.mma_async.sync.aligned.m64n192k16.f32.bf16.bf16 {%0, %1, %2, %3, %4, %5, %6, %7, %8, %9, %10, %11, %12, %13, %14, %15, %16, %17, %18, %19, %20, %21, %22, %23, %24, %25, %26, %27, %28, %29, %30, %31, %32, %33, %34, %35, %36, %37, %38, %39, %40, %41, %42, %43, %44, %45, %46, %47, %48, %49, %50, %51, %52, %53, %54, %55, %56, %57, %58, %59, %60, %61, %62, %63, %64, %65, %66, %67, %68, %69, %70, %71, %72, %73, %74, %75, %76, %77, %78, %79, %80, %81, %82, %83, %84, %85, %86, %87, %88, %89, %90, %91, %92, %93, %94, %95}, %96, %97, p, 1, 1, 0, %99;\n}\n"
    : "+f"(d[0]), "+f"(d[1]), "+f"(d[2]), "+f"(d[3]), "+f"(d[4]), "+f"(d[5]), "+f"(d[6]), "+f"(d[7]), "+f"(d[8]), "+f"(d[9]), "+f"(d[10]), "+f"(d[11]), "+f"(d[12]), "+f"(d[13]), "+f"(d[14]), "+f"(d[15]), "+f"(d[16]), "+f"(d[17]), "+f"(d[18]), "+f"(d[19]), "+f"(d[20]), "+f"(d[21]), "+f"(d[22]), "+f"(d[23]), "+f"(d[24]), "+f"(d[25]), "+f"(d[26]), "+f"(d[27]), "+f"(d[28]), "+f"(d[29]), "+f"(d[30]), "+f"(d[31]), "+f"(d[32]), "+f"(d[33]), "+f"(d[34]), "+f"(d[35]), "+f"(d[36]), "+f"(d[37]), "+f"(d[38]), "+f"(d[39]), "+f"(d[40]), "+f"(d[41]), "+f"(d[42]), "+f"(d[43]), "+f"(d[44]), "+f"(d[45]), "+f"(d[46]), "+f"(d[47]), "+f"(d[48]), "+f"(d[49]), "+f"(d[50]), "+f"(d[51]), "+f"(d[52]), "+f"(d[53]), "+f"(d[54]), "+f"(d[55]), "+f"(d[56]), "+f"(d[57]), "+f"(d[58]), "+f"(d[59]), "+f"(d[60]), "+f"(d[61]), "+f"(d[62]), "+f"(d[63]), "+f"(d[64]), "+f"(d[65]), "+f"(d[66]), "+f"(d[67]), "+f"(d[68]), "+f"(d[69]), "+f"(d[70]), "+f"(d[71]), "+f"(d[72]), "+f"(d[73]), "+f"(d[74]), "+f"(d[75]), "+f"(d[76]), "+f"(d[77]), "+f"(d[78]), "+f"(d[79]), "+f"(d[80]), "+f"(d[81]), "+f"(d[82]), "+f"(d[83]), "+f"(d[84]), "+f"(d[85]), "+f"(d[86]), "+f"(d[87]), "+f"(d[88]), "+f"(d[89]), "+f"(d[90]), "+f"(d[91]), "+f"(d[92]), "+f"(d[93]), "+f"(d[94]), "+f"(d[95])
    : "l"(da), "l"(db), "r"(scale_d), "n"(TB));
}
template<int TB> __device__ __forceinline__ void wgmma_ss_n80(float (&d)[40], uint64_t da, uint64_t db, int scale_d) {
  asm volatile("{\n.reg .pred p;\nsetp.ne.b32 p, %42, 0;\n"
    "wgmma.mma_async.sync.aligned.m64n80k16.f32.bf16.bf16 {%0, %1, %2, %3, %4, %5, %6, %7, %8, %9, %10, %11, %12, %13, %14, %15, %16, %17, %18, %19, %20, %21, %22, %23, %24, %25, %26, %27, %28, %29, %30, %31, %32, %33, %34, %35, %36, %37, %38, %39}, %40, %41, p, 1, 1, 0, %43;\n}\n"
    : "+f"(d[0]), "+f"(d[1]), "+f"(d[2]), "+f"(d[3]), "+f"(d[4]), "+f"(d[5]), "+f"(d[6]), "+f"(d[7]), "+f"(d[8]), "+f"(d[9]), "+f"(d[10]), "+f"(d[11]), "+f"(d[12]), "+f"(d[13]), "+f"(d[14]), "+f"(d[15]), "+f"(d[16]), "+f"(d[17]), "+f"(d[18]), "+f"(d[19]), "+f"(d[20]), "+f"(d[21]), "+f"(d[22]), "+f"(d[23]), "+f"(d[24]), "+f"(d[25]), "+f"(d[26]), "+f"(d[27]), "+f"(d[28]), "+f"(d[29]), "+f"(d[30]), "+f"(d[31]), "+f"(d[32]), "+f"(d[33]), "+f"(d[34]), "+f"(d[35]), "+f"(d[36]), "+f"(d[37]), "+f"(d[38]), "+f"(d[39])
    : "l"(da), "l"(db), "r"(scale_d), "n"(TB));
}

__device__ float g_mod[6 * D_];
__device__ __align__(1024) bf16 g_h[S_ * D_];
__device__ __align__(1024) bf16 g_o[S_ * HD_];
__device__ __align__(1024) bf16 g_xch[16 * 2 * 4 * 4 * 128 * 80];
__device__ __align__(1024) bf16 g_w1t[D_ * D_];
__device__ __align__(1024) bf16 g_w2t[D_ * D_];
__device__ __align__(1024) bf16 g_w4t[D_ * F_];
__device__ __align__(32) float g_st1[S_ * 8];
__device__ __align__(32) float g_st2[S_ * 2];
__device__ __align__(32) float g_vec[3 * D_ + F_ + 8];
__device__ unsigned g_flag[1024];
enum { F_XCH = 0, F_XA = 256, F_US = 272, F_X1 = 288, F_G = 304, F_PREP = 320, F_O = 512 };
__device__ __align__(1024) bf16 g_xa[S_ * D_];
__device__ __align__(1024) bf16 g_us[(S_ + 4) * D_];
__device__ __align__(1024) bf16 g_x1[S_ * D_];
__device__ __align__(1024) bf16 g_g[S_ * F_];

__global__ void __launch_bounds__(256) mod_kernel(const bf16* __restrict__ c, const bf16* __restrict__ w_mod) {
  TL_ENTRY(0);
  pdl_launch();
  __shared__ float red[8][32];
  if (blockIdx.x < 14) { const int i = blockIdx.x * 256 + threadIdx.x; if (i < 3 * D_ + F_) g_vec[i] = 0.f; }
  else if (blockIdx.x < 18) g_flag[(blockIdx.x - 14) * 256 + threadIdx.x] = 0u;
  const int t = threadIdx.x, cg = t & 3, r0 = t >> 2;
  const int col0 = blockIdx.x * 32 + cg * 8;
  uint4 w[10];
#pragma unroll
  for (int i = 0; i < 10; i++) w[i] = __ldg(reinterpret_cast<const uint4*>(w_mod + (size_t)(r0 + 64 * i) * (6 * D_) + col0));
  float acc[8];
#pragma unroll
  for (int j = 0; j < 8; j++) acc[j] = 0.f;
#pragma unroll
  for (int i = 0; i < 10; i++) {
    float cv = __bfloat162float(c[r0 + 64 * i]);
    float s = bf_round(cv / (1.f + __expf(-cv)));
    acc[0] = fmaf(s, bf_lo(w[i].x), acc[0]); acc[1] = fmaf(s, bf_hi(w[i].x), acc[1]);
    acc[2] = fmaf(s, bf_lo(w[i].y), acc[2]); acc[3] = fmaf(s, bf_hi(w[i].y), acc[3]);
    acc[4] = fmaf(s, bf_lo(w[i].z), acc[4]); acc[5] = fmaf(s, bf_hi(w[i].z), acc[5]);
    acc[6] = fmaf(s, bf_lo(w[i].w), acc[6]); acc[7] = fmaf(s, bf_hi(w[i].w), acc[7]);
  }
#pragma unroll
  for (int j = 0; j < 8; j++) {
    acc[j] += __shfl_xor_sync(0xffffffffu, acc[j], 4);
    acc[j] += __shfl_xor_sync(0xffffffffu, acc[j], 8);
    acc[j] += __shfl_xor_sync(0xffffffffu, acc[j], 16);
  }
  if ((t & 31) < 4) {
#pragma unroll
    for (int j = 0; j < 8; j++) red[t >> 5][cg * 8 + j] = acc[j];
  }
  __syncthreads();
  if (t < 32) {
    float s = 0.f;
#pragma unroll
    for (int w8 = 0; w8 < 8; w8++) s += red[w8][t];
    const int col = blockIdx.x * 32 + t;
    s = bf_round(s);
    const int part = col / D_;
    if (part == 1 || part == 4) s = bf_round(1.f + s);
    g_mod[col] = s;
    if (t == 0) TL_END(0);
  }
}

__device__ __forceinline__ void row_stats(const float (&v)[20], float& mean, float& rstd) {
  float s = 0.f;
#pragma unroll
  for (int i = 0; i < 20; i++) s += v[i];
  mean = warp_sum(s) * (1.f / D_);
  float q = 0.f;
#pragma unroll
  for (int i = 0; i < 20; i++) { float d = v[i] - mean; q = fmaf(d, d, q); }
  rstd = rsqrtf(warp_sum(q) * (1.f / D_) + LN_EPS);
}
__device__ __forceinline__ void load_row_bf16(const bf16* p, int lane, float (&v)[20]) {
#pragma unroll
  for (int i = 0; i < 5; i++) {
    uint2 u = *reinterpret_cast<const uint2*>(p + (lane + 32 * i) * 4);
    v[4 * i] = bf_lo(u.x); v[4 * i + 1] = bf_hi(u.x); v[4 * i + 2] = bf_lo(u.y); v[4 * i + 3] = bf_hi(u.y);
  }
}
__device__ __forceinline__ void store_row_bf16(bf16* p, int lane, const float (&v)[20]) {
#pragma unroll
  for (int i = 0; i < 5; i++) {
    uint2 u; u.x = pack_bf16(v[4 * i], v[4 * i + 1]); u.y = pack_bf16(v[4 * i + 2], v[4 * i + 3]);
    *reinterpret_cast<uint2*>(p + (lane + 32 * i) * 4) = u;
  }
}
__device__ __forceinline__ void load_row_f32(const float* p, int lane, float (&v)[20]) {
#pragma unroll
  for (int i = 0; i < 5; i++) {
    float4 u = *reinterpret_cast<const float4*>(p + (lane + 32 * i) * 4);
    v[4 * i] = u.x; v[4 * i + 1] = u.y; v[4 * i + 2] = u.z; v[4 * i + 3] = u.w;
  }
}

__global__ void __launch_bounds__(256) ln1_kernel(const bf16* __restrict__ x) {
  TL_ENTRY(1);
  pdl_launch();
  const int lane = threadIdx.x & 31, row = blockIdx.x * 8 + (threadIdx.x >> 5);
  float v[20];
  load_row_bf16(x + (size_t)row * D_, lane, v);
  float mean, rstd;
  row_stats(v, mean, rstd);
  if (lane < 8) g_st1[row * 8 + lane] = 0.f;
  if (lane < 2) g_st2[row * 2 + lane] = 0.f;
  pdl_wait();
  if (threadIdx.x == 0) TL_WAITED(1);
  float sa[20], ca[20];
  load_row_f32(g_mod, lane, sa);
  load_row_f32(g_mod + D_, lane, ca);
#pragma unroll
  for (int i = 0; i < 20; i++) v[i] = fmaf((v[i] - mean) * rstd, ca[i], sa[i]);
  store_row_bf16(g_h + (size_t)row * D_, lane, v);
  if (threadIdx.x == 0) TL_END(1);
}

constexpr int PREP_JOBS = 200 + 200 + 480 + 480;
struct PrepW { const bf16 *w1, *w2, *w3, *w4; };
__device__ __forceinline__ void prep_warp(const PrepW& pw, bf16 (*tile)[72], int lane) {
#pragma unroll 1
  for (int job = blockIdx.x; job < PREP_JOBS; job += gridDim.x) {
    const bf16* src; bf16* dst; int ld = D_, ldd = D_, kt, nt, kind = 1;
    if (job < 200) { src = pw.w1; dst = g_w1t; kt = job / 10; nt = job % 10; kind = 0; }
    else if (job < 400) { src = pw.w2; dst = g_w2t; kt = (job - 200) / 10; nt = (job - 200) % 10; }
    else if (job < 880) { src = pw.w4; dst = g_w4t; ldd = F_; kt = (job - 400) / 10; nt = (job - 400) % 10; }
    else { src = pw.w3; dst = nullptr; ld = F_; kt = (job - 880) / 24; nt = (job - 880) % 24; kind = 2; }
    src += (size_t)(kt * 32 + (lane >> 3)) * ld + nt * 64 + (lane & 7) * 8;
    __syncwarp();
#pragma unroll
    for (int h = 0; h < 2; h++) {
      uint4 v[4];
#pragma unroll
      for (int i = 0; i < 4; i++) v[i] = __ldg(reinterpret_cast<const uint4*>(src + (size_t)(h * 16 + i * 4) * ld));
#pragma unroll
      for (int i = 0; i < 4; i++) *reinterpret_cast<uint4*>(&tile[h * 16 + i * 4 + (lane >> 3)][(lane & 7) * 8]) = v[i];
    }
    __syncwarp();
    const float* pa = g_mod + 4 * D_ + kt * 32;
    const float* pb = g_mod + 3 * D_ + kt * 32;
#pragma unroll 1
    for (int h = 0; h < 2; h++) {
      const int n = lane + 32 * h;
      float sa = 0.f, sb = 0.f, sc = 0.f;
#pragma unroll 1
      for (int c = 0; c < 4; c++) {
        uint32_t u[4];
#pragma unroll
        for (int e = 0; e < 4; e++) {
          const int k = c * 8 + 2 * e;
          float lo = __bfloat162float(tile[k][n]), hi = __bfloat162float(tile[k + 1][n]);
          sc += lo + hi;
          if (kind == 0) {
            const float2 a = __ldcg(reinterpret_cast<const float2*>(pa + k)), b = __ldcg(reinterpret_cast<const float2*>(pb + k));
            sb = fmaf(b.x, lo, fmaf(b.y, hi, sb));
            lo *= a.x; hi *= a.y;
          }
          u[e] = pack_bf16(lo, hi);
          sa += bf_lo(u[e]) + bf_hi(u[e]);
        }
        if (kind != 2) *reinterpret_cast<uint4*>(dst + (size_t)(nt * 64 + n) * ldd + kt * 32 + c * 8) = make_uint4(u[0], u[1], u[2], u[3]);
      }
      if (kind == 0) { atomicAdd(&g_vec[nt * 64 + n], sa); atomicAdd(&g_vec[D_ + nt * 64 + n], sb); atomicAdd(&g_vec[2 * D_ + nt * 64 + n], sc); }
      else if (kind == 2) atomicAdd(&g_vec[3 * D_ + nt * 64 + n], sc);
    }
  }
  __syncwarp();
  if (lane == 0) {
    asm volatile("fence.acq_rel.gpu;" ::: "memory");
    asm volatile("red.relaxed.gpu.global.add.u32 [%0], 1;" :: "l"(g_flag + F_PREP) : "memory");
  }
}

constexpr int A_NSLOT = 9;
constexpr int A_SLOT = 24576;
constexpr int A_NKV = S_ / 64;
constexpr int PREP_CTAS = 128;

struct Ring {
  uint32_t slot, phase;
  __device__ __forceinline__ void adv(int n) { if (++slot == (uint32_t)n) { slot = 0; phase ^= 1; } }
};
constexpr int T_PAR = A_NSLOT * A_SLOT + 384;
constexpr int T_PREP = T_PAR + 3712;
constexpr int T_SMEM = T_PREP + 32 * 72 * 2 + 1024;
enum { P_OGA = 0, P_OA = 80, P_OB = 160, P_VA = 240, P_VB = 320, P_VC = 400, P_A2 = 480, P_B2 = 560, P_GB = 640, P_CS3 = 720, P_SC = 912 };

__device__ __forceinline__ void flag_wait(const unsigned* p, unsigned target) {
  asm volatile(
      "{\n.reg .pred p;\n.reg .u32 n, v;\n"
      "mov.u32 n, 0;\n"
      "SPIN:\n"
      "ld.relaxed.gpu.global.u32 v, [%0];\n"
      "setp.ge.u32 p, v, %1;\n"
      "@p bra DONE;\n"
      "add.u32 n, n, 1;\n"
      "setp.gt.u32 p, n, 4194304;\n"
      "@p trap;\n"
      "bra SPIN;\n"
      "DONE:\n}\n" :: "l"(p), "r"(target) : "memory");
}
__device__ __forceinline__ void fence_async_global() { asm volatile("fence.proxy.async.global;" ::: "memory"); }
__device__ __forceinline__ float lds_f(uint32_t a) { float v; asm volatile("ld.shared.f32 %0, [%1];" : "=f"(v) : "r"(a)); return v; }
__device__ __forceinline__ float2 lds_f2(uint32_t a) { float2 v; asm volatile("ld.shared.v2.f32 {%0, %1}, [%2];" : "=f"(v.x), "=f"(v.y) : "r"(a)); return v; }
__device__ __forceinline__ uint4 ldcg4(const void* p) { return __ldcg(reinterpret_cast<const uint4*>(p)); }

__device__ __forceinline__ void sts_f2(uint32_t a, float x, float y) { asm volatile("st.shared.v2.f32 [%0], {%1, %2};" :: "r"(a), "f"(x), "f"(y) : "memory"); }
__device__ __forceinline__ void sts_u4(uint32_t a, uint4 v) { asm volatile("st.shared.v4.u32 [%0], {%1, %2, %3, %4};" :: "r"(a), "r"(v.x), "r"(v.y), "r"(v.z), "r"(v.w) : "memory"); }
__device__ __forceinline__ void sts_u1(uint32_t a, uint32_t v) { asm volatile("st.shared.u32 [%0], %1;" :: "r"(a), "r"(v) : "memory"); }
__device__ __forceinline__ void fence_async_smem() { asm volatile("fence.proxy.async.shared::cta;" ::: "memory"); }
__device__ __forceinline__ void bulk_store(void* dst, uint32_t src, uint32_t bytes) {
  asm volatile("cp.async.bulk.global.shared::cta.bulk_group [%0], [%1], %2;" :: "l"(dst), "r"(src), "r"(bytes) : "memory");
}
__device__ __forceinline__ void bulk_red_f32(void* dst, uint32_t src, uint32_t bytes) {
  asm volatile("cp.reduce.async.bulk.global.shared::cta.bulk_group.add.f32 [%0], [%1], %2;" :: "l"(dst), "r"(src), "r"(bytes) : "memory");
}
__device__ __forceinline__ void tma_store2d(const CUtensorMap* m, uint32_t src, int c0, int c1) {
  asm volatile("cp.async.bulk.tensor.2d.global.shared::cta.bulk_group [%0, {%2, %3}], [%1];" :: "l"(m), "r"(src), "r"(c0), "r"(c1) : "memory");
}
__device__ __forceinline__ void bulk_done() { asm volatile("cp.async.bulk.commit_group;\ncp.async.bulk.wait_group 0;" ::: "memory"); }
__device__ __forceinline__ void flag_add(unsigned* f) { asm volatile("red.relaxed.gpu.global.add.u32 [%0], 1;" :: "l"(f) : "memory"); }
__device__ __forceinline__ float4 lds_f4(uint32_t a) { float4 v; asm volatile("ld.shared.v4.f32 {%0, %1, %2, %3}, [%4];" : "=f"(v.x), "=f"(v.y), "=f"(v.z), "=f"(v.w) : "r"(a) : "memory"); return v; }
__device__ __forceinline__ uint4 lds_u4(uint32_t a) { uint4 v; asm volatile("ld.shared.v4.u32 {%0, %1, %2, %3}, [%4];" : "=r"(v.x), "=r"(v.y), "=r"(v.z), "=r"(v.w) : "r"(a) : "memory"); return v; }
__device__ __forceinline__ void lds8(uint32_t a, float (&v)[8]) {
  const float4 p = lds_f4(a), q = lds_f4(a + 16);
  v[0] = p.x; v[1] = p.y; v[2] = p.z; v[3] = p.w; v[4] = q.x; v[5] = q.y; v[6] = q.z; v[7] = q.w;
}
__device__ __forceinline__ void lds8_bf(uint32_t a, float (&v)[8]) {
  const uint4 u = lds_u4(a);
  v[0] = bf_lo(u.x); v[1] = bf_hi(u.x); v[2] = bf_lo(u.y); v[3] = bf_hi(u.y); v[4] = bf_lo(u.z); v[5] = bf_hi(u.z); v[6] = bf_lo(u.w); v[7] = bf_hi(u.w);
}
__device__ __forceinline__ uint4 pack8(const float (&v)[8]) {
  return make_uint4(pack_bf16(v[0], v[1]), pack_bf16(v[2], v[3]), pack_bf16(v[4], v[5]), pack_bf16(v[6], v[7]));
}
__device__ __forceinline__ void mbar_wait_c(uint32_t a, uint32_t ph) {
  asm volatile("{\n.reg .pred p;\nSPIN:\nmbarrier.try_wait.parity.shared::cta.b64 p, [%0], %1;\n@!p bra SPIN;\n}\n" :: "r"(a), "r"(ph) : "memory");
}
constexpr int ST_P = 80;
constexpr int E_TILE = 128 * 80 * 2;

struct Maps { CUtensorMap h, wq, k, v, o, wo3, wo2, xa, w1t, us, w2t, x1, w3, g, w4t, ex, exa, ex1, sxa, sus, sx1, sout; };
struct PfList { const uint8_t* p[6]; };

constexpr int M_AOFF = 102400, M_NA = 7;

__global__ void __cluster_dims__(2, 1, 1) __launch_bounds__(384, 1)
fused_kernel(const __grid_constant__ Maps tm, const __grid_constant__ PfList pf, const __grid_constant__ PrepW pw, const bf16* __restrict__ x, bf16* __restrict__ out) {
  extern __shared__ uint8_t smem_raw[];
  const uint32_t sb = (smem_u32(smem_raw) + 1023) & ~1023u;
  TL_ENTRY(2);
  const uint32_t bar_full = sb + A_NSLOT * A_SLOT;
  const uint32_t bar_empty = bar_full + 8 * A_NSLOT;
  const uint32_t bar_sig = bar_empty + 8 * A_NSLOT;
  const uint32_t mb_full = bar_sig + 16;
  const uint32_t mb_empty = mb_full + 96;
  const uint32_t par = sb + T_PAR;
  float* parf = reinterpret_cast<float*>(smem_raw + (par - smem_u32(smem_raw)));
  uint32_t rank;
  asm volatile("mov.u32 %0, %%cluster_ctarank;" : "=r"(rank));
  const int cid = blockIdx.x >> 1;
  const int wid = __shfl_sync(0xffffffffu, threadIdx.x >> 5, 0);
  const int wg = wid >> 2;
  const int qtile = (cid & 7) * 2 + rank, hbase = cid >> 3;
  const int o_qt = qtile, o_nh = (cid >> 3) & 1, o_ks = cid >> 4;
  const int o_col = o_nh * 320 + o_ks * 80;
  const int qt = cid >> 2, js = (cid & 3) * 2 + rank;
  if (threadIdx.x == 0) {
    for (int i = 0; i < A_NSLOT; i++) { mbar_init(bar_full + 8 * i, 1); mbar_init(bar_empty + 8 * i, 16); }
    mbar_init(bar_sig, 4); mbar_init(bar_sig + 8, 4);
    for (int i = 0; i < 12; i++) { mbar_init(mb_full + 8 * i, 1); mbar_init(mb_empty + 8 * i, i < 5 ? 8 : 16); }
    asm volatile("fence.mbarrier_init.release.cluster;" ::: "memory");
    prefetch_tmap(&tm.h); prefetch_tmap(&tm.wq); prefetch_tmap(&tm.k); prefetch_tmap(&tm.v);
  }
  __syncthreads();
  cluster_sync();

  if (wg == 0) {
    asm volatile("setmaxnreg.dec.sync.aligned.u32 40;");
    if (wid == 0) {
      Ring r{0, 1};
#define P_ACQ(bytes_) do { mbar_wait(bar_empty + 8 * r.slot, r.phase); mbar_expect_e(bar_full + 8 * r.slot, bytes_); } while (0)
#define P_DST (sb + r.slot * A_SLOT)
#define P_BAR (bar_full + 8 * r.slot)
      uint64_t pol_ef;
      asm volatile("createpolicy.fractional.L2::evict_first.b64 %0, 1.0;" : "=l"(pol_ef));
      pdl_wait();
      TL_WAITED(2);
#pragma unroll 1
      for (int item = 0; item < 4; item++) {
        const int head = hbase + 8 * item;
#pragma unroll 1
        for (int kb = 0; kb < 10; kb++) {
          P_ACQ(16384);
          tma2d(P_DST, &tm.h, P_BAR, kb * 64, qtile * 128);
          r.adv(A_NSLOT);
          P_ACQ(A_SLOT);
          if ((uint32_t)(kb & 1) == rank) tma3d_mc_hint(P_DST, &tm.wq, P_BAR, 0, kb * 64, head * 3, 3, pol_ef);
          r.adv(A_NSLOT);
        }
#pragma unroll 1
        for (int j = 0; j <= A_NKV; j++) {
          if (j < A_NKV) {
            P_ACQ(A_SLOT);
            if (rank == 0) tma3d_mc_hint(P_DST, &tm.k, P_BAR, 0, head * S_ + j * 64, 0, 3, pol_ef);
            r.adv(A_NSLOT);
          }
          if (j > 0) {
            P_ACQ(A_SLOT);
            if (rank == 1) tma3d_mc_hint(P_DST, &tm.v, P_BAR, 0, head * S_ + (j - 1) * 64, 0, 3, pol_ef);
            r.adv(A_NSLOT);
          }
          if (item == 3 && (j & 3) == 0) {
            const int c = (j >> 2) * 128 + blockIdx.x;
            if (c < 980) {
              const int li = c < 480 ? 0 : c < 600 ? 1 : c < 720 ? 2 : c < 880 ? 3 : c < 930 ? 4 : 5;
              const int c0 = c < 480 ? 0 : c < 600 ? 480 : c < 720 ? 600 : c < 880 ? 720 : c < 930 ? 880 : 930;
              l2_prefetch16k(pf.p[li] + (size_t)(c - c0) * 16384);
            }
          }
          if (item == 3) {
            if (j >= 6 && j < 24) {
              const int kb = j - 6;
              l2_prefetch_t2d(&tm.o, ((kb / 6) * 8 + 2 * o_ks + (kb % 6) / 3) * DH_ + (kb % 3) * 64, o_qt * 128);
            }
            if (j >= 24 && j < 30) flag_wait(g_flag + F_O + o_qt * 32 + ((j - 24) >> 1) * 8 + 2 * o_ks + (j & 1), 2);
            if (j == 0 && threadIdx.x == 0) {
              prefetch_tmap(&tm.o); prefetch_tmap(&tm.wo3); prefetch_tmap(&tm.wo2); prefetch_tmap(&tm.xa); prefetch_tmap(&tm.w1t); prefetch_tmap(&tm.us);
              prefetch_tmap(&tm.w2t); prefetch_tmap(&tm.x1); prefetch_tmap(&tm.w3); prefetch_tmap(&tm.g); prefetch_tmap(&tm.w4t);
              prefetch_tmap(&tm.ex); prefetch_tmap(&tm.exa); prefetch_tmap(&tm.ex1);
              prefetch_tmap(&tm.sxa); prefetch_tmap(&tm.sus); prefetch_tmap(&tm.sx1); prefetch_tmap(&tm.sout);
            }
          }
        }
      }
#pragma unroll 1
      for (int kb = 0; kb < 24; kb++) {
        const int head = (kb / 6) * 8 + 2 * o_ks + (kb % 6) / 3;
        const int kcol = head * DH_ + (kb % 3) * 64;
        P_ACQ(24576);
        if (rank == 0) tma3d_mc(P_DST, &tm.wo3, P_BAR, 0, kcol, o_nh * 5, 3);
        r.adv(A_NSLOT);
        P_ACQ(16384);
        if (rank == 1) tma3d_mc(P_DST, &tm.wo2, P_BAR, 0, kcol, o_nh * 5 + 3, 3);
        r.adv(A_NSLOT);
        if (kb == 18 || kb == 21) flag_wait(g_flag + F_O + o_qt * 32 + head, 2);
        if (kb % 3 == 0) fence_async_global();
        P_ACQ(16384);
        tma2d(P_DST, &tm.o, P_BAR, kcol, o_qt * 128);
        r.adv(A_NSLOT);
      }
      P_ACQ(E_TILE);
      tma2d(P_DST, &tm.ex, P_BAR, o_col, o_qt * 128);
      r.adv(A_NSLOT);
      flag_wait(g_flag + F_XCH + (o_qt * 2 + o_nh) * 4 + o_ks, 6);
      fence_async_global();
#pragma unroll 1
      for (int i = 0; i < 3; i++) {
        P_ACQ(E_TILE);
        bulk_load(P_DST, g_xch + (size_t)((((o_qt * 2 + o_nh) * 4 + o_ks) * 4) + ((o_ks + 1 + i) & 3)) * (E_TILE / 2), E_TILE, P_BAR);
        r.adv(A_NSLOT);
      }
      flag_wait(g_flag + F_PREP, PREP_CTAS);
      fence_async_global();
#pragma unroll 1
      for (int i = 0; i < A_NSLOT; i++) { mbar_wait(bar_empty + 8 * r.slot, r.phase); r.adv(A_NSLOT); }
      Ring ra{0, 1};
      uint32_t bpar = 0x1f;
#pragma unroll 1
      for (int ph = 0; ph < 4; ph++) {
        const CUtensorMap* ma = ph == 0 ? &tm.xa : ph == 1 ? &tm.us : ph == 2 ? &tm.x1 : &tm.g;
        const CUtensorMap* mb = ph == 0 ? &tm.w1t : ph == 1 ? &tm.w2t : ph == 2 ? &tm.w3 : &tm.w4t;
        const int nkb = ph == 3 ? 24 : 10;
        const int nbl = ph == 2 ? 10 : nkb / 2;
        const int nel = ph == 1 ? 1 : ph == 3 ? 2 : 0;
        const uint32_t nbs = ph == 2 ? 4 : 5, bsz = ph == 2 ? 24576 : 20480;
        int bl = 0; uint32_t bs = 0;
#pragma unroll 1
        for (int i = 0; i < 5; i++) mbar_wait(mb_empty + 8 * i, (bpar >> i) & 1);
#define T_LOADB() do { mbar_wait(mb_empty + 8 * bs, (bpar >> bs) & 1); bpar ^= 1u << bs; mbar_expect_e(mb_full + 8 * bs, bsz);    \
                       if (bl < nbl) tma3d(sb + bs * bsz, mb, mb_full + 8 * bs, 0, ph == 2 ? bl * 64 : js * 80, ph == 2 ? js * 3 : bl * 2); \
                       else tma2d(sb + bs * bsz, bl == nbl ? &tm.exa : &tm.ex1, mb_full + 8 * bs, js * 80, qt * 128); \
                       bl++; if (++bs == nbs) bs = 0; } while (0)
#pragma unroll 1
        for (uint32_t i = 0; i < nbs; i++) T_LOADB();
        TX(8 + ph * 4);
        const unsigned* fl = g_flag + F_XA + 16 * ph;
        flag_wait(fl + qt, 16);
        if (ph == 1) { if (qt > 0) flag_wait(fl + qt - 1, 16); if (qt < 15) flag_wait(fl + qt + 1, 16); }
        TX(9 + ph * 4);
        fence_async_global();
#pragma unroll 1
        for (int kb = 0; kb < nkb; kb++) {
          mbar_wait(mb_empty + 40 + 8 * ra.slot, ra.phase);
          mbar_expect_e(mb_full + 40 + 8 * ra.slot, 16384);
          tma2d_mc(sb + M_AOFF + ra.slot * 16384 + rank * 8192, ma, mb_full + 40 + 8 * ra.slot, kb * 64, qt * 128 + (int)rank * 64, 3);
          ra.adv(M_NA);
          while (bl < nbl + nel && (kb == nkb - 1 || kb >= (ph == 2 ? bl + 2 : 2 * bl - 3))) T_LOADB();
        }
      }
    } else if (wid < 3) {
      const int w = wid - 1, lane = threadIdx.x & 31;
#pragma unroll 1
      for (int sig = 0; sig < 4; sig++) {
        mbar_wait(bar_sig + 8 * w, sig & 1);
        if (lane == 0) {
          asm volatile("fence.acq_rel.gpu;" ::: "memory");
          flag_add(g_flag + F_O + qtile * 32 + hbase + 8 * sig);
        }
        __syncwarp();
      }
    } else {
      const int lane = threadIdx.x & 31;
      pdl_wait();
      prep_warp(pw, reinterpret_cast<bf16(*)[72]>(smem_raw + (sb + T_PREP - smem_u32(smem_raw))), lane);
      flag_wait(g_flag + F_PREP, PREP_CTAS);
#pragma unroll 1
      for (int i = lane; i < P_SC; i += 32) {
        const int v = i < P_CS3 ? i / 80 : 9, j = i - (i < P_CS3 ? v * 80 : P_CS3);
        const float* src = v == 0 ? g_mod + 2 * D_ + o_col : v == 1 ? g_mod + 4 * D_ + o_col : v == 2 ? g_mod + 3 * D_ + o_col
                         : v < 6 ? g_vec + (v - 3) * D_ + js * 80 : v == 6 ? g_mod + 4 * D_ + js * 80 : v == 7 ? g_mod + 3 * D_ + js * 80
                         : v == 8 ? g_mod + 5 * D_ + js * 80 : g_vec + 3 * D_ + js * 192;
        parf[i] = __ldcg(src + j);
      }
      float sv[5] = {0.f, 0.f, 0.f, 0.f, 0.f};
#pragma unroll 1
      for (int i = lane; i < D_; i += 32) {
        const float a = __ldcg(g_mod + 4 * D_ + i), b = __ldcg(g_mod + 3 * D_ + i);
        sv[0] += a; sv[1] = fmaf(a, a, sv[1]); sv[2] = fmaf(a, b, sv[2]); sv[3] += b; sv[4] = fmaf(b, b, sv[4]);
      }
#pragma unroll 1
      for (int o_ = 16; o_ > 0; o_ >>= 1) {
#pragma unroll
        for (int i = 0; i < 5; i++) sv[i] += __shfl_xor_sync(0xffffffffu, sv[i], o_);
      }
      if (lane == 0) {
#pragma unroll
        for (int i = 0; i < 5; i++) parf[P_SC + i] = sv[i];
      }
      bar_arrive(6, 288);
    }
    __syncwarp();
    cluster_sync();
  } else {
    asm volatile("setmaxnreg.inc.sync.aligned.u32 232;");
    const int w = wg - 1;
    const int lane = threadIdx.x & 31;
    const int warp = wid & 3;
    const int tid = threadIdx.x - 128;
    const uint32_t rel_base = mapa(bar_empty, (lane == 0) ? rank : (rank ^ 1));
    Ring r{0, 0};
#define A_RELEASE(slot_) do { if (lane < 2) mbar_arrive_remote(rel_base + 8 * (slot_)); } while (0)
#define SIGNAL() do { __syncwarp(); if (lane == 0) mbar_arrive(bar_sig + 8 * w); } while (0)
    {
    const float SC = 0.07216878364870322f * 1.4426950408889634f;
    float o[96];
    uint32_t q[48];
    float s[32];
    uint32_t p[16], p2[16];
    if (w == 1) bar_arrive(1, 256);
    for (int item = 0; item < 4; item++) {
      const int head = hbase + 8 * item;
      TSA(item, 0);
      uint32_t prevA = 0, prevB = 0;
      for (int kb = 0; kb < 10; kb++) {
        const uint32_t sA = r.slot; mbar_wait_c(bar_full + 8 * sA, r.phase); r.adv(A_NSLOT);
        const uint32_t sB = r.slot; mbar_wait_c(bar_full + 8 * sB, r.phase); r.adv(A_NSLOT);
        const uint64_t da = mkdesc(sb + sA * A_SLOT + w * 8192, 16, 1024);
        const uint64_t db = mkdesc(sb + sB * A_SLOT, 8192, 1024);
        wg_fence();
#pragma unroll
        for (int kk = 0; kk < 4; kk++) wgmma_ss_n192<1>(o, da + kk * 2, db + kk * 128, (kb | kk) != 0);
        wg_commit();
        if (kb > 0) { wg_wait<1>(); A_RELEASE(prevA); A_RELEASE(prevB); }
        prevA = sA; prevB = sB;
      }
      wg_wait<0>();
      fence_regs(o);
      A_RELEASE(prevA); A_RELEASE(prevB);
#pragma unroll
      for (int i = 0; i < 48; i++) q[i] = pack_bf16(o[2 * i], o[2 * i + 1]);

      TSA(item, 1);
      float c0, c1, l0, l1;
      {
        const uint32_t sK = r.slot; mbar_wait_c(bar_full + 8 * sK, r.phase); r.adv(A_NSLOT);
        const uint64_t dk = mkdesc(sb + sK * A_SLOT, 16, 1024);
        bar_sync(1 + w, 256);
        wg_fence();
#pragma unroll
        for (int kk = 0; kk < 12; kk++)
          wgmma_rs_n64<0>(s, q[4 * kk], q[4 * kk + 1], q[4 * kk + 2], q[4 * kk + 3], dk + (kk >> 2) * 512 + (kk & 3) * 2, kk != 0);
        wg_commit();
        bar_arrive(1 + (w ^ 1), 256);
        wg_wait<0>();
        fence_regs(s);
        A_RELEASE(sK);
        float mx0 = fmaxf(s[0], s[1]), mx1 = fmaxf(s[2], s[3]);
#pragma unroll
        for (int i = 1; i < 8; i++) { mx0 = fmaxf(mx0, fmaxf(s[4 * i], s[4 * i + 1])); mx1 = fmaxf(mx1, fmaxf(s[4 * i + 2], s[4 * i + 3])); }
        mx0 = fmaxf(mx0, __shfl_xor_sync(0xffffffffu, mx0, 1)); mx1 = fmaxf(mx1, __shfl_xor_sync(0xffffffffu, mx1, 1));
        mx0 = fmaxf(mx0, __shfl_xor_sync(0xffffffffu, mx0, 2)); mx1 = fmaxf(mx1, __shfl_xor_sync(0xffffffffu, mx1, 2));
        c0 = mx0 * SC; c1 = mx1 * SC;
        l0 = 0.f; l1 = 0.f;
#pragma unroll
        for (int i = 0; i < 8; i++) {
          s[4 * i] = ex2(fmaf(s[4 * i], SC, -c0)); s[4 * i + 1] = ex2(fmaf(s[4 * i + 1], SC, -c0));
          s[4 * i + 2] = ex2(fmaf(s[4 * i + 2], SC, -c1)); s[4 * i + 3] = ex2(fmaf(s[4 * i + 3], SC, -c1));
          l0 += s[4 * i] + s[4 * i + 1]; l1 += s[4 * i + 2] + s[4 * i + 3];
        }
#pragma unroll
        for (int i = 0; i < 16; i++) p[i] = pack_bf16(s[2 * i], s[2 * i + 1]);
      }
      TSA(item, 2);
      uint32_t okn;
      {
        Ring r2 = r; r2.adv(A_NSLOT);
        okn = mbar_try(bar_full + 8 * r.slot, r.phase) & mbar_try(bar_full + 8 * r2.slot, r2.phase);
      }
#define A_STEP(PC, PN, FIRST)                                                                                          \
      {                                                                                                                \
        const uint32_t sK = r.slot, phK = r.phase; r.adv(A_NSLOT);                                                     \
        const uint32_t sV = r.slot, phV = r.phase; r.adv(A_NSLOT);                                                     \
        const uint64_t dk = mkdesc(sb + sK * A_SLOT, 16, 1024);                                                        \
        const uint64_t dv = mkdesc(sb + sV * A_SLOT, 8192, 1024);                                                      \
        if (!okn) { mbar_wait_c(bar_full + 8 * sK, phK); mbar_wait_c(bar_full + 8 * sV, phV); }                            \
        bar_sync(1 + w, 256);                                                                                          \
        wg_fence();                                                                                                    \
        _Pragma("unroll") for (int kk = 0; kk < 12; kk++)                                                              \
          wgmma_rs_n64<0>(s, q[4 * kk], q[4 * kk + 1], q[4 * kk + 2], q[4 * kk + 3], dk + (kk >> 2) * 512 + (kk & 3) * 2, kk != 0); \
        wg_commit();                                                                                                   \
        _Pragma("unroll") for (int kk = 0; kk < 4; kk++)                                                               \
          wgmma_rs_n192<1>(o, PC[4 * kk], PC[4 * kk + 1], PC[4 * kk + 2], PC[4 * kk + 3], dv + kk * 128, !(FIRST) || (kk != 0)); \
        wg_commit();                                                                                                   \
        bar_arrive(1 + (w ^ 1), 256);                                                                                  \
        {                                                                                                              \
          Ring r2 = r; r2.adv(A_NSLOT);                                                                                \
          okn = mbar_try(bar_full + 8 * r.slot, r.phase) & mbar_try(bar_full + 8 * r2.slot, r2.phase);                 \
        }                                                                                                              \
        wg_wait<1>();                                                                                                  \
        fence_regs(s);                                                                                                 \
        A_RELEASE(sK);                                                                                                 \
        float b0 = 0.f, b1 = 0.f;                                                                                      \
        _Pragma("unroll") for (int i = 0; i < 8; i++) {                                                                \
          const float e0 = ex2(fmaf(s[4 * i], SC, -c0)), e1 = ex2(fmaf(s[4 * i + 1], SC, -c0));                        \
          const float e2 = ex2(fmaf(s[4 * i + 2], SC, -c1)), e3 = ex2(fmaf(s[4 * i + 3], SC, -c1));                    \
          b0 += e0 + e1; b1 += e2 + e3;                                                                                \
          PN[2 * i] = pack_bf16(e0, e1); PN[2 * i + 1] = pack_bf16(e2, e3);                                            \
        }                                                                                                              \
        wg_wait<0>();                                                                                                  \
        fence_regs(o);                                                                                                 \
        fence_regs(PC);                                                                                                \
        A_RELEASE(sV);                                                                                                 \
        if (__any_sync(0xffffffffu, !(b0 <= 65536.f) || !(b1 <= 65536.f))) {                                           \
          float mx0 = fmaxf(s[0], s[1]), mx1 = fmaxf(s[2], s[3]);                                                      \
          _Pragma("unroll") for (int i = 1; i < 8; i++) {                                                              \
            mx0 = fmaxf(mx0, fmaxf(s[4 * i], s[4 * i + 1])); mx1 = fmaxf(mx1, fmaxf(s[4 * i + 2], s[4 * i + 3]));     \
          }                                                                                                            \
          mx0 = fmaxf(mx0, __shfl_xor_sync(0xffffffffu, mx0, 1)); mx1 = fmaxf(mx1, __shfl_xor_sync(0xffffffffu, mx1, 1)); \
          mx0 = fmaxf(mx0, __shfl_xor_sync(0xffffffffu, mx0, 2)); mx1 = fmaxf(mx1, __shfl_xor_sync(0xffffffffu, mx1, 2)); \
          const float n0 = fmaxf(c0, mx0 * SC), n1 = fmaxf(c1, mx1 * SC);                                              \
          const float a0 = ex2(c0 - n0), a1 = ex2(c1 - n1);                                                            \
          c0 = n0; c1 = n1;                                                                                            \
          l0 *= a0; l1 *= a1;                                                                                          \
          _Pragma("unroll") for (int i = 0; i < 24; i++) { o[4 * i] *= a0; o[4 * i + 1] *= a0; o[4 * i + 2] *= a1; o[4 * i + 3] *= a1; } \
          b0 = 0.f; b1 = 0.f;                                                                                          \
          _Pragma("unroll") for (int i = 0; i < 8; i++) {                                                              \
            const float e0 = ex2(fmaf(s[4 * i], SC, -c0)), e1 = ex2(fmaf(s[4 * i + 1], SC, -c0));                      \
            const float e2 = ex2(fmaf(s[4 * i + 2], SC, -c1)), e3 = ex2(fmaf(s[4 * i + 3], SC, -c1));                  \
            b0 += e0 + e1; b1 += e2 + e3;                                                                              \
            PN[2 * i] = pack_bf16(e0, e1); PN[2 * i + 1] = pack_bf16(e2, e3);                                          \
          }                                                                                                            \
        }                                                                                                              \
        l0 += b0; l1 += b1;                                                                                            \
      }
      for (int jj = 0; jj < 15; jj++) {
        A_STEP(p, p2, jj == 0)
        A_STEP(p2, p, false)
      }
      A_STEP(p, p2, false)
      TSA(item, 3);
      {
        const uint32_t sV = r.slot; mbar_wait_c(bar_full + 8 * sV, r.phase); r.adv(A_NSLOT);
        const uint64_t dv = mkdesc(sb + sV * A_SLOT, 8192, 1024);
        bar_sync(1 + w, 256);
        wg_fence();
#pragma unroll
        for (int kk = 0; kk < 4; kk++)
          wgmma_rs_n192<1>(o, p2[4 * kk], p2[4 * kk + 1], p2[4 * kk + 2], p2[4 * kk + 3], dv + kk * 128, 1);
        wg_commit();
        bar_arrive(1 + (w ^ 1), 256);
        wg_wait<0>();
        fence_regs(o);
        A_RELEASE(sV);
      }
      TSA(item, 4);
      l0 += __shfl_xor_sync(0xffffffffu, l0, 1); l1 += __shfl_xor_sync(0xffffffffu, l1, 1);
      l0 += __shfl_xor_sync(0xffffffffu, l0, 2); l1 += __shfl_xor_sync(0xffffffffu, l1, 2);
      const float i0 = 1.f / l0, i1 = 1.f / l1;
      bf16* orow = g_o + (size_t)(qtile * 128 + w * 64 + warp * 16 + (lane >> 2)) * HD_ + head * DH_ + (lane & 3) * 8;
#pragma unroll
      for (int g = 0; g < 6; g++) {
        uint32_t u0 = pack_bf16(o[16 * g + 0] * i0, o[16 * g + 1] * i0), u1 = pack_bf16(o[16 * g + 4] * i0, o[16 * g + 5] * i0);
        uint32_t u2 = pack_bf16(o[16 * g + 8] * i0, o[16 * g + 9] * i0), u3 = pack_bf16(o[16 * g + 12] * i0, o[16 * g + 13] * i0);
        quad_transpose(u0, u1, u2, u3, lane);
        *reinterpret_cast<uint4*>(orow + g * 32) = make_uint4(u0, u1, u2, u3);
        uint32_t v0 = pack_bf16(o[16 * g + 2] * i1, o[16 * g + 3] * i1), v1 = pack_bf16(o[16 * g + 6] * i1, o[16 * g + 7] * i1);
        uint32_t v2 = pack_bf16(o[16 * g + 10] * i1, o[16 * g + 11] * i1), v3 = pack_bf16(o[16 * g + 14] * i1, o[16 * g + 15] * i1);
        quad_transpose(v0, v1, v2, v3, lane);
        *reinterpret_cast<uint4*>(orow + (size_t)8 * HD_ + g * 32) = make_uint4(v0, v1, v2, v3);
      }
      SIGNAL();
      TSA(item, 5);
    }
    }
    TS(3, 2);
    const uint32_t st_w = (uint32_t)((warp * 16 + (lane >> 2)) * ST_P + (lane & 3) * 2) * 4;
    const uint32_t st_x = (lane & 8) << 2;
    const int er = (tid & 127) >> 1, eh = tid & 1;
    const uint32_t st_r = (uint32_t)(er * ST_P + (eh ^ ((er >> 1) & 1)) * 8) * 4;
    const uint32_t e_r = (uint32_t)((w * 64 + er) * 160 + eh * 16);
    const uint32_t p_r = par + eh * 32;
    const uint32_t stat = sb + T_PREP + w * 2048;
    const bool leader = (tid & 127) == 0;
#define STAGE10(ACC, BASE)                                                                                             \
    _Pragma("unroll") for (int nb = 0; nb < 10; nb++) {                                                                \
      sts_f2(stg + st_w + ((nb * 32) ^ st_x), ACC(BASE + 4 * nb), ACC(BASE + 4 * nb + 1));                                       \
      sts_f2(stg + st_w + ((nb * 32) ^ st_x) + 8 * ST_P * 4, ACC(BASE + 4 * nb + 2), ACC(BASE + 4 * nb + 3));                    \
    }

    {
      float acc1[96], acc2[64];
      uint32_t p0 = 0, p1 = 0, p2 = 0;
#pragma unroll 1
      for (int kb = 0; kb < 24; kb++) {
        const uint32_t s1 = r.slot; mbar_wait_c(bar_full + 8 * s1, r.phase); r.adv(A_NSLOT);
        const uint32_t s2 = r.slot; mbar_wait_c(bar_full + 8 * s2, r.phase); r.adv(A_NSLOT);
        const uint32_t sa = r.slot; mbar_wait_c(bar_full + 8 * sa, r.phase); r.adv(A_NSLOT);
        const uint64_t da = mkdesc(sb + sa * A_SLOT + w * 8192, 16, 1024);
        const uint64_t d1 = mkdesc(sb + s1 * A_SLOT, 8192, 1024), d2 = mkdesc(sb + s2 * A_SLOT, 8192, 1024);
        wg_fence();
#pragma unroll
        for (int kk = 0; kk < 4; kk++) {
          wgmma_ss_n192<1>(acc1, da + kk * 2, d1 + kk * 128, (kb | kk) != 0);
          wgmma_ss_n128<1>(acc2, da + kk * 2, d2 + kk * 128, (kb | kk) != 0);
        }
        wg_commit();
        if (kb > 0) { wg_wait<1>(); A_RELEASE(p0); A_RELEASE(p1); A_RELEASE(p2); }
        p0 = s1; p1 = s2; p2 = sa;
      }
      wg_wait<0>();
      fence_regs(acc1); fence_regs(acc2);
      A_RELEASE(p2);
      bar_sync(6, 288);
      TS(0, 0);
      const uint32_t stg = sb + (w ? p1 : p0) * A_SLOT;
#define OACC(e) (((e) < 96) ? acc1[(e) < 96 ? (e) : 0] : acc2[(e) >= 96 ? (e) - 96 : 0])
#define PACK10(BASE)                                                                                                   \
      _Pragma("unroll") for (int nb = 0; nb < 10; nb++) {                                                              \
        sts_u1(xo + nb * 16, pack_bf16(OACC(BASE + 4 * nb), OACC(BASE + 4 * nb + 1)));                                 \
        sts_u1(xo + nb * 16 + 8 * 160, pack_bf16(OACC(BASE + 4 * nb + 2), OACC(BASE + 4 * nb + 3)));                   \
      }
      const uint32_t f1 = r.slot + 4 >= A_NSLOT ? r.slot + 4 - A_NSLOT : r.slot + 4, f2 = f1 + 1 >= A_NSLOT ? 0 : f1 + 1;
#pragma unroll
      for (int d = 0; d < 4; d++) {
        if (d != o_ks) {
          const int i = (d - o_ks - 1) & 3;
          const uint32_t xo = sb + (i == 0 ? p2 : i == 1 ? f1 : f2) * A_SLOT + (w * 64 + warp * 16 + (lane >> 2)) * 160 + (lane & 3) * 4;
          PACK10(d * 40)
        }
      }
      fence_async_smem();
      bar_sync(3 + w, 128);
      if (leader) {
#pragma unroll 1
        for (int i = 0; i < 3; i++)
          bulk_store(g_xch + (size_t)((((o_qt * 2 + o_nh) * 4 + ((o_ks + 1 + i) & 3)) * 4) + o_ks) * (E_TILE / 2) + w * (E_TILE / 4),
                     sb + (i == 0 ? p2 : i == 1 ? f1 : f2) * A_SLOT + w * (E_TILE / 2), E_TILE / 2);
        bulk_done();
#pragma unroll 1
        for (int i = 0; i < 3; i++) flag_add(g_flag + F_XCH + (o_qt * 2 + o_nh) * 4 + ((o_ks + 1 + i) & 3));
        TX(40 + w);
      }
      if (o_ks == 0) { STAGE10(OACC, 0) } else if (o_ks == 1) { STAGE10(OACC, 40) } else if (o_ks == 2) { STAGE10(OACC, 80) } else { STAGE10(OACC, 120) }
      bar_sync(3 + w, 128);
      const uint32_t sx = r.slot; mbar_wait_c(bar_full + 8 * sx, r.phase); r.adv(A_NSLOT);
      const uint32_t q0 = r.slot; mbar_wait_c(bar_full + 8 * q0, r.phase); r.adv(A_NSLOT);
      const uint32_t q1 = r.slot; mbar_wait_c(bar_full + 8 * q1, r.phase); r.adv(A_NSLOT);
      const uint32_t q2 = r.slot; mbar_wait_c(bar_full + 8 * q2, r.phase); r.adv(A_NSLOT);
      TS(0, 1);
      float st[6] = {0.f, 0.f, 0.f, 0.f, 0.f, 0.f};
      const uint32_t ot = sb + p2 * A_SLOT;
#pragma unroll 1
      for (int c = 0; c < 5; c++) {
        float v[8], t0[8], t1[8], t2[8];
        lds8(stg + st_r + c * 64, v);
        lds8_bf(sb + q0 * A_SLOT + e_r + c * 32, t0); lds8_bf(sb + q1 * A_SLOT + e_r + c * 32, t1); lds8_bf(sb + q2 * A_SLOT + e_r + c * 32, t2);
#pragma unroll
        for (int e = 0; e < 8; e++) v[e] += (t0[e] + t1[e]) + t2[e];
        lds8_bf(sb + sx * A_SLOT + e_r + c * 32, t0);
        lds8(p_r + P_OGA * 4 + c * 64, t1);
#pragma unroll
        for (int e = 0; e < 8; e++) v[e] = fmaf(t1[e], v[e], t0[e]);
        const uint4 pk = pack8(v);
        sts_u4(ot + e_r + c * 32, pk);
        v[0] = bf_lo(pk.x); v[1] = bf_hi(pk.x); v[2] = bf_lo(pk.y); v[3] = bf_hi(pk.y); v[4] = bf_lo(pk.z); v[5] = bf_hi(pk.z); v[6] = bf_lo(pk.w); v[7] = bf_hi(pk.w);
        lds8(p_r + P_OA * 4 + c * 64, t1);
        lds8(p_r + P_OB * 4 + c * 64, t2);
#pragma unroll
        for (int e = 0; e < 8; e++) {
          const float y = t1[e] * v[e];
          st[0] += v[e]; st[1] = fmaf(v[e], v[e], st[1]); st[2] += y; st[3] = fmaf(t1[e], y, st[3]); st[4] = fmaf(y, y, st[4]); st[5] = fmaf(t2[e], y, st[5]);
        }
      }
#pragma unroll
      for (int i = 0; i < 6; i++) st[i] += __shfl_xor_sync(0xffffffffu, st[i], 1);
      sts_u4(stat + er * 32 + eh * 16, eh ? make_uint4(__float_as_uint(st[4]), __float_as_uint(st[5]), 0u, 0u)
                                          : make_uint4(__float_as_uint(st[0]), __float_as_uint(st[1]), __float_as_uint(st[2]), __float_as_uint(st[3])));
      fence_async_smem();
      bar_sync(3 + w, 128);
      if (leader) {
        tma_store2d(&tm.sxa, ot + w * (E_TILE / 2), o_col, o_qt * 128 + w * 64);
        bulk_red_f32(g_st1 + (size_t)(o_qt * 128 + w * 64) * 8, stat, 2048);
        bulk_done();
        flag_add(g_flag + F_XA + o_qt);
      }
      bar_sync(5, 256);
      A_RELEASE(p0); A_RELEASE(p1); A_RELEASE(sx); A_RELEASE(q0); A_RELEASE(q1); A_RELEASE(q2);
      TS(0, 2);
    }

    Ring ra{0, 0};
    uint32_t bpar = 0;
    const uint32_t rel_a = mapa(mb_empty + 40, (lane == 0) ? rank : (rank ^ 1));
#define B_NEXT(s_) do { s_ = bs; mbar_wait_c(mb_full + 8 * bs, (bpar >> bs) & 1); bpar ^= 1u << bs; if (++bs == nbs) bs = 0; } while (0)
#define A_NEXT(s_) do { s_ = ra.slot; mbar_wait_c(mb_full + 40 + 8 * s_, ra.phase); ra.adv(M_NA); } while (0)
#define B_RELEASE(s_) do { if (lane == 0) mbar_arrive(mb_empty + 8 * (s_)); } while (0)
#define MA_RELEASE(s_) do { if (lane < 2) mbar_arrive_remote(rel_a + 8 * (s_)); } while (0)
    const int grow = qt * 128 + w * 64 + er;
    float mu = 0.f, rs = 0.f;
#pragma unroll 1
    for (int ph = 0; ph < 4; ph++) {
      float acc[96];
      float (&acc80)[40] = *reinterpret_cast<float(*)[40]>(&acc[0]);
      uint32_t pa = 0, pa2 = 0, pb = 0;
      float4 s03 = make_float4(0.f, 0.f, 0.f, 0.f);
      float2 s45 = make_float2(0.f, 0.f);
      const int nit = ph == 3 ? 12 : ph == 2 ? 10 : 5;
      const uint32_t nbs = ph == 2 ? 4 : 5, bsz = ph == 2 ? 24576 : 20480;
      uint32_t bs = 0;
#pragma unroll 1
      for (int it = 0; it < nit; it++) {
        uint32_t sbq, sa, sa2;
        B_NEXT(sbq);
        A_NEXT(sa);
        if (it == 0) TXC(ph);
        const uint64_t da = mkdesc(sb + M_AOFF + sa * 16384 + w * 8192, 16, 1024);
        if (ph == 2) {
          sa2 = sa;
          const uint64_t db = mkdesc(sb + sbq * 24576, 8192, 1024);
          wg_fence();
#pragma unroll
          for (int kk = 0; kk < 4; kk++) wgmma_ss_n192<1>(acc, da + kk * 2, db + kk * 128, (it | kk) != 0);
          wg_commit();
        } else {
          A_NEXT(sa2);
          const uint64_t da2 = mkdesc(sb + M_AOFF + sa2 * 16384 + w * 8192, 16, 1024);
          const uint64_t db = mkdesc(sb + sbq * 20480, 16, 1024);
          wg_fence();
#pragma unroll
          for (int kk = 0; kk < 4; kk++) wgmma_ss_n80<0>(acc80, da + kk * 2, db + kk * 2, (it | kk) != 0);
#pragma unroll
          for (int kk = 0; kk < 4; kk++) wgmma_ss_n80<0>(acc80, da2 + kk * 2, db + 640 + kk * 2, 1);
          wg_commit();
        }
        if (it > 0) { wg_wait<1>(); MA_RELEASE(pa); if (ph != 2) MA_RELEASE(pa2); B_RELEASE(pb); }
        else {
          if (ph == 0) { s03 = __ldcg(reinterpret_cast<const float4*>(g_st1 + (size_t)grow * 8)); s45 = __ldcg(reinterpret_cast<const float2*>(g_st1 + (size_t)grow * 8 + 4)); }
          if (ph == 2) s45 = __ldcg(reinterpret_cast<const float2*>(g_st2 + (size_t)grow * 2));
        }
        pa = sa; pa2 = sa2; pb = sbq;
      }
      wg_wait<0>();
      fence_regs(acc);
      MA_RELEASE(pa); if (ph != 2) MA_RELEASE(pa2);
      bar_sync(5, 256);
      TS(1 + (ph == 3 ? 0 : ph), ph == 3 ? 2 : 0);
      const uint32_t pb1 = pb == 0 ? nbs - 1 : pb - 1, pb2 = pb1 == 0 ? nbs - 1 : pb1 - 1, pb3 = pb2 == 0 ? nbs - 1 : pb2 - 1;
      const uint32_t stg = sb + (w ? pb : pb1) * bsz;
      uint32_t e1 = 0;
#define MACC(e) acc[e]
      if (!(ph & 1)) {
        float c0, c1, c2 = 0.f, c3 = 0.f;
        if (ph == 0) {
          const float4 sc = lds_f4(par + P_SC * 4);
          const float sbb = lds_f(par + (P_SC + 4) * 4);
          mu = s03.x * (1.f / D_);
          rs = rsqrtf(fmaxf(s03.y * (1.f / D_) - mu * mu, 0.f) + LN_EPS);
          const float m2 = (rs * (s03.z - mu * sc.x) + sc.w) * (1.f / D_);
          const float e2 = (rs * rs * (s45.x - 2.f * mu * s03.w + mu * mu * sc.y) + 2.f * rs * (s45.y - mu * sc.z) + sbb) * (1.f / D_);
          c2 = rsqrtf(fmaxf(e2 - m2 * m2, 0.f) + LN_EPS);
          c0 = c2 * rs; c1 = -c0 * mu; c3 = -c2 * m2;
          if (tid < 20) sts_u4(stat + 2048 * 2 + tid * 16, make_uint4(0, 0, 0, 0));
        } else {
          const float m = s45.x * (1.f / D_);
          c0 = rsqrtf(fmaxf(s45.y * (1.f / D_) - m * m, 0.f) + LN_EPS);
          c1 = -c0 * m;
        }
        const int npass = ph == 0 ? 1 : 3, nch = ph == 0 ? 5 : 4;
        const uint32_t ot = ph == 0 ? sb + pb2 * bsz + w * (E_TILE / 2) : sb + (w ? pb2 : pb3) * bsz;
#pragma unroll 1
        for (int ps = 0; ps < npass; ps++) {
          if (ps == 0) { STAGE10(MACC, 0) } else if (ps == 1) { STAGE10(MACC, 32) } else { STAGE10(MACC, 56) }
          bar_sync(3 + w, 128);
          const uint32_t cofs = ps == 2 ? 64 : 0;
          const uint32_t pp = p_r + (ph == 0 ? P_VA : P_CS3 + ps * 64) * 4;
#pragma unroll 1
          for (int c = 0; c < nch; c++) {
            float v[8], t[8];
            lds8(stg + st_r + cofs + c * 64, v);
            lds8(pp + c * 64, t);
#pragma unroll
            for (int e = 0; e < 8; e++) v[e] = fmaf(c0, v[e], c1 * t[e]);
            if (ph == 0) {
              lds8(pp + 320 + c * 64, t);
#pragma unroll
              for (int e = 0; e < 8; e++) v[e] = fmaf(c2, t[e], v[e]);
              lds8(pp + 640 + c * 64, t);
#pragma unroll
              for (int e = 0; e < 8; e++) v[e] = fmaf(c3, t[e], v[e]);
            }
#pragma unroll
            for (int e = 0; e < 8; e++) v[e] = gelu_tanh(v[e]);
            sts_u4(ot + (ph == 0 ? er * 160 + eh * 16 + c * 32 : ps * 8192 + er * 128 + (((2 * c + eh) ^ (er & 7)) << 4)), pack8(v));
          }
          fence_async_smem();
          bar_sync(3 + w, 128);
          if (leader) {
            if (ph == 0) {
              const int grp = js >> 1;
              const int sh = (grp & 2 ? 2 : 1) * (grp & 1 ? -1 : 1);
              tma_store2d(&tm.sus, ot, js * 80, qt * 128 + w * 64 + sh + 2);
              if (w == 0 && qt == (sh > 0 ? 0 : 15)) {
                const int r0 = sh > 0 ? 0 : S_ + sh, n = sh > 0 ? sh : -sh;
                for (int i = 0; i < n; i++) bulk_store(g_us + (size_t)(r0 + i + 2) * D_ + js * 80, stat + 2048 * 2, 160);
              }
            } else {
              tma_store2d(&tm.g, ot + ps * 8192, js * 192 + ps * 64, qt * 128 + w * 64);
            }
          }
        }
      } else {
        STAGE10(MACC, 0)
        uint32_t e2;
        B_NEXT(e1);
        e2 = e1;
        if (ph == 3) B_NEXT(e2);
        bar_sync(3 + w, 128);
        float s1 = 0.f, s2 = 0.f;
        const uint32_t ot = sb + pb2 * bsz;
#pragma unroll 1
        for (int c = 0; c < 5; c++) {
          float v[8], xa[8], t[8];
          lds8(stg + st_r + c * 64, v);
          lds8_bf(sb + e1 * 20480 + e_r + c * 32, xa);
          if (ph == 1) {
            lds8(p_r + P_A2 * 4 + c * 64, t);
#pragma unroll
            for (int e = 0; e < 8; e++) v[e] = fmaf(t[e] * rs, xa[e] - mu, v[e]);
            lds8(p_r + P_B2 * 4 + c * 64, t);
#pragma unroll
            for (int e = 0; e < 8; e++) v[e] += t[e];
          } else {
            lds8_bf(sb + e2 * 20480 + e_r + c * 32, t);
#pragma unroll
            for (int e = 0; e < 8; e++) v[e] += t[e];
            lds8(p_r + P_GB * 4 + c * 64, t);
#pragma unroll
            for (int e = 0; e < 8; e++) v[e] = fmaf(t[e], v[e], xa[e]);
          }
          const uint4 pk = pack8(v);
          sts_u4(ot + e_r + c * 32, pk);
          v[0] = bf_lo(pk.x); v[1] = bf_hi(pk.x); v[2] = bf_lo(pk.y); v[3] = bf_hi(pk.y); v[4] = bf_lo(pk.z); v[5] = bf_hi(pk.z); v[6] = bf_lo(pk.w); v[7] = bf_hi(pk.w);
#pragma unroll
          for (int e = 0; e < 8; e++) { s1 += v[e]; s2 = fmaf(v[e], v[e], s2); }
        }
        s1 += __shfl_xor_sync(0xffffffffu, s1, 1); s2 += __shfl_xor_sync(0xffffffffu, s2, 1);
        if (eh == 0) sts_f2(stat + er * 8, s1, s2);
        fence_async_smem();
        bar_sync(3 + w, 128);
        if (leader) {
          tma_store2d(ph == 1 ? &tm.sx1 : &tm.sout, ot + w * (E_TILE / 2), js * 80, qt * 128 + w * 64);
          if (ph == 1) bulk_red_f32(g_st2 + (size_t)(qt * 128 + w * 64) * 2, stat, 512);
        }
      }
      if (leader) {
        bulk_done();
        if (ph < 3) flag_add(g_flag + F_US + 16 * ph + qt);
      }
      if (ph < 3) {
        bar_sync(5, 256);
        B_RELEASE(pb);
        if (ph == 1) B_RELEASE(e1);
      }
      TS(1 + (ph == 3 ? 0 : ph), ph == 3 ? 3 : 1);
    }
    if ((threadIdx.x & 127) == 0) TL_END(2);
    cluster_sync();
  }
}

typedef CUresult (*EncFn)(CUtensorMap*, CUtensorMapDataType, cuuint32_t, void*, const cuuint64_t*, const cuuint64_t*,
                          const cuuint32_t*, const cuuint32_t*, CUtensorMapInterleave, CUtensorMapSwizzle,
                          CUtensorMapL2promotion, CUtensorMapFloatOOBfill);
static EncFn g_enc = nullptr;

static CUtensorMap map2d(const void* p, uint64_t rows, uint64_t cols, uint32_t box_rows) {
  CUtensorMap m;
  cuuint64_t gd[2] = {cols, rows}; cuuint64_t gs[1] = {cols * 2};
  cuuint32_t bx[2] = {64, box_rows}; cuuint32_t es[2] = {1, 1};
  g_enc(&m, CU_TENSOR_MAP_DATA_TYPE_BFLOAT16, 2, const_cast<void*>(p), gd, gs, bx, es, CU_TENSOR_MAP_INTERLEAVE_NONE,
        CU_TENSOR_MAP_SWIZZLE_128B, CU_TENSOR_MAP_L2_PROMOTION_L2_256B, CU_TENSOR_MAP_FLOAT_OOB_FILL_NONE);
  return m;
}
static CUtensorMap map3d(const void* p, uint64_t rows, uint64_t cols, uint32_t box_rows, uint32_t nblk) {
  CUtensorMap m;
  cuuint64_t gd[3] = {64, rows, cols / 64}; cuuint64_t gs[2] = {cols * 2, 128};
  cuuint32_t bx[3] = {64, box_rows, nblk}; cuuint32_t es[3] = {1, 1, 1};
  g_enc(&m, CU_TENSOR_MAP_DATA_TYPE_BFLOAT16, 3, const_cast<void*>(p), gd, gs, bx, es, CU_TENSOR_MAP_INTERLEAVE_NONE,
        CU_TENSOR_MAP_SWIZZLE_128B, CU_TENSOR_MAP_L2_PROMOTION_L2_256B, CU_TENSOR_MAP_FLOAT_OOB_FILL_NONE);
  return m;
}

static CUtensorMap map_e(const void* p, uint32_t rows, uint64_t total_rows = S_) {
  CUtensorMap m;
  cuuint64_t gd[2] = {D_, total_rows}; cuuint64_t gs[1] = {D_ * 2};
  cuuint32_t bx[2] = {80, rows}; cuuint32_t es[2] = {1, 1};
  g_enc(&m, CU_TENSOR_MAP_DATA_TYPE_BFLOAT16, 2, const_cast<void*>(p), gd, gs, bx, es, CU_TENSOR_MAP_INTERLEAVE_NONE,
        CU_TENSOR_MAP_SWIZZLE_NONE, CU_TENSOR_MAP_L2_PROMOTION_L2_256B, CU_TENSOR_MAP_FLOAT_OOB_FILL_NONE);
  return m;
}

template <typename... KArgs, typename... Args>
static void launch(void (*kern)(KArgs...), dim3 grid, dim3 block, int smem, bool pdl, Args... args) {
  cudaLaunchConfig_t cfg = {};
  cfg.gridDim = grid; cfg.blockDim = block; cfg.dynamicSmemBytes = smem; cfg.stream = cudaStreamPerThread;
  cudaLaunchAttribute at[1];
  at[0].id = cudaLaunchAttributeProgrammaticStreamSerialization;
  at[0].val.programmaticStreamSerializationAllowed = 1;
  cfg.attrs = at; cfg.numAttrs = pdl ? 1 : 0;
  cudaLaunchKernelEx(&cfg, kern, KArgs(args)...);
}

extern "C" void kernel_launch(void* const* d_in, const int* in_sizes, int n_in, void* d_out, int out_size) {
  const bf16* x = (const bf16*)d_in[0];
  const bf16* kc = (const bf16*)d_in[1];
  const bf16* vc = (const bf16*)d_in[2];
  const bf16* wq = (const bf16*)d_in[3];
  const bf16* wo = (const bf16*)d_in[4];
  const bf16* w1 = (const bf16*)d_in[6];
  const bf16* w2 = (const bf16*)d_in[7];
  const bf16* w3 = (const bf16*)d_in[8];
  const bf16* w4 = (const bf16*)d_in[9];
  const bf16* c = (const bf16*)d_in[10];
  const bf16* wmod = (const bf16*)d_in[11];
  bf16* out = (bf16*)d_out;

  static void *p_h, *p_o, *p_xa, *p_us, *p_x1, *p_g, *p_w1t, *p_w2t, *p_w4t;
  if (!g_enc) {
    void* fn = nullptr; cudaDriverEntryPointQueryResult qr;
    cudaGetDriverEntryPoint("cuTensorMapEncodeTiled", &fn, cudaEnableDefault, &qr);
    g_enc = (EncFn)fn;
    cudaGetSymbolAddress(&p_h, g_h); cudaGetSymbolAddress(&p_o, g_o); cudaGetSymbolAddress(&p_xa, g_xa);
    cudaGetSymbolAddress(&p_us, g_us); cudaGetSymbolAddress(&p_x1, g_x1); cudaGetSymbolAddress(&p_g, g_g);
    cudaGetSymbolAddress(&p_w1t, g_w1t); cudaGetSymbolAddress(&p_w2t, g_w2t); cudaGetSymbolAddress(&p_w4t, g_w4t);
    cudaFuncSetAttribute(fused_kernel, cudaFuncAttributeMaxDynamicSharedMemorySize, T_SMEM);
  }
  Maps tm;
  tm.h = map2d(p_h, S_, D_, 128);
  tm.wq = map3d(wq, D_, HD_, 64, 3);
  tm.k = map3d(kc, (uint64_t)H_ * S_, DH_, 64, 3);
  tm.v = map3d(vc, (uint64_t)H_ * S_, DH_, 64, 3);
  tm.o = map2d(p_o, S_, HD_, 128);
  tm.wo3 = map3d(wo, HD_, D_, 64, 3);
  tm.wo2 = map3d(wo, HD_, D_, 64, 2);
  tm.xa = map2d(p_xa, S_, D_, 64);
  tm.w1t = map3d(p_w1t, D_, D_, 80, 2);
  tm.us = map2d((const bf16*)p_us + 2 * D_, S_, D_, 64);
  tm.w2t = map3d(p_w2t, D_, D_, 80, 2);
  tm.x1 = map2d(p_x1, S_, D_, 64);
  tm.w3 = map3d(w3, D_, F_, 64, 3);
  tm.g = map2d(p_g, S_, F_, 64);
  tm.w4t = map3d(p_w4t, D_, F_, 80, 2);
  tm.ex = map_e(x, 128); tm.exa = map_e(p_xa, 128); tm.ex1 = map_e(p_x1, 128);
  tm.sxa = map_e(p_xa, 64); tm.sus = map_e(p_us, 64, S_ + 4); tm.sx1 = map_e(p_x1, 64); tm.sout = map_e(out, 64);
  PfList pf;
  pf.p[0] = (const uint8_t*)wo; pf.p[1] = (const uint8_t*)w3; pf.p[2] = (const uint8_t*)p_w4t;
  pf.p[3] = (const uint8_t*)x; pf.p[4] = (const uint8_t*)p_w1t; pf.p[5] = (const uint8_t*)p_w2t;

  launch(mod_kernel, dim3(120), dim3(256), 0, false, c, wmod);
  launch(ln1_kernel, dim3(256), dim3(256), 0, true, x);
  launch(fused_kernel, dim3(128), dim3(384), T_SMEM, true, tm, pf, PrepW{w1, w2, w3, w4}, x, out);
}
```

```cpp
#include <cuda_runtime.h>
#include <cuda.h>
#include <cuda_bf16.h>
#include <stdint.h>

typedef __nv_bfloat16 bf16;

constexpr int S_  = 2048;
constexpr int D_  = 640;
constexpr int H_  = 32;
constexpr int DH_ = 192;
constexpr int HD_ = H_ * DH_;
constexpr int F_  = 1536;
constexpr float LN_EPS = 1e-5f;

__device__ __forceinline__ uint32_t smem_u32(const void* p) { return (uint32_t)__cvta_generic_to_shared(p); }
__device__ __forceinline__ void mbar_init(uint32_t a, uint32_t c) { asm volatile("mbarrier.init.shared::cta.b64 [%0], %1;" :: "r"(a), "r"(c) : "memory"); }
__device__ __forceinline__ void mbar_expect(uint32_t a, uint32_t b) { asm volatile("mbarrier.arrive.expect_tx.shared::cta.b64 _, [%0], %1;" :: "r"(a), "r"(b) : "memory"); }
__device__ __forceinline__ void mbar_arrive(uint32_t a) { asm volatile("mbarrier.arrive.shared::cta.b64 _, [%0];" :: "r"(a) : "memory"); }
__device__ __forceinline__ void mbar_arrive_remote(uint32_t ra) { asm volatile("mbarrier.arrive.shared::cluster.b64 _, [%0];" :: "r"(ra) : "memory"); }
__device__ __forceinline__ uint32_t mapa(uint32_t a, uint32_t cta) { uint32_t r; asm volatile("mapa.shared::cluster.u32 %0, %1, %2;" : "=r"(r) : "r"(a), "r"(cta)); return r; }
__device__ __forceinline__ uint32_t mbar_try(uint32_t a, uint32_t ph) {
  uint32_t ok;
  asm volatile("{\n.reg .pred p;\nmbarrier.test_wait.parity.shared::cta.b64 p, [%1], %2;\nselp.u32 %0, 1, 0, p;\n}\n" : "=r"(ok) : "r"(a), "r"(ph) : "memory");
  return ok;
}
__device__ __forceinline__ void mbar_wait(uint32_t a, uint32_t ph) {
  asm volatile(
      "{\n.reg .pred p;\n.reg .u32 n;\n"
      "mov.u32 n, 0;\n"
      "SPIN:\n"
      "mbarrier.try_wait.parity.shared::cta.b64 p, [%0], %1;\n"
      "@p bra DONE;\n"
      "add.u32 n, n, 1;\n"
      "setp.le.u32 p, n, 16777216;\n"
      "@p bra SPIN;\n"
      "trap;\n"
      "DONE:\n}\n" :: "r"(a), "r"(ph) : "memory");
}
#define ELECT_ "{\n.reg .pred p;\nelect.sync _|p, 0xffffffff;\n@p "
__device__ __forceinline__ void mbar_expect_e(uint32_t a, uint32_t b) { asm volatile(ELECT_ "mbarrier.arrive.expect_tx.shared::cta.b64 _, [%0], %1;\n}\n" :: "r"(a), "r"(b) : "memory"); }
__device__ __forceinline__ void tma2d(uint32_t dst, const CUtensorMap* m, uint32_t bar, int c0, int c1) {
  asm volatile(ELECT_ "cp.async.bulk.tensor.2d.shared::cluster.global.mbarrier::complete_tx::bytes [%0], [%1, {%3, %4}], [%2];\n}\n"
               :: "r"(dst), "l"(m), "r"(bar), "r"(c0), "r"(c1) : "memory");
}
__device__ __forceinline__ void tma2d_mc(uint32_t dst, const CUtensorMap* m, uint32_t bar, int c0, int c1, uint16_t mask) {
  asm volatile(ELECT_ "cp.async.bulk.tensor.2d.shared::cluster.global.mbarrier::complete_tx::bytes.multicast::cluster [%0], [%1, {%3, %4}], [%2], %5;\n}\n"
               :: "r"(dst), "l"(m), "r"(bar), "r"(c0), "r"(c1), "h"(mask) : "memory");
}
__device__ __forceinline__ void tma3d(uint32_t dst, const CUtensorMap* m, uint32_t bar, int c0, int c1, int c2) {
  asm volatile(ELECT_ "cp.async.bulk.tensor.3d.shared::cluster.global.mbarrier::complete_tx::bytes [%0], [%1, {%3, %4, %5}], [%2];\n}\n"
               :: "r"(dst), "l"(m), "r"(bar), "r"(c0), "r"(c1), "r"(c2) : "memory");
}
__device__ __forceinline__ void tma3d_mc(uint32_t dst, const CUtensorMap* m, uint32_t bar, int c0, int c1, int c2, uint16_t mask) {
  asm volatile(ELECT_ "cp.async.bulk.tensor.3d.shared::cluster.global.mbarrier::complete_tx::bytes.multicast::cluster [%0], [%1, {%3, %4, %5}], [%2], %6;\n}\n"
               :: "r"(dst), "l"(m), "r"(bar), "r"(c0), "r"(c1), "r"(c2), "h"(mask) : "memory");
}
__device__ __forceinline__ void tma3d_mc_hint(uint32_t dst, const CUtensorMap* m, uint32_t bar, int c0, int c1, int c2, uint16_t mask, uint64_t pol) {
  asm volatile(ELECT_ "cp.async.bulk.tensor.3d.shared::cluster.global.mbarrier::complete_tx::bytes.multicast::cluster.L2::cache_hint [%0], [%1, {%3, %4, %5}], [%2], %6, %7;\n}\n"
               :: "r"(dst), "l"(m), "r"(bar), "r"(c0), "r"(c1), "r"(c2), "h"(mask), "l"(pol) : "memory");
}
__device__ __forceinline__ void bulk_load(uint32_t dst, const void* src, uint32_t bytes, uint32_t bar) {
  asm volatile(ELECT_ "cp.async.bulk.shared::cluster.global.mbarrier::complete_tx::bytes [%0], [%1], %2, [%3];\n}\n"
               :: "r"(dst), "l"(src), "r"(bytes), "r"(bar) : "memory");
}
__device__ __forceinline__ void l2_prefetch16k(const void* p) { asm volatile(ELECT_ "cp.async.bulk.prefetch.L2.global [%0], 16384;\n}\n" :: "l"(p) : "memory"); }
__device__ __forceinline__ void l2_prefetch_t2d(const CUtensorMap* m, int c0, int c1) {
  asm volatile(ELECT_ "cp.async.bulk.prefetch.tensor.2d.L2.global [%0, {%1, %2}];\n}\n" :: "l"(m), "r"(c0), "r"(c1) : "memory");
}
__device__ __forceinline__ void stg128(void* p, uint4 v) {
  asm volatile("st.global.v4.u32 [%0], {%1, %2, %3, %4};" :: "l"(p), "r"(v.x), "r"(v.y), "r"(v.z), "r"(v.w) : "memory");
}
__device__ __forceinline__ void prefetch_tmap(const CUtensorMap* m) { asm volatile("prefetch.tensormap [%0];" :: "l"(m) : "memory"); }
__device__ __forceinline__ void wg_fence() { asm volatile("wgmma.fence.sync.aligned;" ::: "memory"); }
__device__ __forceinline__ void wg_commit() { asm volatile("wgmma.commit_group.sync.aligned;" ::: "memory"); }
template <int N> __device__ __forceinline__ void wg_wait() { asm volatile("wgmma.wait_group.sync.aligned %0;" :: "n"(N) : "memory"); }
template <int N> __device__ __forceinline__ void fence_regs(float (&r)[N]) {
#pragma unroll
  for (int i = 0; i < N; i++) asm volatile("" : "+f"(r[i]) :: "memory");
}
template <int N> __device__ __forceinline__ void fence_regs(uint32_t (&r)[N]) {
#pragma unroll
  for (int i = 0; i < N; i++) asm volatile("" : "+r"(r[i]) :: "memory");
}
__device__ __forceinline__ uint64_t mkdesc(uint32_t addr, uint32_t lbo, uint32_t sbo) {
  return (uint64_t)((addr & 0x3FFFF) >> 4) | ((uint64_t)(lbo >> 4) << 16) | ((uint64_t)(sbo >> 4) << 32) | (1ull << 62);
}
__device__ __forceinline__ void bar_sync(int id, int n) { asm volatile("bar.sync %0, %1;" :: "r"(id), "r"(n) : "memory"); }
__device__ __forceinline__ void bar_arrive(int id, int n) { asm volatile("bar.arrive %0, %1;" :: "r"(id), "r"(n) : "memory"); }
__device__ __forceinline__ void cluster_sync() { asm volatile("barrier.cluster.arrive.aligned;\nbarrier.cluster.wait.aligned;" ::: "memory"); }
__device__ __forceinline__ void pdl_wait() { asm volatile("griddepcontrol.wait;" ::: "memory"); }
__device__ __forceinline__ void pdl_launch() { asm volatile("griddepcontrol.launch_dependents;" ::: "memory"); }
__device__ __forceinline__ float ex2(float x) { float y; asm("ex2.approx.ftz.f32 %0, %1;" : "=f"(y) : "f"(x)); return y; }
__device__ __forceinline__ uint32_t pack_bf16(float lo, float hi) { uint32_t r; asm("cvt.rn.bf16x2.f32 %0, %1, %2;" : "=r"(r) : "f"(hi), "f"(lo)); return r; }
__device__ __forceinline__ float bf_lo(uint32_t u) { return __uint_as_float(u << 16); }
__device__ __forceinline__ float bf_hi(uint32_t u) { return __uint_as_float(u & 0xffff0000u); }
__device__ __forceinline__ float bf_round(float x) { return __bfloat162float(__float2bfloat16_rn(x)); }
__device__ __forceinline__ float tanh_fast(float x) { float y; asm("tanh.approx.f32 %0, %1;" : "=f"(y) : "f"(x)); return y; }
__device__ __forceinline__ float gelu_tanh(float x) {
  float u = x * (0.7978845608028654f + 0.035677408136300125f * x * x);
  float hx = 0.5f * x;
  return fmaf(hx, tanh_fast(u), hx);
}
__device__ __forceinline__ float warp_sum(float v) {
#pragma unroll
  for (int o = 16; o > 0; o >>= 1) v += __shfl_xor_sync(0xffffffffu, v, o);
  return v;
}
__device__ __forceinline__ void quad_transpose(uint32_t& v0, uint32_t& v1, uint32_t& v2, uint32_t& v3, int lane) {
  const bool b0 = lane & 1, b1 = lane & 2;
  uint32_t s0 = b0 ? v0 : v1, s1 = b0 ? v2 : v3;
  s0 = __shfl_xor_sync(0xffffffffu, s0, 1); s1 = __shfl_xor_sync(0xffffffffu, s1, 1);
  if (b0) { v0 = s0; v2 = s1; } else { v1 = s0; v3 = s1; }
  uint32_t t0 = b1 ? v0 : v2, t1 = b1 ? v1 : v3;
  t0 = __shfl_xor_sync(0xffffffffu, t0, 2); t1 = __shfl_xor_sync(0xffffffffu, t1, 2);
  if (b1) { v0 = t0; v1 = t1; } else { v2 = t0; v3 = t1; }
}

#define TX(i)
#define TXC(i)
#define TSA(item, i)
#define TL_ENTRY(k)
#define TL_WAITED(k)
#define TL_END(k)
#define TS(item, i)
template<int TB> __device__ __forceinline__ void wgmma_rs_n64(float (&d)[32], uint32_t a0, uint32_t a1, uint32_t a2, uint32_t a3, uint64_t db, int scale_d) {
  asm volatile("{\n.reg .pred p;\nsetp.ne.b32 p, %37, 0;\n"
    "wgmma.mma_async.sync.aligned.m64n64k16.f32.bf16.bf16 {%0, %1, %2, %3, %4, %5, %6, %7, %8, %9, %10, %11, %12, %13, %14, %15, %16, %17, %18, %19, %20, %21, %22, %23, %24, %25, %26, %27, %28, %29, %30, %31}, {%32, %33, %34, %35}, %36, p, 1, 1, %38;\n}\n"
    : "+f"(d[0]), "+f"(d[1]), "+f"(d[2]), "+f"(d[3]), "+f"(d[4]), "+f"(d[5]), "+f"(d[6]), "+f"(d[7]), "+f"(d[8]), "+f"(d[9]), "+f"(d[10]), "+f"(d[11]), "+f"(d[12]), "+f"(d[13]), "+f"(d[14]), "+f"(d[15]), "+f"(d[16]), "+f"(d[17]), "+f"(d[18]), "+f"(d[19]), "+f"(d[20]), "+f"(d[21]), "+f"(d[22]), "+f"(d[23]), "+f"(d[24]), "+f"(d[25]), "+f"(d[26]), "+f"(d[27]), "+f"(d[28]), "+f"(d[29]), "+f"(d[30]), "+f"(d[31])
    : "r"(a0), "r"(a1), "r"(a2), "r"(a3), "l"(db), "r"(scale_d), "n"(TB));
}
template<int TB> __device__ __forceinline__ void wgmma_rs_n192(float (&d)[96], uint32_t a0, uint32_t a1, uint32_t a2, uint32_t a3, uint64_t db, int scale_d) {
  asm volatile("{\n.reg .pred p;\nsetp.ne.b32 p, %101, 0;\n"
    "wgmma.mma_async.sync.aligned.m64n192k16.f32.bf16.bf16 {%0, %1, %2, %3, %4, %5, %6, %7, %8, %9, %10, %11, %12, %13, %14, %15, %16, %17, %18, %19, %20, %21, %22, %23, %24, %25, %26, %27, %28, %29, %30, %31, %32, %33, %34, %35, %36, %37, %38, %39, %40, %41, %42, %43, %44, %45, %46, %47, %48, %49, %50, %51, %52, %53, %54, %55, %56, %57, %58, %59, %60, %61, %62, %63, %64, %65, %66, %67, %68, %69, %70, %71, %72, %73, %74, %75, %76, %77, %78, %79, %80, %81, %82, %83, %84, %85, %86, %87, %88, %89, %90, %91, %92, %93, %94, %95}, {%96, %97, %98, %99}, %100, p, 1, 1, %102;\n}\n"
    : "+f"(d[0]), "+f"(d[1]), "+f"(d[2]), "+f"(d[3]), "+f"(d[4]), "+f"(d[5]), "+f"(d[6]), "+f"(d[7]), "+f"(d[8]), "+f"(d[9]), "+f"(d[10]), "+f"(d[11]), "+f"(d[12]), "+f"(d[13]), "+f"(d[14]), "+f"(d[15]), "+f"(d[16]), "+f"(d[17]), "+f"(d[18]), "+f"(d[19]), "+f"(d[20]), "+f"(d[21]), "+f"(d[22]), "+f"(d[23]), "+f"(d[24]), "+f"(d[25]), "+f"(d[26]), "+f"(d[27]), "+f"(d[28]), "+f"(d[29]), "+f"(d[30]), "+f"(d[31]), "+f"(d[32]), "+f"(d[33]), "+f"(d[34]), "+f"(d[35]), "+f"(d[36]), "+f"(d[37]), "+f"(d[38]), "+f"(d[39]), "+f"(d[40]), "+f"(d[41]), "+f"(d[42]), "+f"(d[43]), "+f"(d[44]), "+f"(d[45]), "+f"(d[46]), "+f"(d[47]), "+f"(d[48]), "+f"(d[49]), "+f"(d[50]), "+f"(d[51]), "+f"(d[52]), "+f"(d[53]), "+f"(d[54]), "+f"(d[55]), "+f"(d[56]), "+f"(d[57]), "+f"(d[58]), "+f"(d[59]), "+f"(d[60]), "+f"(d[61]), "+f"(d[62]), "+f"(d[63]), "+f"(d[64]), "+f"(d[65]), "+f"(d[66]), "+f"(d[67]), "+f"(d[68]), "+f"(d[69]), "+f"(d[70]), "+f"(d[71]), "+f"(d[72]), "+f"(d[73]), "+f"(d[74]), "+f"(d[75]), "+f"(d[76]), "+f"(d[77]), "+f"(d[78]), "+f"(d[79]), "+f"(d[80]), "+f"(d[81]), "+f"(d[82]), "+f"(d[83]), "+f"(d[84]), "+f"(d[85]), "+f"(d[86]), "+f"(d[87]), "+f"(d[88]), "+f"(d[89]), "+f"(d[90]), "+f"(d[91]), "+f"(d[92]), "+f"(d[93]), "+f"(d[94]), "+f"(d[95])
    : "r"(a0), "r"(a1), "r"(a2), "r"(a3), "l"(db), "r"(scale_d), "n"(TB));
}
template<int TB> __device__ __forceinline__ void wgmma_ss_n128(float (&d)[64], uint64_t da, uint64_t db, int scale_d) {
  asm volatile("{\n.reg .pred p;\nsetp.ne.b32 p, %66, 0;\n"
    "wgmma.mma_async.sync.aligned.m64n128k16.f32.bf16.bf16 {%0, %1, %2, %3, %4, %5, %6, %7, %8, %9, %10, %11, %12, %13, %14, %15, %16, %17, %18, %19, %20, %21, %22, %23, %24, %25, %26, %27, %28, %29, %30, %31, %32, %33, %34, %35, %36, %37, %38, %39, %40, %41, %42, %43, %44, %45, %46, %47, %48, %49, %50, %51, %52, %53, %54, %55, %56, %57, %58, %59, %60, %61, %62, %63}, %64, %65, p, 1, 1, 0, %67;\n}\n"
    : "+f"(d[0]), "+f"(d[1]), "+f"(d[2]), "+f"(d[3]), "+f"(d[4]), "+f"(d[5]), "+f"(d[6]), "+f"(d[7]), "+f"(d[8]), "+f"(d[9]), "+f"(d[10]), "+f"(d[11]), "+f"(d[12]), "+f"(d[13]), "+f"(d[14]), "+f"(d[15]), "+f"(d[16]), "+f"(d[17]), "+f"(d[18]), "+f"(d[19]), "+f"(d[20]), "+f"(d[21]), "+f"(d[22]), "+f"(d[23]), "+f"(d[24]), "+f"(d[25]), "+f"(d[26]), "+f"(d[27]), "+f"(d[28]), "+f"(d[29]), "+f"(d[30]), "+f"(d[31]), "+f"(d[32]), "+f"(d[33]), "+f"(d[34]), "+f"(d[35]), "+f"(d[36]), "+f"(d[37]), "+f"(d[38]), "+f"(d[39]), "+f"(d[40]), "+f"(d[41]), "+f"(d[42]), "+f"(d[43]), "+f"(d[44]), "+f"(d[45]), "+f"(d[46]), "+f"(d[47]), "+f"(d[48]), "+f"(d[49]), "+f"(d[50]), "+f"(d[51]), "+f"(d[52]), "+f"(d[53]), "+f"(d[54]), "+f"(d[55]), "+f"(d[56]), "+f"(d[57]), "+f"(d[58]), "+f"(d[59]), "+f"(d[60]), "+f"(d[61]), "+f"(d[62]), "+f"(d[63])
    : "l"(da), "l"(db), "r"(scale_d), "n"(TB));
}
template<int TB> __device__ __forceinline__ void wgmma_ss_n192(float (&d)[96], uint64_t da, uint64_t db, int scale_d) {
  asm volatile("{\n.reg .pred p;\nsetp.ne.b32 p, %98, 0;\n"
    "wgmma.mma_async.sync.aligned.m64n192k16.f32.bf16.bf16 {%0, %1, %2, %3, %4, %5, %6, %7, %8, %9, %10, %11, %12, %13, %14, %15, %16, %17, %18, %19, %20, %21, %22, %23, %24, %25, %26, %27, %28, %29, %30, %31, %32, %33, %34, %35, %36, %37, %38, %39, %40, %41, %42, %43, %44, %45, %46, %47, %48, %49, %50, %51, %52, %53, %54, %55, %56, %57, %58, %59, %60, %61, %62, %63, %64, %65, %66, %67, %68, %69, %70, %71, %72, %73, %74, %75, %76, %77, %78, %79, %80, %81, %82, %83, %84, %85, %86, %87, %88, %89, %90, %91, %92, %93, %94, %95}, %96, %97, p, 1, 1, 0, %99;\n}\n"
    : "+f"(d[0]), "+f"(d[1]), "+f"(d[2]), "+f"(d[3]), "+f"(d[4]), "+f"(d[5]), "+f"(d[6]), "+f"(d[7]), "+f"(d[8]), "+f"(d[9]), "+f"(d[10]), "+f"(d[11]), "+f"(d[12]), "+f"(d[13]), "+f"(d[14]), "+f"(d[15]), "+f"(d[16]), "+f"(d[17]), "+f"(d[18]), "+f"(d[19]), "+f"(d[20]), "+f"(d[21]), "+f"(d[22]), "+f"(d[23]), "+f"(d[24]), "+f"(d[25]), "+f"(d[26]), "+f"(d[27]), "+f"(d[28]), "+f"(d[29]), "+f"(d[30]), "+f"(d[31]), "+f"(d[32]), "+f"(d[33]), "+f"(d[34]), "+f"(d[35]), "+f"(d[36]), "+f"(d[37]), "+f"(d[38]), "+f"(d[39]), "+f"(d[40]), "+f"(d[41]), "+f"(d[42]), "+f"(d[43]), "+f"(d[44]), "+f"(d[45]), "+f"(d[46]), "+f"(d[47]), "+f"(d[48]), "+f"(d[49]), "+f"(d[50]), "+f"(d[51]), "+f"(d[52]), "+f"(d[53]), "+f"(d[54]), "+f"(d[55]), "+f"(d[56]), "+f"(d[57]), "+f"(d[58]), "+f"(d[59]), "+f"(d[60]), "+f"(d[61]), "+f"(d[62]), "+f"(d[63]), "+f"(d[64]), "+f"(d[65]), "+f"(d[66]), "+f"(d[67]), "+f"(d[68]), "+f"(d[69]), "+f"(d[70]), "+f"(d[71]), "+f"(d[72]), "+f"(d[73]), "+f"(d[74]), "+f"(d[75]), "+f"(d[76]), "+f"(d[77]), "+f"(d[78]), "+f"(d[79]), "+f"(d[80]), "+f"(d[81]), "+f"(d[82]), "+f"(d[83]), "+f"(d[84]), "+f"(d[85]), "+f"(d[86]), "+f"(d[87]), "+f"(d[88]), "+f"(d[89]), "+f"(d[90]), "+f"(d[91]), "+f"(d[92]), "+f"(d[93]), "+f"(d[94]), "+f"(d[95])
    : "l"(da), "l"(db), "r"(scale_d), "n"(TB));
}
template<int TB> __device__ __forceinline__ void wgmma_ss_n80(float (&d)[40], uint64_t da, uint64_t db, int scale_d) {
  asm volatile("{\n.reg .pred p;\nsetp.ne.b32 p, %42, 0;\n"
    "wgmma.mma_async.sync.aligned.m64n80k16.f32.bf16.bf16 {%0, %1, %2, %3, %4, %5, %6, %7, %8, %9, %10, %11, %12, %13, %14, %15, %16, %17, %18, %19, %20, %21, %22, %23, %24, %25, %26, %27, %28, %29, %30, %31, %32, %33, %34, %35, %36, %37, %38, %39}, %40, %41, p, 1, 1, 0, %43;\n}\n"
    : "+f"(d[0]), "+f"(d[1]), "+f"(d[2]), "+f"(d[3]), "+f"(d[4]), "+f"(d[5]), "+f"(d[6]), "+f"(d[7]), "+f"(d[8]), "+f"(d[9]), "+f"(d[10]), "+f"(d[11]), "+f"(d[12]), "+f"(d[13]), "+f"(d[14]), "+f"(d[15]), "+f"(d[16]), "+f"(d[17]), "+f"(d[18]), "+f"(d[19]), "+f"(d[20]), "+f"(d[21]), "+f"(d[22]), "+f"(d[23]), "+f"(d[24]), "+f"(d[25]), "+f"(d[26]), "+f"(d[27]), "+f"(d[28]), "+f"(d[29]), "+f"(d[30]), "+f"(d[31]), "+f"(d[32]), "+f"(d[33]), "+f"(d[34]), "+f"(d[35]), "+f"(d[36]), "+f"(d[37]), "+f"(d[38]), "+f"(d[39])
    : "l"(da), "l"(db), "r"(scale_d), "n"(TB));
}

__device__ float g_mod[6 * D_];
__device__ __align__(1024) bf16 g_h[S_ * D_];
__device__ __align__(1024) bf16 g_o[S_ * HD_];
__device__ __align__(1024) bf16 g_xch[16 * 2 * 4 * 4 * 128 * 80];
__device__ __align__(1024) bf16 g_w1t[D_ * D_];
__device__ __align__(1024) bf16 g_w2t[D_ * D_];
__device__ __align__(1024) bf16 g_w4t[D_ * F_];
__device__ __align__(32) float g_st1[S_ * 8];
__device__ __align__(32) float g_st2[S_ * 2];
__device__ __align__(32) float g_vec[3 * D_ + F_ + 8];
__device__ unsigned g_flag[1024];
enum { F_XCH = 0, F_XA = 256, F_US = 272, F_X1 = 288, F_G = 304, F_PREP = 320, F_O = 512 };
__device__ __align__(1024) bf16 g_xa[S_ * D_];
__device__ __align__(1024) bf16 g_us[(S_ + 4) * D_];
__device__ __align__(1024) bf16 g_x1[S_ * D_];
__device__ __align__(1024) bf16 g_g[S_ * F_];

__global__ void __launch_bounds__(256) mod_kernel(const bf16* __restrict__ c, const bf16* __restrict__ w_mod) {
  TL_ENTRY(0);
  pdl_launch();
  __shared__ float red[8][32];
  if (blockIdx.x < 14) { const int i = blockIdx.x * 256 + threadIdx.x; if (i < 3 * D_ + F_) g_vec[i] = 0.f; }
  else if (blockIdx.x < 18) g_flag[(blockIdx.x - 14) * 256 + threadIdx.x] = 0u;
  const int t = threadIdx.x, cg = t & 3, r0 = t >> 2;
  const int col0 = blockIdx.x * 32 + cg * 8;
  uint4 w[10];
#pragma unroll
  for (int i = 0; i < 10; i++) w[i] = __ldg(reinterpret_cast<const uint4*>(w_mod + (size_t)(r0 + 64 * i) * (6 * D_) + col0));
  float acc[8];
#pragma unroll
  for (int j = 0; j < 8; j++) acc[j] = 0.f;
#pragma unroll
  for (int i = 0; i < 10; i++) {
    float cv = __bfloat162float(c[r0 + 64 * i]);
    float s = bf_round(cv / (1.f + __expf(-cv)));
    acc[0] = fmaf(s, bf_lo(w[i].x), acc[0]); acc[1] = fmaf(s, bf_hi(w[i].x), acc[1]);
    acc[2] = fmaf(s, bf_lo(w[i].y), acc[2]); acc[3] = fmaf(s, bf_hi(w[i].y), acc[3]);
    acc[4] = fmaf(s, bf_lo(w[i].z), acc[4]); acc[5] = fmaf(s, bf_hi(w[i].z), acc[5]);
    acc[6] = fmaf(s, bf_lo(w[i].w), acc[6]); acc[7] = fmaf(s, bf_hi(w[i].w), acc[7]);
  }
#pragma unroll
  for (int j = 0; j < 8; j++) {
    acc[j] += __shfl_xor_sync(0xffffffffu, acc[j], 4);
    acc[j] += __shfl_xor_sync(0xffffffffu, acc[j], 8);
    acc[j] += __shfl_xor_sync(0xffffffffu, acc[j], 16);
  }
  if ((t & 31) < 4) {
#pragma unroll
    for (int j = 0; j < 8; j++) red[t >> 5][cg * 8 + j] = acc[j];
  }
  __syncthreads();
  if (t < 32) {
    float s = 0.f;
#pragma unroll
    for (int w8 = 0; w8 < 8; w8++) s += red[w8][t];
    const int col = blockIdx.x * 32 + t;
    s = bf_round(s);
    const int part = col / D_;
    if (part == 1 || part == 4) s = bf_round(1.f + s);
    g_mod[col] = s;
    if (t == 0) TL_END(0);
  }
}

__device__ __forceinline__ void row_stats(const float (&v)[20], float& mean, float& rstd) {
  float s = 0.f;
#pragma unroll
  for (int i = 0; i < 20; i++) s += v[i];
  mean = warp_sum(s) * (1.f / D_);
  float q = 0.f;
#pragma unroll
  for (int i = 0; i < 20; i++) { float d = v[i] - mean; q = fmaf(d, d, q); }
  rstd = rsqrtf(warp_sum(q) * (1.f / D_) + LN_EPS);
}
__device__ __forceinline__ void load_row_bf16(const bf16* p, int lane, float (&v)[20]) {
#pragma unroll
  for (int i = 0; i < 5; i++) {
    uint2 u = *reinterpret_cast<const uint2*>(p + (lane + 32 * i) * 4);
    v[4 * i] = bf_lo(u.x); v[4 * i + 1] = bf_hi(u.x); v[4 * i + 2] = bf_lo(u.y); v[4 * i + 3] = bf_hi(u.y);
  }
}
__device__ __forceinline__ void store_row_bf16(bf16* p, int lane, const float (&v)[20]) {
#pragma unroll
  for (int i = 0; i < 5; i++) {
    uint2 u; u.x = pack_bf16(v[4 * i], v[4 * i + 1]); u.y = pack_bf16(v[4 * i + 2], v[4 * i + 3]);
    *reinterpret_cast<uint2*>(p + (lane + 32 * i) * 4) = u;
  }
}
__device__ __forceinline__ void load_row_f32(const float* p, int lane, float (&v)[20]) {
#pragma unroll
  for (int i = 0; i < 5; i++) {
    float4 u = *reinterpret_cast<const float4*>(p + (lane + 32 * i) * 4);
    v[4 * i] = u.x; v[4 * i + 1] = u.y; v[4 * i + 2] = u.z; v[4 * i + 3] = u.w;
  }
}

__global__ void __launch_bounds__(256) ln1_kernel(const bf16* __restrict__ x) {
  TL_ENTRY(1);
  pdl_launch();
  const int lane = threadIdx.x & 31, row = blockIdx.x * 8 + (threadIdx.x >> 5);
  float v[20];
  load_row_bf16(x + (size_t)row * D_, lane, v);
  float mean, rstd;
  row_stats(v, mean, rstd);
  if (lane < 8) g_st1[row * 8 + lane] = 0.f;
  if (lane < 2) g_st2[row * 2 + lane] = 0.f;
  pdl_wait();
  if (threadIdx.x == 0) TL_WAITED(1);
  float sa[20], ca[20];
  load_row_f32(g_mod, lane, sa);
  load_row_f32(g_mod + D_, lane, ca);
#pragma unroll
  for (int i = 0; i < 20; i++) v[i] = fmaf((v[i] - mean) * rstd, ca[i], sa[i]);
  store_row_bf16(g_h + (size_t)row * D_, lane, v);
  if (threadIdx.x == 0) TL_END(1);
}

constexpr int PREP_JOBS = 200 + 200 + 480 + 480;
struct PrepW { const bf16 *w1, *w2, *w3, *w4; };
__device__ __forceinline__ void prep_warp(const PrepW& pw, bf16 (*tile)[72], int lane) {
#pragma unroll 1
  for (int job = blockIdx.x; job < PREP_JOBS; job += gridDim.x) {
    const bf16* src; bf16* dst; int ld = D_, ldd = D_, kt, nt, kind = 1;
    if (job < 200) { src = pw.w1; dst = g_w1t; kt = job / 10; nt = job % 10; kind = 0; }
    else if (job < 400) { src = pw.w2; dst = g_w2t; kt = (job - 200) / 10; nt = (job - 200) % 10; }
    else if (job < 880) { src = pw.w4; dst = g_w4t; ldd = F_; kt = (job - 400) / 10; nt = (job - 400) % 10; }
    else { src = pw.w3; dst = nullptr; ld = F_; kt = (job - 880) / 24; nt = (job - 880) % 24; kind = 2; }
    src += (size_t)(kt * 32 + (lane >> 3)) * ld + nt * 64 + (lane & 7) * 8;
    __syncwarp();
#pragma unroll
    for (int h = 0; h < 2; h++) {
      uint4 v[4];
#pragma unroll
      for (int i = 0; i < 4; i++) v[i] = __ldg(reinterpret_cast<const uint4*>(src + (size_t)(h * 16 + i * 4) * ld));
#pragma unroll
      for (int i = 0; i < 4; i++) *reinterpret_cast<uint4*>(&tile[h * 16 + i * 4 + (lane >> 3)][(lane & 7) * 8]) = v[i];
    }
    __syncwarp();
    const float* pa = g_mod + 4 * D_ + kt * 32;
    const float* pb = g_mod + 3 * D_ + kt * 32;
#pragma unroll 1
    for (int h = 0; h < 2; h++) {
      const int n = lane + 32 * h;
      float sa = 0.f, sb = 0.f, sc = 0.f;
#pragma unroll 1
      for (int c = 0; c < 4; c++) {
        uint32_t u[4];
#pragma unroll
        for (int e = 0; e < 4; e++) {
          const int k = c * 8 + 2 * e;
          float lo = __bfloat162float(tile[k][n]), hi = __bfloat162float(tile[k + 1][n]);
          sc += lo + hi;
          if (kind == 0) {
            const float2 a = __ldcg(reinterpret_cast<const float2*>(pa + k)), b = __ldcg(reinterpret_cast<const float2*>(pb + k));
            sb = fmaf(b.x, lo, fmaf(b.y, hi, sb));
            lo *= a.x; hi *= a.y;
          }
          u[e] = pack_bf16(lo, hi);
          sa += bf_lo(u[e]) + bf_hi(u[e]);
        }
        if (kind != 2) *reinterpret_cast<uint4*>(dst + (size_t)(nt * 64 + n) * ldd + kt * 32 + c * 8) = make_uint4(u[0], u[1], u[2], u[3]);
      }
      if (kind == 0) { atomicAdd(&g_vec[nt * 64 + n], sa); atomicAdd(&g_vec[D_ + nt * 64 + n], sb); atomicAdd(&g_vec[2 * D_ + nt * 64 + n], sc); }
      else if (kind == 2) atomicAdd(&g_vec[3 * D_ + nt * 64 + n], sc);
    }
  }
  __syncwarp();
  if (lane == 0) {
    asm volatile("fence.acq_rel.gpu;" ::: "memory");
    asm volatile("red.relaxed.gpu.global.add.u32 [%0], 1;" :: "l"(g_flag + F_PREP) : "memory");
  }
}

constexpr int A_NSLOT = 9;
constexpr int A_SLOT = 24576;
constexpr int A_NKV = S_ / 64;
constexpr int PREP_CTAS = 128;

struct Ring {
  uint32_t slot, phase;
  __device__ __forceinline__ void adv(int n) { if (++slot == (uint32_t)n) { slot = 0; phase ^= 1; } }
};
constexpr int T_PAR = A_NSLOT * A_SLOT + 384;
constexpr int T_PREP = T_PAR + 3712;
constexpr int T_SMEM = T_PREP + 32 * 72 * 2 + 1024;
enum { P_OGA = 0, P_OA = 80, P_OB = 160, P_VA = 240, P_VB = 320, P_VC = 400, P_A2 = 480, P_B2 = 560, P_GB = 640, P_CS3 = 720, P_SC = 912 };

__device__ __forceinline__ void flag_wait(const unsigned* p, unsigned target) {
  asm volatile(
      "{\n.reg .pred p;\n.reg .u32 n, v;\n"
      "mov.u32 n, 0;\n"
      "SPIN:\n"
      "ld.relaxed.gpu.global.u32 v, [%0];\n"
      "setp.ge.u32 p, v, %1;\n"
      "@p bra DONE;\n"
      "add.u32 n, n, 1;\n"
      "setp.gt.u32 p, n, 4194304;\n"
      "@p trap;\n"
      "bra SPIN;\n"
      "DONE:\n}\n" :: "l"(p), "r"(target) : "memory");
}
__device__ __forceinline__ void fence_async_global() { asm volatile("fence.proxy.async.global;" ::: "memory"); }
__device__ __forceinline__ float lds_f(uint32_t a) { float v; asm volatile("ld.shared.f32 %0, [%1];" : "=f"(v) : "r"(a)); return v; }
__device__ __forceinline__ float2 lds_f2(uint32_t a) { float2 v; asm volatile("ld.shared.v2.f32 {%0, %1}, [%2];" : "=f"(v.x), "=f"(v.y) : "r"(a)); return v; }
__device__ __forceinline__ uint4 ldcg4(const void* p) { return __ldcg(reinterpret_cast<const uint4*>(p)); }

__device__ __forceinline__ void sts_f2(uint32_t a, float x, float y) { asm volatile("st.shared.v2.f32 [%0], {%1, %2};" :: "r"(a), "f"(x), "f"(y) : "memory"); }
__device__ __forceinline__ void sts_u4(uint32_t a, uint4 v) { asm volatile("st.shared.v4.u32 [%0], {%1, %2, %3, %4};" :: "r"(a), "r"(v.x), "r"(v.y), "r"(v.z), "r"(v.w) : "memory"); }
__device__ __forceinline__ void sts_u1(uint32_t a, uint32_t v) { asm volatile("st.shared.u32 [%0], %1;" :: "r"(a), "r"(v) : "memory"); }
__device__ __forceinline__ void fence_async_smem() { asm volatile("fence.proxy.async.shared::cta;" ::: "memory"); }
__device__ __forceinline__ void bulk_store(void* dst, uint32_t src, uint32_t bytes) {
  asm volatile("cp.async.bulk.global.shared::cta.bulk_group [%0], [%1], %2;" :: "l"(dst), "r"(src), "r"(bytes) : "memory");
}
__device__ __forceinline__ void bulk_red_f32(void* dst, uint32_t src, uint32_t bytes) {
  asm volatile("cp.reduce.async.bulk.global.shared::cta.bulk_group.add.f32 [%0], [%1], %2;" :: "l"(dst), "r"(src), "r"(bytes) : "memory");
}
__device__ __forceinline__ void tma_store2d(const CUtensorMap* m, uint32_t src, int c0, int c1) {
  asm volatile("cp.async.bulk.tensor.2d.global.shared::cta.bulk_group [%0, {%2, %3}], [%1];" :: "l"(m), "r"(src), "r"(c0), "r"(c1) : "memory");
}
__device__ __forceinline__ void bulk_done() { asm volatile("cp.async.bulk.commit_group;\ncp.async.bulk.wait_group 0;" ::: "memory"); }
__device__ __forceinline__ void flag_add(unsigned* f) { asm volatile("red.relaxed.gpu.global.add.u32 [%0], 1;" :: "l"(f) : "memory"); }
__device__ __forceinline__ float4 lds_f4(uint32_t a) { float4 v; asm volatile("ld.shared.v4.f32 {%0, %1, %2, %3}, [%4];" : "=f"(v.x), "=f"(v.y), "=f"(v.z), "=f"(v.w) : "r"(a) : "memory"); return v; }
__device__ __forceinline__ uint4 lds_u4(uint32_t a) { uint4 v; asm volatile("ld.shared.v4.u32 {%0, %1, %2, %3}, [%4];" : "=r"(v.x), "=r"(v.y), "=r"(v.z), "=r"(v.w) : "r"(a) : "memory"); return v; }
__device__ __forceinline__ void lds8(uint32_t a, float (&v)[8]) {
  const float4 p = lds_f4(a), q = lds_f4(a + 16);
  v[0] = p.x; v[1] = p.y; v[2] = p.z; v[3] = p.w; v[4] = q.x; v[5] = q.y; v[6] = q.z; v[7] = q.w;
}
__device__ __forceinline__ void lds8_bf(uint32_t a, float (&v)[8]) {
  const uint4 u = lds_u4(a);
  v[0] = bf_lo(u.x); v[1] = bf_hi(u.x); v[2] = bf_lo(u.y); v[3] = bf_hi(u.y); v[4] = bf_lo(u.z); v[5] = bf_hi(u.z); v[6] = bf_lo(u.w); v[7] = bf_hi(u.w);
}
__device__ __forceinline__ uint4 pack8(const float (&v)[8]) {
  return make_uint4(pack_bf16(v[0], v[1]), pack_bf16(v[2], v[3]), pack_bf16(v[4], v[5]), pack_bf16(v[6], v[7]));
}
__device__ __forceinline__ void mbar_wait_c(uint32_t a, uint32_t ph) {
  asm volatile("{\n.reg .pred p;\nSPIN:\nmbarrier.try_wait.parity.shared::cta.b64 p, [%0], %1;\n@!p bra SPIN;\n}\n" :: "r"(a), "r"(ph) : "memory");
}
constexpr int ST_P = 80;
constexpr int E_TILE = 128 * 80 * 2;

struct Maps { CUtensorMap h, wq, k, v, o, wo3, wo2, xa, w1t, us, w2t, x1, w3, g, w4t, ex, exa, ex1, sxa, sus, sx1, sout; };
struct PfList { const uint8_t* p[6]; };

constexpr int M_AOFF = 102400, M_NA = 7;

__global__ void __cluster_dims__(2, 1, 1) __launch_bounds__(384, 1)
fused_kernel(const __grid_constant__ Maps tm, const __grid_constant__ PfList pf, const __grid_constant__ PrepW pw, const bf16* __restrict__ x, bf16* __restrict__ out) {
  extern __shared__ uint8_t smem_raw[];
  const uint32_t sb = (smem_u32(smem_raw) + 1023) & ~1023u;
  TL_ENTRY(2);
  const uint32_t bar_full = sb + A_NSLOT * A_SLOT;
  const uint32_t bar_empty = bar_full + 8 * A_NSLOT;
  const uint32_t bar_sig = bar_empty + 8 * A_NSLOT;
  const uint32_t mb_full = bar_sig + 16;
  const uint32_t mb_empty = mb_full + 96;
  const uint32_t par = sb + T_PAR;
  float* parf = reinterpret_cast<float*>(smem_raw + (par - smem_u32(smem_raw)));
  uint32_t rank;
  asm volatile("mov.u32 %0, %%cluster_ctarank;" : "=r"(rank));
  const int cid = blockIdx.x >> 1;
  const int wid = __shfl_sync(0xffffffffu, threadIdx.x >> 5, 0);
  const int wg = wid >> 2;
  const int qtile = (cid & 7) * 2 + rank, hbase = cid >> 3;
  const int o_qt = qtile, o_nh = (cid >> 3) & 1, o_ks = cid >> 4;
  const int o_col = o_nh * 320 + o_ks * 80;
  const int qt = cid >> 2, js = (cid & 3) * 2 + rank;
  if (threadIdx.x == 0) {
    for (int i = 0; i < A_NSLOT; i++) { mbar_init(bar_full + 8 * i, 1); mbar_init(bar_empty + 8 * i, 16); }
    mbar_init(bar_sig, 4); mbar_init(bar_sig + 8, 4);
    for (int i = 0; i < 12; i++) { mbar_init(mb_full + 8 * i, 1); mbar_init(mb_empty + 8 * i, i < 5 ? 8 : 16); }
    asm volatile("fence.mbarrier_init.release.cluster;" ::: "memory");
    prefetch_tmap(&tm.h); prefetch_tmap(&tm.wq); prefetch_tmap(&tm.k); prefetch_tmap(&tm.v);
  }
  __syncthreads();
  cluster_sync();

  if (wg == 0) {
    asm volatile("setmaxnreg.dec.sync.aligned.u32 40;");
    if (wid == 0) {
      Ring r{0, 1};
#define P_ACQ(bytes_) do { mbar_wait(bar_empty + 8 * r.slot, r.phase); mbar_expect_e(bar_full + 8 * r.slot, bytes_); } while (0)
#define P_DST (sb + r.slot * A_SLOT)
#define P_BAR (bar_full + 8 * r.slot)
      uint64_t pol_ef;
      asm volatile("createpolicy.fractional.L2::evict_first.b64 %0, 1.0;" : "=l"(pol_ef));
      pdl_wait();
      TL_WAITED(2);
#pragma unroll 1
      for (int item = 0; item < 4; item++) {
        const int head = hbase + 8 * item;
#pragma unroll 1
        for (int kb = 0; kb < 10; kb++) {
          P_ACQ(16384);
          tma2d(P_DST, &tm.h, P_BAR, kb * 64, qtile * 128);
          r.adv(A_NSLOT);
          P_ACQ(A_SLOT);
          if ((uint32_t)(kb & 1) == rank) tma3d_mc_hint(P_DST, &tm.wq, P_BAR, 0, kb * 64, head * 3, 3, pol_ef);
          r.adv(A_NSLOT);
        }
#pragma unroll 1
        for (int j = 0; j <= A_NKV; j++) {
          if (j < A_NKV) {
            P_ACQ(A_SLOT);
            if (rank == 0) tma3d_mc_hint(P_DST, &tm.k, P_BAR, 0, head * S_ + j * 64, 0, 3, pol_ef);
            r.adv(A_NSLOT);
          }
          if (j > 0) {
            P_ACQ(A_SLOT);
            if (rank == 1) tma3d_mc_hint(P_DST, &tm.v, P_BAR, 0, head * S_ + (j - 1) * 64, 0, 3, pol_ef);
            r.adv(A_NSLOT);
          }
          if (item == 3 && (j & 3) == 0) {
            const int c = (j >> 2) * 128 + blockIdx.x;
            if (c < 980) {
              const int li = c < 480 ? 0 : c < 600 ? 1 : c < 720 ? 2 : c < 880 ? 3 : c < 930 ? 4 : 5;
              const int c0 = c < 480 ? 0 : c < 600 ? 480 : c < 720 ? 600 : c < 880 ? 720 : c < 930 ? 880 : 930;
              l2_prefetch16k(pf.p[li] + (size_t)(c - c0) * 16384);
            }
          }
          if (item == 3) {
            if (j >= 6 && j < 24) {
              const int kb = j - 6;
              l2_prefetch_t2d(&tm.o, ((kb / 6) * 8 + 2 * o_ks + (kb % 6) / 3) * DH_ + (kb % 3) * 64, o_qt * 128);
            }
            if (j >= 24 && j < 30) flag_wait(g_flag + F_O + o_qt * 32 + ((j - 24) >> 1) * 8 + 2 * o_ks + (j & 1), 2);
            if (j == 0 && threadIdx.x == 0) {
              prefetch_tmap(&tm.o); prefetch_tmap(&tm.wo3); prefetch_tmap(&tm.wo2); prefetch_tmap(&tm.xa); prefetch_tmap(&tm.w1t); prefetch_tmap(&tm.us);
              prefetch_tmap(&tm.w2t); prefetch_tmap(&tm.x1); prefetch_tmap(&tm.w3); prefetch_tmap(&tm.g); prefetch_tmap(&tm.w4t);
              prefetch_tmap(&tm.ex); prefetch_tmap(&tm.exa); prefetch_tmap(&tm.ex1);
              prefetch_tmap(&tm.sxa); prefetch_tmap(&tm.sus); prefetch_tmap(&tm.sx1); prefetch_tmap(&tm.sout);
            }
          }
        }
      }
#pragma unroll 1
      for (int kb = 0; kb < 24; kb++) {
        const int head = (kb / 6) * 8 + 2 * o_ks + (kb % 6) / 3;
        const int kcol = head * DH_ + (kb % 3) * 64;
        P_ACQ(24576);
        if (rank == 0) tma3d_mc(P_DST, &tm.wo3, P_BAR, 0, kcol, o_nh * 5, 3);
        r.adv(A_NSLOT);
        P_ACQ(16384);
        if (rank == 1) tma3d_mc(P_DST, &tm.wo2, P_BAR, 0, kcol, o_nh * 5 + 3, 3);
        r.adv(A_NSLOT);
        if (kb == 18 || kb == 21) flag_wait(g_flag + F_O + o_qt * 32 + head, 2);
        if (kb % 3 == 0) fence_async_global();
        P_ACQ(16384);
        tma2d(P_DST, &tm.o, P_BAR, kcol, o_qt * 128);
        r.adv(A_NSLOT);
      }
      P_ACQ(E_TILE);
      tma2d(P_DST, &tm.ex, P_BAR, o_col, o_qt * 128);
      r.adv(A_NSLOT);
      flag_wait(g_flag + F_XCH + (o_qt * 2 + o_nh) * 4 + o_ks, 6);
      fence_async_global();
#pragma unroll 1
      for (int i = 0; i < 3; i++) {
        P_ACQ(E_TILE);
        bulk_load(P_DST, g_xch + (size_t)((((o_qt * 2 + o_nh) * 4 + o_ks) * 4) + ((o_ks + 1 + i) & 3)) * (E_TILE / 2), E_TILE, P_BAR);
        r.adv(A_NSLOT);
      }
      flag_wait(g_flag + F_PREP, PREP_CTAS);
      fence_async_global();
#pragma unroll 1
      for (int i = 0; i < A_NSLOT; i++) { mbar_wait(bar_empty + 8 * r.slot, r.phase); r.adv(A_NSLOT); }
      Ring ra{0, 1};
      uint32_t bpar = 0x1f;
#pragma unroll 1
      for (int ph = 0; ph < 4; ph++) {
        const CUtensorMap* ma = ph == 0 ? &tm.xa : ph == 1 ? &tm.us : ph == 2 ? &tm.x1 : &tm.g;
        const CUtensorMap* mb = ph == 0 ? &tm.w1t : ph == 1 ? &tm.w2t : ph == 2 ? &tm.w3 : &tm.w4t;
        const int nkb = ph == 3 ? 24 : 10;
        const int nbl = ph == 2 ? 10 : nkb / 2;
        const int nel = ph == 1 ? 1 : ph == 3 ? 2 : 0;
        const uint32_t nbs = ph == 2 ? 4 : 5, bsz = ph == 2 ? 24576 : 20480;
        int bl = 0; uint32_t bs = 0;
#pragma unroll 1
        for (int i = 0; i < 5; i++) mbar_wait(mb_empty + 8 * i, (bpar >> i) & 1);
#define T_LOADB() do { mbar_wait(mb_empty + 8 * bs, (bpar >> bs) & 1); bpar ^= 1u << bs; mbar_expect_e(mb_full + 8 * bs, bsz);    \
                       if (bl < nbl) tma3d(sb + bs * bsz, mb, mb_full + 8 * bs, 0, ph == 2 ? bl * 64 : js * 80, ph == 2 ? js * 3 : bl * 2); \
                       else tma2d(sb + bs * bsz, bl == nbl ? &tm.exa : &tm.ex1, mb_full + 8 * bs, js * 80, qt * 128); \
                       bl++; if (++bs == nbs) bs = 0; } while (0)
#pragma unroll 1
        for (uint32_t i = 0; i < nbs; i++) T_LOADB();
        TX(8 + ph * 4);
        const unsigned* fl = g_flag + F_XA + 16 * ph;
        flag_wait(fl + qt, 16);
        if (ph == 1) { if (qt > 0) flag_wait(fl + qt - 1, 16); if (qt < 15) flag_wait(fl + qt + 1, 16); }
        TX(9 + ph * 4);
        fence_async_global();
#pragma unroll 1
        for (int kb = 0; kb < nkb; kb++) {
          mbar_wait(mb_empty + 40 + 8 * ra.slot, ra.phase);
          mbar_expect_e(mb_full + 40 + 8 * ra.slot, 16384);
          tma2d_mc(sb + M_AOFF + ra.slot * 16384 + rank * 8192, ma, mb_full + 40 + 8 * ra.slot, kb * 64, qt * 128 + (int)rank * 64, 3);
          ra.adv(M_NA);
          while (bl < nbl + nel && (kb == nkb - 1 || kb >= (ph == 2 ? bl + 2 : 2 * bl - 3))) T_LOADB();
        }
      }
    } else if (wid < 3) {
      const int w = wid - 1, lane = threadIdx.x & 31;
#pragma unroll 1
      for (int sig = 0; sig < 4; sig++) {
        mbar_wait(bar_sig + 8 * w, sig & 1);
        if (lane == 0) {
          asm volatile("fence.acq_rel.gpu;" ::: "memory");
          flag_add(g_flag + F_O + qtile * 32 + hbase + 8 * sig);
        }
        __syncwarp();
      }
    } else {
      const int lane = threadIdx.x & 31;
      pdl_wait();
      prep_warp(pw, reinterpret_cast<bf16(*)[72]>(smem_raw + (sb + T_PREP - smem_u32(smem_raw))), lane);
      flag_wait(g_flag + F_PREP, PREP_CTAS);
#pragma unroll 1
      for (int i = lane; i < P_SC; i += 32) {
        const int v = i < P_CS3 ? i / 80 : 9, j = i - (i < P_CS3 ? v * 80 : P_CS3);
        const float* src = v == 0 ? g_mod + 2 * D_ + o_col : v == 1 ? g_mod + 4 * D_ + o_col : v == 2 ? g_mod + 3 * D_ + o_col
                         : v < 6 ? g_vec + (v - 3) * D_ + js * 80 : v == 6 ? g_mod + 4 * D_ + js * 80 : v == 7 ? g_mod + 3 * D_ + js * 80
                         : v == 8 ? g_mod + 5 * D_ + js * 80 : g_vec + 3 * D_ + js * 192;
        parf[i] = __ldcg(src + j);
      }
      float sv[5] = {0.f, 0.f, 0.f, 0.f, 0.f};
#pragma unroll 1
      for (int i = lane; i < D_; i += 32) {
        const float a = __ldcg(g_mod + 4 * D_ + i), b = __ldcg(g_mod + 3 * D_ + i);
        sv[0] += a; sv[1] = fmaf(a, a, sv[1]); sv[2] = fmaf(a, b, sv[2]); sv[3] += b; sv[4] = fmaf(b, b, sv[4]);
      }
#pragma unroll 1
      for (int o_ = 16; o_ > 0; o_ >>= 1) {
#pragma unroll
        for (int i = 0; i < 5; i++) sv[i] += __shfl_xor_sync(0xffffffffu, sv[i], o_);
      }
      if (lane == 0) {
#pragma unroll
        for (int i = 0; i < 5; i++) parf[P_SC + i] = sv[i];
      }
      bar_arrive(6, 288);
    }
    __syncwarp();
    cluster_sync();
  } else {
    asm volatile("setmaxnreg.inc.sync.aligned.u32 232;");
    const int w = wg - 1;
    const int lane = threadIdx.x & 31;
    const int warp = wid & 3;
    const int tid = threadIdx.x - 128;
    const uint32_t rel_base = mapa(bar_empty, (lane == 0) ? rank : (rank ^ 1));
    Ring r{0, 0};
#define A_RELEASE(slot_) do { if (lane < 2) mbar_arrive_remote(rel_base + 8 * (slot_)); } while (0)
#define SIGNAL() do { __syncwarp(); if (lane == 0) mbar_arrive(bar_sig + 8 * w); } while (0)
    {
    const float SC = 0.07216878364870322f * 1.4426950408889634f;
    float o[96];
    uint32_t q[48];
    float s[32];
    uint32_t p[16], p2[16];
    if (w == 1) bar_arrive(1, 256);
    for (int item = 0; item < 4; item++) {
      const int head = hbase + 8 * item;
      TSA(item, 0);
      uint32_t prevA = 0, prevB = 0;
      for (int kb = 0; kb < 10; kb++) {
        const uint32_t sA = r.slot; mbar_wait_c(bar_full + 8 * sA, r.phase); r.adv(A_NSLOT);
        const uint32_t sB = r.slot; mbar_wait_c(bar_full + 8 * sB, r.phase); r.adv(A_NSLOT);
        const uint64_t da = mkdesc(sb + sA * A_SLOT + w * 8192, 16, 1024);
        const uint64_t db = mkdesc(sb + sB * A_SLOT, 8192, 1024);
        wg_fence();
#pragma unroll
        for (int kk = 0; kk < 4; kk++) wgmma_ss_n192<1>(o, da + kk * 2, db + kk * 128, (kb | kk) != 0);
        wg_commit();
        if (kb > 0) { wg_wait<1>(); A_RELEASE(prevA); A_RELEASE(prevB); }
        prevA = sA; prevB = sB;
      }
      wg_wait<0>();
      fence_regs(o);
      A_RELEASE(prevA); A_RELEASE(prevB);
#pragma unroll
      for (int i = 0; i < 48; i++) q[i] = pack_bf16(o[2 * i], o[2 * i + 1]);

      TSA(item, 1);
      float c0, c1, l0, l1;
      {
        const uint32_t sK = r.slot; mbar_wait_c(bar_full + 8 * sK, r.phase); r.adv(A_NSLOT);
        const uint64_t dk = mkdesc(sb + sK * A_SLOT, 16, 1024);
        bar_sync(1 + w, 256);
        wg_fence();
#pragma unroll
        for (int kk = 0; kk < 12; kk++)
          wgmma_rs_n64<0>(s, q[4 * kk], q[4 * kk + 1], q[4 * kk + 2], q[4 * kk + 3], dk + (kk >> 2) * 512 + (kk & 3) * 2, kk != 0);
        wg_commit();
        bar_arrive(1 + (w ^ 1), 256);
        wg_wait<0>();
        fence_regs(s);
        A_RELEASE(sK);
        float mx0 = fmaxf(s[0], s[1]), mx1 = fmaxf(s[2], s[3]);
#pragma unroll
        for (int i = 1; i < 8; i++) { mx0 = fmaxf(mx0, fmaxf(s[4 * i], s[4 * i + 1])); mx1 = fmaxf(mx1, fmaxf(s[4 * i + 2], s[4 * i + 3])); }
        mx0 = fmaxf(mx0, __shfl_xor_sync(0xffffffffu, mx0, 1)); mx1 = fmaxf(mx1, __shfl_xor_sync(0xffffffffu, mx1, 1));
        mx0 = fmaxf(mx0, __shfl_xor_sync(0xffffffffu, mx0, 2)); mx1 = fmaxf(mx1, __shfl_xor_sync(0xffffffffu, mx1, 2));
        c0 = mx0 * SC; c1 = mx1 * SC;
        l0 = 0.f; l1 = 0.f;
#pragma unroll
        for (int i = 0; i < 8; i++) {
          s[4 * i] = ex2(fmaf(s[4 * i], SC, -c0)); s[4 * i + 1] = ex2(fmaf(s[4 * i + 1], SC, -c0));
          s[4 * i + 2] = ex2(fmaf(s[4 * i + 2], SC, -c1)); s[4 * i + 3] = ex2(fmaf(s[4 * i + 3], SC, -c1));
          l0 += s[4 * i] + s[4 * i + 1]; l1 += s[4 * i + 2] + s[4 * i + 3];
        }
#pragma unroll
        for (int i = 0; i < 16; i++) p[i] = pack_bf16(s[2 * i], s[2 * i + 1]);
      }
      TSA(item, 2);
      uint32_t okn;
      {
        Ring r2 = r; r2.adv(A_NSLOT);
        okn = mbar_try(bar_full + 8 * r.slot, r.phase) & mbar_try(bar_full + 8 * r2.slot, r2.phase);
      }
#define A_STEP(PC, PN, FIRST)                                                                                          \
      {                                                                                                                \
        const uint32_t sK = r.slot, phK = r.phase; r.adv(A_NSLOT);                                                     \
        const uint32_t sV = r.slot, phV = r.phase; r.adv(A_NSLOT);                                                     \
        const uint64_t dk = mkdesc(sb + sK * A_SLOT, 16, 1024);                                                        \
        const uint64_t dv = mkdesc(sb + sV * A_SLOT, 8192, 1024);                                                      \
        if (!okn) { mbar_wait_c(bar_full + 8 * sK, phK); mbar_wait_c(bar_full + 8 * sV, phV); }                            \
        bar_sync(1 + w, 256);                                                                                          \
        wg_fence();                                                                                                    \
        _Pragma("unroll") for (int kk = 0; kk < 12; kk++)                                                              \
          wgmma_rs_n64<0>(s, q[4 * kk], q[4 * kk + 1], q[4 * kk + 2], q[4 * kk + 3], dk + (kk >> 2) * 512 + (kk & 3) * 2, kk != 0); \
        wg_commit();                                                                                                   \
        _Pragma("unroll") for (int kk = 0; kk < 4; kk++)                                                               \
          wgmma_rs_n192<1>(o, PC[4 * kk], PC[4 * kk + 1], PC[4 * kk + 2], PC[4 * kk + 3], dv + kk * 128, !(FIRST) || (kk != 0)); \
        wg_commit();                                                                                                   \
        bar_arrive(1 + (w ^ 1), 256);                                                                                  \
        {                                                                                                              \
          Ring r2 = r; r2.adv(A_NSLOT);                                                                                \
          okn = mbar_try(bar_full + 8 * r.slot, r.phase) & mbar_try(bar_full + 8 * r2.slot, r2.phase);                 \
        }                                                                                                              \
        wg_wait<1>();                                                                                                  \
        fence_regs(s);                                                                                                 \
        A_RELEASE(sK);                                                                                                 \
        float b0 = 0.f, b1 = 0.f;                                                                                      \
        _Pragma("unroll") for (int i = 0; i < 8; i++) {                                                                \
          const float e0 = ex2(fmaf(s[4 * i], SC, -c0)), e1 = ex2(fmaf(s[4 * i + 1], SC, -c0));                        \
          const float e2 = ex2(fmaf(s[4 * i + 2], SC, -c1)), e3 = ex2(fmaf(s[4 * i + 3], SC, -c1));                    \
          b0 += e0 + e1; b1 += e2 + e3;                                                                                \
          PN[2 * i] = pack_bf16(e0, e1); PN[2 * i + 1] = pack_bf16(e2, e3);                                            \
        }                                                                                                              \
        wg_wait<0>();                                                                                                  \
        fence_regs(o);                                                                                                 \
        fence_regs(PC);                                                                                                \
        A_RELEASE(sV);                                                                                                 \
        if (__any_sync(0xffffffffu, !(b0 <= 65536.f) || !(b1 <= 65536.f))) {                                           \
          float mx0 = fmaxf(s[0], s[1]), mx1 = fmaxf(s[2], s[3]);                                                      \
          _Pragma("unroll") for (int i = 1; i < 8; i++) {                                                              \
            mx0 = fmaxf(mx0, fmaxf(s[4 * i], s[4 * i + 1])); mx1 = fmaxf(mx1, fmaxf(s[4 * i + 2], s[4 * i + 3]));     \
          }                                                                                                            \
          mx0 = fmaxf(mx0, __shfl_xor_sync(0xffffffffu, mx0, 1)); mx1 = fmaxf(mx1, __shfl_xor_sync(0xffffffffu, mx1, 1)); \
          mx0 = fmaxf(mx0, __shfl_xor_sync(0xffffffffu, mx0, 2)); mx1 = fmaxf(mx1, __shfl_xor_sync(0xffffffffu, mx1, 2)); \
          const float n0 = fmaxf(c0, mx0 * SC), n1 = fmaxf(c1, mx1 * SC);                                              \
          const float a0 = ex2(c0 - n0), a1 = ex2(c1 - n1);                                                            \
          c0 = n0; c1 = n1;                                                                                            \
          l0 *= a0; l1 *= a1;                                                                                          \
          _Pragma("unroll") for (int i = 0; i < 24; i++) { o[4 * i] *= a0; o[4 * i + 1] *= a0; o[4 * i + 2] *= a1; o[4 * i + 3] *= a1; } \
          b0 = 0.f; b1 = 0.f;                                                                                          \
          _Pragma("unroll") for (int i = 0; i < 8; i++) {                                                              \
            const float e0 = ex2(fmaf(s[4 * i], SC, -c0)), e1 = ex2(fmaf(s[4 * i + 1], SC, -c0));                      \
            const float e2 = ex2(fmaf(s[4 * i + 2], SC, -c1)), e3 = ex2(fmaf(s[4 * i + 3], SC, -c1));                  \
            b0 += e0 + e1; b1 += e2 + e3;                                                                              \
            PN[2 * i] = pack_bf16(e0, e1); PN[2 * i + 1] = pack_bf16(e2, e3);                                          \
          }                                                                                                            \
        }                                                                                                              \
        l0 += b0; l1 += b1;                                                                                            \
      }
      for (int jj = 0; jj < 15; jj++) {
        A_STEP(p, p2, jj == 0)
        A_STEP(p2, p, false)
      }
      A_STEP(p, p2, false)
      TSA(item, 3);
      {
        const uint32_t sV = r.slot; mbar_wait_c(bar_full + 8 * sV, r.phase); r.adv(A_NSLOT);
        const uint64_t dv = mkdesc(sb + sV * A_SLOT, 8192, 1024);
        bar_sync(1 + w, 256);
        wg_fence();
#pragma unroll
        for (int kk = 0; kk < 4; kk++)
          wgmma_rs_n192<1>(o, p2[4 * kk], p2[4 * kk + 1], p2[4 * kk + 2], p2[4 * kk + 3], dv + kk * 128, 1);
        wg_commit();
        bar_arrive(1 + (w ^ 1), 256);
        wg_wait<0>();
        fence_regs(o);
        A_RELEASE(sV);
      }
      TSA(item, 4);
      l0 += __shfl_xor_sync(0xffffffffu, l0, 1); l1 += __shfl_xor_sync(0xffffffffu, l1, 1);
      l0 += __shfl_xor_sync(0xffffffffu, l0, 2); l1 += __shfl_xor_sync(0xffffffffu, l1, 2);
      const float i0 = 1.f / l0, i1 = 1.f / l1;
      bf16* orow = g_o + (size_t)(qtile * 128 + w * 64 + warp * 16 + (lane >> 2)) * HD_ + head * DH_ + (lane & 3) * 8;
#pragma unroll
      for (int g = 0; g < 6; g++) {
        uint32_t u0 = pack_bf16(o[16 * g + 0] * i0, o[16 * g + 1] * i0), u1 = pack_bf16(o[16 * g + 4] * i0, o[16 * g + 5] * i0);
        uint32_t u2 = pack_bf16(o[16 * g + 8] * i0, o[16 * g + 9] * i0), u3 = pack_bf16(o[16 * g + 12] * i0, o[16 * g + 13] * i0);
        quad_transpose(u0, u1, u2, u3, lane);
        *reinterpret_cast<uint4*>(orow + g * 32) = make_uint4(u0, u1, u2, u3);
        uint32_t v0 = pack_bf16(o[16 * g + 2] * i1, o[16 * g + 3] * i1), v1 = pack_bf16(o[16 * g + 6] * i1, o[16 * g + 7] * i1);
        uint32_t v2 = pack_bf16(o[16 * g + 10] * i1, o[16 * g + 11] * i1), v3 = pack_bf16(o[16 * g + 14] * i1, o[16 * g + 15] * i1);
        quad_transpose(v0, v1, v2, v3, lane);
        *reinterpret_cast<uint4*>(orow + (size_t)8 * HD_ + g * 32) = make_uint4(v0, v1, v2, v3);
      }
      SIGNAL();
      TSA(item, 5);
    }
    }
    TS(3, 2);
    const uint32_t st_w = (uint32_t)((warp * 16 + (lane >> 2)) * ST_P + (lane & 3) * 2) * 4;
    const uint32_t st_x = (lane & 8) << 2;
    const int er = (tid & 127) >> 1, eh = tid & 1;
    const uint32_t st_r = (uint32_t)(er * ST_P + (eh ^ ((er >> 1) & 1)) * 8) * 4;
    const uint32_t e_r = (uint32_t)((w * 64 + er) * 160 + eh * 16);
    const uint32_t p_r = par + eh * 32;
    const uint32_t stat = sb + T_PREP + w * 2048;
    const bool leader = (tid & 127) == 0;
#define STAGE10(ACC, BASE)                                                                                             \
    _Pragma("unroll") for (int nb = 0; nb < 10; nb++) if (live) {                                                                \
      sts_f2(stg + st_w + ((nb * 32) ^ st_x), ACC(BASE + 4 * nb), ACC(BASE + 4 * nb + 1));                                       \
      sts_f2(stg + st_w + ((nb * 32) ^ st_x) + 8 * ST_P * 4, ACC(BASE + 4 * nb + 2), ACC(BASE + 4 * nb + 3));                    \
    }

    {
      float acc1[96], acc2[64];
      uint32_t p0 = 0, p1 = 0, p2 = 0;
#pragma unroll 1
      for (int kb = 0; kb < 24; kb++) {
        const uint32_t s1 = r.slot; mbar_wait_c(bar_full + 8 * s1, r.phase); r.adv(A_NSLOT);
        const uint32_t s2 = r.slot; mbar_wait_c(bar_full + 8 * s2, r.phase); r.adv(A_NSLOT);
        const uint32_t sa = r.slot; mbar_wait_c(bar_full + 8 * sa, r.phase); r.adv(A_NSLOT);
        const uint64_t da = mkdesc(sb + sa * A_SLOT + w * 8192, 16, 1024);
        const uint64_t d1 = mkdesc(sb + s1 * A_SLOT, 8192, 1024), d2 = mkdesc(sb + s2 * A_SLOT, 8192, 1024);
        wg_fence();
#pragma unroll
        for (int kk = 0; kk < 4; kk++) {
          wgmma_ss_n192<1>(acc1, da + kk * 2, d1 + kk * 128, (kb | kk) != 0);
          wgmma_ss_n128<1>(acc2, da + kk * 2, d2 + kk * 128, (kb | kk) != 0);
        }
        wg_commit();
        if (kb > 0) { wg_wait<1>(); A_RELEASE(p0); A_RELEASE(p1); A_RELEASE(p2); }
        p0 = s1; p1 = s2; p2 = sa;
      }
      wg_wait<0>();
      fence_regs(acc1); fence_regs(acc2);
      A_RELEASE(p2);
      bar_sync(6, 288);
      TS(0, 0);
      const uint32_t stg = sb + (w ? p1 : p0) * A_SLOT;
#define OACC(e) (((e) < 96) ? acc1[(e) < 96 ? (e) : 0] : acc2[(e) >= 96 ? (e) - 96 : 0])
#define PACK10(BASE)                                                                                                   \
      _Pragma("unroll") for (int nb = 0; nb < 10; nb++) {                                                              \
        sts_u1(xo + nb * 16, pack_bf16(OACC(BASE + 4 * nb), OACC(BASE + 4 * nb + 1)));                                 \
        sts_u1(xo + nb * 16 + 8 * 160, pack_bf16(OACC(BASE + 4 * nb + 2), OACC(BASE + 4 * nb + 3)));                   \
      }
      const uint32_t f1 = r.slot + 4 >= A_NSLOT ? r.slot + 4 - A_NSLOT : r.slot + 4, f2 = f1 + 1 >= A_NSLOT ? 0 : f1 + 1;
#pragma unroll
      for (int d = 0; d < 4; d++) {
        if (d != o_ks) {
          const int i = (d - o_ks - 1) & 3;
          const uint32_t xo = sb + (i == 0 ? p2 : i == 1 ? f1 : f2) * A_SLOT + (w * 64 + warp * 16 + (lane >> 2)) * 160 + (lane & 3) * 4;
          PACK10(d * 40)
        }
      }
      fence_async_smem();
      bar_sync(3 + w, 128);
      if (leader) {
#pragma unroll 1
        for (int i = 0; i < 3; i++)
          bulk_store(g_xch + (size_t)((((o_qt * 2 + o_nh) * 4 + ((o_ks + 1 + i) & 3)) * 4) + o_ks) * (E_TILE / 2) + w * (E_TILE / 4),
                     sb + (i == 0 ? p2 : i == 1 ? f1 : f2) * A_SLOT + w * (E_TILE / 2), E_TILE / 2);
        bulk_done();
#pragma unroll 1
        for (int i = 0; i < 3; i++) flag_add(g_flag + F_XCH + (o_qt * 2 + o_nh) * 4 + ((o_ks + 1 + i) & 3));
        TX(40 + w);
      }
      { const bool live = true;
      if (o_ks == 0) { STAGE10(OACC, 0) } else if (o_ks == 1) { STAGE10(OACC, 40) } else if (o_ks == 2) { STAGE10(OACC, 80) } else { STAGE10(OACC, 120) } }
      bar_sync(3 + w, 128);
      Ring rq = r;
      const uint32_t sx = rq.slot; rq.adv(A_NSLOT);
      const uint32_t q0 = rq.slot; rq.adv(A_NSLOT);
      const uint32_t q1 = rq.slot; rq.adv(A_NSLOT);
      const uint32_t q2 = rq.slot;
      const uint32_t ot = sb + p2 * A_SLOT;
#pragma unroll 1
      for (int pass = 0; pass < 2; pass++) {
      const bool live = pass;
      if (live) {
#pragma unroll 1
        for (int i = 0; i < 4; i++) { mbar_wait_c(bar_full + 8 * r.slot, r.phase); r.adv(A_NSLOT); }
        TS(0, 1);
      }
      float st[6] = {0.f, 0.f, 0.f, 0.f, 0.f, 0.f};
#pragma unroll 1
      for (int c = 0; c < (live ? 5 : 1); c++) {
        float v[8], t0[8], t1[8], t2[8];
        lds8(stg + st_r + c * 64, v);
        lds8_bf(sb + q0 * A_SLOT + e_r + c * 32, t0); lds8_bf(sb + q1 * A_SLOT + e_r + c * 32, t1); lds8_bf(sb + q2 * A_SLOT + e_r + c * 32, t2);
#pragma unroll
        for (int e = 0; e < 8; e++) v[e] += (t0[e] + t1[e]) + t2[e];
        lds8_bf(sb + sx * A_SLOT + e_r + c * 32, t0);
        lds8(p_r + P_OGA * 4 + c * 64, t1);
#pragma unroll
        for (int e = 0; e < 8; e++) v[e] = fmaf(t1[e], v[e], t0[e]);
        const uint4 pk = pack8(v);
        if (live) sts_u4(ot + e_r + c * 32, pk);
        v[0] = bf_lo(pk.x); v[1] = bf_hi(pk.x); v[2] = bf_lo(pk.y); v[3] = bf_hi(pk.y); v[4] = bf_lo(pk.z); v[5] = bf_hi(pk.z); v[6] = bf_lo(pk.w); v[7] = bf_hi(pk.w);
        lds8(p_r + P_OA * 4 + c * 64, t1);
        lds8(p_r + P_OB * 4 + c * 64, t2);
#pragma unroll
        for (int e = 0; e < 8; e++) {
          const float y = t1[e] * v[e];
          st[0] += v[e]; st[1] = fmaf(v[e], v[e], st[1]); st[2] += y; st[3] = fmaf(t1[e], y, st[3]); st[4] = fmaf(y, y, st[4]); st[5] = fmaf(t2[e], y, st[5]);
        }
      }
#pragma unroll
      for (int i = 0; i < 6; i++) st[i] += __shfl_xor_sync(0xffffffffu, st[i], 1);
      if (live) sts_u4(stat + er * 32 + eh * 16, eh ? make_uint4(__float_as_uint(st[4]), __float_as_uint(st[5]), 0u, 0u)
                                          : make_uint4(__float_as_uint(st[0]), __float_as_uint(st[1]), __float_as_uint(st[2]), __float_as_uint(st[3])));
      }
      fence_async_smem();
      bar_sync(3 + w, 128);
      if (leader) {
        tma_store2d(&tm.sxa, ot + w * (E_TILE / 2), o_col, o_qt * 128 + w * 64);
        bulk_red_f32(g_st1 + (size_t)(o_qt * 128 + w * 64) * 8, stat, 2048);
        bulk_done();
        flag_add(g_flag + F_XA + o_qt);
      }
      bar_sync(5, 256);
      A_RELEASE(p0); A_RELEASE(p1); A_RELEASE(sx); A_RELEASE(q0); A_RELEASE(q1); A_RELEASE(q2);
      TS(0, 2);
    }

    Ring ra{0, 0};
    uint32_t bpar = 0;
    const uint32_t rel_a = mapa(mb_empty + 40, (lane == 0) ? rank : (rank ^ 1));
#define B_NEXT(s_) do { s_ = bs; mbar_wait_c(mb_full + 8 * bs, (bpar >> bs) & 1); bpar ^= 1u << bs; if (++bs == nbs) bs = 0; } while (0)
#define A_NEXT(s_) do { s_ = ra.slot; mbar_wait_c(mb_full + 40 + 8 * s_, ra.phase); ra.adv(M_NA); } while (0)
#define B_RELEASE(s_) do { if (lane == 0) mbar_arrive(mb_empty + 8 * (s_)); } while (0)
#define MA_RELEASE(s_) do { if (lane < 2) mbar_arrive_remote(rel_a + 8 * (s_)); } while (0)
    const int grow = qt * 128 + w * 64 + er;
    float mu = 0.f, rs = 0.f;
#pragma unroll 1
    for (int ph = 0; ph < 4; ph++) {
      float acc[96];
      float (&acc80)[40] = *reinterpret_cast<float(*)[40]>(&acc[0]);
      uint32_t pa = 0, pa2 = 0, pb = 0;
      float4 s03 = make_float4(0.f, 0.f, 0.f, 0.f);
      float2 s45 = make_float2(0.f, 0.f);
      const int nit = ph == 3 ? 12 : ph == 2 ? 10 : 5;
      const uint32_t nbs = ph == 2 ? 4 : 5, bsz = ph == 2 ? 24576 : 20480;
      uint32_t bs = 0;
#pragma unroll 1
      for (int pass = (ph < 2 ? 0 : 1); pass < 2; pass++) {
      const bool live = pass;
      if (live) {
#pragma unroll 1
      for (int it = 0; it < nit; it++) {
        uint32_t sbq, sa, sa2;
        B_NEXT(sbq);
        A_NEXT(sa);
        if (it == 0) TXC(ph);
        const uint64_t da = mkdesc(sb + M_AOFF + sa * 16384 + w * 8192, 16, 1024);
        if (ph == 2) {
          sa2 = sa;
          const uint64_t db = mkdesc(sb + sbq * 24576, 8192, 1024);
          wg_fence();
#pragma unroll
          for (int kk = 0; kk < 4; kk++) wgmma_ss_n192<1>(acc, da + kk * 2, db + kk * 128, (it | kk) != 0);
          wg_commit();
        } else {
          A_NEXT(sa2);
          const uint64_t da2 = mkdesc(sb + M_AOFF + sa2 * 16384 + w * 8192, 16, 1024);
          const uint64_t db = mkdesc(sb + sbq * 20480, 16, 1024);
          wg_fence();
#pragma unroll
          for (int kk = 0; kk < 4; kk++) wgmma_ss_n80<0>(acc80, da + kk * 2, db + kk * 2, (it | kk) != 0);
#pragma unroll
          for (int kk = 0; kk < 4; kk++) wgmma_ss_n80<0>(acc80, da2 + kk * 2, db + 640 + kk * 2, 1);
          wg_commit();
        }
        if (it > 0) { wg_wait<1>(); MA_RELEASE(pa); if (ph != 2) MA_RELEASE(pa2); B_RELEASE(pb); }
        else {
          if (ph == 0) { s03 = __ldcg(reinterpret_cast<const float4*>(g_st1 + (size_t)grow * 8)); s45 = __ldcg(reinterpret_cast<const float2*>(g_st1 + (size_t)grow * 8 + 4)); }
          if (ph == 2) s45 = __ldcg(reinterpret_cast<const float2*>(g_st2 + (size_t)grow * 2));
        }
        pa = sa; pa2 = sa2; pb = sbq;
      }
      wg_wait<0>();
      fence_regs(acc);
      MA_RELEASE(pa); if (ph != 2) MA_RELEASE(pa2);
      bar_sync(5, 256);
      TS(1 + (ph == 3 ? 0 : ph), ph == 3 ? 2 : 0);
      }
      const uint32_t pb1 = pb == 0 ? nbs - 1 : pb - 1, pb2 = pb1 == 0 ? nbs - 1 : pb1 - 1, pb3 = pb2 == 0 ? nbs - 1 : pb2 - 1;
      const uint32_t stg = sb + (w ? pb : pb1) * bsz;
      uint32_t e1 = 0;
#define MACC(e) acc[e]
      if (!(ph & 1)) {
        float c0, c1, c2 = 0.f, c3 = 0.f;
        if (ph == 0) {
          const float4 sc = lds_f4(par + P_SC * 4);
          const float sbb = lds_f(par + (P_SC + 4) * 4);
          mu = s03.x * (1.f / D_);
          rs = rsqrtf(fmaxf(s03.y * (1.f / D_) - mu * mu, 0.f) + LN_EPS);
          const float m2 = (rs * (s03.z - mu * sc.x) + sc.w) * (1.f / D_);
          const float e2 = (rs * rs * (s45.x - 2.f * mu * s03.w + mu * mu * sc.y) + 2.f * rs * (s45.y - mu * sc.z) + sbb) * (1.f / D_);
          c2 = rsqrtf(fmaxf(e2 - m2 * m2, 0.f) + LN_EPS);
          c0 = c2 * rs; c1 = -c0 * mu; c3 = -c2 * m2;
          if (live && tid < 20) sts_u4(stat + 2048 * 2 + tid * 16, make_uint4(0, 0, 0, 0));
        } else {
          const float m = s45.x * (1.f / D_);
          c0 = rsqrtf(fmaxf(s45.y * (1.f / D_) - m * m, 0.f) + LN_EPS);
          c1 = -c0 * m;
        }
        const int npass = ph == 0 ? 1 : 3, nch = !live ? 1 : ph == 0 ? 5 : 4;
        const uint32_t ot = ph == 0 ? sb + pb2 * bsz + w * (E_TILE / 2) : sb + (w ? pb2 : pb3) * bsz;
#pragma unroll 1
        for (int ps = 0; ps < npass; ps++) {
          if (ps == 0) { STAGE10(MACC, 0) } else if (ps == 1) { STAGE10(MACC, 32) } else { STAGE10(MACC, 56) }
          bar_sync(3 + w, 128);
          const uint32_t cofs = ps == 2 ? 64 : 0;
          const uint32_t pp = p_r + (ph == 0 ? P_VA : P_CS3 + ps * 64) * 4;
#pragma unroll 1
          for (int c = 0; c < nch; c++) {
            float v[8], t[8];
            lds8(stg + st_r + cofs + c * 64, v);
            lds8(pp + c * 64, t);
#pragma unroll
            for (int e = 0; e < 8; e++) v[e] = fmaf(c0, v[e], c1 * t[e]);
            if (ph == 0) {
              lds8(pp + 320 + c * 64, t);
#pragma unroll
              for (int e = 0; e < 8; e++) v[e] = fmaf(c2, t[e], v[e]);
              lds8(pp + 640 + c * 64, t);
#pragma unroll
              for (int e = 0; e < 8; e++) v[e] = fmaf(c3, t[e], v[e]);
            }
#pragma unroll
            for (int e = 0; e < 8; e++) v[e] = gelu_tanh(v[e]);
            if (live) sts_u4(ot + (ph == 0 ? er * 160 + eh * 16 + c * 32 : ps * 8192 + er * 128 + (((2 * c + eh) ^ (er & 7)) << 4)), pack8(v));
          }
          fence_async_smem();
          bar_sync(3 + w, 128);
          if (leader && live) {
            if (ph == 0) {
              const int grp = js >> 1;
              const int sh = (grp & 2 ? 2 : 1) * (grp & 1 ? -1 : 1);
              tma_store2d(&tm.sus, ot, js * 80, qt * 128 + w * 64 + sh + 2);
              if (w == 0 && qt == (sh > 0 ? 0 : 15)) {
                const int r0 = sh > 0 ? 0 : S_ + sh, n = sh > 0 ? sh : -sh;
                for (int i = 0; i < n; i++) bulk_store(g_us + (size_t)(r0 + i + 2) * D_ + js * 80, stat + 2048 * 2, 160);
              }
            } else {
              tma_store2d(&tm.g, ot + ps * 8192, js * 192 + ps * 64, qt * 128 + w * 64);
            }
          }
        }
      } else {
        STAGE10(MACC, 0)
        uint32_t e2 = 0;
        if (live) {
          B_NEXT(e1);
          e2 = e1;
          if (ph == 3) B_NEXT(e2);
        }
        bar_sync(3 + w, 128);
        float s1 = 0.f, s2 = 0.f;
        const uint32_t ot = sb + pb2 * bsz;
#pragma unroll 1
        for (int c = 0; c < (live ? 5 : 1); c++) {
          float v[8], xa[8], t[8];
          lds8(stg + st_r + c * 64, v);
          lds8_bf(sb + e1 * 20480 + e_r + c * 32, xa);
          if (ph == 1) {
            lds8(p_r + P_A2 * 4 + c * 64, t);
#pragma unroll
            for (int e = 0; e < 8; e++) v[e] = fmaf(t[e] * rs, xa[e] - mu, v[e]);
            lds8(p_r + P_B2 * 4 + c * 64, t);
#pragma unroll
            for (int e = 0; e < 8; e++) v[e] += t[e];
          } else {
            lds8_bf(sb + e2 * 20480 + e_r + c * 32, t);
#pragma unroll
            for (int e = 0; e < 8; e++) v[e] += t[e];
            lds8(p_r + P_GB * 4 + c * 64, t);
#pragma unroll
            for (int e = 0; e < 8; e++) v[e] = fmaf(t[e], v[e], xa[e]);
          }
          const uint4 pk = pack8(v);
          if (live) sts_u4(ot + e_r + c * 32, pk);
          v[0] = bf_lo(pk.x); v[1] = bf_hi(pk.x); v[2] = bf_lo(pk.y); v[3] = bf_hi(pk.y); v[4] = bf_lo(pk.z); v[5] = bf_hi(pk.z); v[6] = bf_lo(pk.w); v[7] = bf_hi(pk.w);
#pragma unroll
          for (int e = 0; e < 8; e++) { s1 += v[e]; s2 = fmaf(v[e], v[e], s2); }
        }
        s1 += __shfl_xor_sync(0xffffffffu, s1, 1); s2 += __shfl_xor_sync(0xffffffffu, s2, 1);
        if (live && eh == 0) sts_f2(stat + er * 8, s1, s2);
        fence_async_smem();
        bar_sync(3 + w, 128);
        if (leader && live) {
          tma_store2d(ph == 1 ? &tm.sx1 : &tm.sout, ot + w * (E_TILE / 2), js * 80, qt * 128 + w * 64);
          if (ph == 1) bulk_red_f32(g_st2 + (size_t)(qt * 128 + w * 64) * 2, stat, 512);
        }
      }
      if (!live) continue;
      if (leader) {
        bulk_done();
        if (ph < 3) flag_add(g_flag + F_US + 16 * ph + qt);
      }
      if (ph < 3) {
        bar_sync(5, 256);
        B_RELEASE(pb);
        if (ph == 1) B_RELEASE(e1);
      }
      TS(1 + (ph == 3 ? 0 : ph), ph == 3 ? 3 : 1);
      }
    }
    if ((threadIdx.x & 127) == 0) TL_END(2);
    cluster_sync();
  }
}

typedef CUresult (*EncFn)(CUtensorMap*, CUtensorMapDataType, cuuint32_t, void*, const cuuint64_t*, const cuuint64_t*,
                          const cuuint32_t*, const cuuint32_t*, CUtensorMapInterleave, CUtensorMapSwizzle,
                          CUtensorMapL2promotion, CUtensorMapFloatOOBfill);
static EncFn g_enc = nullptr;

static CUtensorMap map2d(const void* p, uint64_t rows, uint64_t cols, uint32_t box_rows) {
  CUtensorMap m;
  cuuint64_t gd[2] = {cols, rows}; cuuint64_t gs[1] = {cols * 2};
  cuuint32_t bx[2] = {64, box_rows}; cuuint32_t es[2] = {1, 1};
  g_enc(&m, CU_TENSOR_MAP_DATA_TYPE_BFLOAT16, 2, const_cast<void*>(p), gd, gs, bx, es, CU_TENSOR_MAP_INTERLEAVE_NONE,
        CU_TENSOR_MAP_SWIZZLE_128B, CU_TENSOR_MAP_L2_PROMOTION_L2_256B, CU_TENSOR_MAP_FLOAT_OOB_FILL_NONE);
  return m;
}
static CUtensorMap map3d(const void* p, uint64_t rows, uint64_t cols, uint32_t box_rows, uint32_t nblk) {
  CUtensorMap m;
  cuuint64_t gd[3] = {64, rows, cols / 64}; cuuint64_t gs[2] = {cols * 2, 128};
  cuuint32_t bx[3] = {64, box_rows, nblk}; cuuint32_t es[3] = {1, 1, 1};
  g_enc(&m, CU_TENSOR_MAP_DATA_TYPE_BFLOAT16, 3, const_cast<void*>(p), gd, gs, bx, es, CU_TENSOR_MAP_INTERLEAVE_NONE,
        CU_TENSOR_MAP_SWIZZLE_128B, CU_TENSOR_MAP_L2_PROMOTION_L2_256B, CU_TENSOR_MAP_FLOAT_OOB_FILL_NONE);
  return m;
}

static CUtensorMap map_e(const void* p, uint32_t rows, uint64_t total_rows = S_) {
  CUtensorMap m;
  cuuint64_t gd[2] = {D_, total_rows}; cuuint64_t gs[1] = {D_ * 2};
  cuuint32_t bx[2] = {80, rows}; cuuint32_t es[2] = {1, 1};
  g_enc(&m, CU_TENSOR_MAP_DATA_TYPE_BFLOAT16, 2, const_cast<void*>(p), gd, gs, bx, es, CU_TENSOR_MAP_INTERLEAVE_NONE,
        CU_TENSOR_MAP_SWIZZLE_NONE, CU_TENSOR_MAP_L2_PROMOTION_L2_256B, CU_TENSOR_MAP_FLOAT_OOB_FILL_NONE);
  return m;
}

template <typename... KArgs, typename... Args>
static void launch(void (*kern)(KArgs...), dim3 grid, dim3 block, int smem, bool pdl, Args... args) {
  cudaLaunchConfig_t cfg = {};
  cfg.gridDim = grid; cfg.blockDim = block; cfg.dynamicSmemBytes = smem; cfg.stream = cudaStreamPerThread;
  cudaLaunchAttribute at[1];
  at[0].id = cudaLaunchAttributeProgrammaticStreamSerialization;
  at[0].val.programmaticStreamSerializationAllowed = 1;
  cfg.attrs = at; cfg.numAttrs = pdl ? 1 : 0;
  cudaLaunchKernelEx(&cfg, kern, KArgs(args)...);
}

extern "C" void kernel_launch(void* const* d_in, const int* in_sizes, int n_in, void* d_out, int out_size) {
  const bf16* x = (const bf16*)d_in[0];
  const bf16* kc = (const bf16*)d_in[1];
  const bf16* vc = (const bf16*)d_in[2];
  const bf16* wq = (const bf16*)d_in[3];
  const bf16* wo = (const bf16*)d_in[4];
  const bf16* w1 = (const bf16*)d_in[6];
  const bf16* w2 = (const bf16*)d_in[7];
  const bf16* w3 = (const bf16*)d_in[8];
  const bf16* w4 = (const bf16*)d_in[9];
  const bf16* c = (const bf16*)d_in[10];
  const bf16* wmod = (const bf16*)d_in[11];
  bf16* out = (bf16*)d_out;

  static void *p_h, *p_o, *p_xa, *p_us, *p_x1, *p_g, *p_w1t, *p_w2t, *p_w4t;
  if (!g_enc) {
    void* fn = nullptr; cudaDriverEntryPointQueryResult qr;
    cudaGetDriverEntryPoint("cuTensorMapEncodeTiled", &fn, cudaEnableDefault, &qr);
    g_enc = (EncFn)fn;
    cudaGetSymbolAddress(&p_h, g_h); cudaGetSymbolAddress(&p_o, g_o); cudaGetSymbolAddress(&p_xa, g_xa);
    cudaGetSymbolAddress(&p_us, g_us); cudaGetSymbolAddress(&p_x1, g_x1); cudaGetSymbolAddress(&p_g, g_g);
    cudaGetSymbolAddress(&p_w1t, g_w1t); cudaGetSymbolAddress(&p_w2t, g_w2t); cudaGetSymbolAddress(&p_w4t, g_w4t);
    cudaFuncSetAttribute(fused_kernel, cudaFuncAttributeMaxDynamicSharedMemorySize, T_SMEM);
  }
  Maps tm;
  tm.h = map2d(p_h, S_, D_, 128);
  tm.wq = map3d(wq, D_, HD_, 64, 3);
  tm.k = map3d(kc, (uint64_t)H_ * S_, DH_, 64, 3);
  tm.v = map3d(vc, (uint64_t)H_ * S_, DH_, 64, 3);
  tm.o = map2d(p_o, S_, HD_, 128);
  tm.wo3 = map3d(wo, HD_, D_, 64, 3);
  tm.wo2 = map3d(wo, HD_, D_, 64, 2);
  tm.xa = map2d(p_xa, S_, D_, 64);
  tm.w1t = map3d(p_w1t, D_, D_, 80, 2);
  tm.us = map2d((const bf16*)p_us + 2 * D_, S_, D_, 64);
  tm.w2t = map3d(p_w2t, D_, D_, 80, 2);
  tm.x1 = map2d(p_x1, S_, D_, 64);
  tm.w3 = map3d(w3, D_, F_, 64, 3);
  tm.g = map2d(p_g, S_, F_, 64);
  tm.w4t = map3d(p_w4t, D_, F_, 80, 2);
  tm.ex = map_e(x, 128); tm.exa = map_e(p_xa, 128); tm.ex1 = map_e(p_x1, 128);
  tm.sxa = map_e(p_xa, 64); tm.sus = map_e(p_us, 64, S_ + 4); tm.sx1 = map_e(p_x1, 64); tm.sout = map_e(out, 64);
  PfList pf;
  pf.p[0] = (const uint8_t*)wo; pf.p[1] = (const uint8_t*)w3; pf.p[2] = (const uint8_t*)p_w4t;
  pf.p[3] = (const uint8_t*)x; pf.p[4] = (const uint8_t*)p_w1t; pf.p[5] = (const uint8_t*)p_w2t;

  launch(mod_kernel, dim3(120), dim3(256), 0, false, c, wmod);
  launch(ln1_kernel, dim3(256), dim3(256), 0, true, x);
  launch(fused_kernel, dim3(128), dim3(384), T_SMEM, true, tm, pf, PrepW{w1, w2, w3, w4}, x, out);
}
```

```cpp
#include <cuda_runtime.h>
#include <cuda.h>
#include <cuda_bf16.h>
#include <stdint.h>

typedef __nv_bfloat16 bf16;

constexpr int S_  = 2048;
constexpr int D_  = 640;
constexpr int H_  = 32;
constexpr int DH_ = 192;
constexpr int HD_ = H_ * DH_;
constexpr int F_  = 1536;
constexpr float LN_EPS = 1e-5f;

__device__ __forceinline__ uint32_t smem_u32(const void* p) { return (uint32_t)__cvta_generic_to_shared(p); }
__device__ __forceinline__ void mbar_init(uint32_t a, uint32_t c) { asm volatile("mbarrier.init.shared::cta.b64 [%0], %1;" :: "r"(a), "r"(c) : "memory"); }
__device__ __forceinline__ void mbar_expect(uint32_t a, uint32_t b) { asm volatile("mbarrier.arrive.expect_tx.shared::cta.b64 _, [%0], %1;" :: "r"(a), "r"(b) : "memory"); }
__device__ __forceinline__ void mbar_arrive(uint32_t a) { asm volatile("mbarrier.arrive.shared::cta.b64 _, [%0];" :: "r"(a) : "memory"); }
__device__ __forceinline__ void mbar_arrive_remote(uint32_t ra) { asm volatile("mbarrier.arrive.shared::cluster.b64 _, [%0];" :: "r"(ra) : "memory"); }
__device__ __forceinline__ uint32_t mapa(uint32_t a, uint32_t cta) { uint32_t r; asm volatile("mapa.shared::cluster.u32 %0, %1, %2;" : "=r"(r) : "r"(a), "r"(cta)); return r; }
__device__ __forceinline__ uint32_t mbar_try(uint32_t a, uint32_t ph) {
  uint32_t ok;
  asm volatile("{\n.reg .pred p;\nmbarrier.test_wait.parity.shared::cta.b64 p, [%1], %2;\nselp.u32 %0, 1, 0, p;\n}\n" : "=r"(ok) : "r"(a), "r"(ph) : "memory");
  return ok;
}
__device__ __forceinline__ void mbar_wait(uint32_t a, uint32_t ph) {
  asm volatile(
      "{\n.reg .pred p;\n.reg .u32 n;\n"
      "mov.u32 n, 0;\n"
      "SPIN:\n"
      "mbarrier.try_wait.parity.shared::cta.b64 p, [%0], %1;\n"
      "@p bra DONE;\n"
      "add.u32 n, n, 1;\n"
      "setp.le.u32 p, n, 16777216;\n"
      "@p bra SPIN;\n"
      "trap;\n"
      "DONE:\n}\n" :: "r"(a), "r"(ph) : "memory");
}
#define ELECT_ "{\n.reg .pred p;\nelect.sync _|p, 0xffffffff;\n@p "
__device__ __forceinline__ void mbar_expect_e(uint32_t a, uint32_t b) { asm volatile(ELECT_ "mbarrier.arrive.expect_tx.shared::cta.b64 _, [%0], %1;\n}\n" :: "r"(a), "r"(b) : "memory"); }
__device__ __forceinline__ void tma2d(uint32_t dst, const CUtensorMap* m, uint32_t bar, int c0, int c1) {
  asm volatile(ELECT_ "cp.async.bulk.tensor.2d.shared::cluster.global.mbarrier::complete_tx::bytes [%0], [%1, {%3, %4}], [%2];\n}\n"
               :: "r"(dst), "l"(m), "r"(bar), "r"(c0), "r"(c1) : "memory");
}
__device__ __forceinline__ void tma2d_mc(uint32_t dst, const CUtensorMap* m, uint32_t bar, int c0, int c1, uint16_t mask) {
  asm volatile(ELECT_ "cp.async.bulk.tensor.2d.shared::cluster.global.mbarrier::complete_tx::bytes.multicast::cluster [%0], [%1, {%3, %4}], [%2], %5;\n}\n"
               :: "r"(dst), "l"(m), "r"(bar), "r"(c0), "r"(c1), "h"(mask) : "memory");
}
__device__ __forceinline__ void tma3d(uint32_t dst, const CUtensorMap* m, uint32_t bar, int c0, int c1, int c2) {
  asm volatile(ELECT_ "cp.async.bulk.tensor.3d.shared::cluster.global.mbarrier::complete_tx::bytes [%0], [%1, {%3, %4, %5}], [%2];\n}\n"
               :: "r"(dst), "l"(m), "r"(bar), "r"(c0), "r"(c1), "r"(c2) : "memory");
}
__device__ __forceinline__ void tma3d_mc(uint32_t dst, const CUtensorMap* m, uint32_t bar, int c0, int c1, int c2, uint16_t mask) {
  asm volatile(ELECT_ "cp.async.bulk.tensor.3d.shared::cluster.global.mbarrier::complete_tx::bytes.multicast::cluster [%0], [%1, {%3, %4, %5}], [%2], %6;\n}\n"
               :: "r"(dst), "l"(m), "r"(bar), "r"(c0), "r"(c1), "r"(c2), "h"(mask) : "memory");
}
__device__ __forceinline__ void tma3d_mc_hint(uint32_t dst, const CUtensorMap* m, uint32_t bar, int c0, int c1, int c2, uint16_t mask, uint64_t pol) {
  asm volatile(ELECT_ "cp.async.bulk.tensor.3d.shared::cluster.global.mbarrier::complete_tx::bytes.multicast::cluster.L2::cache_hint [%0], [%1, {%3, %4, %5}], [%2], %6, %7;\n}\n"
               :: "r"(dst), "l"(m), "r"(bar), "r"(c0), "r"(c1), "r"(c2), "h"(mask), "l"(pol) : "memory");
}
__device__ __forceinline__ void bulk_load(uint32_t dst, const void* src, uint32_t bytes, uint32_t bar) {
  asm volatile(ELECT_ "cp.async.bulk.shared::cluster.global.mbarrier::complete_tx::bytes [%0], [%1], %2, [%3];\n}\n"
               :: "r"(dst), "l"(src), "r"(bytes), "r"(bar) : "memory");
}
__device__ __forceinline__ void l2_prefetch16k(const void* p) { asm volatile(ELECT_ "cp.async.bulk.prefetch.L2.global [%0], 16384;\n}\n" :: "l"(p) : "memory"); }
__device__ __forceinline__ void l2_prefetch_t2d(const CUtensorMap* m, int c0, int c1) {
  asm volatile(ELECT_ "cp.async.bulk.prefetch.tensor.2d.L2.global [%0, {%1, %2}];\n}\n" :: "l"(m), "r"(c0), "r"(c1) : "memory");
}
__device__ __forceinline__ void stg128(void* p, uint4 v) {
  asm volatile("st.global.v4.u32 [%0], {%1, %2, %3, %4};" :: "l"(p), "r"(v.x), "r"(v.y), "r"(v.z), "r"(v.w) : "memory");
}
__device__ __forceinline__ void prefetch_tmap(const CUtensorMap* m) { asm volatile("prefetch.tensormap [%0];" :: "l"(m) : "memory"); }
__device__ __forceinline__ void wg_fence() { asm volatile("wgmma.fence.sync.aligned;" ::: "memory"); }
__device__ __forceinline__ void wg_commit() { asm volatile("wgmma.commit_group.sync.aligned;" ::: "memory"); }
template <int N> __device__ __forceinline__ void wg_wait() { asm volatile("wgmma.wait_group.sync.aligned %0;" :: "n"(N) : "memory"); }
template <int N> __device__ __forceinline__ void fence_regs(float (&r)[N]) {
#pragma unroll
  for (int i = 0; i < N; i++) asm volatile("" : "+f"(r[i]) :: "memory");
}
template <int N> __device__ __forceinline__ void fence_regs(uint32_t (&r)[N]) {
#pragma unroll
  for (int i = 0; i < N; i++) asm volatile("" : "+r"(r[i]) :: "memory");
}
__device__ __forceinline__ uint64_t mkdesc(uint32_t addr, uint32_t lbo, uint32_t sbo) {
  return (uint64_t)((addr & 0x3FFFF) >> 4) | ((uint64_t)(lbo >> 4) << 16) | ((uint64_t)(sbo >> 4) << 32) | (1ull << 62);
}
__device__ __forceinline__ void bar_sync(int id, int n) { asm volatile("bar.sync %0, %1;" :: "r"(id), "r"(n) : "memory"); }
__device__ __forceinline__ void bar_arrive(int id, int n) { asm volatile("bar.arrive %0, %1;" :: "r"(id), "r"(n) : "memory"); }
__device__ __forceinline__ void cluster_sync() { asm volatile("barrier.cluster.arrive.aligned;\nbarrier.cluster.wait.aligned;" ::: "memory"); }
__device__ __forceinline__ void pdl_wait() { asm volatile("griddepcontrol.wait;" ::: "memory"); }
__device__ __forceinline__ void pdl_launch() { asm volatile("griddepcontrol.launch_dependents;" ::: "memory"); }
__device__ __forceinline__ float ex2(float x) { float y; asm("ex2.approx.ftz.f32 %0, %1;" : "=f"(y) : "f"(x)); return y; }
__device__ __forceinline__ uint32_t pack_bf16(float lo, float hi) { uint32_t r; asm("cvt.rn.bf16x2.f32 %0, %1, %2;" : "=r"(r) : "f"(hi), "f"(lo)); return r; }
__device__ __forceinline__ float bf_lo(uint32_t u) { return __uint_as_float(u << 16); }
__device__ __forceinline__ float bf_hi(uint32_t u) { return __uint_as_float(u & 0xffff0000u); }
__device__ __forceinline__ float bf_round(float x) { return __bfloat162float(__float2bfloat16_rn(x)); }
__device__ __forceinline__ float tanh_fast(float x) { float y; asm("tanh.approx.f32 %0, %1;" : "=f"(y) : "f"(x)); return y; }
__device__ __forceinline__ float gelu_tanh(float x) {
  float u = x * (0.7978845608028654f + 0.035677408136300125f * x * x);
  float hx = 0.5f * x;
  return fmaf(hx, tanh_fast(u), hx);
}
__device__ __forceinline__ float warp_sum(float v) {
#pragma unroll
  for (int o = 16; o > 0; o >>= 1) v += __shfl_xor_sync(0xffffffffu, v, o);
  return v;
}
__device__ __forceinline__ void quad_transpose(uint32_t& v0, uint32_t& v1, uint32_t& v2, uint32_t& v3, int lane) {
  const bool b0 = lane & 1, b1 = lane & 2;
  uint32_t s0 = b0 ? v0 : v1, s1 = b0 ? v2 : v3;
  s0 = __shfl_xor_sync(0xffffffffu, s0, 1); s1 = __shfl_xor_sync(0xffffffffu, s1, 1);
  if (b0) { v0 = s0; v2 = s1; } else { v1 = s0; v3 = s1; }
  uint32_t t0 = b1 ? v0 : v2, t1 = b1 ? v1 : v3;
  t0 = __shfl_xor_sync(0xffffffffu, t0, 2); t1 = __shfl_xor_sync(0xffffffffu, t1, 2);
  if (b1) { v0 = t0; v1 = t1; } else { v2 = t0; v3 = t1; }
}

#define TX(i)
#define TXC(i)
#define TSA(item, i)
#define TL_ENTRY(k)
#define TL_WAITED(k)
#define TL_END(k)
#define TS(item, i)
template<int TB> __device__ __forceinline__ void wgmma_rs_n64(float (&d)[32], uint32_t a0, uint32_t a1, uint32_t a2, uint32_t a3, uint64_t db, int scale_d) {
  asm volatile("{\n.reg .pred p;\nsetp.ne.b32 p, %37, 0;\n"
    "wgmma.mma_async.sync.aligned.m64n64k16.f32.bf16.bf16 {%0, %1, %2, %3, %4, %5, %6, %7, %8, %9, %10, %11, %12, %13, %14, %15, %16, %17, %18, %19, %20, %21, %22, %23, %24, %25, %26, %27, %28, %29, %30, %31}, {%32, %33, %34, %35}, %36, p, 1, 1, %38;\n}\n"
    : "+f"(d[0]), "+f"(d[1]), "+f"(d[2]), "+f"(d[3]), "+f"(d[4]), "+f"(d[5]), "+f"(d[6]), "+f"(d[7]), "+f"(d[8]), "+f"(d[9]), "+f"(d[10]), "+f"(d[11]), "+f"(d[12]), "+f"(d[13]), "+f"(d[14]), "+f"(d[15]), "+f"(d[16]), "+f"(d[17]), "+f"(d[18]), "+f"(d[19]), "+f"(d[20]), "+f"(d[21]), "+f"(d[22]), "+f"(d[23]), "+f"(d[24]), "+f"(d[25]), "+f"(d[26]), "+f"(d[27]), "+f"(d[28]), "+f"(d[29]), "+f"(d[30]), "+f"(d[31])
    : "r"(a0), "r"(a1), "r"(a2), "r"(a3), "l"(db), "r"(scale_d), "n"(TB));
}
template<int TB> __device__ __forceinline__ void wgmma_rs_n192(float (&d)[96], uint32_t a0, uint32_t a1, uint32_t a2, uint32_t a3, uint64_t db, int scale_d) {
  asm volatile("{\n.reg .pred p;\nsetp.ne.b32 p, %101, 0;\n"
    "wgmma.mma_async.sync.aligned.m64n192k16.f32.bf16.bf16 {%0, %1, %2, %3, %4, %5, %6, %7, %8, %9, %10, %11, %12, %13, %14, %15, %16, %17, %18, %19, %20, %21, %22, %23, %24, %25, %26, %27, %28, %29, %30, %31, %32, %33, %34, %35, %36, %37, %38, %39, %40, %41, %42, %43, %44, %45, %46, %47, %48, %49, %50, %51, %52, %53, %54, %55, %56, %57, %58, %59, %60, %61, %62, %63, %64, %65, %66, %67, %68, %69, %70, %71, %72, %73, %74, %75, %76, %77, %78, %79, %80, %81, %82, %83, %84, %85, %86, %87, %88, %89, %90, %91, %92, %93, %94, %95}, {%96, %97, %98, %99}, %100, p, 1, 1, %102;\n}\n"
    : "+f"(d[0]), "+f"(d[1]), "+f"(d[2]), "+f"(d[3]), "+f"(d[4]), "+f"(d[5]), "+f"(d[6]), "+f"(d[7]), "+f"(d[8]), "+f"(d[9]), "+f"(d[10]), "+f"(d[11]), "+f"(d[12]), "+f"(d[13]), "+f"(d[14]), "+f"(d[15]), "+f"(d[16]), "+f"(d[17]), "+f"(d[18]), "+f"(d[19]), "+f"(d[20]), "+f"(d[21]), "+f"(d[22]), "+f"(d[23]), "+f"(d[24]), "+f"(d[25]), "+f"(d[26]), "+f"(d[27]), "+f"(d[28]), "+f"(d[29]), "+f"(d[30]), "+f"(d[31]), "+f"(d[32]), "+f"(d[33]), "+f"(d[34]), "+f"(d[35]), "+f"(d[36]), "+f"(d[37]), "+f"(d[38]), "+f"(d[39]), "+f"(d[40]), "+f"(d[41]), "+f"(d[42]), "+f"(d[43]), "+f"(d[44]), "+f"(d[45]), "+f"(d[46]), "+f"(d[47]), "+f"(d[48]), "+f"(d[49]), "+f"(d[50]), "+f"(d[51]), "+f"(d[52]), "+f"(d[53]), "+f"(d[54]), "+f"(d[55]), "+f"(d[56]), "+f"(d[57]), "+f"(d[58]), "+f"(d[59]), "+f"(d[60]), "+f"(d[61]), "+f"(d[62]), "+f"(d[63]), "+f"(d[64]), "+f"(d[65]), "+f"(d[66]), "+f"(d[67]), "+f"(d[68]), "+f"(d[69]), "+f"(d[70]), "+f"(d[71]), "+f"(d[72]), "+f"(d[73]), "+f"(d[74]), "+f"(d[75]), "+f"(d[76]), "+f"(d[77]), "+f"(d[78]), "+f"(d[79]), "+f"(d[80]), "+f"(d[81]), "+f"(d[82]), "+f"(d[83]), "+f"(d[84]), "+f"(d[85]), "+f"(d[86]), "+f"(d[87]), "+f"(d[88]), "+f"(d[89]), "+f"(d[90]), "+f"(d[91]), "+f"(d[92]), "+f"(d[93]), "+f"(d[94]), "+f"(d[95])
    : "r"(a0), "r"(a1), "r"(a2), "r"(a3), "l"(db), "r"(scale_d), "n"(TB));
}
template<int TB> __device__ __forceinline__ void wgmma_ss_n128(float (&d)[64], uint64_t da, uint64_t db, int scale_d) {
  asm volatile("{\n.reg .pred p;\nsetp.ne.b32 p, %66, 0;\n"
    "wgmma.mma_async.sync.aligned.m64n128k16.f32.bf16.bf16 {%0, %1, %2, %3, %4, %5, %6, %7, %8, %9, %10, %11, %12, %13, %14, %15, %16, %17, %18, %19, %20, %21, %22, %23, %24, %25, %26, %27, %28, %29, %30, %31, %32, %33, %34, %35, %36, %37, %38, %39, %40, %41, %42, %43, %44, %45, %46, %47, %48, %49, %50, %51, %52, %53, %54, %55, %56, %57, %58, %59, %60, %61, %62, %63}, %64, %65, p, 1, 1, 0, %67;\n}\n"
    : "+f"(d[0]), "+f"(d[1]), "+f"(d[2]), "+f"(d[3]), "+f"(d[4]), "+f"(d[5]), "+f"(d[6]), "+f"(d[7]), "+f"(d[8]), "+f"(d[9]), "+f"(d[10]), "+f"(d[11]), "+f"(d[12]), "+f"(d[13]), "+f"(d[14]), "+f"(d[15]), "+f"(d[16]), "+f"(d[17]), "+f"(d[18]), "+f"(d[19]), "+f"(d[20]), "+f"(d[21]), "+f"(d[22]), "+f"(d[23]), "+f"(d[24]), "+f"(d[25]), "+f"(d[26]), "+f"(d[27]), "+f"(d[28]), "+f"(d[29]), "+f"(d[30]), "+f"(d[31]), "+f"(d[32]), "+f"(d[33]), "+f"(d[34]), "+f"(d[35]), "+f"(d[36]), "+f"(d[37]), "+f"(d[38]), "+f"(d[39]), "+f"(d[40]), "+f"(d[41]), "+f"(d[42]), "+f"(d[43]), "+f"(d[44]), "+f"(d[45]), "+f"(d[46]), "+f"(d[47]), "+f"(d[48]), "+f"(d[49]), "+f"(d[50]), "+f"(d[51]), "+f"(d[52]), "+f"(d[53]), "+f"(d[54]), "+f"(d[55]), "+f"(d[56]), "+f"(d[57]), "+f"(d[58]), "+f"(d[59]), "+f"(d[60]), "+f"(d[61]), "+f"(d[62]), "+f"(d[63])
    : "l"(da), "l"(db), "r"(scale_d), "n"(TB));
}
template<int TB> __device__ __forceinline__ void wgmma_ss_n192(float (&d)[96], uint64_t da, uint64_t db, int scale_d) {
  asm volatile("{\n.reg .pred p;\nsetp.ne.b32 p, %98, 0;\n"
    "wgmma.mma_async.sync.aligned.m64n192k16.f32.bf16.bf16 {%0, %1, %2, %3, %4, %5, %6, %7, %8, %9, %10, %11, %12, %13, %14, %15, %16, %17, %18, %19, %20, %21, %22, %23, %24, %25, %26, %27, %28, %29, %30, %31, %32, %33, %34, %35, %36, %37, %38, %39, %40, %41, %42, %43, %44, %45, %46, %47, %48, %49, %50, %51, %52, %53, %54, %55, %56, %57, %58, %59, %60, %61, %62, %63, %64, %65, %66, %67, %68, %69, %70, %71, %72, %73, %74, %75, %76, %77, %78, %79, %80, %81, %82, %83, %84, %85, %86, %87, %88, %89, %90, %91, %92, %93, %94, %95}, %96, %97, p, 1, 1, 0, %99;\n}\n"
    : "+f"(d[0]), "+f"(d[1]), "+f"(d[2]), "+f"(d[3]), "+f"(d[4]), "+f"(d[5]), "+f"(d[6]), "+f"(d[7]), "+f"(d[8]), "+f"(d[9]), "+f"(d[10]), "+f"(d[11]), "+f"(d[12]), "+f"(d[13]), "+f"(d[14]), "+f"(d[15]), "+f"(d[16]), "+f"(d[17]), "+f"(d[18]), "+f"(d[19]), "+f"(d[20]), "+f"(d[21]), "+f"(d[22]), "+f"(d[23]), "+f"(d[24]), "+f"(d[25]), "+f"(d[26]), "+f"(d[27]), "+f"(d[28]), "+f"(d[29]), "+f"(d[30]), "+f"(d[31]), "+f"(d[32]), "+f"(d[33]), "+f"(d[34]), "+f"(d[35]), "+f"(d[36]), "+f"(d[37]), "+f"(d[38]), "+f"(d[39]), "+f"(d[40]), "+f"(d[41]), "+f"(d[42]), "+f"(d[43]), "+f"(d[44]), "+f"(d[45]), "+f"(d[46]), "+f"(d[47]), "+f"(d[48]), "+f"(d[49]), "+f"(d[50]), "+f"(d[51]), "+f"(d[52]), "+f"(d[53]), "+f"(d[54]), "+f"(d[55]), "+f"(d[56]), "+f"(d[57]), "+f"(d[58]), "+f"(d[59]), "+f"(d[60]), "+f"(d[61]), "+f"(d[62]), "+f"(d[63]), "+f"(d[64]), "+f"(d[65]), "+f"(d[66]), "+f"(d[67]), "+f"(d[68]), "+f"(d[69]), "+f"(d[70]), "+f"(d[71]), "+f"(d[72]), "+f"(d[73]), "+f"(d[74]), "+f"(d[75]), "+f"(d[76]), "+f"(d[77]), "+f"(d[78]), "+f"(d[79]), "+f"(d[80]), "+f"(d[81]), "+f"(d[82]), "+f"(d[83]), "+f"(d[84]), "+f"(d[85]), "+f"(d[86]), "+f"(d[87]), "+f"(d[88]), "+f"(d[89]), "+f"(d[90]), "+f"(d[91]), "+f"(d[92]), "+f"(d[93]), "+f"(d[94]), "+f"(d[95])
    : "l"(da), "l"(db), "r"(scale_d), "n"(TB));
}
template<int TB> __device__ __forceinline__ void wgmma_ss_n80(float (&d)[40], uint64_t da, uint64_t db, int scale_d) {
  asm volatile("{\n.reg .pred p;\nsetp.ne.b32 p, %42, 0;\n"
    "wgmma.mma_async.sync.aligned.m64n80k16.f32.bf16.bf16 {%0, %1, %2, %3, %4, %5, %6, %7, %8, %9, %10, %11, %12, %13, %14, %15, %16, %17, %18, %19, %20, %21, %22, %23, %24, %25, %26, %27, %28, %29, %30, %31, %32, %33, %34, %35, %36, %37, %38, %39}, %40, %41, p, 1, 1, 0, %43;\n}\n"
    : "+f"(d[0]), "+f"(d[1]), "+f"(d[2]), "+f"(d[3]), "+f"(d[4]), "+f"(d[5]), "+f"(d[6]), "+f"(d[7]), "+f"(d[8]), "+f"(d[9]), "+f"(d[10]), "+f"(d[11]), "+f"(d[12]), "+f"(d[13]), "+f"(d[14]), "+f"(d[15]), "+f"(d[16]), "+f"(d[17]), "+f"(d[18]), "+f"(d[19]), "+f"(d[20]), "+f"(d[21]), "+f"(d[22]), "+f"(d[23]), "+f"(d[24]), "+f"(d[25]), "+f"(d[26]), "+f"(d[27]), "+f"(d[28]), "+f"(d[29]), "+f"(d[30]), "+f"(d[31]), "+f"(d[32]), "+f"(d[33]), "+f"(d[34]), "+f"(d[35]), "+f"(d[36]), "+f"(d[37]), "+f"(d[38]), "+f"(d[39])
    : "l"(da), "l"(db), "r"(scale_d), "n"(TB));
}

__device__ float g_mod[6 * D_];
__device__ __align__(1024) bf16 g_h[S_ * D_];
__device__ __align__(1024) bf16 g_o[S_ * HD_];
__device__ __align__(1024) bf16 g_xch[16 * 2 * 4 * 4 * 128 * 80];
__device__ __align__(1024) bf16 g_w1t[D_ * D_];
__device__ __align__(1024) bf16 g_w2t[D_ * D_];
__device__ __align__(1024) bf16 g_w4t[D_ * F_];
__device__ __align__(32) float g_st1[S_ * 8];
__device__ __align__(32) float g_st2[S_ * 2];
__device__ __align__(32) float g_vec[3 * D_ + F_ + 8];
__device__ unsigned g_flag[1024];
enum { F_XCH = 0, F_XA = 256, F_US = 272, F_X1 = 288, F_G = 304, F_PREP = 320, F_O = 512 };
__device__ __align__(1024) bf16 g_xa[S_ * D_];
__device__ __align__(1024) bf16 g_us[(S_ + 4) * D_];
__device__ __align__(1024) bf16 g_x1[S_ * D_];
__device__ __align__(1024) bf16 g_g[S_ * F_];

__global__ void __launch_bounds__(256) mod_kernel(const bf16* __restrict__ c, const bf16* __restrict__ w_mod) {
  TL_ENTRY(0);
  pdl_launch();
  __shared__ float red[8][32];
  if (blockIdx.x < 14) { const int i = blockIdx.x * 256 + threadIdx.x; if (i < 3 * D_ + F_) g_vec[i] = 0.f; }
  else if (blockIdx.x < 18) g_flag[(blockIdx.x - 14) * 256 + threadIdx.x] = 0u;
  const int t = threadIdx.x, cg = t & 3, r0 = t >> 2;
  const int col0 = blockIdx.x * 32 + cg * 8;
  uint4 w[10];
#pragma unroll
  for (int i = 0; i < 10; i++) w[i] = __ldg(reinterpret_cast<const uint4*>(w_mod + (size_t)(r0 + 64 * i) * (6 * D_) + col0));
  float acc[8];
#pragma unroll
  for (int j = 0; j < 8; j++) acc[j] = 0.f;
#pragma unroll
  for (int i = 0; i < 10; i++) {
    float cv = __bfloat162float(c[r0 + 64 * i]);
    float s = bf_round(cv / (1.f + __expf(-cv)));
    acc[0] = fmaf(s, bf_lo(w[i].x), acc[0]); acc[1] = fmaf(s, bf_hi(w[i].x), acc[1]);
    acc[2] = fmaf(s, bf_lo(w[i].y), acc[2]); acc[3] = fmaf(s, bf_hi(w[i].y), acc[3]);
    acc[4] = fmaf(s, bf_lo(w[i].z), acc[4]); acc[5] = fmaf(s, bf_hi(w[i].z), acc[5]);
    acc[6] = fmaf(s, bf_lo(w[i].w), acc[6]); acc[7] = fmaf(s, bf_hi(w[i].w), acc[7]);
  }
#pragma unroll
  for (int j = 0; j < 8; j++) {
    acc[j] += __shfl_xor_sync(0xffffffffu, acc[j], 4);
    acc[j] += __shfl_xor_sync(0xffffffffu, acc[j], 8);
    acc[j] += __shfl_xor_sync(0xffffffffu, acc[j], 16);
  }
  if ((t & 31) < 4) {
#pragma unroll
    for (int j = 0; j < 8; j++) red[t >> 5][cg * 8 + j] = acc[j];
  }
  __syncthreads();
  if (t < 32) {
    float s = 0.f;
#pragma unroll
    for (int w8 = 0; w8 < 8; w8++) s += red[w8][t];
    const int col = blockIdx.x * 32 + t;
    s = bf_round(s);
    const int part = col / D_;
    if (part == 1 || part == 4) s = bf_round(1.f + s);
    g_mod[col] = s;
    if (t == 0) TL_END(0);
  }
}

__device__ __forceinline__ void row_stats(const float (&v)[20], float& mean, float& rstd) {
  float s = 0.f;
#pragma unroll
  for (int i = 0; i < 20; i++) s += v[i];
  mean = warp_sum(s) * (1.f / D_);
  float q = 0.f;
#pragma unroll
  for (int i = 0; i < 20; i++) { float d = v[i] - mean; q = fmaf(d, d, q); }
  rstd = rsqrtf(warp_sum(q) * (1.f / D_) + LN_EPS);
}
__device__ __forceinline__ void load_row_bf16(const bf16* p, int lane, float (&v)[20]) {
#pragma unroll
  for (int i = 0; i < 5; i++) {
    uint2 u = *reinterpret_cast<const uint2*>(p + (lane + 32 * i) * 4);
    v[4 * i] = bf_lo(u.x); v[4 * i + 1] = bf_hi(u.x); v[4 * i + 2] = bf_lo(u.y); v[4 * i + 3] = bf_hi(u.y);
  }
}
__device__ __forceinline__ void store_row_bf16(bf16* p, int lane, const float (&v)[20]) {
#pragma unroll
  for (int i = 0; i < 5; i++) {
    uint2 u; u.x = pack_bf16(v[4 * i], v[4 * i + 1]); u.y = pack_bf16(v[4 * i + 2], v[4 * i + 3]);
    *reinterpret_cast<uint2*>(p + (lane + 32 * i) * 4) = u;
  }
}
__device__ __forceinline__ void load_row_f32(const float* p, int lane, float (&v)[20]) {
#pragma unroll
  for (int i = 0; i < 5; i++) {
    float4 u = *reinterpret_cast<const float4*>(p + (lane + 32 * i) * 4);
    v[4 * i] = u.x; v[4 * i + 1] = u.y; v[4 * i + 2] = u.z; v[4 * i + 3] = u.w;
  }
}

__global__ void __launch_bounds__(256) ln1_kernel(const bf16* __restrict__ x) {
  TL_ENTRY(1);
  pdl_launch();
  const int lane = threadIdx.x & 31, row = blockIdx.x * 8 + (threadIdx.x >> 5);
  float v[20];
  load_row_bf16(x + (size_t)row * D_, lane, v);
  float mean, rstd;
  row_stats(v, mean, rstd);
  if (lane < 8) g_st1[row * 8 + lane] = 0.f;
  if (lane < 2) g_st2[row * 2 + lane] = 0.f;
  pdl_wait();
  if (threadIdx.x == 0) TL_WAITED(1);
  float sa[20], ca[20];
  load_row_f32(g_mod, lane, sa);
  load_row_f32(g_mod + D_, lane, ca);
#pragma unroll
  for (int i = 0; i < 20; i++) v[i] = fmaf((v[i] - mean) * rstd, ca[i], sa[i]);
  store_row_bf16(g_h + (size_t)row * D_, lane, v);
  if (threadIdx.x == 0) TL_END(1);
}

constexpr int PREP_JOBS = 200 + 200 + 480 + 480;
struct PrepW { const bf16 *w1, *w2, *w3, *w4; };
__device__ __forceinline__ void prep_warp(const PrepW& pw, bf16 (*tile)[72], int lane) {
#pragma unroll 1
  for (int job = blockIdx.x; job < PREP_JOBS; job += gridDim.x) {
    const bf16* src; bf16* dst; int ld = D_, ldd = D_, kt, nt, kind = 1;
    if (job < 200) { src = pw.w1; dst = g_w1t; kt = job / 10; nt = job % 10; kind = 0; }
    else if (job < 400) { src = pw.w2; dst = g_w2t; kt = (job - 200) / 10; nt = (job - 200) % 10; }
    else if (job < 880) { src = pw.w4; dst = g_w4t; ldd = F_; kt = (job - 400) / 10; nt = (job - 400) % 10; }
    else { src = pw.w3; dst = nullptr; ld = F_; kt = (job - 880) / 24; nt = (job - 880) % 24; kind = 2; }
    src += (size_t)(kt * 32 + (lane >> 3)) * ld + nt * 64 + (lane & 7) * 8;
    __syncwarp();
#pragma unroll
    for (int h = 0; h < 2; h++) {
      uint4 v[4];
#pragma unroll
      for (int i = 0; i < 4; i++) v[i] = __ldg(reinterpret_cast<const uint4*>(src + (size_t)(h * 16 + i * 4) * ld));
#pragma unroll
      for (int i = 0; i < 4; i++) *reinterpret_cast<uint4*>(&tile[h * 16 + i * 4 + (lane >> 3)][(lane & 7) * 8]) = v[i];
    }
    __syncwarp();
    const float* pa = g_mod + 4 * D_ + kt * 32;
    const float* pb = g_mod + 3 * D_ + kt * 32;
#pragma unroll 1
    for (int h = 0; h < 2; h++) {
      const int n = lane + 32 * h;
      float sa = 0.f, sb = 0.f, sc = 0.f;
#pragma unroll 1
      for (int c = 0; c < 4; c++) {
        uint32_t u[4];
#pragma unroll
        for (int e = 0; e < 4; e++) {
          const int k = c * 8 + 2 * e;
          float lo = __bfloat162float(tile[k][n]), hi = __bfloat162float(tile[k + 1][n]);
          sc += lo + hi;
          if (kind == 0) {
            const float2 a = __ldcg(reinterpret_cast<const float2*>(pa + k)), b = __ldcg(reinterpret_cast<const float2*>(pb + k));
            sb = fmaf(b.x, lo, fmaf(b.y, hi, sb));
            lo *= a.x; hi *= a.y;
          }
          u[e] = pack_bf16(lo, hi);
          sa += bf_lo(u[e]) + bf_hi(u[e]);
        }
        if (kind != 2) *reinterpret_cast<uint4*>(dst + (size_t)(nt * 64 + n) * ldd + kt * 32 + c * 8) = make_uint4(u[0], u[1], u[2], u[3]);
      }
      if (kind == 0) { atomicAdd(&g_vec[nt * 64 + n], sa); atomicAdd(&g_vec[D_ + nt * 64 + n], sb); atomicAdd(&g_vec[2 * D_ + nt * 64 + n], sc); }
      else if (kind == 2) atomicAdd(&g_vec[3 * D_ + nt * 64 + n], sc);
    }
  }
  __syncwarp();
  if (lane == 0) {
    asm volatile("fence.acq_rel.gpu;" ::: "memory");
    asm volatile("red.relaxed.gpu.global.add.u32 [%0], 1;" :: "l"(g_flag + F_PREP) : "memory");
  }
}

constexpr int A_NSLOT = 9;
constexpr int A_SLOT = 24576;
constexpr int A_NKV = S_ / 64;
constexpr int PREP_CTAS = 128;

struct Ring {
  uint32_t slot, phase;
  __device__ __forceinline__ void adv(int n) { if (++slot == (uint32_t)n) { slot = 0; phase ^= 1; } }
};
constexpr int T_PAR = A_NSLOT * A_SLOT + 384;
constexpr int T_PREP = T_PAR + 3712;
constexpr int T_SMEM = T_PREP + 32 * 72 * 2 + 1024;
enum { P_OGA = 0, P_OA = 80, P_OB = 160, P_VA = 240, P_VB = 320, P_VC = 400, P_A2 = 480, P_B2 = 560, P_GB = 640, P_CS3 = 720, P_SC = 912 };

__device__ __forceinline__ void flag_wait(const unsigned* p, unsigned target) {
  asm volatile(
      "{\n.reg .pred p;\n.reg .u32 n, v;\n"
      "mov.u32 n, 0;\n"
      "SPIN:\n"
      "ld.relaxed.gpu.global.u32 v, [%0];\n"
      "setp.ge.u32 p, v, %1;\n"
      "@p bra DONE;\n"
      "add.u32 n, n, 1;\n"
      "setp.gt.u32 p, n, 4194304;\n"
      "@p trap;\n"
      "bra SPIN;\n"
      "DONE:\n}\n" :: "l"(p), "r"(target) : "memory");
}
__device__ __forceinline__ void fence_async_global() { asm volatile("fence.proxy.async.global;" ::: "memory"); }
__device__ __forceinline__ float lds_f(uint32_t a) { float v; asm volatile("ld.shared.f32 %0, [%1];" : "=f"(v) : "r"(a)); return v; }
__device__ __forceinline__ float2 lds_f2(uint32_t a) { float2 v; asm volatile("ld.shared.v2.f32 {%0, %1}, [%2];" : "=f"(v.x), "=f"(v.y) : "r"(a)); return v; }
__device__ __forceinline__ uint4 ldcg4(const void* p) { return __ldcg(reinterpret_cast<const uint4*>(p)); }

__device__ __forceinline__ void sts_f2(uint32_t a, float x, float y) { asm volatile("st.shared.v2.f32 [%0], {%1, %2};" :: "r"(a), "f"(x), "f"(y) : "memory"); }
__device__ __forceinline__ void sts_u4(uint32_t a, uint4 v) { asm volatile("st.shared.v4.u32 [%0], {%1, %2, %3, %4};" :: "r"(a), "r"(v.x), "r"(v.y), "r"(v.z), "r"(v.w) : "memory"); }
__device__ __forceinline__ void sts_u1(uint32_t a, uint32_t v) { asm volatile("st.shared.u32 [%0], %1;" :: "r"(a), "r"(v) : "memory"); }
__device__ __forceinline__ void fence_async_smem() { asm volatile("fence.proxy.async.shared::cta;" ::: "memory"); }
__device__ __forceinline__ void bulk_store(void* dst, uint32_t src, uint32_t bytes) {
  asm volatile("cp.async.bulk.global.shared::cta.bulk_group [%0], [%1], %2;" :: "l"(dst), "r"(src), "r"(bytes) : "memory");
}
__device__ __forceinline__ void bulk_red_f32(void* dst, uint32_t src, uint32_t bytes) {
  asm volatile("cp.reduce.async.bulk.global.shared::cta.bulk_group.add.f32 [%0], [%1], %2;" :: "l"(dst), "r"(src), "r"(bytes) : "memory");
}
__device__ __forceinline__ void tma_store2d(const CUtensorMap* m, uint32_t src, int c0, int c1) {
  asm volatile("cp.async.bulk.tensor.2d.global.shared::cta.bulk_group [%0, {%2, %3}], [%1];" :: "l"(m), "r"(src), "r"(c0), "r"(c1) : "memory");
}
__device__ __forceinline__ void bulk_done() { asm volatile("cp.async.bulk.commit_group;\ncp.async.bulk.wait_group 0;" ::: "memory"); }
__device__ __forceinline__ void flag_add(unsigned* f) { asm volatile("red.relaxed.gpu.global.add.u32 [%0], 1;" :: "l"(f) : "memory"); }
__device__ __forceinline__ float4 lds_f4(uint32_t a) { float4 v; asm volatile("ld.shared.v4.f32 {%0, %1, %2, %3}, [%4];" : "=f"(v.x), "=f"(v.y), "=f"(v.z), "=f"(v.w) : "r"(a) : "memory"); return v; }
__device__ __forceinline__ uint4 lds_u4(uint32_t a) { uint4 v; asm volatile("ld.shared.v4.u32 {%0, %1, %2, %3}, [%4];" : "=r"(v.x), "=r"(v.y), "=r"(v.z), "=r"(v.w) : "r"(a) : "memory"); return v; }
__device__ __forceinline__ void lds8(uint32_t a, float (&v)[8]) {
  const float4 p = lds_f4(a), q = lds_f4(a + 16);
  v[0] = p.x; v[1] = p.y; v[2] = p.z; v[3] = p.w; v[4] = q.x; v[5] = q.y; v[6] = q.z; v[7] = q.w;
}
__device__ __forceinline__ void lds8_bf(uint32_t a, float (&v)[8]) {
  const uint4 u = lds_u4(a);
  v[0] = bf_lo(u.x); v[1] = bf_hi(u.x); v[2] = bf_lo(u.y); v[3] = bf_hi(u.y); v[4] = bf_lo(u.z); v[5] = bf_hi(u.z); v[6] = bf_lo(u.w); v[7] = bf_hi(u.w);
}
__device__ __forceinline__ uint4 pack8(const float (&v)[8]) {
  return make_uint4(pack_bf16(v[0], v[1]), pack_bf16(v[2], v[3]), pack_bf16(v[4], v[5]), pack_bf16(v[6], v[7]));
}
__device__ __forceinline__ float quad_sum(float v) {
  v += __shfl_xor_sync(0xffffffffu, v, 1);
  v += __shfl_xor_sync(0xffffffffu, v, 2);
  return v;
}
__device__ __forceinline__ void mbar_wait_c(uint32_t a, uint32_t ph) {
  asm volatile("{\n.reg .pred p;\nSPIN:\nmbarrier.try_wait.parity.shared::cta.b64 p, [%0], %1;\n@!p bra SPIN;\n}\n" :: "r"(a), "r"(ph) : "memory");
}
constexpr int E_TILE = 128 * 80 * 2;

struct Maps { CUtensorMap h, wq, k, v, o, wo3, wo2, xa, w1t, us, w2t, x1, w3, g, w4t, ex, exa, ex1, sxa, sus, sx1, sout; };
struct PfList { const uint8_t* p[6]; };

constexpr int M_AOFF = 102400, M_NA = 7;

__global__ void __cluster_dims__(2, 1, 1) __launch_bounds__(384, 1)
fused_kernel(const __grid_constant__ Maps tm, const __grid_constant__ PfList pf, const __grid_constant__ PrepW pw, const bf16* __restrict__ x, bf16* __restrict__ out) {
  extern __shared__ uint8_t smem_raw[];
  const uint32_t sb = (smem_u32(smem_raw) + 1023) & ~1023u;
  TL_ENTRY(2);
  const uint32_t bar_full = sb + A_NSLOT * A_SLOT;
  const uint32_t bar_empty = bar_full + 8 * A_NSLOT;
  const uint32_t bar_sig = bar_empty + 8 * A_NSLOT;
  const uint32_t mb_full = bar_sig + 16;
  const uint32_t mb_empty = mb_full + 96;
  const uint32_t par = sb + T_PAR;
  float* parf = reinterpret_cast<float*>(smem_raw + (par - smem_u32(smem_raw)));
  uint32_t rank;
  asm volatile("mov.u32 %0, %%cluster_ctarank;" : "=r"(rank));
  const int cid = blockIdx.x >> 1;
  const int wid = __shfl_sync(0xffffffffu, threadIdx.x >> 5, 0);
  const int wg = wid >> 2;
  const int qtile = (cid & 7) * 2 + rank, hbase = cid >> 3;
  const int o_qt = qtile, o_nh = (cid >> 3) & 1, o_ks = cid >> 4;
  const int o_col = o_nh * 320 + o_ks * 80;
  const int qt = cid >> 2, js = (cid & 3) * 2 + rank;
  if (threadIdx.x == 0) {
    for (int i = 0; i < A_NSLOT; i++) { mbar_init(bar_full + 8 * i, 1); mbar_init(bar_empty + 8 * i, 16); }
    mbar_init(bar_sig, 4); mbar_init(bar_sig + 8, 4);
    for (int i = 0; i < 12; i++) { mbar_init(mb_full + 8 * i, 1); mbar_init(mb_empty + 8 * i, i < 5 ? 8 : 16); }
    asm volatile("fence.mbarrier_init.release.cluster;" ::: "memory");
    prefetch_tmap(&tm.h); prefetch_tmap(&tm.wq); prefetch_tmap(&tm.k); prefetch_tmap(&tm.v);
  }
  __syncthreads();
  cluster_sync();

  if (wg == 0) {
    asm volatile("setmaxnreg.dec.sync.aligned.u32 40;");
    if (wid == 0) {
      Ring r{0, 1};
#define P_ACQ(bytes_) do { mbar_wait(bar_empty + 8 * r.slot, r.phase); mbar_expect_e(bar_full + 8 * r.slot, bytes_); } while (0)
#define P_DST (sb + r.slot * A_SLOT)
#define P_BAR (bar_full + 8 * r.slot)
      uint64_t pol_ef;
      asm volatile("createpolicy.fractional.L2::evict_first.b64 %0, 1.0;" : "=l"(pol_ef));
      pdl_wait();
      TL_WAITED(2);
#pragma unroll 1
      for (int item = 0; item < 4; item++) {
        const int head = hbase + 8 * item;
#pragma unroll 1
        for (int kb = 0; kb < 10; kb++) {
          P_ACQ(16384);
          tma2d(P_DST, &tm.h, P_BAR, kb * 64, qtile * 128);
          r.adv(A_NSLOT);
          P_ACQ(A_SLOT);
          if ((uint32_t)(kb & 1) == rank) tma3d_mc_hint(P_DST, &tm.wq, P_BAR, 0, kb * 64, head * 3, 3, pol_ef);
          r.adv(A_NSLOT);
        }
#pragma unroll 1
        for (int j = 0; j <= A_NKV; j++) {
          if (j < A_NKV) {
            P_ACQ(A_SLOT);
            if (rank == 0) tma3d_mc_hint(P_DST, &tm.k, P_BAR, 0, head * S_ + j * 64, 0, 3, pol_ef);
            r.adv(A_NSLOT);
          }
          if (j > 0) {
            P_ACQ(A_SLOT);
            if (rank == 1) tma3d_mc_hint(P_DST, &tm.v, P_BAR, 0, head * S_ + (j - 1) * 64, 0, 3, pol_ef);
            r.adv(A_NSLOT);
          }
          if (item == 3 && (j & 3) == 0) {
            const int c = (j >> 2) * 128 + blockIdx.x;
            if (c < 980) {
              const int li = c < 480 ? 0 : c < 600 ? 1 : c < 720 ? 2 : c < 880 ? 3 : c < 930 ? 4 : 5;
              const int c0 = c < 480 ? 0 : c < 600 ? 480 : c < 720 ? 600 : c < 880 ? 720 : c < 930 ? 880 : 930;
              l2_prefetch16k(pf.p[li] + (size_t)(c - c0) * 16384);
            }
          }
          if (item == 3) {
            if (j >= 6 && j < 24) {
              const int kb = j - 6;
              l2_prefetch_t2d(&tm.o, ((kb / 6) * 8 + 2 * o_ks + (kb % 6) / 3) * DH_ + (kb % 3) * 64, o_qt * 128);
            }
            if (j >= 24 && j < 30) flag_wait(g_flag + F_O + o_qt * 32 + ((j - 24) >> 1) * 8 + 2 * o_ks + (j & 1), 2);
            if (j == 0 && threadIdx.x == 0) {
              prefetch_tmap(&tm.o); prefetch_tmap(&tm.wo3); prefetch_tmap(&tm.wo2); prefetch_tmap(&tm.xa); prefetch_tmap(&tm.w1t); prefetch_tmap(&tm.us);
              prefetch_tmap(&tm.w2t); prefetch_tmap(&tm.x1); prefetch_tmap(&tm.w3); prefetch_tmap(&tm.g); prefetch_tmap(&tm.w4t);
              prefetch_tmap(&tm.ex); prefetch_tmap(&tm.exa); prefetch_tmap(&tm.ex1);
              prefetch_tmap(&tm.sxa); prefetch_tmap(&tm.sus); prefetch_tmap(&tm.sx1); prefetch_tmap(&tm.sout);
            }
          }
        }
      }
#pragma unroll 1
      for (int kb = 0; kb < 24; kb++) {
        const int head = (kb / 6) * 8 + 2 * o_ks + (kb % 6) / 3;
        const int kcol = head * DH_ + (kb % 3) * 64;
        P_ACQ(24576);
        if (rank == 0) tma3d_mc(P_DST, &tm.wo3, P_BAR, 0, kcol, o_nh * 5, 3);
        r.adv(A_NSLOT);
        P_ACQ(16384);
        if (rank == 1) tma3d_mc(P_DST, &tm.wo2, P_BAR, 0, kcol, o_nh * 5 + 3, 3);
        r.adv(A_NSLOT);
        if (kb == 18 || kb == 21) flag_wait(g_flag + F_O + o_qt * 32 + head, 2);
        if (kb % 3 == 0) fence_async_global();
        P_ACQ(16384);
        tma2d(P_DST, &tm.o, P_BAR, kcol, o_qt * 128);
        r.adv(A_NSLOT);
      }
      P_ACQ(E_TILE);
      tma2d(P_DST, &tm.ex, P_BAR, o_col, o_qt * 128);
      r.adv(A_NSLOT);
      flag_wait(g_flag + F_XCH + (o_qt * 2 + o_nh) * 4 + o_ks, 6);
      fence_async_global();
#pragma unroll 1
      for (int i = 0; i < 3; i++) {
        P_ACQ(E_TILE);
        bulk_load(P_DST, g_xch + (size_t)((((o_qt * 2 + o_nh) * 4 + o_ks) * 4) + ((o_ks + 1 + i) & 3)) * (E_TILE / 2), E_TILE, P_BAR);
        r.adv(A_NSLOT);
      }
      flag_wait(g_flag + F_PREP, PREP_CTAS);
      fence_async_global();
#pragma unroll 1
      for (int i = 0; i < A_NSLOT; i++) { mbar_wait(bar_empty + 8 * r.slot, r.phase); r.adv(A_NSLOT); }
      Ring ra{0, 1};
      uint32_t bpar = 0x1f;
#pragma unroll 1
      for (int ph = 0; ph < 4; ph++) {
        const CUtensorMap* ma = ph == 0 ? &tm.xa : ph == 1 ? &tm.us : ph == 2 ? &tm.x1 : &tm.g;
        const CUtensorMap* mb = ph == 0 ? &tm.w1t : ph == 1 ? &tm.w2t : ph == 2 ? &tm.w3 : &tm.w4t;
        const int nkb = ph == 3 ? 24 : 10;
        const int nbl = ph == 2 ? 10 : nkb / 2;
        const int nel = ph == 1 ? 1 : ph == 3 ? 2 : 0;
        const uint32_t nbs = ph == 2 ? 4 : 5, bsz = ph == 2 ? 24576 : 20480;
        int bl = 0; uint32_t bs = 0;
#pragma unroll 1
        for (int i = 0; i < 5; i++) mbar_wait(mb_empty + 8 * i, (bpar >> i) & 1);
#define T_LOADB() do { mbar_wait(mb_empty + 8 * bs, (bpar >> bs) & 1); bpar ^= 1u << bs; mbar_expect_e(mb_full + 8 * bs, bsz);    \
                       if (bl < nbl) tma3d(sb + bs * bsz, mb, mb_full + 8 * bs, 0, ph == 2 ? bl * 64 : js * 80, ph == 2 ? js * 3 : bl * 2); \
                       else tma2d(sb + bs * bsz, bl == nbl ? &tm.exa : &tm.ex1, mb_full + 8 * bs, js * 80, qt * 128); \
                       bl++; if (++bs == nbs) bs = 0; } while (0)
#pragma unroll 1
        for (uint32_t i = 0; i < nbs; i++) T_LOADB();
        TX(8 + ph * 4);
        const unsigned* fl = g_flag + F_XA + 16 * ph;
        flag_wait(fl + qt, 16);
        if (ph == 1) { if (qt > 0) flag_wait(fl + qt - 1, 16); if (qt < 15) flag_wait(fl + qt + 1, 16); }
        TX(9 + ph * 4);
        fence_async_global();
#pragma unroll 1
        for (int kb = 0; kb < nkb; kb++) {
          mbar_wait(mb_empty + 40 + 8 * ra.slot, ra.phase);
          mbar_expect_e(mb_full + 40 + 8 * ra.slot, 16384);
          tma2d_mc(sb + M_AOFF + ra.slot * 16384 + rank * 8192, ma, mb_full + 40 + 8 * ra.slot, kb * 64, qt * 128 + (int)rank * 64, 3);
          ra.adv(M_NA);
          while (bl < nbl + nel && (kb == nkb - 1 || kb >= (ph == 2 ? bl + 2 : 2 * bl - 3))) T_LOADB();
        }
      }
    } else if (wid < 3) {
      const int w = wid - 1, lane = threadIdx.x & 31;
#pragma unroll 1
      for (int sig = 0; sig < 4; sig++) {
        mbar_wait(bar_sig + 8 * w, sig & 1);
        if (lane == 0) {
          asm volatile("fence.acq_rel.gpu;" ::: "memory");
          flag_add(g_flag + F_O + qtile * 32 + hbase + 8 * sig);
        }
        __syncwarp();
      }
    } else {
      const int lane = threadIdx.x & 31;
      pdl_wait();
      prep_warp(pw, reinterpret_cast<bf16(*)[72]>(smem_raw + (sb + T_PREP - smem_u32(smem_raw))), lane);
      flag_wait(g_flag + F_PREP, PREP_CTAS);
#pragma unroll 1
      for (int i = lane; i < P_SC; i += 32) {
        const int v = i < P_CS3 ? i / 80 : 9, j = i - (i < P_CS3 ? v * 80 : P_CS3);
        const float* src = v == 0 ? g_mod + 2 * D_ + o_col : v == 1 ? g_mod + 4 * D_ + o_col : v == 2 ? g_mod + 3 * D_ + o_col
                         : v < 6 ? g_vec + (v - 3) * D_ + js * 80 : v == 6 ? g_mod + 4 * D_ + js * 80 : v == 7 ? g_mod + 3 * D_ + js * 80
                         : v == 8 ? g_mod + 5 * D_ + js * 80 : g_vec + 3 * D_ + js * 192;
        parf[i] = __ldcg(src + j);
      }
      float sv[5] = {0.f, 0.f, 0.f, 0.f, 0.f};
#pragma unroll 1
      for (int i = lane; i < D_; i += 32) {
        const float a = __ldcg(g_mod + 4 * D_ + i), b = __ldcg(g_mod + 3 * D_ + i);
        sv[0] += a; sv[1] = fmaf(a, a, sv[1]); sv[2] = fmaf(a, b, sv[2]); sv[3] += b; sv[4] = fmaf(b, b, sv[4]);
      }
#pragma unroll 1
      for (int o_ = 16; o_ > 0; o_ >>= 1) {
#pragma unroll
        for (int i = 0; i < 5; i++) sv[i] += __shfl_xor_sync(0xffffffffu, sv[i], o_);
      }
      if (lane == 0) {
#pragma unroll
        for (int i = 0; i < 5; i++) parf[P_SC + i] = sv[i];
      }
      bar_arrive(6, 288);
    }
    __syncwarp();
    cluster_sync();
  } else {
    asm volatile("setmaxnreg.inc.sync.aligned.u32 232;");
    const int w = wg - 1;
    const int lane = threadIdx.x & 31;
    const int warp = wid & 3;
    const int tid = threadIdx.x - 128;
    const uint32_t rel_base = mapa(bar_empty, (lane == 0) ? rank : (rank ^ 1));
    Ring r{0, 0};
#define A_RELEASE(slot_) do { if (lane < 2) mbar_arrive_remote(rel_base + 8 * (slot_)); } while (0)
#define SIGNAL() do { __syncwarp(); if (lane == 0) mbar_arrive(bar_sig + 8 * w); } while (0)
    {
    const float SC = 0.07216878364870322f * 1.4426950408889634f;
    float o[96];
    uint32_t q[48];
    float s[32];
    uint32_t p[16], p2[16];
    if (w == 1) bar_arrive(1, 256);
    for (int item = 0; item < 4; item++) {
      const int head = hbase + 8 * item;
      TSA(item, 0);
      uint32_t prevA = 0, prevB = 0;
      for (int kb = 0; kb < 10; kb++) {
        const uint32_t sA = r.slot; mbar_wait_c(bar_full + 8 * sA, r.phase); r.adv(A_NSLOT);
        const uint32_t sB = r.slot; mbar_wait_c(bar_full + 8 * sB, r.phase); r.adv(A_NSLOT);
        const uint64_t da = mkdesc(sb + sA * A_SLOT + w * 8192, 16, 1024);
        const uint64_t db = mkdesc(sb + sB * A_SLOT, 8192, 1024);
        wg_fence();
#pragma unroll
        for (int kk = 0; kk < 4; kk++) wgmma_ss_n192<1>(o, da + kk * 2, db + kk * 128, (kb | kk) != 0);
        wg_commit();
        if (kb > 0) { wg_wait<1>(); A_RELEASE(prevA); A_RELEASE(prevB); }
        prevA = sA; prevB = sB;
      }
      wg_wait<0>();
      fence_regs(o);
      A_RELEASE(prevA); A_RELEASE(prevB);
#pragma unroll
      for (int i = 0; i < 48; i++) q[i] = pack_bf16(o[2 * i], o[2 * i + 1]);

      TSA(item, 1);
      float c0, c1, l0, l1;
      {
        const uint32_t sK = r.slot; mbar_wait_c(bar_full + 8 * sK, r.phase); r.adv(A_NSLOT);
        const uint64_t dk = mkdesc(sb + sK * A_SLOT, 16, 1024);
        bar_sync(1 + w, 256);
        wg_fence();
#pragma unroll
        for (int kk = 0; kk < 12; kk++)
          wgmma_rs_n64<0>(s, q[4 * kk], q[4 * kk + 1], q[4 * kk + 2], q[4 * kk + 3], dk + (kk >> 2) * 512 + (kk & 3) * 2, kk != 0);
        wg_commit();
        bar_arrive(1 + (w ^ 1), 256);
        wg_wait<0>();
        fence_regs(s);
        A_RELEASE(sK);
        float mx0 = fmaxf(s[0], s[1]), mx1 = fmaxf(s[2], s[3]);
#pragma unroll
        for (int i = 1; i < 8; i++) { mx0 = fmaxf(mx0, fmaxf(s[4 * i], s[4 * i + 1])); mx1 = fmaxf(mx1, fmaxf(s[4 * i + 2], s[4 * i + 3])); }
        mx0 = fmaxf(mx0, __shfl_xor_sync(0xffffffffu, mx0, 1)); mx1 = fmaxf(mx1, __shfl_xor_sync(0xffffffffu, mx1, 1));
        mx0 = fmaxf(mx0, __shfl_xor_sync(0xffffffffu, mx0, 2)); mx1 = fmaxf(mx1, __shfl_xor_sync(0xffffffffu, mx1, 2));
        c0 = mx0 * SC; c1 = mx1 * SC;
        l0 = 0.f; l1 = 0.f;
#pragma unroll
        for (int i = 0; i < 8; i++) {
          s[4 * i] = ex2(fmaf(s[4 * i], SC, -c0)); s[4 * i + 1] = ex2(fmaf(s[4 * i + 1], SC, -c0));
          s[4 * i + 2] = ex2(fmaf(s[4 * i + 2], SC, -c1)); s[4 * i + 3] = ex2(fmaf(s[4 * i + 3], SC, -c1));
          l0 += s[4 * i] + s[4 * i + 1]; l1 += s[4 * i + 2] + s[4 * i + 3];
        }
#pragma unroll
        for (int i = 0; i < 16; i++) p[i] = pack_bf16(s[2 * i], s[2 * i + 1]);
      }
      TSA(item, 2);
      uint32_t okn;
      {
        Ring r2 = r; r2.adv(A_NSLOT);
        okn = mbar_try(bar_full + 8 * r.slot, r.phase) & mbar_try(bar_full + 8 * r2.slot, r2.phase);
      }
#define A_STEP(PC, PN, FIRST)                                                                                          \
      {                                                                                                                \
        const uint32_t sK = r.slot, phK = r.phase; r.adv(A_NSLOT);                                                     \
        const uint32_t sV = r.slot, phV = r.phase; r.adv(A_NSLOT);                                                     \
        const uint64_t dk = mkdesc(sb + sK * A_SLOT, 16, 1024);                                                        \
        const uint64_t dv = mkdesc(sb + sV * A_SLOT, 8192, 1024);                                                      \
        if (!okn) { mbar_wait_c(bar_full + 8 * sK, phK); mbar_wait_c(bar_full + 8 * sV, phV); }                            \
        bar_sync(1 + w, 256);                                                                                          \
        wg_fence();                                                                                                    \
        _Pragma("unroll") for (int kk = 0; kk < 12; kk++)                                                              \
          wgmma_rs_n64<0>(s, q[4 * kk], q[4 * kk + 1], q[4 * kk + 2], q[4 * kk + 3], dk + (kk >> 2) * 512 + (kk & 3) * 2, kk != 0); \
        wg_commit();                                                                                                   \
        _Pragma("unroll") for (int kk = 0; kk < 4; kk++)                                                               \
          wgmma_rs_n192<1>(o, PC[4 * kk], PC[4 * kk + 1], PC[4 * kk + 2], PC[4 * kk + 3], dv + kk * 128, !(FIRST) || (kk != 0)); \
        wg_commit();                                                                                                   \
        bar_arrive(1 + (w ^ 1), 256);                                                                                  \
        {                                                                                                              \
          Ring r2 = r; r2.adv(A_NSLOT);                                                                                \
          okn = mbar_try(bar_full + 8 * r.slot, r.phase) & mbar_try(bar_full + 8 * r2.slot, r2.phase);                 \
        }                                                                                                              \
        wg_wait<1>();                                                                                                  \
        fence_regs(s);                                                                                                 \
        A_RELEASE(sK);                                                                                                 \
        float b0 = 0.f, b1 = 0.f;                                                                                      \
        _Pragma("unroll") for (int i = 0; i < 8; i++) {                                                                \
          const float e0 = ex2(fmaf(s[4 * i], SC, -c0)), e1 = ex2(fmaf(s[4 * i + 1], SC, -c0));                        \
          const float e2 = ex2(fmaf(s[4 * i + 2], SC, -c1)), e3 = ex2(fmaf(s[4 * i + 3], SC, -c1));                    \
          b0 += e0 + e1; b1 += e2 + e3;                                                                                \
          PN[2 * i] = pack_bf16(e0, e1); PN[2 * i + 1] = pack_bf16(e2, e3);                                            \
        }                                                                                                              \
        wg_wait<0>();                                                                                                  \
        fence_regs(o);                                                                                                 \
        fence_regs(PC);                                                                                                \
        A_RELEASE(sV);                                                                                                 \
        if (__any_sync(0xffffffffu, !(b0 <= 65536.f) || !(b1 <= 65536.f))) {                                           \
          float mx0 = fmaxf(s[0], s[1]), mx1 = fmaxf(s[2], s[3]);                                                      \
          _Pragma("unroll") for (int i = 1; i < 8; i++) {                                                              \
            mx0 = fmaxf(mx0, fmaxf(s[4 * i], s[4 * i + 1])); mx1 = fmaxf(mx1, fmaxf(s[4 * i + 2], s[4 * i + 3]));     \
          }                                                                                                            \
          mx0 = fmaxf(mx0, __shfl_xor_sync(0xffffffffu, mx0, 1)); mx1 = fmaxf(mx1, __shfl_xor_sync(0xffffffffu, mx1, 1)); \
          mx0 = fmaxf(mx0, __shfl_xor_sync(0xffffffffu, mx0, 2)); mx1 = fmaxf(mx1, __shfl_xor_sync(0xffffffffu, mx1, 2)); \
          const float n0 = fmaxf(c0, mx0 * SC), n1 = fmaxf(c1, mx1 * SC);                                              \
          const float a0 = ex2(c0 - n0), a1 = ex2(c1 - n1);                                                            \
          c0 = n0; c1 = n1;                                                                                            \
          l0 *= a0; l1 *= a1;                                                                                          \
          _Pragma("unroll") for (int i = 0; i < 24; i++) { o[4 * i] *= a0; o[4 * i + 1] *= a0; o[4 * i + 2] *= a1; o[4 * i + 3] *= a1; } \
          b0 = 0.f; b1 = 0.f;                                                                                          \
          _Pragma("unroll") for (int i = 0; i < 8; i++) {                                                              \
            const float e0 = ex2(fmaf(s[4 * i], SC, -c0)), e1 = ex2(fmaf(s[4 * i + 1], SC, -c0));                      \
            const float e2 = ex2(fmaf(s[4 * i + 2], SC, -c1)), e3 = ex2(fmaf(s[4 * i + 3], SC, -c1));                  \
            b0 += e0 + e1; b1 += e2 + e3;                                                                              \
            PN[2 * i] = pack_bf16(e0, e1); PN[2 * i + 1] = pack_bf16(e2, e3);                                          \
          }                                                                                                            \
        }                                                                                                              \
        l0 += b0; l1 += b1;                                                                                            \
      }
      for (int jj = 0; jj < 15; jj++) {
        A_STEP(p, p2, jj == 0)
        A_STEP(p2, p, false)
      }
      A_STEP(p, p2, false)
      TSA(item, 3);
      {
        const uint32_t sV = r.slot; mbar_wait_c(bar_full + 8 * sV, r.phase); r.adv(A_NSLOT);
        const uint64_t dv = mkdesc(sb + sV * A_SLOT, 8192, 1024);
        bar_sync(1 + w, 256);
        wg_fence();
#pragma unroll
        for (int kk = 0; kk < 4; kk++)
          wgmma_rs_n192<1>(o, p2[4 * kk], p2[4 * kk + 1], p2[4 * kk + 2], p2[4 * kk + 3], dv + kk * 128, 1);
        wg_commit();
        bar_arrive(1 + (w ^ 1), 256);
        wg_wait<0>();
        fence_regs(o);
        A_RELEASE(sV);
      }
      TSA(item, 4);
      l0 += __shfl_xor_sync(0xffffffffu, l0, 1); l1 += __shfl_xor_sync(0xffffffffu, l1, 1);
      l0 += __shfl_xor_sync(0xffffffffu, l0, 2); l1 += __shfl_xor_sync(0xffffffffu, l1, 2);
      const float i0 = 1.f / l0, i1 = 1.f / l1;
      bf16* orow = g_o + (size_t)(qtile * 128 + w * 64 + warp * 16 + (lane >> 2)) * HD_ + head * DH_ + (lane & 3) * 8;
#pragma unroll
      for (int g = 0; g < 6; g++) {
        uint32_t u0 = pack_bf16(o[16 * g + 0] * i0, o[16 * g + 1] * i0), u1 = pack_bf16(o[16 * g + 4] * i0, o[16 * g + 5] * i0);
        uint32_t u2 = pack_bf16(o[16 * g + 8] * i0, o[16 * g + 9] * i0), u3 = pack_bf16(o[16 * g + 12] * i0, o[16 * g + 13] * i0);
        quad_transpose(u0, u1, u2, u3, lane);
        *reinterpret_cast<uint4*>(orow + g * 32) = make_uint4(u0, u1, u2, u3);
        uint32_t v0 = pack_bf16(o[16 * g + 2] * i1, o[16 * g + 3] * i1), v1 = pack_bf16(o[16 * g + 6] * i1, o[16 * g + 7] * i1);
        uint32_t v2 = pack_bf16(o[16 * g + 10] * i1, o[16 * g + 11] * i1), v3 = pack_bf16(o[16 * g + 14] * i1, o[16 * g + 15] * i1);
        quad_transpose(v0, v1, v2, v3, lane);
        *reinterpret_cast<uint4*>(orow + (size_t)8 * HD_ + g * 32) = make_uint4(v0, v1, v2, v3);
      }
      SIGNAL();
      TSA(item, 5);
    }
    }
    TS(3, 2);
    uint8_t* const sm = smem_raw + (sb - smem_u32(smem_raw));
    const int fr = w * 64 + warp * 16 + (lane >> 2);
    const uint32_t f_e = (uint32_t)(fr * 160 + (lane & 3) * 4);
    const float2* const pf2 = reinterpret_cast<const float2*>(parf) + (lane & 3);
    const uint32_t stat = sb + T_PREP + w * 2048;
    float* const statf = reinterpret_cast<float*>(sm + T_PREP + w * 2048);
    const bool leader = (tid & 127) == 0;
#define SM32(off) (*reinterpret_cast<uint32_t*>(sm + (off)))

    {
      float acc1[96], acc2[64];
      uint32_t p0 = 0, p1 = 0, p2 = 0;
#pragma unroll 1
      for (int kb = 0; kb < 24; kb++) {
        const uint32_t s1 = r.slot; mbar_wait_c(bar_full + 8 * s1, r.phase); r.adv(A_NSLOT);
        const uint32_t s2 = r.slot; mbar_wait_c(bar_full + 8 * s2, r.phase); r.adv(A_NSLOT);
        const uint32_t sa = r.slot; mbar_wait_c(bar_full + 8 * sa, r.phase); r.adv(A_NSLOT);
        const uint64_t da = mkdesc(sb + sa * A_SLOT + w * 8192, 16, 1024);
        const uint64_t d1 = mkdesc(sb + s1 * A_SLOT, 8192, 1024), d2 = mkdesc(sb + s2 * A_SLOT, 8192, 1024);
        wg_fence();
#pragma unroll
        for (int kk = 0; kk < 4; kk++) {
          wgmma_ss_n192<1>(acc1, da + kk * 2, d1 + kk * 128, (kb | kk) != 0);
          wgmma_ss_n128<1>(acc2, da + kk * 2, d2 + kk * 128, (kb | kk) != 0);
        }
        wg_commit();
        if (kb > 0) { wg_wait<1>(); A_RELEASE(p0); A_RELEASE(p1); A_RELEASE(p2); }
        p0 = s1; p1 = s2; p2 = sa;
      }
      wg_wait<0>();
      fence_regs(acc1); fence_regs(acc2);
      bar_sync(6, 288);
      TS(0, 0);
#define OACC(e) (((e) < 96) ? acc1[(e) < 96 ? (e) : 0] : acc2[(e) >= 96 ? (e) - 96 : 0])
      float at[40];
#pragma unroll
      for (int d = 0; d < 4; d++) {
        if (d != o_ks) {
          const int i = (d - o_ks - 1) & 3;
          const uint32_t xo = (i == 0 ? p0 : i == 1 ? p1 : p2) * A_SLOT + f_e;
#pragma unroll
          for (int nb = 0; nb < 10; nb++) {
            SM32(xo + nb * 16) = pack_bf16(OACC(d * 40 + 4 * nb), OACC(d * 40 + 4 * nb + 1));
            SM32(xo + nb * 16 + 1280) = pack_bf16(OACC(d * 40 + 4 * nb + 2), OACC(d * 40 + 4 * nb + 3));
          }
        } else {
#pragma unroll
          for (int i = 0; i < 40; i++) at[i] = OACC(d * 40 + i);
        }
      }
      fence_async_smem();
      bar_sync(3 + w, 128);
      if (leader) {
#pragma unroll 1
        for (int i = 0; i < 3; i++)
          bulk_store(g_xch + (size_t)((((o_qt * 2 + o_nh) * 4 + ((o_ks + 1 + i) & 3)) * 4) + o_ks) * (E_TILE / 2) + w * (E_TILE / 4),
                     sb + (i == 0 ? p0 : i == 1 ? p1 : p2) * A_SLOT + w * (E_TILE / 2), E_TILE / 2);
        bulk_done();
#pragma unroll 1
        for (int i = 0; i < 3; i++) flag_add(g_flag + F_XCH + (o_qt * 2 + o_nh) * 4 + ((o_ks + 1 + i) & 3));
        TX(40 + w);
      }
      __syncwarp();
      const uint32_t sx = r.slot; mbar_wait_c(bar_full + 8 * sx, r.phase); r.adv(A_NSLOT);
      const uint32_t q0 = r.slot; mbar_wait_c(bar_full + 8 * q0, r.phase); r.adv(A_NSLOT);
      const uint32_t q1 = r.slot; mbar_wait_c(bar_full + 8 * q1, r.phase); r.adv(A_NSLOT);
      const uint32_t q2 = r.slot; mbar_wait_c(bar_full + 8 * q2, r.phase); r.adv(A_NSLOT);
      TS(0, 1);
      float st[2][6];
#pragma unroll
      for (int i = 0; i < 6; i++) { st[0][i] = 0.f; st[1][i] = 0.f; }
      const uint32_t ot = r.slot * A_SLOT;
#pragma unroll
      for (int nb = 0; nb < 10; nb++) {
        const float2 ga = pf2[(P_OGA + 8 * nb) / 2], a = pf2[(P_OA + 8 * nb) / 2], b = pf2[(P_OB + 8 * nb) / 2];
#pragma unroll
        for (int h = 0; h < 2; h++) {
          const uint32_t o_ = f_e + nb * 16 + h * 1280;
          const uint32_t u0 = SM32(q0 * A_SLOT + o_), u1 = SM32(q1 * A_SLOT + o_), u2 = SM32(q2 * A_SLOT + o_), ux = SM32(sx * A_SLOT + o_);
          const float t0 = at[4 * nb + 2 * h] + ((bf_lo(u0) + bf_lo(u1)) + bf_lo(u2)), t1 = at[4 * nb + 2 * h + 1] + ((bf_hi(u0) + bf_hi(u1)) + bf_hi(u2));
          const uint32_t pk = pack_bf16(fmaf(ga.x, t0, bf_lo(ux)), fmaf(ga.y, t1, bf_hi(ux)));
          SM32(ot + o_) = pk;
          const float v0 = bf_lo(pk), v1 = bf_hi(pk);
          const float y0 = a.x * v0, y1 = a.y * v1;
          st[h][0] += v0 + v1; st[h][1] = fmaf(v0, v0, fmaf(v1, v1, st[h][1]));
          st[h][2] += y0 + y1; st[h][3] = fmaf(a.x, y0, fmaf(a.y, y1, st[h][3]));
          st[h][4] = fmaf(y0, y0, fmaf(y1, y1, st[h][4])); st[h][5] = fmaf(b.x, y0, fmaf(b.y, y1, st[h][5]));
        }
      }
#pragma unroll
      for (int h = 0; h < 2; h++) {
#pragma unroll
        for (int i = 0; i < 6; i++) st[h][i] = quad_sum(st[h][i]);
        float4 rec = (lane & 1) ? make_float4(st[h][4], st[h][5], 0.f, 0.f) : make_float4(st[h][0], st[h][1], st[h][2], st[h][3]);
        if ((lane & 3) < 2) *reinterpret_cast<float4*>(statf + (warp * 16 + (lane >> 2) + 8 * h) * 8 + (lane & 1) * 4) = rec;
      }
      fence_async_smem();
      bar_sync(3 + w, 128);
      if (leader) {
        tma_store2d(&tm.sxa, sb + ot + w * (E_TILE / 2), o_col, o_qt * 128 + w * 64);
        bulk_red_f32(g_st1 + (size_t)(o_qt * 128 + w * 64) * 8, stat, 2048);
        bulk_done();
        flag_add(g_flag + F_XA + o_qt);
      }
      __syncwarp();
      bar_sync(5, 256);
      A_RELEASE(p0); A_RELEASE(p1); A_RELEASE(p2); A_RELEASE(sx); A_RELEASE(q0); A_RELEASE(q1); A_RELEASE(q2);
      TS(0, 2);
    }

    Ring ra{0, 0};
    uint32_t bpar = 0;
    const uint32_t rel_a = mapa(mb_empty + 40, (lane == 0) ? rank : (rank ^ 1));
#define B_NEXT(s_) do { s_ = bs; mbar_wait_c(mb_full + 8 * bs, (bpar >> bs) & 1); bpar ^= 1u << bs; if (++bs == nbs) bs = 0; } while (0)
#define A_NEXT(s_) do { s_ = ra.slot; mbar_wait_c(mb_full + 40 + 8 * s_, ra.phase); ra.adv(M_NA); } while (0)
#define B_RELEASE(s_) do { if (lane == 0) mbar_arrive(mb_empty + 8 * (s_)); } while (0)
#define MA_RELEASE(s_) do { if (lane < 2) mbar_arrive_remote(rel_a + 8 * (s_)); } while (0)
    const int grow = qt * 128 + fr;
    float mu[2] = {0.f, 0.f}, rs[2] = {0.f, 0.f};
#pragma unroll 1
    for (int ph = 0; ph < 4; ph++) {
      float acc[96];
      float (&acc80)[40] = *reinterpret_cast<float(*)[40]>(&acc[0]);
      uint32_t pa = 0, pa2 = 0, pb = 0;
      float4 s03[2];
      float2 s45[2];
      const int nit = ph == 3 ? 12 : ph == 2 ? 10 : 5;
      const uint32_t nbs = ph == 2 ? 4 : 5, bsz = ph == 2 ? 24576 : 20480;
      uint32_t bs = 0;
#pragma unroll 1
      for (int it = 0; it < nit; it++) {
        uint32_t sbq, sa, sa2;
        B_NEXT(sbq);
        A_NEXT(sa);
        if (it == 0) TXC(ph);
        const uint64_t da = mkdesc(sb + M_AOFF + sa * 16384 + w * 8192, 16, 1024);
        if (ph == 2) {
          sa2 = sa;
          const uint64_t db = mkdesc(sb + sbq * 24576, 8192, 1024);
          wg_fence();
#pragma unroll
          for (int kk = 0; kk < 4; kk++) wgmma_ss_n192<1>(acc, da + kk * 2, db + kk * 128, (it | kk) != 0);
          wg_commit();
        } else {
          A_NEXT(sa2);
          const uint64_t da2 = mkdesc(sb + M_AOFF + sa2 * 16384 + w * 8192, 16, 1024);
          const uint64_t db = mkdesc(sb + sbq * 20480, 16, 1024);
          wg_fence();
#pragma unroll
          for (int kk = 0; kk < 4; kk++) wgmma_ss_n80<0>(acc80, da + kk * 2, db + kk * 2, (it | kk) != 0);
#pragma unroll
          for (int kk = 0; kk < 4; kk++) wgmma_ss_n80<0>(acc80, da2 + kk * 2, db + 640 + kk * 2, 1);
          wg_commit();
        }
        if (it > 0) { wg_wait<1>(); MA_RELEASE(pa); if (ph != 2) MA_RELEASE(pa2); B_RELEASE(pb); }
        else {
#pragma unroll
          for (int h = 0; h < 2; h++) {
            s03[h] = __ldcg(reinterpret_cast<const float4*>(g_st1 + (size_t)(grow + 8 * h) * 8));
            s45[h] = __ldcg(reinterpret_cast<const float2*>(ph == 0 ? g_st1 + (size_t)(grow + 8 * h) * 8 + 4 : g_st2 + (size_t)(grow + 8 * h) * 2));
          }
        }
        pa = sa; pa2 = sa2; pb = sbq;
      }
      wg_wait<0>();
      fence_regs(acc);
      MA_RELEASE(pa); if (ph != 2) MA_RELEASE(pa2);
      bar_sync(5, 256);
      TS(1 + (ph == 3 ? 0 : ph), ph == 3 ? 2 : 0);
      const uint32_t pb1 = pb == 0 ? nbs - 1 : pb - 1;
      uint32_t e1 = 0;
      if (ph == 0) {
        float c0[2], c1[2], c2[2], c3[2];
        const float4 sc = *reinterpret_cast<const float4*>(parf + P_SC);
        const float sbb = parf[P_SC + 4];
#pragma unroll
        for (int h = 0; h < 2; h++) {
          mu[h] = s03[h].x * (1.f / D_);
          rs[h] = rsqrtf(fmaxf(s03[h].y * (1.f / D_) - mu[h] * mu[h], 0.f) + LN_EPS);
          const float m2 = (rs[h] * (s03[h].z - mu[h] * sc.x) + sc.w) * (1.f / D_);
          const float e2 = (rs[h] * rs[h] * (s45[h].x - 2.f * mu[h] * s03[h].w + mu[h] * mu[h] * sc.y) + 2.f * rs[h] * (s45[h].y - mu[h] * sc.z) + sbb) * (1.f / D_);
          c2[h] = rsqrtf(fmaxf(e2 - m2 * m2, 0.f) + LN_EPS);
          c0[h] = c2[h] * rs[h]; c1[h] = -c0[h] * mu[h]; c3[h] = -c2[h] * m2;
        }
        if (tid < 20) *reinterpret_cast<uint4*>(sm + T_PREP + 4096 + tid * 16) = make_uint4(0, 0, 0, 0);
        const uint32_t ot = pb * bsz;
#pragma unroll
        for (int nb = 0; nb < 10; nb++) {
          const float2 va = pf2[(P_VA + 8 * nb) / 2], vb = pf2[(P_VB + 8 * nb) / 2], vc = pf2[(P_VC + 8 * nb) / 2];
#pragma unroll
          for (int h = 0; h < 2; h++) {
            const float z0 = fmaf(c0[h], acc[4 * nb + 2 * h], fmaf(c1[h], va.x, fmaf(c2[h], vb.x, c3[h] * vc.x)));
            const float z1 = fmaf(c0[h], acc[4 * nb + 2 * h + 1], fmaf(c1[h], va.y, fmaf(c2[h], vb.y, c3[h] * vc.y)));
            SM32(ot + f_e + nb * 16 + h * 1280) = pack_bf16(gelu_tanh(z0), gelu_tanh(z1));
          }
        }
        fence_async_smem();
        bar_sync(3 + w, 128);
        if (leader) {
          const int grp = js >> 1;
          const int sh = (grp & 2 ? 2 : 1) * (grp & 1 ? -1 : 1);
          tma_store2d(&tm.sus, sb + ot + w * (E_TILE / 2), js * 80, qt * 128 + w * 64 + sh + 2);
          if (w == 0 && qt == (sh > 0 ? 0 : 15)) {
            const int r0 = sh > 0 ? 0 : S_ + sh, n = sh > 0 ? sh : -sh;
#pragma unroll 1
            for (int i = 0; i < n; i++) bulk_store(g_us + (size_t)(r0 + i + 2) * D_ + js * 80, sb + T_PREP + 4096, 160);
          }
        }
      } else if (ph == 2) {
        float c0[2], c1[2];
#pragma unroll
        for (int h = 0; h < 2; h++) {
          const float m = s45[h].x * (1.f / D_);
          c0[h] = rsqrtf(fmaxf(s45[h].y * (1.f / D_) - m * m, 0.f) + LN_EPS);
          c1[h] = -c0[h] * m;
        }
        const uint32_t ot = (w ? pb : pb1) * bsz;
        const uint32_t o_ = ot + (warp * 16 + (lane >> 2)) * 128 + (lane & 3) * 4, xr = (lane >> 2) << 4;
#pragma unroll
        for (int ps = 0; ps < 3; ps++) {
#pragma unroll
          for (int i = 0; i < 8; i++) {
            const int nb = ps * 8 + i;
            const float2 cs = pf2[(P_CS3 + 8 * nb) / 2];
#pragma unroll
            for (int h = 0; h < 2; h++)
              SM32(o_ + ps * 8192 + h * 1024 + ((i << 4) ^ xr)) =
                  pack_bf16(gelu_tanh(fmaf(c0[h], acc[4 * nb + 2 * h], c1[h] * cs.x)), gelu_tanh(fmaf(c0[h], acc[4 * nb + 2 * h + 1], c1[h] * cs.y)));
          }
          fence_async_smem();
          bar_sync(3 + w, 128);
          if (leader) tma_store2d(&tm.g, sb + ot + ps * 8192, js * 192 + ps * 64, qt * 128 + w * 64);
          __syncwarp();
        }
      } else {
        uint32_t e2;
        B_NEXT(e1);
        e2 = e1;
        if (ph == 3) B_NEXT(e2);
        float s1[2] = {0.f, 0.f}, s2[2] = {0.f, 0.f};
        const uint32_t ot = pb * bsz;
        const int pa_ = ph == 1 ? P_A2 : P_GB;
#pragma unroll
        for (int nb = 0; nb < 10; nb++) {
          const float2 a = pf2[(pa_ + 8 * nb) / 2], b = pf2[(P_B2 + 8 * nb) / 2];
#pragma unroll
          for (int h = 0; h < 2; h++) {
            const uint32_t o_ = f_e + nb * 16 + h * 1280;
            const uint32_t ua = SM32(e1 * 20480 + o_), u1 = SM32(e2 * 20480 + o_);
            const float v0 = acc[4 * nb + 2 * h], v1 = acc[4 * nb + 2 * h + 1];
            const uint32_t pk = ph == 1 ? pack_bf16(fmaf(a.x * rs[h], bf_lo(ua) - mu[h], b.x) + v0, fmaf(a.y * rs[h], bf_hi(ua) - mu[h], b.y) + v1)
                                        : pack_bf16(fmaf(a.x, bf_lo(u1) + v0, bf_lo(ua)), fmaf(a.y, bf_hi(u1) + v1, bf_hi(ua)));
            SM32(ot + o_) = pk;
            const float y0 = bf_lo(pk), y1 = bf_hi(pk);
            s1[h] += y0 + y1; s2[h] = fmaf(y0, y0, fmaf(y1, y1, s2[h]));
          }
        }
#pragma unroll
        for (int h = 0; h < 2; h++) {
          s1[h] = quad_sum(s1[h]); s2[h] = quad_sum(s2[h]);
          if ((lane & 3) == 0) *reinterpret_cast<float2*>(statf + (warp * 16 + (lane >> 2) + 8 * h) * 2) = make_float2(s1[h], s2[h]);
        }
        fence_async_smem();
        bar_sync(3 + w, 128);
        if (leader) {
          tma_store2d(ph == 1 ? &tm.sx1 : &tm.sout, sb + ot + w * (E_TILE / 2), js * 80, qt * 128 + w * 64);
          if (ph == 1) bulk_red_f32(g_st2 + (size_t)(qt * 128 + w * 64) * 2, stat, 512);
        }
      }
      if (leader) {
        bulk_done();
        if (ph < 3) flag_add(g_flag + F_US + 16 * ph + qt);
      }
      __syncwarp();
      if (ph < 3) {
        bar_sync(5, 256);
        B_RELEASE(pb);
        if (ph == 1) B_RELEASE(e1);
      }
      TS(1 + (ph == 3 ? 0 : ph), ph == 3 ? 3 : 1);
    }
    if ((threadIdx.x & 127) == 0) TL_END(2);
    cluster_sync();
  }
}

typedef CUresult (*EncFn)(CUtensorMap*, CUtensorMapDataType, cuuint32_t, void*, const cuuint64_t*, const cuuint64_t*,
                          const cuuint32_t*, const cuuint32_t*, CUtensorMapInterleave, CUtensorMapSwizzle,
                          CUtensorMapL2promotion, CUtensorMapFloatOOBfill);
static EncFn g_enc = nullptr;

static CUtensorMap map2d(const void* p, uint64_t rows, uint64_t cols, uint32_t box_rows) {
  CUtensorMap m;
  cuuint64_t gd[2] = {cols, rows}; cuuint64_t gs[1] = {cols * 2};
  cuuint32_t bx[2] = {64, box_rows}; cuuint32_t es[2] = {1, 1};
  g_enc(&m, CU_TENSOR_MAP_DATA_TYPE_BFLOAT16, 2, const_cast<void*>(p), gd, gs, bx, es, CU_TENSOR_MAP_INTERLEAVE_NONE,
        CU_TENSOR_MAP_SWIZZLE_128B, CU_TENSOR_MAP_L2_PROMOTION_L2_256B, CU_TENSOR_MAP_FLOAT_OOB_FILL_NONE);
  return m;
}
static CUtensorMap map3d(const void* p, uint64_t rows, uint64_t cols, uint32_t box_rows, uint32_t nblk) {
  CUtensorMap m;
  cuuint64_t gd[3] = {64, rows, cols / 64}; cuuint64_t gs[2] = {cols * 2, 128};
  cuuint32_t bx[3] = {64, box_rows, nblk}; cuuint32_t es[3] = {1, 1, 1};
  g_enc(&m, CU_TENSOR_MAP_DATA_TYPE_BFLOAT16, 3, const_cast<void*>(p), gd, gs, bx, es, CU_TENSOR_MAP_INTERLEAVE_NONE,
        CU_TENSOR_MAP_SWIZZLE_128B, CU_TENSOR_MAP_L2_PROMOTION_L2_256B, CU_TENSOR_MAP_FLOAT_OOB_FILL_NONE);
  return m;
}

static CUtensorMap map_e(const void* p, uint32_t rows, uint64_t total_rows = S_) {
  CUtensorMap m;
  cuuint64_t gd[2] = {D_, total_rows}; cuuint64_t gs[1] = {D_ * 2};
  cuuint32_t bx[2] = {80, rows}; cuuint32_t es[2] = {1, 1};
  g_enc(&m, CU_TENSOR_MAP_DATA_TYPE_BFLOAT16, 2, const_cast<void*>(p), gd, gs, bx, es, CU_TENSOR_MAP_INTERLEAVE_NONE,
        CU_TENSOR_MAP_SWIZZLE_NONE, CU_TENSOR_MAP_L2_PROMOTION_L2_256B, CU_TENSOR_MAP_FLOAT_OOB_FILL_NONE);
  return m;
}

template <typename... KArgs, typename... Args>
static void launch(void (*kern)(KArgs...), dim3 grid, dim3 block, int smem, bool pdl, Args... args) {
  cudaLaunchConfig_t cfg = {};
  cfg.gridDim = grid; cfg.blockDim = block; cfg.dynamicSmemBytes = smem; cfg.stream = cudaStreamPerThread;
  cudaLaunchAttribute at[1];
  at[0].id = cudaLaunchAttributeProgrammaticStreamSerialization;
  at[0].val.programmaticStreamSerializationAllowed = 1;
  cfg.attrs = at; cfg.numAttrs = pdl ? 1 : 0;
  cudaLaunchKernelEx(&cfg, kern, KArgs(args)...);
}

extern "C" void kernel_launch(void* const* d_in, const int* in_sizes, int n_in, void* d_out, int out_size) {
  const bf16* x = (const bf16*)d_in[0];
  const bf16* kc = (const bf16*)d_in[1];
  const bf16* vc = (const bf16*)d_in[2];
  const bf16* wq = (const bf16*)d_in[3];
  const bf16* wo = (const bf16*)d_in[4];
  const bf16* w1 = (const bf16*)d_in[6];
  const bf16* w2 = (const bf16*)d_in[7];
  const bf16* w3 = (const bf16*)d_in[8];
  const bf16* w4 = (const bf16*)d_in[9];
  const bf16* c = (const bf16*)d_in[10];
  const bf16* wmod = (const bf16*)d_in[11];
  bf16* out = (bf16*)d_out;

  static void *p_h, *p_o, *p_xa, *p_us, *p_x1, *p_g, *p_w1t, *p_w2t, *p_w4t;
  if (!g_enc) {
    void* fn = nullptr; cudaDriverEntryPointQueryResult qr;
    cudaGetDriverEntryPoint("cuTensorMapEncodeTiled", &fn, cudaEnableDefault, &qr);
    g_enc = (EncFn)fn;
    cudaGetSymbolAddress(&p_h, g_h); cudaGetSymbolAddress(&p_o, g_o); cudaGetSymbolAddress(&p_xa, g_xa);
    cudaGetSymbolAddress(&p_us, g_us); cudaGetSymbolAddress(&p_x1, g_x1); cudaGetSymbolAddress(&p_g, g_g);
    cudaGetSymbolAddress(&p_w1t, g_w1t); cudaGetSymbolAddress(&p_w2t, g_w2t); cudaGetSymbolAddress(&p_w4t, g_w4t);
    cudaFuncSetAttribute(fused_kernel, cudaFuncAttributeMaxDynamicSharedMemorySize, T_SMEM);
  }
  Maps tm;
  tm.h = map2d(p_h, S_, D_, 128);
  tm.wq = map3d(wq, D_, HD_, 64, 3);
  tm.k = map3d(kc, (uint64_t)H_ * S_, DH_, 64, 3);
  tm.v = map3d(vc, (uint64_t)H_ * S_, DH_, 64, 3);
  tm.o = map2d(p_o, S_, HD_, 128);
  tm.wo3 = map3d(wo, HD_, D_, 64, 3);
  tm.wo2 = map3d(wo, HD_, D_, 64, 2);
  tm.xa = map2d(p_xa, S_, D_, 64);
  tm.w1t = map3d(p_w1t, D_, D_, 80, 2);
  tm.us = map2d((const bf16*)p_us + 2 * D_, S_, D_, 64);
  tm.w2t = map3d(p_w2t, D_, D_, 80, 2);
  tm.x1 = map2d(p_x1, S_, D_, 64);
  tm.w3 = map3d(w3, D_, F_, 64, 3);
  tm.g = map2d(p_g, S_, F_, 64);
  tm.w4t = map3d(p_w4t, D_, F_, 80, 2);
  tm.ex = map_e(x, 128); tm.exa = map_e(p_xa, 128); tm.ex1 = map_e(p_x1, 128);
  tm.sxa = map_e(p_xa, 64); tm.sus = map_e(p_us, 64, S_ + 4); tm.sx1 = map_e(p_x1, 64); tm.sout = map_e(out, 64);
  PfList pf;
  pf.p[0] = (const uint8_t*)wo; pf.p[1] = (const uint8_t*)w3; pf.p[2] = (const uint8_t*)p_w4t;
  pf.p[3] = (const uint8_t*)x; pf.p[4] = (const uint8_t*)p_w1t; pf.p[5] = (const uint8_t*)p_w2t;

  launch(mod_kernel, dim3(120), dim3(256), 0, false, c, wmod);
  launch(ln1_kernel, dim3(256), dim3(256), 0, true, x);
  launch(fused_kernel, dim3(128), dim3(384), T_SMEM, true, tm, pf, PrepW{w1, w2, w3, w4}, x, out);
}
```

```cpp
#include <cuda_runtime.h>
#include <cuda.h>
#include <cuda_bf16.h>
#include <stdint.h>

typedef __nv_bfloat16 bf16;

constexpr int S_  = 2048;
constexpr int D_  = 640;
constexpr int H_  = 32;
constexpr int DH_ = 192;
constexpr int HD_ = H_ * DH_;
constexpr int F_  = 1536;
constexpr float LN_EPS = 1e-5f;

__device__ __forceinline__ uint32_t smem_u32(const void* p) { return (uint32_t)__cvta_generic_to_shared(p); }
__device__ __forceinline__ void mbar_init(uint32_t a, uint32_t c) { asm volatile("mbarrier.init.shared::cta.b64 [%0], %1;" :: "r"(a), "r"(c) : "memory"); }
__device__ __forceinline__ void mbar_expect(uint32_t a, uint32_t b) { asm volatile("mbarrier.arrive.expect_tx.shared::cta.b64 _, [%0], %1;" :: "r"(a), "r"(b) : "memory"); }
__device__ __forceinline__ void mbar_arrive(uint32_t a) { asm volatile("mbarrier.arrive.shared::cta.b64 _, [%0];" :: "r"(a) : "memory"); }
__device__ __forceinline__ void mbar_arrive_remote(uint32_t ra) { asm volatile("mbarrier.arrive.shared::cluster.b64 _, [%0];" :: "r"(ra) : "memory"); }
__device__ __forceinline__ uint32_t mapa(uint32_t a, uint32_t cta) { uint32_t r; asm volatile("mapa.shared::cluster.u32 %0, %1, %2;" : "=r"(r) : "r"(a), "r"(cta)); return r; }
__device__ __forceinline__ uint32_t mbar_try(uint32_t a, uint32_t ph) {
  uint32_t ok;
  asm volatile("{\n.reg .pred p;\nmbarrier.test_wait.parity.shared::cta.b64 p, [%1], %2;\nselp.u32 %0, 1, 0, p;\n}\n" : "=r"(ok) : "r"(a), "r"(ph) : "memory");
  return ok;
}
__device__ __forceinline__ void mbar_wait(uint32_t a, uint32_t ph) {
  asm volatile(
      "{\n.reg .pred p;\n.reg .u32 n;\n"
      "mov.u32 n, 0;\n"
      "SPIN:\n"
      "mbarrier.try_wait.parity.shared::cta.b64 p, [%0], %1;\n"
      "@p bra DONE;\n"
      "add.u32 n, n, 1;\n"
      "setp.le.u32 p, n, 16777216;\n"
      "@p bra SPIN;\n"
      "trap;\n"
      "DONE:\n}\n" :: "r"(a), "r"(ph) : "memory");
}
#define ELECT_ "{\n.reg .pred p;\nelect.sync _|p, 0xffffffff;\n@p "
__device__ __forceinline__ void mbar_expect_e(uint32_t a, uint32_t b) { asm volatile(ELECT_ "mbarrier.arrive.expect_tx.shared::cta.b64 _, [%0], %1;\n}\n" :: "r"(a), "r"(b) : "memory"); }
__device__ __forceinline__ void tma2d(uint32_t dst, const CUtensorMap* m, uint32_t bar, int c0, int c1) {
  asm volatile(ELECT_ "cp.async.bulk.tensor.2d.shared::cluster.global.mbarrier::complete_tx::bytes [%0], [%1, {%3, %4}], [%2];\n}\n"
               :: "r"(dst), "l"(m), "r"(bar), "r"(c0), "r"(c1) : "memory");
}
__device__ __forceinline__ void tma2d_mc(uint32_t dst, const CUtensorMap* m, uint32_t bar, int c0, int c1, uint16_t mask) {
  asm volatile(ELECT_ "cp.async.bulk.tensor.2d.shared::cluster.global.mbarrier::complete_tx::bytes.multicast::cluster [%0], [%1, {%3, %4}], [%2], %5;\n}\n"
               :: "r"(dst), "l"(m), "r"(bar), "r"(c0), "r"(c1), "h"(mask) : "memory");
}
__device__ __forceinline__ void tma3d(uint32_t dst, const CUtensorMap* m, uint32_t bar, int c0, int c1, int c2) {
  asm volatile(ELECT_ "cp.async.bulk.tensor.3d.shared::cluster.global.mbarrier::complete_tx::bytes [%0], [%1, {%3, %4, %5}], [%2];\n}\n"
               :: "r"(dst), "l"(m), "r"(bar), "r"(c0), "r"(c1), "r"(c2) : "memory");
}
__device__ __forceinline__ void tma3d_mc(uint32_t dst, const CUtensorMap* m, uint32_t bar, int c0, int c1, int c2, uint16_t mask) {
  asm volatile(ELECT_ "cp.async.bulk.tensor.3d.shared::cluster.global.mbarrier::complete_tx::bytes.multicast::cluster [%0], [%1, {%3, %4, %5}], [%2], %6;\n}\n"
               :: "r"(dst), "l"(m), "r"(bar), "r"(c0), "r"(c1), "r"(c2), "h"(mask) : "memory");
}
__device__ __forceinline__ void tma3d_mc_hint(uint32_t dst, const CUtensorMap* m, uint32_t bar, int c0, int c1, int c2, uint16_t mask, uint64_t pol) {
  asm volatile(ELECT_ "cp.async.bulk.tensor.3d.shared::cluster.global.mbarrier::complete_tx::bytes.multicast::cluster.L2::cache_hint [%0], [%1, {%3, %4, %5}], [%2], %6, %7;\n}\n"
               :: "r"(dst), "l"(m), "r"(bar), "r"(c0), "r"(c1), "r"(c2), "h"(mask), "l"(pol) : "memory");
}
__device__ __forceinline__ void bulk_load(uint32_t dst, const void* src, uint32_t bytes, uint32_t bar) {
  asm volatile(ELECT_ "cp.async.bulk.shared::cluster.global.mbarrier::complete_tx::bytes [%0], [%1], %2, [%3];\n}\n"
               :: "r"(dst), "l"(src), "r"(bytes), "r"(bar) : "memory");
}
__device__ __forceinline__ void l2_prefetch16k(const void* p) { asm volatile(ELECT_ "cp.async.bulk.prefetch.L2.global [%0], 16384;\n}\n" :: "l"(p) : "memory"); }
__device__ __forceinline__ void l2_prefetch_t2d(const CUtensorMap* m, int c0, int c1) {
  asm volatile(ELECT_ "cp.async.bulk.prefetch.tensor.2d.L2.global [%0, {%1, %2}];\n}\n" :: "l"(m), "r"(c0), "r"(c1) : "memory");
}
__device__ __forceinline__ void stg128(void* p, uint4 v) {
  asm volatile("st.global.v4.u32 [%0], {%1, %2, %3, %4};" :: "l"(p), "r"(v.x), "r"(v.y), "r"(v.z), "r"(v.w) : "memory");
}
__device__ __forceinline__ void prefetch_tmap(const CUtensorMap* m) { asm volatile("prefetch.tensormap [%0];" :: "l"(m) : "memory"); }
__device__ __forceinline__ void wg_fence() { asm volatile("wgmma.fence.sync.aligned;" ::: "memory"); }
__device__ __forceinline__ void wg_commit() { asm volatile("wgmma.commit_group.sync.aligned;" ::: "memory"); }
template <int N> __device__ __forceinline__ void wg_wait() { asm volatile("wgmma.wait_group.sync.aligned %0;" :: "n"(N) : "memory"); }
template <int N> __device__ __forceinline__ void fence_regs(float (&r)[N]) {
#pragma unroll
  for (int i = 0; i < N; i++) asm volatile("" : "+f"(r[i]) :: "memory");
}
template <int N> __device__ __forceinline__ void fence_regs(uint32_t (&r)[N]) {
#pragma unroll
  for (int i = 0; i < N; i++) asm volatile("" : "+r"(r[i]) :: "memory");
}
__device__ __forceinline__ uint64_t mkdesc(uint32_t addr, uint32_t lbo, uint32_t sbo) {
  return (uint64_t)((addr & 0x3FFFF) >> 4) | ((uint64_t)(lbo >> 4) << 16) | ((uint64_t)(sbo >> 4) << 32) | (1ull << 62);
}
__device__ __forceinline__ void bar_sync(int id, int n) { asm volatile("bar.sync %0, %1;" :: "r"(id), "r"(n) : "memory"); }
__device__ __forceinline__ void bar_arrive(int id, int n) { asm volatile("bar.arrive %0, %1;" :: "r"(id), "r"(n) : "memory"); }
__device__ __forceinline__ void cluster_sync() { asm volatile("barrier.cluster.arrive.aligned;\nbarrier.cluster.wait.aligned;" ::: "memory"); }
__device__ __forceinline__ void pdl_wait() { asm volatile("griddepcontrol.wait;" ::: "memory"); }
__device__ __forceinline__ void pdl_launch() { asm volatile("griddepcontrol.launch_dependents;" ::: "memory"); }
__device__ __forceinline__ float ex2(float x) { float y; asm("ex2.approx.ftz.f32 %0, %1;" : "=f"(y) : "f"(x)); return y; }
__device__ __forceinline__ uint32_t pack_bf16(float lo, float hi) { uint32_t r; asm("cvt.rn.bf16x2.f32 %0, %1, %2;" : "=r"(r) : "f"(hi), "f"(lo)); return r; }
__device__ __forceinline__ float bf_lo(uint32_t u) { return __uint_as_float(u << 16); }
__device__ __forceinline__ float bf_hi(uint32_t u) { return __uint_as_float(u & 0xffff0000u); }
__device__ __forceinline__ float bf_round(float x) { return __bfloat162float(__float2bfloat16_rn(x)); }
__device__ __forceinline__ float tanh_fast(float x) { float y; asm("tanh.approx.f32 %0, %1;" : "=f"(y) : "f"(x)); return y; }
__device__ __forceinline__ float gelu_tanh(float x) {
  float u = x * (0.7978845608028654f + 0.035677408136300125f * x * x);
  float hx = 0.5f * x;
  return fmaf(hx, tanh_fast(u), hx);
}
__device__ __forceinline__ float warp_sum(float v) {
#pragma unroll
  for (int o = 16; o > 0; o >>= 1) v += __shfl_xor_sync(0xffffffffu, v, o);
  return v;
}
__device__ __forceinline__ void quad_transpose(uint32_t& v0, uint32_t& v1, uint32_t& v2, uint32_t& v3, int lane) {
  const bool b0 = lane & 1, b1 = lane & 2;
  uint32_t s0 = b0 ? v0 : v1, s1 = b0 ? v2 : v3;
  s0 = __shfl_xor_sync(0xffffffffu, s0, 1); s1 = __shfl_xor_sync(0xffffffffu, s1, 1);
  if (b0) { v0 = s0; v2 = s1; } else { v1 = s0; v3 = s1; }
  uint32_t t0 = b1 ? v0 : v2, t1 = b1 ? v1 : v3;
  t0 = __shfl_xor_sync(0xffffffffu, t0, 2); t1 = __shfl_xor_sync(0xffffffffu, t1, 2);
  if (b1) { v0 = t0; v1 = t1; } else { v2 = t0; v3 = t1; }
}

#define TX(i)
#define TXC(i)
#define TSA(item, i)
#define TL_ENTRY(k)
#define TL_WAITED(k)
#define TL_END(k)
#define TS(item, i)
template<int TB> __device__ __forceinline__ void wgmma_rs_n64(float (&d)[32], uint32_t a0, uint32_t a1, uint32_t a2, uint32_t a3, uint64_t db, int scale_d) {
  asm volatile("{\n.reg .pred p;\nsetp.ne.b32 p, %37, 0;\n"
    "wgmma.mma_async.sync.aligned.m64n64k16.f32.bf16.bf16 {%0, %1, %2, %3, %4, %5, %6, %7, %8, %9, %10, %11, %12, %13, %14, %15, %16, %17, %18, %19, %20, %21, %22, %23, %24, %25, %26, %27, %28, %29, %30, %31}, {%32, %33, %34, %35}, %36, p, 1, 1, %38;\n}\n"
    : "+f"(d[0]), "+f"(d[1]), "+f"(d[2]), "+f"(d[3]), "+f"(d[4]), "+f"(d[5]), "+f"(d[6]), "+f"(d[7]), "+f"(d[8]), "+f"(d[9]), "+f"(d[10]), "+f"(d[11]), "+f"(d[12]), "+f"(d[13]), "+f"(d[14]), "+f"(d[15]), "+f"(d[16]), "+f"(d[17]), "+f"(d[18]), "+f"(d[19]), "+f"(d[20]), "+f"(d[21]), "+f"(d[22]), "+f"(d[23]), "+f"(d[24]), "+f"(d[25]), "+f"(d[26]), "+f"(d[27]), "+f"(d[28]), "+f"(d[29]), "+f"(d[30]), "+f"(d[31])
    : "r"(a0), "r"(a1), "r"(a2), "r"(a3), "l"(db), "r"(scale_d), "n"(TB));
}
template<int TB> __device__ __forceinline__ void wgmma_rs_n192(float (&d)[96], uint32_t a0, uint32_t a1, uint32_t a2, uint32_t a3, uint64_t db, int scale_d) {
  asm volatile("{\n.reg .pred p;\nsetp.ne.b32 p, %101, 0;\n"
    "wgmma.mma_async.sync.aligned.m64n192k16.f32.bf16.bf16 {%0, %1, %2, %3, %4, %5, %6, %7, %8, %9, %10, %11, %12, %13, %14, %15, %16, %17, %18, %19, %20, %21, %22, %23, %24, %25, %26, %27, %28, %29, %30, %31, %32, %33, %34, %35, %36, %37, %38, %39, %40, %41, %42, %43, %44, %45, %46, %47, %48, %49, %50, %51, %52, %53, %54, %55, %56, %57, %58, %59, %60, %61, %62, %63, %64, %65, %66, %67, %68, %69, %70, %71, %72, %73, %74, %75, %76, %77, %78, %79, %80, %81, %82, %83, %84, %85, %86, %87, %88, %89, %90, %91, %92, %93, %94, %95}, {%96, %97, %98, %99}, %100, p, 1, 1, %102;\n}\n"
    : "+f"(d[0]), "+f"(d[1]), "+f"(d[2]), "+f"(d[3]), "+f"(d[4]), "+f"(d[5]), "+f"(d[6]), "+f"(d[7]), "+f"(d[8]), "+f"(d[9]), "+f"(d[10]), "+f"(d[11]), "+f"(d[12]), "+f"(d[13]), "+f"(d[14]), "+f"(d[15]), "+f"(d[16]), "+f"(d[17]), "+f"(d[18]), "+f"(d[19]), "+f"(d[20]), "+f"(d[21]), "+f"(d[22]), "+f"(d[23]), "+f"(d[24]), "+f"(d[25]), "+f"(d[26]), "+f"(d[27]), "+f"(d[28]), "+f"(d[29]), "+f"(d[30]), "+f"(d[31]), "+f"(d[32]), "+f"(d[33]), "+f"(d[34]), "+f"(d[35]), "+f"(d[36]), "+f"(d[37]), "+f"(d[38]), "+f"(d[39]), "+f"(d[40]), "+f"(d[41]), "+f"(d[42]), "+f"(d[43]), "+f"(d[44]), "+f"(d[45]), "+f"(d[46]), "+f"(d[47]), "+f"(d[48]), "+f"(d[49]), "+f"(d[50]), "+f"(d[51]), "+f"(d[52]), "+f"(d[53]), "+f"(d[54]), "+f"(d[55]), "+f"(d[56]), "+f"(d[57]), "+f"(d[58]), "+f"(d[59]), "+f"(d[60]), "+f"(d[61]), "+f"(d[62]), "+f"(d[63]), "+f"(d[64]), "+f"(d[65]), "+f"(d[66]), "+f"(d[67]), "+f"(d[68]), "+f"(d[69]), "+f"(d[70]), "+f"(d[71]), "+f"(d[72]), "+f"(d[73]), "+f"(d[74]), "+f"(d[75]), "+f"(d[76]), "+f"(d[77]), "+f"(d[78]), "+f"(d[79]), "+f"(d[80]), "+f"(d[81]), "+f"(d[82]), "+f"(d[83]), "+f"(d[84]), "+f"(d[85]), "+f"(d[86]), "+f"(d[87]), "+f"(d[88]), "+f"(d[89]), "+f"(d[90]), "+f"(d[91]), "+f"(d[92]), "+f"(d[93]), "+f"(d[94]), "+f"(d[95])
    : "r"(a0), "r"(a1), "r"(a2), "r"(a3), "l"(db), "r"(scale_d), "n"(TB));
}
template<int TB> __device__ __forceinline__ void wgmma_ss_n128(float (&d)[64], uint64_t da, uint64_t db, int scale_d) {
  asm volatile("{\n.reg .pred p;\nsetp.ne.b32 p, %66, 0;\n"
    "wgmma.mma_async.sync.aligned.m64n128k16.f32.bf16.bf16 {%0, %1, %2, %3, %4, %5, %6, %7, %8, %9, %10, %11, %12, %13, %14, %15, %16, %17, %18, %19, %20, %21, %22, %23, %24, %25, %26, %27, %28, %29, %30, %31, %32, %33, %34, %35, %36, %37, %38, %39, %40, %41, %42, %43, %44, %45, %46, %47, %48, %49, %50, %51, %52, %53, %54, %55, %56, %57, %58, %59, %60, %61, %62, %63}, %64, %65, p, 1, 1, 0, %67;\n}\n"
    : "+f"(d[0]), "+f"(d[1]), "+f"(d[2]), "+f"(d[3]), "+f"(d[4]), "+f"(d[5]), "+f"(d[6]), "+f"(d[7]), "+f"(d[8]), "+f"(d[9]), "+f"(d[10]), "+f"(d[11]), "+f"(d[12]), "+f"(d[13]), "+f"(d[14]), "+f"(d[15]), "+f"(d[16]), "+f"(d[17]), "+f"(d[18]), "+f"(d[19]), "+f"(d[20]), "+f"(d[21]), "+f"(d[22]), "+f"(d[23]), "+f"(d[24]), "+f"(d[25]), "+f"(d[26]), "+f"(d[27]), "+f"(d[28]), "+f"(d[29]), "+f"(d[30]), "+f"(d[31]), "+f"(d[32]), "+f"(d[33]), "+f"(d[34]), "+f"(d[35]), "+f"(d[36]), "+f"(d[37]), "+f"(d[38]), "+f"(d[39]), "+f"(d[40]), "+f"(d[41]), "+f"(d[42]), "+f"(d[43]), "+f"(d[44]), "+f"(d[45]), "+f"(d[46]), "+f"(d[47]), "+f"(d[48]), "+f"(d[49]), "+f"(d[50]), "+f"(d[51]), "+f"(d[52]), "+f"(d[53]), "+f"(d[54]), "+f"(d[55]), "+f"(d[56]), "+f"(d[57]), "+f"(d[58]), "+f"(d[59]), "+f"(d[60]), "+f"(d[61]), "+f"(d[62]), "+f"(d[63])
    : "l"(da), "l"(db), "r"(scale_d), "n"(TB));
}
template<int TB> __device__ __forceinline__ void wgmma_ss_n192(float (&d)[96], uint64_t da, uint64_t db, int scale_d) {
  asm volatile("{\n.reg .pred p;\nsetp.ne.b32 p, %98, 0;\n"
    "wgmma.mma_async.sync.aligned.m64n192k16.f32.bf16.bf16 {%0, %1, %2, %3, %4, %5, %6, %7, %8, %9, %10, %11, %12, %13, %14, %15, %16, %17, %18, %19, %20, %21, %22, %23, %24, %25, %26, %27, %28, %29, %30, %31, %32, %33, %34, %35, %36, %37, %38, %39, %40, %41, %42, %43, %44, %45, %46, %47, %48, %49, %50, %51, %52, %53, %54, %55, %56, %57, %58, %59, %60, %61, %62, %63, %64, %65, %66, %67, %68, %69, %70, %71, %72, %73, %74, %75, %76, %77, %78, %79, %80, %81, %82, %83, %84, %85, %86, %87, %88, %89, %90, %91, %92, %93, %94, %95}, %96, %97, p, 1, 1, 0, %99;\n}\n"
    : "+f"(d[0]), "+f"(d[1]), "+f"(d[2]), "+f"(d[3]), "+f"(d[4]), "+f"(d[5]), "+f"(d[6]), "+f"(d[7]), "+f"(d[8]), "+f"(d[9]), "+f"(d[10]), "+f"(d[11]), "+f"(d[12]), "+f"(d[13]), "+f"(d[14]), "+f"(d[15]), "+f"(d[16]), "+f"(d[17]), "+f"(d[18]), "+f"(d[19]), "+f"(d[20]), "+f"(d[21]), "+f"(d[22]), "+f"(d[23]), "+f"(d[24]), "+f"(d[25]), "+f"(d[26]), "+f"(d[27]), "+f"(d[28]), "+f"(d[29]), "+f"(d[30]), "+f"(d[31]), "+f"(d[32]), "+f"(d[33]), "+f"(d[34]), "+f"(d[35]), "+f"(d[36]), "+f"(d[37]), "+f"(d[38]), "+f"(d[39]), "+f"(d[40]), "+f"(d[41]), "+f"(d[42]), "+f"(d[43]), "+f"(d[44]), "+f"(d[45]), "+f"(d[46]), "+f"(d[47]), "+f"(d[48]), "+f"(d[49]), "+f"(d[50]), "+f"(d[51]), "+f"(d[52]), "+f"(d[53]), "+f"(d[54]), "+f"(d[55]), "+f"(d[56]), "+f"(d[57]), "+f"(d[58]), "+f"(d[59]), "+f"(d[60]), "+f"(d[61]), "+f"(d[62]), "+f"(d[63]), "+f"(d[64]), "+f"(d[65]), "+f"(d[66]), "+f"(d[67]), "+f"(d[68]), "+f"(d[69]), "+f"(d[70]), "+f"(d[71]), "+f"(d[72]), "+f"(d[73]), "+f"(d[74]), "+f"(d[75]), "+f"(d[76]), "+f"(d[77]), "+f"(d[78]), "+f"(d[79]), "+f"(d[80]), "+f"(d[81]), "+f"(d[82]), "+f"(d[83]), "+f"(d[84]), "+f"(d[85]), "+f"(d[86]), "+f"(d[87]), "+f"(d[88]), "+f"(d[89]), "+f"(d[90]), "+f"(d[91]), "+f"(d[92]), "+f"(d[93]), "+f"(d[94]), "+f"(d[95])
    : "l"(da), "l"(db), "r"(scale_d), "n"(TB));
}
template<int TB> __device__ __forceinline__ void wgmma_ss_n80(float (&d)[40], uint64_t da, uint64_t db, int scale_d) {
  asm volatile("{\n.reg .pred p;\nsetp.ne.b32 p, %42, 0;\n"
    "wgmma.mma_async.sync.aligned.m64n80k16.f32.bf16.bf16 {%0, %1, %2, %3, %4, %5, %6, %7, %8, %9, %10, %11, %12, %13, %14, %15, %16, %17, %18, %19, %20, %21, %22, %23, %24, %25, %26, %27, %28, %29, %30, %31, %32, %33, %34, %35, %36, %37, %38, %39}, %40, %41, p, 1, 1, 0, %43;\n}\n"
    : "+f"(d[0]), "+f"(d[1]), "+f"(d[2]), "+f"(d[3]), "+f"(d[4]), "+f"(d[5]), "+f"(d[6]), "+f"(d[7]), "+f"(d[8]), "+f"(d[9]), "+f"(d[10]), "+f"(d[11]), "+f"(d[12]), "+f"(d[13]), "+f"(d[14]), "+f"(d[15]), "+f"(d[16]), "+f"(d[17]), "+f"(d[18]), "+f"(d[19]), "+f"(d[20]), "+f"(d[21]), "+f"(d[22]), "+f"(d[23]), "+f"(d[24]), "+f"(d[25]), "+f"(d[26]), "+f"(d[27]), "+f"(d[28]), "+f"(d[29]), "+f"(d[30]), "+f"(d[31]), "+f"(d[32]), "+f"(d[33]), "+f"(d[34]), "+f"(d[35]), "+f"(d[36]), "+f"(d[37]), "+f"(d[38]), "+f"(d[39])
    : "l"(da), "l"(db), "r"(scale_d), "n"(TB));
}

__device__ float g_mod[6 * D_];
__device__ __align__(1024) bf16 g_h[S_ * D_];
__device__ __align__(1024) bf16 g_o[S_ * HD_];
__device__ __align__(1024) bf16 g_xch[16 * 2 * 4 * 4 * 128 * 80];
__device__ __align__(1024) bf16 g_w1t[D_ * D_];
__device__ __align__(1024) bf16 g_w2t[D_ * D_];
__device__ __align__(1024) bf16 g_w4t[D_ * F_];
__device__ __align__(32) float g_st1[S_ * 8];
__device__ __align__(32) float g_st2[S_ * 2];
__device__ __align__(32) float g_vec[3 * D_ + F_ + 8];
__device__ unsigned g_flag[1024];
enum { F_XCH = 0, F_XA = 256, F_US = 272, F_X1 = 288, F_G = 304, F_PREP = 320, F_O = 512 };
__device__ __align__(1024) bf16 g_xa[S_ * D_];
__device__ __align__(1024) bf16 g_us[(S_ + 4) * D_];
__device__ __align__(1024) bf16 g_x1[S_ * D_];
__device__ __align__(1024) bf16 g_g[S_ * F_];

__global__ void __launch_bounds__(256) mod_kernel(const bf16* __restrict__ c, const bf16* __restrict__ w_mod) {
  TL_ENTRY(0);
  pdl_launch();
  __shared__ float red[8][32];
  if (blockIdx.x < 14) { const int i = blockIdx.x * 256 + threadIdx.x; if (i < 3 * D_ + F_) g_vec[i] = 0.f; }
  else if (blockIdx.x < 18) g_flag[(blockIdx.x - 14) * 256 + threadIdx.x] = 0u;
  const int t = threadIdx.x, cg = t & 3, r0 = t >> 2;
  const int col0 = blockIdx.x * 32 + cg * 8;
  uint4 w[10];
#pragma unroll
  for (int i = 0; i < 10; i++) w[i] = __ldg(reinterpret_cast<const uint4*>(w_mod + (size_t)(r0 + 64 * i) * (6 * D_) + col0));
  float acc[8];
#pragma unroll
  for (int j = 0; j < 8; j++) acc[j] = 0.f;
#pragma unroll
  for (int i = 0; i < 10; i++) {
    float cv = __bfloat162float(c[r0 + 64 * i]);
    float s = bf_round(cv / (1.f + __expf(-cv)));
    acc[0] = fmaf(s, bf_lo(w[i].x), acc[0]); acc[1] = fmaf(s, bf_hi(w[i].x), acc[1]);
    acc[2] = fmaf(s, bf_lo(w[i].y), acc[2]); acc[3] = fmaf(s, bf_hi(w[i].y), acc[3]);
    acc[4] = fmaf(s, bf_lo(w[i].z), acc[4]); acc[5] = fmaf(s, bf_hi(w[i].z), acc[5]);
    acc[6] = fmaf(s, bf_lo(w[i].w), acc[6]); acc[7] = fmaf(s, bf_hi(w[i].w), acc[7]);
  }
#pragma unroll
  for (int j = 0; j < 8; j++) {
    acc[j] += __shfl_xor_sync(0xffffffffu, acc[j], 4);
    acc[j] += __shfl_xor_sync(0xffffffffu, acc[j], 8);
    acc[j] += __shfl_xor_sync(0xffffffffu, acc[j], 16);
  }
  if ((t & 31) < 4) {
#pragma unroll
    for (int j = 0; j < 8; j++) red[t >> 5][cg * 8 + j] = acc[j];
  }
  __syncthreads();
  if (t < 32) {
    float s = 0.f;
#pragma unroll
    for (int w8 = 0; w8 < 8; w8++) s += red[w8][t];
    const int col = blockIdx.x * 32 + t;
    s = bf_round(s);
    const int part = col / D_;
    if (part == 1 || part == 4) s = bf_round(1.f + s);
    g_mod[col] = s;
    if (t == 0) TL_END(0);
  }
}

__device__ __forceinline__ void row_stats(const float (&v)[20], float& mean, float& rstd) {
  float s = 0.f;
#pragma unroll
  for (int i = 0; i < 20; i++) s += v[i];
  mean = warp_sum(s) * (1.f / D_);
  float q = 0.f;
#pragma unroll
  for (int i = 0; i < 20; i++) { float d = v[i] - mean; q = fmaf(d, d, q); }
  rstd = rsqrtf(warp_sum(q) * (1.f / D_) + LN_EPS);
}
__device__ __forceinline__ void load_row_bf16(const bf16* p, int lane, float (&v)[20]) {
#pragma unroll
  for (int i = 0; i < 5; i++) {
    uint2 u = *reinterpret_cast<const uint2*>(p + (lane + 32 * i) * 4);
    v[4 * i] = bf_lo(u.x); v[4 * i + 1] = bf_hi(u.x); v[4 * i + 2] = bf_lo(u.y); v[4 * i + 3] = bf_hi(u.y);
  }
}
__device__ __forceinline__ void store_row_bf16(bf16* p, int lane, const float (&v)[20]) {
#pragma unroll
  for (int i = 0; i < 5; i++) {
    uint2 u; u.x = pack_bf16(v[4 * i], v[4 * i + 1]); u.y = pack_bf16(v[4 * i + 2], v[4 * i + 3]);
    *reinterpret_cast<uint2*>(p + (lane + 32 * i) * 4) = u;
  }
}
__device__ __forceinline__ void load_row_f32(const float* p, int lane, float (&v)[20]) {
#pragma unroll
  for (int i = 0; i < 5; i++) {
    float4 u = *reinterpret_cast<const float4*>(p + (lane + 32 * i) * 4);
    v[4 * i] = u.x; v[4 * i + 1] = u.y; v[4 * i + 2] = u.z; v[4 * i + 3] = u.w;
  }
}

__global__ void __launch_bounds__(256) ln1_kernel(const bf16* __restrict__ x) {
  TL_ENTRY(1);
  pdl_launch();
  const int lane = threadIdx.x & 31, row = blockIdx.x * 8 + (threadIdx.x >> 5);
  float v[20];
  load_row_bf16(x + (size_t)row * D_, lane, v);
  float mean, rstd;
  row_stats(v, mean, rstd);
  if (lane < 8) g_st1[row * 8 + lane] = 0.f;
  if (lane < 2) g_st2[row * 2 + lane] = 0.f;
  pdl_wait();
  if (threadIdx.x == 0) TL_WAITED(1);
  float sa[20], ca[20];
  load_row_f32(g_mod, lane, sa);
  load_row_f32(g_mod + D_, lane, ca);
#pragma unroll
  for (int i = 0; i < 20; i++) v[i] = fmaf((v[i] - mean) * rstd, ca[i], sa[i]);
  store_row_bf16(g_h + (size_t)row * D_, lane, v);
  if (threadIdx.x == 0) TL_END(1);
}

constexpr int PREP_JOBS = 200 + 200 + 480 + 480;
struct PrepW { const bf16 *w1, *w2, *w3, *w4; };
__device__ __forceinline__ void prep_warp(const PrepW& pw, bf16 (*tile)[72], int lane) {
#pragma unroll 1
  for (int job = blockIdx.x; job < PREP_JOBS; job += gridDim.x) {
    const bf16* src; bf16* dst; int ld = D_, ldd = D_, kt, nt, kind = 1;
    if (job < 200) { src = pw.w1; dst = g_w1t; kt = job / 10; nt = job % 10; kind = 0; }
    else if (job < 400) { src = pw.w2; dst = g_w2t; kt = (job - 200) / 10; nt = (job - 200) % 10; }
    else if (job < 880) { src = pw.w4; dst = g_w4t; ldd = F_; kt = (job - 400) / 10; nt = (job - 400) % 10; }
    else { src = pw.w3; dst = nullptr; ld = F_; kt = (job - 880) / 24; nt = (job - 880) % 24; kind = 2; }
    src += (size_t)(kt * 32 + (lane >> 3)) * ld + nt * 64 + (lane & 7) * 8;
    __syncwarp();
#pragma unroll
    for (int h = 0; h < 2; h++) {
      uint4 v[4];
#pragma unroll
      for (int i = 0; i < 4; i++) v[i] = __ldg(reinterpret_cast<const uint4*>(src + (size_t)(h * 16 + i * 4) * ld));
#pragma unroll
      for (int i = 0; i < 4; i++) *reinterpret_cast<uint4*>(&tile[h * 16 + i * 4 + (lane >> 3)][(lane & 7) * 8]) = v[i];
    }
    __syncwarp();
    const float* pa = g_mod + 4 * D_ + kt * 32;
    const float* pb = g_mod + 3 * D_ + kt * 32;
#pragma unroll 1
    for (int h = 0; h < 2; h++) {
      const int n = lane + 32 * h;
      float sa = 0.f, sb = 0.f, sc = 0.f;
#pragma unroll 1
      for (int c = 0; c < 4; c++) {
        uint32_t u[4];
#pragma unroll
        for (int e = 0; e < 4; e++) {
          const int k = c * 8 + 2 * e;
          float lo = __bfloat162float(tile[k][n]), hi = __bfloat162float(tile[k + 1][n]);
          sc += lo + hi;
          if (kind == 0) {
            const float2 a = __ldcg(reinterpret_cast<const float2*>(pa + k)), b = __ldcg(reinterpret_cast<const float2*>(pb + k));
            sb = fmaf(b.x, lo, fmaf(b.y, hi, sb));
            lo *= a.x; hi *= a.y;
          }
          u[e] = pack_bf16(lo, hi);
          sa += bf_lo(u[e]) + bf_hi(u[e]);
        }
        if (kind != 2) *reinterpret_cast<uint4*>(dst + (size_t)(nt * 64 + n) * ldd + kt * 32 + c * 8) = make_uint4(u[0], u[1], u[2], u[3]);
      }
      if (kind == 0) { atomicAdd(&g_vec[nt * 64 + n], sa); atomicAdd(&g_vec[D_ + nt * 64 + n], sb); atomicAdd(&g_vec[2 * D_ + nt * 64 + n], sc); }
      else if (kind == 2) atomicAdd(&g_vec[3 * D_ + nt * 64 + n], sc);
    }
  }
  __syncwarp();
  if (lane == 0) {
    asm volatile("fence.acq_rel.gpu;" ::: "memory");
    asm volatile("red.relaxed.gpu.global.add.u32 [%0], 1;" :: "l"(g_flag + F_PREP) : "memory");
  }
}

constexpr int A_NSLOT = 9;
constexpr int A_SLOT = 24576;
constexpr int A_NKV = S_ / 64;
constexpr int PREP_CTAS = 128;

struct Ring {
  uint32_t slot, phase;
  __device__ __forceinline__ void adv(int n) { if (++slot == (uint32_t)n) { slot = 0; phase ^= 1; } }
};
constexpr int T_PAR = A_NSLOT * A_SLOT + 384;
constexpr int T_PREP = T_PAR + 3712;
constexpr int T_SMEM = T_PREP + 32 * 72 * 2 + 1024;
enum { P_OGA = 0, P_OA = 80, P_OB = 160, P_VA = 240, P_VB = 320, P_VC = 400, P_A2 = 480, P_B2 = 560, P_GB = 640, P_CS3 = 720, P_SC = 912 };

__device__ __forceinline__ void flag_wait(const unsigned* p, unsigned target) {
  asm volatile(
      "{\n.reg .pred p;\n.reg .u32 n, v;\n"
      "mov.u32 n, 0;\n"
      "SPIN:\n"
      "ld.relaxed.gpu.global.u32 v, [%0];\n"
      "setp.ge.u32 p, v, %1;\n"
      "@p bra DONE;\n"
      "add.u32 n, n, 1;\n"
      "setp.gt.u32 p, n, 4194304;\n"
      "@p trap;\n"
      "bra SPIN;\n"
      "DONE:\n}\n" :: "l"(p), "r"(target) : "memory");
}
__device__ __forceinline__ void fence_async_global() { asm volatile("fence.proxy.async.global;" ::: "memory"); }
__device__ __forceinline__ float lds_f(uint32_t a) { float v; asm volatile("ld.shared.f32 %0, [%1];" : "=f"(v) : "r"(a)); return v; }
__device__ __forceinline__ float2 lds_f2(uint32_t a) { float2 v; asm volatile("ld.shared.v2.f32 {%0, %1}, [%2];" : "=f"(v.x), "=f"(v.y) : "r"(a)); return v; }
__device__ __forceinline__ uint4 ldcg4(const void* p) { return __ldcg(reinterpret_cast<const uint4*>(p)); }

__device__ __forceinline__ void sts_f2(uint32_t a, float x, float y) { asm volatile("st.shared.v2.f32 [%0], {%1, %2};" :: "r"(a), "f"(x), "f"(y) : "memory"); }
__device__ __forceinline__ void sts_u4(uint32_t a, uint4 v) { asm volatile("st.shared.v4.u32 [%0], {%1, %2, %3, %4};" :: "r"(a), "r"(v.x), "r"(v.y), "r"(v.z), "r"(v.w) : "memory"); }
__device__ __forceinline__ void sts_u1(uint32_t a, uint32_t v) { asm volatile("st.shared.u32 [%0], %1;" :: "r"(a), "r"(v) : "memory"); }
__device__ __forceinline__ void fence_async_smem() { asm volatile("fence.proxy.async.shared::cta;" ::: "memory"); }
__device__ __forceinline__ void bulk_store(void* dst, uint32_t src, uint32_t bytes) {
  asm volatile("cp.async.bulk.global.shared::cta.bulk_group [%0], [%1], %2;" :: "l"(dst), "r"(src), "r"(bytes) : "memory");
}
__device__ __forceinline__ void bulk_red_f32(void* dst, uint32_t src, uint32_t bytes) {
  asm volatile("cp.reduce.async.bulk.global.shared::cta.bulk_group.add.f32 [%0], [%1], %2;" :: "l"(dst), "r"(src), "r"(bytes) : "memory");
}
__device__ __forceinline__ void tma_store2d(const CUtensorMap* m, uint32_t src, int c0, int c1) {
  asm volatile("cp.async.bulk.tensor.2d.global.shared::cta.bulk_group [%0, {%2, %3}], [%1];" :: "l"(m), "r"(src), "r"(c0), "r"(c1) : "memory");
}
__device__ __forceinline__ void bulk_done() { asm volatile("cp.async.bulk.commit_group;\ncp.async.bulk.wait_group 0;" ::: "memory"); }
__device__ __forceinline__ void flag_add(unsigned* f) { asm volatile("red.relaxed.gpu.global.add.u32 [%0], 1;" :: "l"(f) : "memory"); }
__device__ __forceinline__ float4 lds_f4(uint32_t a) { return *reinterpret_cast<const float4*>(__cvta_shared_to_generic(a)); }
__device__ __forceinline__ uint4 lds_u4(uint32_t a) { return *reinterpret_cast<const uint4*>(__cvta_shared_to_generic(a)); }
__device__ __forceinline__ void lds8(uint32_t a, float (&v)[8]) {
  const float4 p = lds_f4(a), q = lds_f4(a + 16);
  v[0] = p.x; v[1] = p.y; v[2] = p.z; v[3] = p.w; v[4] = q.x; v[5] = q.y; v[6] = q.z; v[7] = q.w;
}
__device__ __forceinline__ void lds8_bf(uint32_t a, float (&v)[8]) {
  const uint4 u = lds_u4(a);
  v[0] = bf_lo(u.x); v[1] = bf_hi(u.x); v[2] = bf_lo(u.y); v[3] = bf_hi(u.y); v[4] = bf_lo(u.z); v[5] = bf_hi(u.z); v[6] = bf_lo(u.w); v[7] = bf_hi(u.w);
}
__device__ __forceinline__ uint4 pack8(const float (&v)[8]) {
  return make_uint4(pack_bf16(v[0], v[1]), pack_bf16(v[2], v[3]), pack_bf16(v[4], v[5]), pack_bf16(v[6], v[7]));
}
__device__ __forceinline__ void mbar_wait_c(uint32_t a, uint32_t ph) {
  asm volatile("{\n.reg .pred p;\nSPIN:\nmbarrier.try_wait.parity.shared::cta.b64 p, [%0], %1;\n@!p bra SPIN;\n}\n" :: "r"(a), "r"(ph) : "memory");
}
constexpr int ST_P = 80;
constexpr int E_TILE = 128 * 80 * 2;

struct Maps { CUtensorMap h, wq, k, v, o, wo3, wo2, xa, w1t, us, w2t, x1, w3, g, w4t, ex, exa, ex1, sxa, sus, sx1, sout; };
struct PfList { const uint8_t* p[6]; };

constexpr int M_AOFF = 102400, M_NA = 7;

__global__ void __cluster_dims__(2, 1, 1) __launch_bounds__(384, 1)
fused_kernel(const __grid_constant__ Maps tm, const __grid_constant__ PfList pf, const __grid_constant__ PrepW pw, const bf16* __restrict__ x, bf16* __restrict__ out) {
  extern __shared__ uint8_t smem_raw[];
  const uint32_t sb = (smem_u32(smem_raw) + 1023) & ~1023u;
  TL_ENTRY(2);
  const uint32_t bar_full = sb + A_NSLOT * A_SLOT;
  const uint32_t bar_empty = bar_full + 8 * A_NSLOT;
  const uint32_t bar_sig = bar_empty + 8 * A_NSLOT;
  const uint32_t mb_full = bar_sig + 16;
  const uint32_t mb_empty = mb_full + 96;
  const uint32_t par = sb + T_PAR;
  float* parf = reinterpret_cast<float*>(smem_raw + (par - smem_u32(smem_raw)));
  uint32_t rank;
  asm volatile("mov.u32 %0, %%cluster_ctarank;" : "=r"(rank));
  const int cid = blockIdx.x >> 1;
  const int wid = __shfl_sync(0xffffffffu, threadIdx.x >> 5, 0);
  const int wg = wid >> 2;
  const int qtile = (cid & 7) * 2 + rank, hbase = cid >> 3;
  const int o_qt = qtile, o_nh = (cid >> 3) & 1, o_ks = cid >> 4;
  const int o_col = o_nh * 320 + o_ks * 80;
  const int qt = cid >> 2, js = (cid & 3) * 2 + rank;
  if (threadIdx.x == 0) {
    for (int i = 0; i < A_NSLOT; i++) { mbar_init(bar_full + 8 * i, 1); mbar_init(bar_empty + 8 * i, 16); }
    mbar_init(bar_sig, 4); mbar_init(bar_sig + 8, 4);
    for (int i = 0; i < 12; i++) { mbar_init(mb_full + 8 * i, 1); mbar_init(mb_empty + 8 * i, i < 5 ? 8 : 16); }
    asm volatile("fence.mbarrier_init.release.cluster;" ::: "memory");
    prefetch_tmap(&tm.h); prefetch_tmap(&tm.wq); prefetch_tmap(&tm.k); prefetch_tmap(&tm.v);
  }
  __syncthreads();
  cluster_sync();

  if (wg == 0) {
    asm volatile("setmaxnreg.dec.sync.aligned.u32 40;");
    if (wid == 0) {
      Ring r{0, 1};
#define P_ACQ(bytes_) do { mbar_wait(bar_empty + 8 * r.slot, r.phase); mbar_expect_e(bar_full + 8 * r.slot, bytes_); } while (0)
#define P_DST (sb + r.slot * A_SLOT)
#define P_BAR (bar_full + 8 * r.slot)
      uint64_t pol_ef;
      asm volatile("createpolicy.fractional.L2::evict_first.b64 %0, 1.0;" : "=l"(pol_ef));
      pdl_wait();
      TL_WAITED(2);
#pragma unroll 1
      for (int item = 0; item < 4; item++) {
        const int head = hbase + 8 * item;
#pragma unroll 1
        for (int kb = 0; kb < 10; kb++) {
          P_ACQ(16384);
          tma2d(P_DST, &tm.h, P_BAR, kb * 64, qtile * 128);
          r.adv(A_NSLOT);
          P_ACQ(A_SLOT);
          if ((uint32_t)(kb & 1) == rank) tma3d_mc_hint(P_DST, &tm.wq, P_BAR, 0, kb * 64, head * 3, 3, pol_ef);
          r.adv(A_NSLOT);
        }
#pragma unroll 1
        for (int j = 0; j <= A_NKV; j++) {
          if (j < A_NKV) {
            P_ACQ(A_SLOT);
            if (rank == 0) tma3d_mc_hint(P_DST, &tm.k, P_BAR, 0, head * S_ + j * 64, 0, 3, pol_ef);
            r.adv(A_NSLOT);
          }
          if (j > 0) {
            P_ACQ(A_SLOT);
            if (rank == 1) tma3d_mc_hint(P_DST, &tm.v, P_BAR, 0, head * S_ + (j - 1) * 64, 0, 3, pol_ef);
            r.adv(A_NSLOT);
          }
          if (item == 3 && (j & 3) == 0) {
            const int c = (j >> 2) * 128 + blockIdx.x;
            if (c < 980) {
              const int li = c < 480 ? 0 : c < 600 ? 1 : c < 720 ? 2 : c < 880 ? 3 : c < 930 ? 4 : 5;
              const int c0 = c < 480 ? 0 : c < 600 ? 480 : c < 720 ? 600 : c < 880 ? 720 : c < 930 ? 880 : 930;
              l2_prefetch16k(pf.p[li] + (size_t)(c - c0) * 16384);
            }
          }
          if (item == 3) {
            if (j >= 6 && j < 24) {
              const int kb = j - 6;
              l2_prefetch_t2d(&tm.o, ((kb / 6) * 8 + 2 * o_ks + (kb % 6) / 3) * DH_ + (kb % 3) * 64, o_qt * 128);
            }
            if (j >= 24 && j < 30) flag_wait(g_flag + F_O + o_qt * 32 + ((j - 24) >> 1) * 8 + 2 * o_ks + (j & 1), 2);
            if (j == 0 && threadIdx.x == 0) {
              prefetch_tmap(&tm.o); prefetch_tmap(&tm.wo3); prefetch_tmap(&tm.wo2); prefetch_tmap(&tm.xa); prefetch_tmap(&tm.w1t); prefetch_tmap(&tm.us);
              prefetch_tmap(&tm.w2t); prefetch_tmap(&tm.x1); prefetch_tmap(&tm.w3); prefetch_tmap(&tm.g); prefetch_tmap(&tm.w4t);
              prefetch_tmap(&tm.ex); prefetch_tmap(&tm.exa); prefetch_tmap(&tm.ex1);
              prefetch_tmap(&tm.sxa); prefetch_tmap(&tm.sus); prefetch_tmap(&tm.sx1); prefetch_tmap(&tm.sout);
            }
          }
        }
      }
#pragma unroll 1
      for (int kb = 0; kb < 24; kb++) {
        const int head = (kb / 6) * 8 + 2 * o_ks + (kb % 6) / 3;
        const int kcol = head * DH_ + (kb % 3) * 64;
        P_ACQ(24576);
        if (rank == 0) tma3d_mc(P_DST, &tm.wo3, P_BAR, 0, kcol, o_nh * 5, 3);
        r.adv(A_NSLOT);
        P_ACQ(16384);
        if (rank == 1) tma3d_mc(P_DST, &tm.wo2, P_BAR, 0, kcol, o_nh * 5 + 3, 3);
        r.adv(A_NSLOT);
        if (kb == 18 || kb == 21) flag_wait(g_flag + F_O + o_qt * 32 + head, 2);
        if (kb % 3 == 0) fence_async_global();
        P_ACQ(16384);
        tma2d(P_DST, &tm.o, P_BAR, kcol, o_qt * 128);
        r.adv(A_NSLOT);
      }
      P_ACQ(E_TILE);
      tma2d(P_DST, &tm.ex, P_BAR, o_col, o_qt * 128);
      r.adv(A_NSLOT);
      flag_wait(g_flag + F_XCH + (o_qt * 2 + o_nh) * 4 + o_ks, 6);
      fence_async_global();
#pragma unroll 1
      for (int i = 0; i < 3; i++) {
        P_ACQ(E_TILE);
        bulk_load(P_DST, g_xch + (size_t)((((o_qt * 2 + o_nh) * 4 + o_ks) * 4) + ((o_ks + 1 + i) & 3)) * (E_TILE / 2), E_TILE, P_BAR);
        r.adv(A_NSLOT);
      }
      flag_wait(g_flag + F_PREP, PREP_CTAS);
      fence_async_global();
#pragma unroll 1
      for (int i = 0; i < A_NSLOT; i++) { mbar_wait(bar_empty + 8 * r.slot, r.phase); r.adv(A_NSLOT); }
      Ring ra{0, 1};
      uint32_t bpar = 0x1f;
#pragma unroll 1
      for (int ph = 0; ph < 4; ph++) {
        const CUtensorMap* ma = ph == 0 ? &tm.xa : ph == 1 ? &tm.us : ph == 2 ? &tm.x1 : &tm.g;
        const CUtensorMap* mb = ph == 0 ? &tm.w1t : ph == 1 ? &tm.w2t : ph == 2 ? &tm.w3 : &tm.w4t;
        const int nkb = ph == 3 ? 24 : 10;
        const int nbl = ph == 2 ? 10 : nkb / 2;
        const int nel = ph == 1 ? 1 : ph == 3 ? 2 : 0;
        const uint32_t nbs = ph == 2 ? 4 : 5, bsz = ph == 2 ? 24576 : 20480;
        int bl = 0; uint32_t bs = 0;
#pragma unroll 1
        for (int i = 0; i < 5; i++) mbar_wait(mb_empty + 8 * i, (bpar >> i) & 1);
#define T_LOADB() do { mbar_wait(mb_empty + 8 * bs, (bpar >> bs) & 1); bpar ^= 1u << bs; mbar_expect_e(mb_full + 8 * bs, bsz);    \
                       if (bl < nbl) tma3d(sb + bs * bsz, mb, mb_full + 8 * bs, 0, ph == 2 ? bl * 64 : js * 80, ph == 2 ? js * 3 : bl * 2); \
                       else tma2d(sb + bs * bsz, bl == nbl ? &tm.exa : &tm.ex1, mb_full + 8 * bs, js * 80, qt * 128); \
                       bl++; if (++bs == nbs) bs = 0; } while (0)
#pragma unroll 1
        for (uint32_t i = 0; i < nbs; i++) T_LOADB();
        TX(8 + ph * 4);
        const unsigned* fl = g_flag + F_XA + 16 * ph;
        flag_wait(fl + qt, 16);
        if (ph == 1) { if (qt > 0) flag_wait(fl + qt - 1, 16); if (qt < 15) flag_wait(fl + qt + 1, 16); }
        TX(9 + ph * 4);
        fence_async_global();
#pragma unroll 1
        for (int kb = 0; kb < nkb; kb++) {
          mbar_wait(mb_empty + 40 + 8 * ra.slot, ra.phase);
          mbar_expect_e(mb_full + 40 + 8 * ra.slot, 16384);
          tma2d_mc(sb + M_AOFF + ra.slot * 16384 + rank * 8192, ma, mb_full + 40 + 8 * ra.slot, kb * 64, qt * 128 + (int)rank * 64, 3);
          ra.adv(M_NA);
          while (bl < nbl + nel && (kb == nkb - 1 || kb >= (ph == 2 ? bl + 2 : 2 * bl - 3))) T_LOADB();
        }
      }
    } else if (wid < 3) {
      const int w = wid - 1, lane = threadIdx.x & 31;
#pragma unroll 1
      for (int sig = 0; sig < 4; sig++) {
        mbar_wait(bar_sig + 8 * w, sig & 1);
        if (lane == 0) {
          asm volatile("fence.acq_rel.gpu;" ::: "memory");
          flag_add(g_flag + F_O + qtile * 32 + hbase + 8 * sig);
        }
        __syncwarp();
      }
    } else {
      const int lane = threadIdx.x & 31;
      pdl_wait();
      prep_warp(pw, reinterpret_cast<bf16(*)[72]>(smem_raw + (sb + T_PREP - smem_u32(smem_raw))), lane);
      flag_wait(g_flag + F_PREP, PREP_CTAS);
#pragma unroll 1
      for (int i = lane; i < P_SC; i += 32) {
        const int v = i < P_CS3 ? i / 80 : 9, j = i - (i < P_CS3 ? v * 80 : P_CS3);
        const float* src = v == 0 ? g_mod + 2 * D_ + o_col : v == 1 ? g_mod + 4 * D_ + o_col : v == 2 ? g_mod + 3 * D_ + o_col
                         : v < 6 ? g_vec + (v - 3) * D_ + js * 80 : v == 6 ? g_mod + 4 * D_ + js * 80 : v == 7 ? g_mod + 3 * D_ + js * 80
                         : v == 8 ? g_mod + 5 * D_ + js * 80 : g_vec + 3 * D_ + js * 192;
        parf[i] = __ldcg(src + j);
      }
      float sv[5] = {0.f, 0.f, 0.f, 0.f, 0.f};
#pragma unroll 1
      for (int i = lane; i < D_; i += 32) {
        const float a = __ldcg(g_mod + 4 * D_ + i), b = __ldcg(g_mod + 3 * D_ + i);
        sv[0] += a; sv[1] = fmaf(a, a, sv[1]); sv[2] = fmaf(a, b, sv[2]); sv[3] += b; sv[4] = fmaf(b, b, sv[4]);
      }
#pragma unroll 1
      for (int o_ = 16; o_ > 0; o_ >>= 1) {
#pragma unroll
        for (int i = 0; i < 5; i++) sv[i] += __shfl_xor_sync(0xffffffffu, sv[i], o_);
      }
      if (lane == 0) {
#pragma unroll
        for (int i = 0; i < 5; i++) parf[P_SC + i] = sv[i];
      }
      bar_arrive(6, 288);
    }
    __syncwarp();
    cluster_sync();
  } else {
    asm volatile("setmaxnreg.inc.sync.aligned.u32 232;");
    const int w = wg - 1;
    const int lane = threadIdx.x & 31;
    const int warp = wid & 3;
    const int tid = threadIdx.x - 128;
    const uint32_t rel_base = mapa(bar_empty, (lane == 0) ? rank : (rank ^ 1));
    Ring r{0, 0};
#define A_RELEASE(slot_) do { if (lane < 2) mbar_arrive_remote(rel_base + 8 * (slot_)); } while (0)
#define SIGNAL() do { __syncwarp(); if (lane == 0) mbar_arrive(bar_sig + 8 * w); } while (0)
    {
    const float SC = 0.07216878364870322f * 1.4426950408889634f;
    float o[96];
    uint32_t q[48];
    float s[32];
    uint32_t p[16], p2[16];
    if (w == 1) bar_arrive(1, 256);
    for (int item = 0; item < 4; item++) {
      const int head = hbase + 8 * item;
      TSA(item, 0);
      uint32_t prevA = 0, prevB = 0;
      for (int kb = 0; kb < 10; kb++) {
        const uint32_t sA = r.slot; mbar_wait_c(bar_full + 8 * sA, r.phase); r.adv(A_NSLOT);
        const uint32_t sB = r.slot; mbar_wait_c(bar_full + 8 * sB, r.phase); r.adv(A_NSLOT);
        const uint64_t da = mkdesc(sb + sA * A_SLOT + w * 8192, 16, 1024);
        const uint64_t db = mkdesc(sb + sB * A_SLOT, 8192, 1024);
        wg_fence();
#pragma unroll
        for (int kk = 0; kk < 4; kk++) wgmma_ss_n192<1>(o, da + kk * 2, db + kk * 128, (kb | kk) != 0);
        wg_commit();
        if (kb > 0) { wg_wait<1>(); A_RELEASE(prevA); A_RELEASE(prevB); }
        prevA = sA; prevB = sB;
      }
      wg_wait<0>();
      fence_regs(o);
      A_RELEASE(prevA); A_RELEASE(prevB);
#pragma unroll
      for (int i = 0; i < 48; i++) q[i] = pack_bf16(o[2 * i], o[2 * i + 1]);

      TSA(item, 1);
      float c0, c1, l0, l1;
      {
        const uint32_t sK = r.slot; mbar_wait_c(bar_full + 8 * sK, r.phase); r.adv(A_NSLOT);
        const uint64_t dk = mkdesc(sb + sK * A_SLOT, 16, 1024);
        bar_sync(1 + w, 256);
        wg_fence();
#pragma unroll
        for (int kk = 0; kk < 12; kk++)
          wgmma_rs_n64<0>(s, q[4 * kk], q[4 * kk + 1], q[4 * kk + 2], q[4 * kk + 3], dk + (kk >> 2) * 512 + (kk & 3) * 2, kk != 0);
        wg_commit();
        bar_arrive(1 + (w ^ 1), 256);
        wg_wait<0>();
        fence_regs(s);
        A_RELEASE(sK);
        float mx0 = fmaxf(s[0], s[1]), mx1 = fmaxf(s[2], s[3]);
#pragma unroll
        for (int i = 1; i < 8; i++) { mx0 = fmaxf(mx0, fmaxf(s[4 * i], s[4 * i + 1])); mx1 = fmaxf(mx1, fmaxf(s[4 * i + 2], s[4 * i + 3])); }
        mx0 = fmaxf(mx0, __shfl_xor_sync(0xffffffffu, mx0, 1)); mx1 = fmaxf(mx1, __shfl_xor_sync(0xffffffffu, mx1, 1));
        mx0 = fmaxf(mx0, __shfl_xor_sync(0xffffffffu, mx0, 2)); mx1 = fmaxf(mx1, __shfl_xor_sync(0xffffffffu, mx1, 2));
        c0 = mx0 * SC; c1 = mx1 * SC;
        l0 = 0.f; l1 = 0.f;
#pragma unroll
        for (int i = 0; i < 8; i++) {
          s[4 * i] = ex2(fmaf(s[4 * i], SC, -c0)); s[4 * i + 1] = ex2(fmaf(s[4 * i + 1], SC, -c0));
          s[4 * i + 2] = ex2(fmaf(s[4 * i + 2], SC, -c1)); s[4 * i + 3] = ex2(fmaf(s[4 * i + 3], SC, -c1));
          l0 += s[4 * i] + s[4 * i + 1]; l1 += s[4 * i + 2] + s[4 * i + 3];
        }
#pragma unroll
        for (int i = 0; i < 16; i++) p[i] = pack_bf16(s[2 * i], s[2 * i + 1]);
      }
      TSA(item, 2);
      uint32_t okn;
      {
        Ring r2 = r; r2.adv(A_NSLOT);
        okn = mbar_try(bar_full + 8 * r.slot, r.phase) & mbar_try(bar_full + 8 * r2.slot, r2.phase);
      }
#define A_STEP(PC, PN, FIRST)                                                                                          \
      {                                                                                                                \
        const uint32_t sK = r.slot, phK = r.phase; r.adv(A_NSLOT);                                                     \
        const uint32_t sV = r.slot, phV = r.phase; r.adv(A_NSLOT);                                                     \
        const uint64_t dk = mkdesc(sb + sK * A_SLOT, 16, 1024);                                                        \
        const uint64_t dv = mkdesc(sb + sV * A_SLOT, 8192, 1024);                                                      \
        if (!okn) { mbar_wait_c(bar_full + 8 * sK, phK); mbar_wait_c(bar_full + 8 * sV, phV); }                            \
        bar_sync(1 + w, 256);                                                                                          \
        wg_fence();                                                                                                    \
        _Pragma("unroll") for (int kk = 0; kk < 12; kk++)                                                              \
          wgmma_rs_n64<0>(s, q[4 * kk], q[4 * kk + 1], q[4 * kk + 2], q[4 * kk + 3], dk + (kk >> 2) * 512 + (kk & 3) * 2, kk != 0); \
        wg_commit();                                                                                                   \
        _Pragma("unroll") for (int kk = 0; kk < 4; kk++)                                                               \
          wgmma_rs_n192<1>(o, PC[4 * kk], PC[4 * kk + 1], PC[4 * kk + 2], PC[4 * kk + 3], dv + kk * 128, !(FIRST) || (kk != 0)); \
        wg_commit();                                                                                                   \
        bar_arrive(1 + (w ^ 1), 256);                                                                                  \
        {                                                                                                              \
          Ring r2 = r; r2.adv(A_NSLOT);                                                                                \
          okn = mbar_try(bar_full + 8 * r.slot, r.phase) & mbar_try(bar_full + 8 * r2.slot, r2.phase);                 \
        }                                                                                                              \
        wg_wait<1>();                                                                                                  \
        fence_regs(s);                                                                                                 \
        A_RELEASE(sK);                                                                                                 \
        float b0 = 0.f, b1 = 0.f;                                                                                      \
        _Pragma("unroll") for (int i = 0; i < 8; i++) {                                                                \
          const float e0 = ex2(fmaf(s[4 * i], SC, -c0)), e1 = ex2(fmaf(s[4 * i + 1], SC, -c0));                        \
          const float e2 = ex2(fmaf(s[4 * i + 2], SC, -c1)), e3 = ex2(fmaf(s[4 * i + 3], SC, -c1));                    \
          b0 += e0 + e1; b1 += e2 + e3;                                                                                \
          PN[2 * i] = pack_bf16(e0, e1); PN[2 * i + 1] = pack_bf16(e2, e3);                                            \
        }                                                                                                              \
        wg_wait<0>();                                                                                                  \
        fence_regs(o);                                                                                                 \
        fence_regs(PC);                                                                                                \
        A_RELEASE(sV);                                                                                                 \
        if (__any_sync(0xffffffffu, !(b0 <= 65536.f) || !(b1 <= 65536.f))) {                                           \
          float mx0 = fmaxf(s[0], s[1]), mx1 = fmaxf(s[2], s[3]);                                                      \
          _Pragma("unroll") for (int i = 1; i < 8; i++) {                                                              \
            mx0 = fmaxf(mx0, fmaxf(s[4 * i], s[4 * i + 1])); mx1 = fmaxf(mx1, fmaxf(s[4 * i + 2], s[4 * i + 3]));     \
          }                                                                                                            \
          mx0 = fmaxf(mx0, __shfl_xor_sync(0xffffffffu, mx0, 1)); mx1 = fmaxf(mx1, __shfl_xor_sync(0xffffffffu, mx1, 1)); \
          mx0 = fmaxf(mx0, __shfl_xor_sync(0xffffffffu, mx0, 2)); mx1 = fmaxf(mx1, __shfl_xor_sync(0xffffffffu, mx1, 2)); \
          const float n0 = fmaxf(c0, mx0 * SC), n1 = fmaxf(c1, mx1 * SC);                                              \
          const float a0 = ex2(c0 - n0), a1 = ex2(c1 - n1);                                                            \
          c0 = n0; c1 = n1;                                                                                            \
          l0 *= a0; l1 *= a1;                                                                                          \
          _Pragma("unroll") for (int i = 0; i < 24; i++) { o[4 * i] *= a0; o[4 * i + 1] *= a0; o[4 * i + 2] *= a1; o[4 * i + 3] *= a1; } \
          b0 = 0.f; b1 = 0.f;                                                                                          \
          _Pragma("unroll") for (int i = 0; i < 8; i++) {                                                              \
            const float e0 = ex2(fmaf(s[4 * i], SC, -c0)), e1 = ex2(fmaf(s[4 * i + 1], SC, -c0));                      \
            const float e2 = ex2(fmaf(s[4 * i + 2], SC, -c1)), e3 = ex2(fmaf(s[4 * i + 3], SC, -c1));                  \
            b0 += e0 + e1; b1 += e2 + e3;                                                                              \
            PN[2 * i] = pack_bf16(e0, e1); PN[2 * i + 1] = pack_bf16(e2, e3);                                          \
          }                                                                                                            \
        }                                                                                                              \
        l0 += b0; l1 += b1;                                                                                            \
      }
      for (int jj = 0; jj < 15; jj++) {
        A_STEP(p, p2, jj == 0)
        A_STEP(p2, p, false)
      }
      A_STEP(p, p2, false)
      TSA(item, 3);
      {
        const uint32_t sV = r.slot; mbar_wait_c(bar_full + 8 * sV, r.phase); r.adv(A_NSLOT);
        const uint64_t dv = mkdesc(sb + sV * A_SLOT, 8192, 1024);
        bar_sync(1 + w, 256);
        wg_fence();
#pragma unroll
        for (int kk = 0; kk < 4; kk++)
          wgmma_rs_n192<1>(o, p2[4 * kk], p2[4 * kk + 1], p2[4 * kk + 2], p2[4 * kk + 3], dv + kk * 128, 1);
        wg_commit();
        bar_arrive(1 + (w ^ 1), 256);
        wg_wait<0>();
        fence_regs(o);
        A_RELEASE(sV);
      }
      TSA(item, 4);
      l0 += __shfl_xor_sync(0xffffffffu, l0, 1); l1 += __shfl_xor_sync(0xffffffffu, l1, 1);
      l0 += __shfl_xor_sync(0xffffffffu, l0, 2); l1 += __shfl_xor_sync(0xffffffffu, l1, 2);
      const float i0 = 1.f / l0, i1 = 1.f / l1;
      bf16* orow = g_o + (size_t)(qtile * 128 + w * 64 + warp * 16 + (lane >> 2)) * HD_ + head * DH_ + (lane & 3) * 8;
#pragma unroll
      for (int g = 0; g < 6; g++) {
        uint32_t u0 = pack_bf16(o[16 * g + 0] * i0, o[16 * g + 1] * i0), u1 = pack_bf16(o[16 * g + 4] * i0, o[16 * g + 5] * i0);
        uint32_t u2 = pack_bf16(o[16 * g + 8] * i0, o[16 * g + 9] * i0), u3 = pack_bf16(o[16 * g + 12] * i0, o[16 * g + 13] * i0);
        quad_transpose(u0, u1, u2, u3, lane);
        *reinterpret_cast<uint4*>(orow + g * 32) = make_uint4(u0, u1, u2, u3);
        uint32_t v0 = pack_bf16(o[16 * g + 2] * i1, o[16 * g + 3] * i1), v1 = pack_bf16(o[16 * g + 6] * i1, o[16 * g + 7] * i1);
        uint32_t v2 = pack_bf16(o[16 * g + 10] * i1, o[16 * g + 11] * i1), v3 = pack_bf16(o[16 * g + 14] * i1, o[16 * g + 15] * i1);
        quad_transpose(v0, v1, v2, v3, lane);
        *reinterpret_cast<uint4*>(orow + (size_t)8 * HD_ + g * 32) = make_uint4(v0, v1, v2, v3);
      }
      SIGNAL();
      TSA(item, 5);
    }
    }
    TS(3, 2);
    const uint32_t st_w = (uint32_t)((warp * 16 + (lane >> 2)) * ST_P + (lane & 3) * 2) * 4;
    const uint32_t st_x = (lane & 8) << 2;
    const int er = (tid & 127) >> 1, eh = tid & 1;
    const uint32_t st_r = (uint32_t)(er * ST_P + (eh ^ ((er >> 1) & 1)) * 8) * 4;
    const uint32_t e_r = (uint32_t)((w * 64 + er) * 160 + eh * 16);
    const uint32_t p_r = par + eh * 32;
    const uint32_t stat = sb + T_PREP + w * 2048;
    const bool leader = (tid & 127) == 0;
#define STAGE10(ACC, BASE)                                                                                             \
    _Pragma("unroll") for (int nb = 0; nb < 10; nb++) {                                                                \
      sts_f2(stg + st_w + ((nb * 32) ^ st_x), ACC(BASE + 4 * nb), ACC(BASE + 4 * nb + 1));                                       \
      sts_f2(stg + st_w + ((nb * 32) ^ st_x) + 8 * ST_P * 4, ACC(BASE + 4 * nb + 2), ACC(BASE + 4 * nb + 3));                    \
    }

    {
      float acc1[96], acc2[64];
      uint32_t p0 = 0, p1 = 0, p2 = 0;
#pragma unroll 1
      for (int kb = 0; kb < 24; kb++) {
        const uint32_t s1 = r.slot; mbar_wait_c(bar_full + 8 * s1, r.phase); r.adv(A_NSLOT);
        const uint32_t s2 = r.slot; mbar_wait_c(bar_full + 8 * s2, r.phase); r.adv(A_NSLOT);
        const uint32_t sa = r.slot; mbar_wait_c(bar_full + 8 * sa, r.phase); r.adv(A_NSLOT);
        const uint64_t da = mkdesc(sb + sa * A_SLOT + w * 8192, 16, 1024);
        const uint64_t d1 = mkdesc(sb + s1 * A_SLOT, 8192, 1024), d2 = mkdesc(sb + s2 * A_SLOT, 8192, 1024);
        wg_fence();
#pragma unroll
        for (int kk = 0; kk < 4; kk++) {
          wgmma_ss_n192<1>(acc1, da + kk * 2, d1 + kk * 128, (kb | kk) != 0);
          wgmma_ss_n128<1>(acc2, da + kk * 2, d2 + kk * 128, (kb | kk) != 0);
        }
        wg_commit();
        if (kb > 0) { wg_wait<1>(); A_RELEASE(p0); A_RELEASE(p1); A_RELEASE(p2); }
        p0 = s1; p1 = s2; p2 = sa;
      }
      wg_wait<0>();
      fence_regs(acc1); fence_regs(acc2);
      A_RELEASE(p2);
      bar_sync(6, 288);
      TS(0, 0);
      const uint32_t stg = sb + (w ? p1 : p0) * A_SLOT;
#define OACC(e) (((e) < 96) ? acc1[(e) < 96 ? (e) : 0] : acc2[(e) >= 96 ? (e) - 96 : 0])
#define PACK10(BASE)                                                                                                   \
      _Pragma("unroll") for (int nb = 0; nb < 10; nb++) {                                                              \
        sts_u1(xo + nb * 16, pack_bf16(OACC(BASE + 4 * nb), OACC(BASE + 4 * nb + 1)));                                 \
        sts_u1(xo + nb * 16 + 8 * 160, pack_bf16(OACC(BASE + 4 * nb + 2), OACC(BASE + 4 * nb + 3)));                   \
      }
      const uint32_t f1 = r.slot + 4 >= A_NSLOT ? r.slot + 4 - A_NSLOT : r.slot + 4, f2 = f1 + 1 >= A_NSLOT ? 0 : f1 + 1;
#pragma unroll
      for (int d = 0; d < 4; d++) {
        if (d != o_ks) {
          const int i = (d - o_ks - 1) & 3;
          const uint32_t xo = sb + (i == 0 ? p2 : i == 1 ? f1 : f2) * A_SLOT + (w * 64 + warp * 16 + (lane >> 2)) * 160 + (lane & 3) * 4;
          PACK10(d * 40)
        }
      }
      fence_async_smem();
      bar_sync(3 + w, 128);
      if (leader) {
#pragma unroll 1
        for (int i = 0; i < 3; i++)
          bulk_store(g_xch + (size_t)((((o_qt * 2 + o_nh) * 4 + ((o_ks + 1 + i) & 3)) * 4) + o_ks) * (E_TILE / 2) + w * (E_TILE / 4),
                     sb + (i == 0 ? p2 : i == 1 ? f1 : f2) * A_SLOT + w * (E_TILE / 2), E_TILE / 2);
        bulk_done();
#pragma unroll 1
        for (int i = 0; i < 3; i++) flag_add(g_flag + F_XCH + (o_qt * 2 + o_nh) * 4 + ((o_ks + 1 + i) & 3));
        TX(40 + w);
      }
      if (o_ks == 0) { STAGE10(OACC, 0) } else if (o_ks == 1) { STAGE10(OACC, 40) } else if (o_ks == 2) { STAGE10(OACC, 80) } else { STAGE10(OACC, 120) }
      bar_sync(3 + w, 128);
      const uint32_t sx = r.slot; mbar_wait_c(bar_full + 8 * sx, r.phase); r.adv(A_NSLOT);
      const uint32_t q0 = r.slot; mbar_wait_c(bar_full + 8 * q0, r.phase); r.adv(A_NSLOT);
      const uint32_t q1 = r.slot; mbar_wait_c(bar_full + 8 * q1, r.phase); r.adv(A_NSLOT);
      const uint32_t q2 = r.slot; mbar_wait_c(bar_full + 8 * q2, r.phase); r.adv(A_NSLOT);
      TS(0, 1);
      float st[6] = {0.f, 0.f, 0.f, 0.f, 0.f, 0.f};
      const uint32_t ot = sb + p2 * A_SLOT;
#pragma unroll 1
      for (int c = 0; c < 5; c++) {
        float v[8], t0[8], t1[8], t2[8], xv[8], pg[8], pa_[8], pb_[8];
        lds8(stg + st_r + c * 64, v);
        lds8_bf(sb + q0 * A_SLOT + e_r + c * 32, t0); lds8_bf(sb + q1 * A_SLOT + e_r + c * 32, t1); lds8_bf(sb + q2 * A_SLOT + e_r + c * 32, t2);
        lds8_bf(sb + sx * A_SLOT + e_r + c * 32, xv);
        lds8(p_r + P_OGA * 4 + c * 64, pg); lds8(p_r + P_OA * 4 + c * 64, pa_); lds8(p_r + P_OB * 4 + c * 64, pb_);
#pragma unroll
        for (int e = 0; e < 8; e++) v[e] = fmaf(pg[e], v[e] + ((t0[e] + t1[e]) + t2[e]), xv[e]);
        const uint4 pk = pack8(v);
        sts_u4(ot + e_r + c * 32, pk);
        v[0] = bf_lo(pk.x); v[1] = bf_hi(pk.x); v[2] = bf_lo(pk.y); v[3] = bf_hi(pk.y); v[4] = bf_lo(pk.z); v[5] = bf_hi(pk.z); v[6] = bf_lo(pk.w); v[7] = bf_hi(pk.w);
#pragma unroll
        for (int e = 0; e < 8; e++) {
          const float y = pa_[e] * v[e];
          st[0] += v[e]; st[1] = fmaf(v[e], v[e], st[1]); st[2] += y; st[3] = fmaf(pa_[e], y, st[3]); st[4] = fmaf(y, y, st[4]); st[5] = fmaf(pb_[e], y, st[5]);
        }
      }
#pragma unroll
      for (int i = 0; i < 6; i++) st[i] += __shfl_xor_sync(0xffffffffu, st[i], 1);
      sts_u4(stat + er * 32 + eh * 16, eh ? make_uint4(__float_as_uint(st[4]), __float_as_uint(st[5]), 0u, 0u)
                                          : make_uint4(__float_as_uint(st[0]), __float_as_uint(st[1]), __float_as_uint(st[2]), __float_as_uint(st[3])));
      fence_async_smem();
      bar_sync(3 + w, 128);
      if (leader) {
        tma_store2d(&tm.sxa, ot + w * (E_TILE / 2), o_col, o_qt * 128 + w * 64);
        bulk_red_f32(g_st1 + (size_t)(o_qt * 128 + w * 64) * 8, stat, 2048);
        bulk_done();
        flag_add(g_flag + F_XA + o_qt);
      }
      bar_sync(5, 256);
      A_RELEASE(p0); A_RELEASE(p1); A_RELEASE(sx); A_RELEASE(q0); A_RELEASE(q1); A_RELEASE(q2);
      TS(0, 2);
    }

    Ring ra{0, 0};
    uint32_t bpar = 0;
    const uint32_t rel_a = mapa(mb_empty + 40, (lane == 0) ? rank : (rank ^ 1));
#define B_NEXT(s_) do { s_ = bs; mbar_wait_c(mb_full + 8 * bs, (bpar >> bs) & 1); bpar ^= 1u << bs; if (++bs == nbs) bs = 0; } while (0)
#define A_NEXT(s_) do { s_ = ra.slot; mbar_wait_c(mb_full + 40 + 8 * s_, ra.phase); ra.adv(M_NA); } while (0)
#define B_RELEASE(s_) do { if (lane == 0) mbar_arrive(mb_empty + 8 * (s_)); } while (0)
#define MA_RELEASE(s_) do { if (lane < 2) mbar_arrive_remote(rel_a + 8 * (s_)); } while (0)
    const int grow = qt * 128 + w * 64 + er;
    float mu = 0.f, rs = 0.f;
#pragma unroll 1
    for (int ph = 0; ph < 4; ph++) {
      float acc[96];
      float (&acc80)[40] = *reinterpret_cast<float(*)[40]>(&acc[0]);
      uint32_t pa = 0, pa2 = 0, pb = 0;
      float4 s03 = make_float4(0.f, 0.f, 0.f, 0.f);
      float2 s45 = make_float2(0.f, 0.f);
      const int nit = ph == 3 ? 12 : ph == 2 ? 10 : 5;
      const uint32_t nbs = ph == 2 ? 4 : 5, bsz = ph == 2 ? 24576 : 20480;
      uint32_t bs = 0;
#pragma unroll 1
      for (int it = 0; it < nit; it++) {
        uint32_t sbq, sa, sa2;
        B_NEXT(sbq);
        A_NEXT(sa);
        if (it == 0) TXC(ph);
        const uint64_t da = mkdesc(sb + M_AOFF + sa * 16384 + w * 8192, 16, 1024);
        if (ph == 2) {
          sa2 = sa;
          const uint64_t db = mkdesc(sb + sbq * 24576, 8192, 1024);
          wg_fence();
#pragma unroll
          for (int kk = 0; kk < 4; kk++) wgmma_ss_n192<1>(acc, da + kk * 2, db + kk * 128, (it | kk) != 0);
          wg_commit();
        } else {
          A_NEXT(sa2);
          const uint64_t da2 = mkdesc(sb + M_AOFF + sa2 * 16384 + w * 8192, 16, 1024);
          const uint64_t db = mkdesc(sb + sbq * 20480, 16, 1024);
          wg_fence();
#pragma unroll
          for (int kk = 0; kk < 4; kk++) wgmma_ss_n80<0>(acc80, da + kk * 2, db + kk * 2, (it | kk) != 0);
#pragma unroll
          for (int kk = 0; kk < 4; kk++) wgmma_ss_n80<0>(acc80, da2 + kk * 2, db + 640 + kk * 2, 1);
          wg_commit();
        }
        if (it > 0) { wg_wait<1>(); MA_RELEASE(pa); if (ph != 2) MA_RELEASE(pa2); B_RELEASE(pb); }
        else {
          if (ph == 0) { s03 = __ldcg(reinterpret_cast<const float4*>(g_st1 + (size_t)grow * 8)); s45 = __ldcg(reinterpret_cast<const float2*>(g_st1 + (size_t)grow * 8 + 4)); }
          if (ph == 2) s45 = __ldcg(reinterpret_cast<const float2*>(g_st2 + (size_t)grow * 2));
        }
        pa = sa; pa2 = sa2; pb = sbq;
      }
      wg_wait<0>();
      fence_regs(acc);
      MA_RELEASE(pa); if (ph != 2) MA_RELEASE(pa2);
      bar_sync(5, 256);
      TS(1 + (ph == 3 ? 0 : ph), ph == 3 ? 2 : 0);
      const uint32_t pb1 = pb == 0 ? nbs - 1 : pb - 1, pb2 = pb1 == 0 ? nbs - 1 : pb1 - 1, pb3 = pb2 == 0 ? nbs - 1 : pb2 - 1;
      const uint32_t stg = sb + (w ? pb : pb1) * bsz;
      uint32_t e1 = 0;
#define MACC(e) acc[e]
      if (!(ph & 1)) {
        float c0, c1, c2 = 0.f, c3 = 0.f;
        if (ph == 0) {
          const float4 sc = lds_f4(par + P_SC * 4);
          const float sbb = lds_f(par + (P_SC + 4) * 4);
          mu = s03.x * (1.f / D_);
          rs = rsqrtf(fmaxf(s03.y * (1.f / D_) - mu * mu, 0.f) + LN_EPS);
          const float m2 = (rs * (s03.z - mu * sc.x) + sc.w) * (1.f / D_);
          const float e2 = (rs * rs * (s45.x - 2.f * mu * s03.w + mu * mu * sc.y) + 2.f * rs * (s45.y - mu * sc.z) + sbb) * (1.f / D_);
          c2 = rsqrtf(fmaxf(e2 - m2 * m2, 0.f) + LN_EPS);
          c0 = c2 * rs; c1 = -c0 * mu; c3 = -c2 * m2;
          if (tid < 20) sts_u4(stat + 2048 * 2 + tid * 16, make_uint4(0, 0, 0, 0));
        } else {
          const float m = s45.x * (1.f / D_);
          c0 = rsqrtf(fmaxf(s45.y * (1.f / D_) - m * m, 0.f) + LN_EPS);
          c1 = -c0 * m;
        }
        const int npass = ph == 0 ? 1 : 3, nch = ph == 0 ? 5 : 4;
        const uint32_t ot = ph == 0 ? sb + pb2 * bsz + w * (E_TILE / 2) : sb + (w ? pb2 : pb3) * bsz;
#pragma unroll 1
        for (int ps = 0; ps < npass; ps++) {
          if (ps == 0) { STAGE10(MACC, 0) } else if (ps == 1) { STAGE10(MACC, 32) } else { STAGE10(MACC, 56) }
          bar_sync(3 + w, 128);
          const uint32_t cofs = ps == 2 ? 64 : 0;
          const uint32_t pp = p_r + (ph == 0 ? P_VA : P_CS3 + ps * 64) * 4, pq = p_r + P_VB * 4;
#pragma unroll 1
          for (int c = 0; c < nch; c++) {
            float v[8], t[8], t2[8], t3[8];
            lds8(stg + st_r + cofs + c * 64, v);
            lds8(pp + c * 64, t); lds8(pq + c * 64, t2); lds8(pq + 320 + c * 64, t3);
#pragma unroll
            for (int e = 0; e < 8; e++) v[e] = gelu_tanh(fmaf(c0, v[e], fmaf(c1, t[e], fmaf(c2, t2[e], c3 * t3[e]))));
            sts_u4(ot + (ph == 0 ? er * 160 + eh * 16 + c * 32 : ps * 8192 + er * 128 + (((2 * c + eh) ^ (er & 7)) << 4)), pack8(v));
          }
          fence_async_smem();
          bar_sync(3 + w, 128);
          if (leader) {
            if (ph == 0) {
              const int grp = js >> 1;
              const int sh = (grp & 2 ? 2 : 1) * (grp & 1 ? -1 : 1);
              tma_store2d(&tm.sus, ot, js * 80, qt * 128 + w * 64 + sh + 2);
              if (w == 0 && qt == (sh > 0 ? 0 : 15)) {
                const int r0 = sh > 0 ? 0 : S_ + sh, n = sh > 0 ? sh : -sh;
                for (int i = 0; i < n; i++) bulk_store(g_us + (size_t)(r0 + i + 2) * D_ + js * 80, stat + 2048 * 2, 160);
              }
            } else {
              tma_store2d(&tm.g, ot + ps * 8192, js * 192 + ps * 64, qt * 128 + w * 64);
            }
          }
        }
      } else {
        STAGE10(MACC, 0)
        uint32_t e2;
        B_NEXT(e1);
        e2 = e1;
        if (ph == 3) B_NEXT(e2);
        bar_sync(3 + w, 128);
        float s1 = 0.f, s2 = 0.f;
        const uint32_t ot = sb + pb2 * bsz;
#pragma unroll 1
        for (int c = 0; c < 5; c++) {
          float v[8], xa[8], x1[8], ta[8], tb[8];
          lds8(stg + st_r + c * 64, v);
          lds8_bf(sb + e1 * 20480 + e_r + c * 32, xa); lds8_bf(sb + e2 * 20480 + e_r + c * 32, x1);
          lds8(p_r + (ph == 1 ? P_A2 : P_GB) * 4 + c * 64, ta); lds8(p_r + P_B2 * 4 + c * 64, tb);
          if (ph == 1) {
#pragma unroll
            for (int e = 0; e < 8; e++) v[e] += fmaf(ta[e] * rs, xa[e] - mu, tb[e]);
          } else {
#pragma unroll
            for (int e = 0; e < 8; e++) v[e] = fmaf(ta[e], v[e] + x1[e], xa[e]);
          }
          const uint4 pk = pack8(v);
          sts_u4(ot + e_r + c * 32, pk);
          v[0] = bf_lo(pk.x); v[1] = bf_hi(pk.x); v[2] = bf_lo(pk.y); v[3] = bf_hi(pk.y); v[4] = bf_lo(pk.z); v[5] = bf_hi(pk.z); v[6] = bf_lo(pk.w); v[7] = bf_hi(pk.w);
#pragma unroll
          for (int e = 0; e < 8; e++) { s1 += v[e]; s2 = fmaf(v[e], v[e], s2); }
        }
        s1 += __shfl_xor_sync(0xffffffffu, s1, 1); s2 += __shfl_xor_sync(0xffffffffu, s2, 1);
        if (eh == 0) sts_f2(stat + er * 8, s1, s2);
        fence_async_smem();
        bar_sync(3 + w, 128);
        if (leader) {
          tma_store2d(ph == 1 ? &tm.sx1 : &tm.sout, ot + w * (E_TILE / 2), js * 80, qt * 128 + w * 64);
          if (ph == 1) bulk_red_f32(g_st2 + (size_t)(qt * 128 + w * 64) * 2, stat, 512);
        }
      }
      if (leader) {
        bulk_done();
        if (ph < 3) flag_add(g_flag + F_US + 16 * ph + qt);
      }
      if (ph < 3) {
        bar_sync(5, 256);
        B_RELEASE(pb);
        if (ph == 1) B_RELEASE(e1);
      }
      TS(1 + (ph == 3 ? 0 : ph), ph == 3 ? 3 : 1);
    }
    if ((threadIdx.x & 127) == 0) TL_END(2);
    cluster_sync();
  }
}

typedef CUresult (*EncFn)(CUtensorMap*, CUtensorMapDataType, cuuint32_t, void*, const cuuint64_t*, const cuuint64_t*,
                          const cuuint32_t*, const cuuint32_t*, CUtensorMapInterleave, CUtensorMapSwizzle,
                          CUtensorMapL2promotion, CUtensorMapFloatOOBfill);
static EncFn g_enc = nullptr;

static CUtensorMap map2d(const void* p, uint64_t rows, uint64_t cols, uint32_t box_rows) {
  CUtensorMap m;
  cuuint64_t gd[2] = {cols, rows}; cuuint64_t gs[1] = {cols * 2};
  cuuint32_t bx[2] = {64, box_rows}; cuuint32_t es[2] = {1, 1};
  g_enc(&m, CU_TENSOR_MAP_DATA_TYPE_BFLOAT16, 2, const_cast<void*>(p), gd, gs, bx, es, CU_TENSOR_MAP_INTERLEAVE_NONE,
        CU_TENSOR_MAP_SWIZZLE_128B, CU_TENSOR_MAP_L2_PROMOTION_L2_256B, CU_TENSOR_MAP_FLOAT_OOB_FILL_NONE);
  return m;
}
static CUtensorMap map3d(const void* p, uint64_t rows, uint64_t cols, uint32_t box_rows, uint32_t nblk) {
  CUtensorMap m;
  cuuint64_t gd[3] = {64, rows, cols / 64}; cuuint64_t gs[2] = {cols * 2, 128};
  cuuint32_t bx[3] = {64, box_rows, nblk}; cuuint32_t es[3] = {1, 1, 1};
  g_enc(&m, CU_TENSOR_MAP_DATA_TYPE_BFLOAT16, 3, const_cast<void*>(p), gd, gs, bx, es, CU_TENSOR_MAP_INTERLEAVE_NONE,
        CU_TENSOR_MAP_SWIZZLE_128B, CU_TENSOR_MAP_L2_PROMOTION_L2_256B, CU_TENSOR_MAP_FLOAT_OOB_FILL_NONE);
  return m;
}

static CUtensorMap map_e(const void* p, uint32_t rows, uint64_t total_rows = S_) {
  CUtensorMap m;
  cuuint64_t gd[2] = {D_, total_rows}; cuuint64_t gs[1] = {D_ * 2};
  cuuint32_t bx[2] = {80, rows}; cuuint32_t es[2] = {1, 1};
  g_enc(&m, CU_TENSOR_MAP_DATA_TYPE_BFLOAT16, 2, const_cast<void*>(p), gd, gs, bx, es, CU_TENSOR_MAP_INTERLEAVE_NONE,
        CU_TENSOR_MAP_SWIZZLE_NONE, CU_TENSOR_MAP_L2_PROMOTION_L2_256B, CU_TENSOR_MAP_FLOAT_OOB_FILL_NONE);
  return m;
}

template <typename... KArgs, typename... Args>
static void launch(void (*kern)(KArgs...), dim3 grid, dim3 block, int smem, bool pdl, Args... args) {
  cudaLaunchConfig_t cfg = {};
  cfg.gridDim = grid; cfg.blockDim = block; cfg.dynamicSmemBytes = smem; cfg.stream = cudaStreamPerThread;
  cudaLaunchAttribute at[1];
  at[0].id = cudaLaunchAttributeProgrammaticStreamSerialization;
  at[0].val.programmaticStreamSerializationAllowed = 1;
  cfg.attrs = at; cfg.numAttrs = pdl ? 1 : 0;
  cudaLaunchKernelEx(&cfg, kern, KArgs(args)...);
}

extern "C" void kernel_launch(void* const* d_in, const int* in_sizes, int n_in, void* d_out, int out_size) {
  const bf16* x = (const bf16*)d_in[0];
  const bf16* kc = (const bf16*)d_in[1];
  const bf16* vc = (const bf16*)d_in[2];
  const bf16* wq = (const bf16*)d_in[3];
  const bf16* wo = (const bf16*)d_in[4];
  const bf16* w1 = (const bf16*)d_in[6];
  const bf16* w2 = (const bf16*)d_in[7];
  const bf16* w3 = (const bf16*)d_in[8];
  const bf16* w4 = (const bf16*)d_in[9];
  const bf16* c = (const bf16*)d_in[10];
  const bf16* wmod = (const bf16*)d_in[11];
  bf16* out = (bf16*)d_out;

  static void *p_h, *p_o, *p_xa, *p_us, *p_x1, *p_g, *p_w1t, *p_w2t, *p_w4t;
  if (!g_enc) {
    void* fn = nullptr; cudaDriverEntryPointQueryResult qr;
    cudaGetDriverEntryPoint("cuTensorMapEncodeTiled", &fn, cudaEnableDefault, &qr);
    g_enc = (EncFn)fn;
    cudaGetSymbolAddress(&p_h, g_h); cudaGetSymbolAddress(&p_o, g_o); cudaGetSymbolAddress(&p_xa, g_xa);
    cudaGetSymbolAddress(&p_us, g_us); cudaGetSymbolAddress(&p_x1, g_x1); cudaGetSymbolAddress(&p_g, g_g);
    cudaGetSymbolAddress(&p_w1t, g_w1t); cudaGetSymbolAddress(&p_w2t, g_w2t); cudaGetSymbolAddress(&p_w4t, g_w4t);
    cudaFuncSetAttribute(fused_kernel, cudaFuncAttributeMaxDynamicSharedMemorySize, T_SMEM);
  }
  Maps tm;
  tm.h = map2d(p_h, S_, D_, 128);
  tm.wq = map3d(wq, D_, HD_, 64, 3);
  tm.k = map3d(kc, (uint64_t)H_ * S_, DH_, 64, 3);
  tm.v = map3d(vc, (uint64_t)H_ * S_, DH_, 64, 3);
  tm.o = map2d(p_o, S_, HD_, 128);
  tm.wo3 = map3d(wo, HD_, D_, 64, 3);
  tm.wo2 = map3d(wo, HD_, D_, 64, 2);
  tm.xa = map2d(p_xa, S_, D_, 64);
  tm.w1t = map3d(p_w1t, D_, D_, 80, 2);
  tm.us = map2d((const bf16*)p_us + 2 * D_, S_, D_, 64);
  tm.w2t = map3d(p_w2t, D_, D_, 80, 2);
  tm.x1 = map2d(p_x1, S_, D_, 64);
  tm.w3 = map3d(w3, D_, F_, 64, 3);
  tm.g = map2d(p_g, S_, F_, 64);
  tm.w4t = map3d(p_w4t, D_, F_, 80, 2);
  tm.ex = map_e(x, 128); tm.exa = map_e(p_xa, 128); tm.ex1 = map_e(p_x1, 128);
  tm.sxa = map_e(p_xa, 64); tm.sus = map_e(p_us, 64, S_ + 4); tm.sx1 = map_e(p_x1, 64); tm.sout = map_e(out, 64);
  PfList pf;
  pf.p[0] = (const uint8_t*)wo; pf.p[1] = (const uint8_t*)w3; pf.p[2] = (const uint8_t*)p_w4t;
  pf.p[3] = (const uint8_t*)x; pf.p[4] = (const uint8_t*)p_w1t; pf.p[5] = (const uint8_t*)p_w2t;

  launch(mod_kernel, dim3(120), dim3(256), 0, false, c, wmod);
  launch(ln1_kernel, dim3(256), dim3(256), 0, true, x);
  launch(fused_kernel, dim3(128), dim3(384), T_SMEM, true, tm, pf, PrepW{w1, w2, w3, w4}, x, out);
}
```

```cpp
#include <cuda_runtime.h>
#include <cuda.h>
#include <cuda_bf16.h>
#include <stdint.h>

typedef __nv_bfloat16 bf16;

constexpr int S_  = 2048;
constexpr int D_  = 640;
constexpr int H_  = 32;
constexpr int DH_ = 192;
constexpr int HD_ = H_ * DH_;
constexpr int F_  = 1536;
constexpr float LN_EPS = 1e-5f;

__device__ __forceinline__ uint32_t smem_u32(const void* p) { return (uint32_t)__cvta_generic_to_shared(p); }
__device__ __forceinline__ void mbar_init(uint32_t a, uint32_t c) { asm volatile("mbarrier.init.shared::cta.b64 [%0], %1;" :: "r"(a), "r"(c) : "memory"); }
__device__ __forceinline__ void mbar_expect(uint32_t a, uint32_t b) { asm volatile("mbarrier.arrive.expect_tx.shared::cta.b64 _, [%0], %1;" :: "r"(a), "r"(b) : "memory"); }
__device__ __forceinline__ void mbar_arrive(uint32_t a) { asm volatile("mbarrier.arrive.shared::cta.b64 _, [%0];" :: "r"(a) : "memory"); }
__device__ __forceinline__ void mbar_arrive_remote(uint32_t ra) { asm volatile("mbarrier.arrive.shared::cluster.b64 _, [%0];" :: "r"(ra) : "memory"); }
__device__ __forceinline__ uint32_t mapa(uint32_t a, uint32_t cta) { uint32_t r; asm volatile("mapa.shared::cluster.u32 %0, %1, %2;" : "=r"(r) : "r"(a), "r"(cta)); return r; }
__device__ __forceinline__ uint32_t mbar_try(uint32_t a, uint32_t ph) {
  uint32_t ok;
  asm volatile("{\n.reg .pred p;\nmbarrier.test_wait.parity.shared::cta.b64 p, [%1], %2;\nselp.u32 %0, 1, 0, p;\n}\n" : "=r"(ok) : "r"(a), "r"(ph) : "memory");
  return ok;
}
__device__ __forceinline__ void mbar_wait(uint32_t a, uint32_t ph) {
  asm volatile(
      "{\n.reg .pred p;\n.reg .u32 n;\n"
      "mov.u32 n, 0;\n"
      "SPIN:\n"
      "mbarrier.try_wait.parity.shared::cta.b64 p, [%0], %1;\n"
      "@p bra DONE;\n"
      "add.u32 n, n, 1;\n"
      "setp.le.u32 p, n, 16777216;\n"
      "@p bra SPIN;\n"
      "trap;\n"
      "DONE:\n}\n" :: "r"(a), "r"(ph) : "memory");
}
#define ELECT_ "{\n.reg .pred p;\nelect.sync _|p, 0xffffffff;\n@p "
__device__ __forceinline__ void mbar_expect_e(uint32_t a, uint32_t b) { asm volatile(ELECT_ "mbarrier.arrive.expect_tx.shared::cta.b64 _, [%0], %1;\n}\n" :: "r"(a), "r"(b) : "memory"); }
__device__ __forceinline__ void tma2d(uint32_t dst, const CUtensorMap* m, uint32_t bar, int c0, int c1) {
  asm volatile(ELECT_ "cp.async.bulk.tensor.2d.shared::cluster.global.mbarrier::complete_tx::bytes [%0], [%1, {%3, %4}], [%2];\n}\n"
               :: "r"(dst), "l"(m), "r"(bar), "r"(c0), "r"(c1) : "memory");
}
__device__ __forceinline__ void tma2d_mc(uint32_t dst, const CUtensorMap* m, uint32_t bar, int c0, int c1, uint16_t mask) {
  asm volatile(ELECT_ "cp.async.bulk.tensor.2d.shared::cluster.global.mbarrier::complete_tx::bytes.multicast::cluster [%0], [%1, {%3, %4}], [%2], %5;\n}\n"
               :: "r"(dst), "l"(m), "r"(bar), "r"(c0), "r"(c1), "h"(mask) : "memory");
}
__device__ __forceinline__ void tma3d(uint32_t dst, const CUtensorMap* m, uint32_t bar, int c0, int c1, int c2) {
  asm volatile(ELECT_ "cp.async.bulk.tensor.3d.shared::cluster.global.mbarrier::complete_tx::bytes [%0], [%1, {%3, %4, %5}], [%2];\n}\n"
               :: "r"(dst), "l"(m), "r"(bar), "r"(c0), "r"(c1), "r"(c2) : "memory");
}
__device__ __forceinline__ void tma3d_mc(uint32_t dst, const CUtensorMap* m, uint32_t bar, int c0, int c1, int c2, uint16_t mask) {
  asm volatile(ELECT_ "cp.async.bulk.tensor.3d.shared::cluster.global.mbarrier::complete_tx::bytes.multicast::cluster [%0], [%1, {%3, %4, %5}], [%2], %6;\n}\n"
               :: "r"(dst), "l"(m), "r"(bar), "r"(c0), "r"(c1), "r"(c2), "h"(mask) : "memory");
}
__device__ __forceinline__ void tma3d_mc_hint(uint32_t dst, const CUtensorMap* m, uint32_t bar, int c0, int c1, int c2, uint16_t mask, uint64_t pol) {
  asm volatile(ELECT_ "cp.async.bulk.tensor.3d.shared::cluster.global.mbarrier::complete_tx::bytes.multicast::cluster.L2::cache_hint [%0], [%1, {%3, %4, %5}], [%2], %6, %7;\n}\n"
               :: "r"(dst), "l"(m), "r"(bar), "r"(c0), "r"(c1), "r"(c2), "h"(mask), "l"(pol) : "memory");
}
__device__ __forceinline__ void bulk_load(uint32_t dst, const void* src, uint32_t bytes, uint32_t bar) {
  asm volatile(ELECT_ "cp.async.bulk.shared::cluster.global.mbarrier::complete_tx::bytes [%0], [%1], %2, [%3];\n}\n"
               :: "r"(dst), "l"(src), "r"(bytes), "r"(bar) : "memory");
}
__device__ __forceinline__ void l2_prefetch16k(const void* p) { asm volatile(ELECT_ "cp.async.bulk.prefetch.L2.global [%0], 16384;\n}\n" :: "l"(p) : "memory"); }
__device__ __forceinline__ void l2_prefetch_t2d(const CUtensorMap* m, int c0, int c1) {
  asm volatile(ELECT_ "cp.async.bulk.prefetch.tensor.2d.L2.global [%0, {%1, %2}];\n}\n" :: "l"(m), "r"(c0), "r"(c1) : "memory");
}
__device__ __forceinline__ void stg128(void* p, uint4 v) {
  asm volatile("st.global.v4.u32 [%0], {%1, %2, %3, %4};" :: "l"(p), "r"(v.x), "r"(v.y), "r"(v.z), "r"(v.w) : "memory");
}
__device__ __forceinline__ void prefetch_tmap(const CUtensorMap* m) { asm volatile("prefetch.tensormap [%0];" :: "l"(m) : "memory"); }
__device__ __forceinline__ void wg_fence() { asm volatile("wgmma.fence.sync.aligned;" ::: "memory"); }
__device__ __forceinline__ void wg_commit() { asm volatile("wgmma.commit_group.sync.aligned;" ::: "memory"); }
template <int N> __device__ __forceinline__ void wg_wait() { asm volatile("wgmma.wait_group.sync.aligned %0;" :: "n"(N) : "memory"); }
template <int N> __device__ __forceinline__ void fence_regs(float (&r)[N]) {
#pragma unroll
  for (int i = 0; i < N; i++) asm volatile("" : "+f"(r[i]) :: "memory");
}
template <int N> __device__ __forceinline__ void fence_regs(uint32_t (&r)[N]) {
#pragma unroll
  for (int i = 0; i < N; i++) asm volatile("" : "+r"(r[i]) :: "memory");
}
__device__ __forceinline__ uint64_t mkdesc(uint32_t addr, uint32_t lbo, uint32_t sbo) {
  return (uint64_t)((addr & 0x3FFFF) >> 4) | ((uint64_t)(lbo >> 4) << 16) | ((uint64_t)(sbo >> 4) << 32) | (1ull << 62);
}
__device__ __forceinline__ void bar_sync(int id, int n) { asm volatile("bar.sync %0, %1;" :: "r"(id), "r"(n) : "memory"); }
__device__ __forceinline__ void bar_arrive(int id, int n) { asm volatile("bar.arrive %0, %1;" :: "r"(id), "r"(n) : "memory"); }
__device__ __forceinline__ void cluster_sync() { asm volatile("barrier.cluster.arrive.aligned;\nbarrier.cluster.wait.aligned;" ::: "memory"); }
__device__ __forceinline__ void pdl_wait() { asm volatile("griddepcontrol.wait;" ::: "memory"); }
__device__ __forceinline__ void pdl_launch() { asm volatile("griddepcontrol.launch_dependents;" ::: "memory"); }
__device__ __forceinline__ float ex2(float x) { float y; asm("ex2.approx.ftz.f32 %0, %1;" : "=f"(y) : "f"(x)); return y; }
__device__ __forceinline__ uint32_t pack_bf16(float lo, float hi) { uint32_t r; asm("cvt.rn.bf16x2.f32 %0, %1, %2;" : "=r"(r) : "f"(hi), "f"(lo)); return r; }
__device__ __forceinline__ float bf_lo(uint32_t u) { return __uint_as_float(u << 16); }
__device__ __forceinline__ float bf_hi(uint32_t u) { return __uint_as_float(u & 0xffff0000u); }
__device__ __forceinline__ float bf_round(float x) { return __bfloat162float(__float2bfloat16_rn(x)); }
__device__ __forceinline__ float tanh_fast(float x) { float y; asm("tanh.approx.f32 %0, %1;" : "=f"(y) : "f"(x)); return y; }
__device__ __forceinline__ float gelu_tanh(float x) {
  float u = x * (0.7978845608028654f + 0.035677408136300125f * x * x);
  float hx = 0.5f * x;
  return fmaf(hx, tanh_fast(u), hx);
}
__device__ __forceinline__ float warp_sum(float v) {
#pragma unroll
  for (int o = 16; o > 0; o >>= 1) v += __shfl_xor_sync(0xffffffffu, v, o);
  return v;
}
__device__ __forceinline__ void quad_transpose(uint32_t& v0, uint32_t& v1, uint32_t& v2, uint32_t& v3, int lane) {
  const bool b0 = lane & 1, b1 = lane & 2;
  uint32_t s0 = b0 ? v0 : v1, s1 = b0 ? v2 : v3;
  s0 = __shfl_xor_sync(0xffffffffu, s0, 1); s1 = __shfl_xor_sync(0xffffffffu, s1, 1);
  if (b0) { v0 = s0; v2 = s1; } else { v1 = s0; v3 = s1; }
  uint32_t t0 = b1 ? v0 : v2, t1 = b1 ? v1 : v3;
  t0 = __shfl_xor_sync(0xffffffffu, t0, 2); t1 = __shfl_xor_sync(0xffffffffu, t1, 2);
  if (b1) { v0 = t0; v1 = t1; } else { v2 = t0; v3 = t1; }
}

#define TX(i)
#define TXC(i)
#define TSA(item, i)
#define TL_ENTRY(k)
#define TL_WAITED(k)
#define TL_END(k)
#define TS(item, i)
template<int TB> __device__ __forceinline__ void wgmma_rs_n64(float (&d)[32], uint32_t a0, uint32_t a1, uint32_t a2, uint32_t a3, uint64_t db, int scale_d) {
  asm volatile("{\n.reg .pred p;\nsetp.ne.b32 p, %37, 0;\n"
    "wgmma.mma_async.sync.aligned.m64n64k16.f32.bf16.bf16 {%0, %1, %2, %3, %4, %5, %6, %7, %8, %9, %10, %11, %12, %13, %14, %15, %16, %17, %18, %19, %20, %21, %22, %23, %24, %25, %26, %27, %28, %29, %30, %31}, {%32, %33, %34, %35}, %36, p, 1, 1, %38;\n}\n"
    : "+f"(d[0]), "+f"(d[1]), "+f"(d[2]), "+f"(d[3]), "+f"(d[4]), "+f"(d[5]), "+f"(d[6]), "+f"(d[7]), "+f"(d[8]), "+f"(d[9]), "+f"(d[10]), "+f"(d[11]), "+f"(d[12]), "+f"(d[13]), "+f"(d[14]), "+f"(d[15]), "+f"(d[16]), "+f"(d[17]), "+f"(d[18]), "+f"(d[19]), "+f"(d[20]), "+f"(d[21]), "+f"(d[22]), "+f"(d[23]), "+f"(d[24]), "+f"(d[25]), "+f"(d[26]), "+f"(d[27]), "+f"(d[28]), "+f"(d[29]), "+f"(d[30]), "+f"(d[31])
    : "r"(a0), "r"(a1), "r"(a2), "r"(a3), "l"(db), "r"(scale_d), "n"(TB));
}
template<int TB> __device__ __forceinline__ void wgmma_rs_n192(float (&d)[96], uint32_t a0, uint32_t a1, uint32_t a2, uint32_t a3, uint64_t db, int scale_d) {
  asm volatile("{\n.reg .pred p;\nsetp.ne.b32 p, %101, 0;\n"
    "wgmma.mma_async.sync.aligned.m64n192k16.f32.bf16.bf16 {%0, %1, %2, %3, %4, %5, %6, %7, %8, %9, %10, %11, %12, %13, %14, %15, %16, %17, %18, %19, %20, %21, %22, %23, %24, %25, %26, %27, %28, %29, %30, %31, %32, %33, %34, %35, %36, %37, %38, %39, %40, %41, %42, %43, %44, %45, %46, %47, %48, %49, %50, %51, %52, %53, %54, %55, %56, %57, %58, %59, %60, %61, %62, %63, %64, %65, %66, %67, %68, %69, %70, %71, %72, %73, %74, %75, %76, %77, %78, %79, %80, %81, %82, %83, %84, %85, %86, %87, %88, %89, %90, %91, %92, %93, %94, %95}, {%96, %97, %98, %99}, %100, p, 1, 1, %102;\n}\n"
    : "+f"(d[0]), "+f"(d[1]), "+f"(d[2]), "+f"(d[3]), "+f"(d[4]), "+f"(d[5]), "+f"(d[6]), "+f"(d[7]), "+f"(d[8]), "+f"(d[9]), "+f"(d[10]), "+f"(d[11]), "+f"(d[12]), "+f"(d[13]), "+f"(d[14]), "+f"(d[15]), "+f"(d[16]), "+f"(d[17]), "+f"(d[18]), "+f"(d[19]), "+f"(d[20]), "+f"(d[21]), "+f"(d[22]), "+f"(d[23]), "+f"(d[24]), "+f"(d[25]), "+f"(d[26]), "+f"(d[27]), "+f"(d[28]), "+f"(d[29]), "+f"(d[30]), "+f"(d[31]), "+f"(d[32]), "+f"(d[33]), "+f"(d[34]), "+f"(d[35]), "+f"(d[36]), "+f"(d[37]), "+f"(d[38]), "+f"(d[39]), "+f"(d[40]), "+f"(d[41]), "+f"(d[42]), "+f"(d[43]), "+f"(d[44]), "+f"(d[45]), "+f"(d[46]), "+f"(d[47]), "+f"(d[48]), "+f"(d[49]), "+f"(d[50]), "+f"(d[51]), "+f"(d[52]), "+f"(d[53]), "+f"(d[54]), "+f"(d[55]), "+f"(d[56]), "+f"(d[57]), "+f"(d[58]), "+f"(d[59]), "+f"(d[60]), "+f"(d[61]), "+f"(d[62]), "+f"(d[63]), "+f"(d[64]), "+f"(d[65]), "+f"(d[66]), "+f"(d[67]), "+f"(d[68]), "+f"(d[69]), "+f"(d[70]), "+f"(d[71]), "+f"(d[72]), "+f"(d[73]), "+f"(d[74]), "+f"(d[75]), "+f"(d[76]), "+f"(d[77]), "+f"(d[78]), "+f"(d[79]), "+f"(d[80]), "+f"(d[81]), "+f"(d[82]), "+f"(d[83]), "+f"(d[84]), "+f"(d[85]), "+f"(d[86]), "+f"(d[87]), "+f"(d[88]), "+f"(d[89]), "+f"(d[90]), "+f"(d[91]), "+f"(d[92]), "+f"(d[93]), "+f"(d[94]), "+f"(d[95])
    : "r"(a0), "r"(a1), "r"(a2), "r"(a3), "l"(db), "r"(scale_d), "n"(TB));
}
template<int TB> __device__ __forceinline__ void wgmma_ss_n128(float (&d)[64], uint64_t da, uint64_t db, int scale_d) {
  asm volatile("{\n.reg .pred p;\nsetp.ne.b32 p, %66, 0;\n"
    "wgmma.mma_async.sync.aligned.m64n128k16.f32.bf16.bf16 {%0, %1, %2, %3, %4, %5, %6, %7, %8, %9, %10, %11, %12, %13, %14, %15, %16, %17, %18, %19, %20, %21, %22, %23, %24, %25, %26, %27, %28, %29, %30, %31, %32, %33, %34, %35, %36, %37, %38, %39, %40, %41, %42, %43, %44, %45, %46, %47, %48, %49, %50, %51, %52, %53, %54, %55, %56, %57, %58, %59, %60, %61, %62, %63}, %64, %65, p, 1, 1, 0, %67;\n}\n"
    : "+f"(d[0]), "+f"(d[1]), "+f"(d[2]), "+f"(d[3]), "+f"(d[4]), "+f"(d[5]), "+f"(d[6]), "+f"(d[7]), "+f"(d[8]), "+f"(d[9]), "+f"(d[10]), "+f"(d[11]), "+f"(d[12]), "+f"(d[13]), "+f"(d[14]), "+f"(d[15]), "+f"(d[16]), "+f"(d[17]), "+f"(d[18]), "+f"(d[19]), "+f"(d[20]), "+f"(d[21]), "+f"(d[22]), "+f"(d[23]), "+f"(d[24]), "+f"(d[25]), "+f"(d[26]), "+f"(d[27]), "+f"(d[28]), "+f"(d[29]), "+f"(d[30]), "+f"(d[31]), "+f"(d[32]), "+f"(d[33]), "+f"(d[34]), "+f"(d[35]), "+f"(d[36]), "+f"(d[37]), "+f"(d[38]), "+f"(d[39]), "+f"(d[40]), "+f"(d[41]), "+f"(d[42]), "+f"(d[43]), "+f"(d[44]), "+f"(d[45]), "+f"(d[46]), "+f"(d[47]), "+f"(d[48]), "+f"(d[49]), "+f"(d[50]), "+f"(d[51]), "+f"(d[52]), "+f"(d[53]), "+f"(d[54]), "+f"(d[55]), "+f"(d[56]), "+f"(d[57]), "+f"(d[58]), "+f"(d[59]), "+f"(d[60]), "+f"(d[61]), "+f"(d[62]), "+f"(d[63])
    : "l"(da), "l"(db), "r"(scale_d), "n"(TB));
}
template<int TB> __device__ __forceinline__ void wgmma_ss_n192(float (&d)[96], uint64_t da, uint64_t db, int scale_d) {
  asm volatile("{\n.reg .pred p;\nsetp.ne.b32 p, %98, 0;\n"
    "wgmma.mma_async.sync.aligned.m64n192k16.f32.bf16.bf16 {%0, %1, %2, %3, %4, %5, %6, %7, %8, %9, %10, %11, %12, %13, %14, %15, %16, %17, %18, %19, %20, %21, %22, %23, %24, %25, %26, %27, %28, %29, %30, %31, %32, %33, %34, %35, %36, %37, %38, %39, %40, %41, %42, %43, %44, %45, %46, %47, %48, %49, %50, %51, %52, %53, %54, %55, %56, %57, %58, %59, %60, %61, %62, %63, %64, %65, %66, %67, %68, %69, %70, %71, %72, %73, %74, %75, %76, %77, %78, %79, %80, %81, %82, %83, %84, %85, %86, %87, %88, %89, %90, %91, %92, %93, %94, %95}, %96, %97, p, 1, 1, 0, %99;\n}\n"
    : "+f"(d[0]), "+f"(d[1]), "+f"(d[2]), "+f"(d[3]), "+f"(d[4]), "+f"(d[5]), "+f"(d[6]), "+f"(d[7]), "+f"(d[8]), "+f"(d[9]), "+f"(d[10]), "+f"(d[11]), "+f"(d[12]), "+f"(d[13]), "+f"(d[14]), "+f"(d[15]), "+f"(d[16]), "+f"(d[17]), "+f"(d[18]), "+f"(d[19]), "+f"(d[20]), "+f"(d[21]), "+f"(d[22]), "+f"(d[23]), "+f"(d[24]), "+f"(d[25]), "+f"(d[26]), "+f"(d[27]), "+f"(d[28]), "+f"(d[29]), "+f"(d[30]), "+f"(d[31]), "+f"(d[32]), "+f"(d[33]), "+f"(d[34]), "+f"(d[35]), "+f"(d[36]), "+f"(d[37]), "+f"(d[38]), "+f"(d[39]), "+f"(d[40]), "+f"(d[41]), "+f"(d[42]), "+f"(d[43]), "+f"(d[44]), "+f"(d[45]), "+f"(d[46]), "+f"(d[47]), "+f"(d[48]), "+f"(d[49]), "+f"(d[50]), "+f"(d[51]), "+f"(d[52]), "+f"(d[53]), "+f"(d[54]), "+f"(d[55]), "+f"(d[56]), "+f"(d[57]), "+f"(d[58]), "+f"(d[59]), "+f"(d[60]), "+f"(d[61]), "+f"(d[62]), "+f"(d[63]), "+f"(d[64]), "+f"(d[65]), "+f"(d[66]), "+f"(d[67]), "+f"(d[68]), "+f"(d[69]), "+f"(d[70]), "+f"(d[71]), "+f"(d[72]), "+f"(d[73]), "+f"(d[74]), "+f"(d[75]), "+f"(d[76]), "+f"(d[77]), "+f"(d[78]), "+f"(d[79]), "+f"(d[80]), "+f"(d[81]), "+f"(d[82]), "+f"(d[83]), "+f"(d[84]), "+f"(d[85]), "+f"(d[86]), "+f"(d[87]), "+f"(d[88]), "+f"(d[89]), "+f"(d[90]), "+f"(d[91]), "+f"(d[92]), "+f"(d[93]), "+f"(d[94]), "+f"(d[95])
    : "l"(da), "l"(db), "r"(scale_d), "n"(TB));
}
template<int TB> __device__ __forceinline__ void wgmma_ss_n80(float (&d)[40], uint64_t da, uint64_t db, int scale_d) {
  asm volatile("{\n.reg .pred p;\nsetp.ne.b32 p, %42, 0;\n"
    "wgmma.mma_async.sync.aligned.m64n80k16.f32.bf16.bf16 {%0, %1, %2, %3, %4, %5, %6, %7, %8, %9, %10, %11, %12, %13, %14, %15, %16, %17, %18, %19, %20, %21, %22, %23, %24, %25, %26, %27, %28, %29, %30, %31, %32, %33, %34, %35, %36, %37, %38, %39}, %40, %41, p, 1, 1, 0, %43;\n}\n"
    : "+f"(d[0]), "+f"(d[1]), "+f"(d[2]), "+f"(d[3]), "+f"(d[4]), "+f"(d[5]), "+f"(d[6]), "+f"(d[7]), "+f"(d[8]), "+f"(d[9]), "+f"(d[10]), "+f"(d[11]), "+f"(d[12]), "+f"(d[13]), "+f"(d[14]), "+f"(d[15]), "+f"(d[16]), "+f"(d[17]), "+f"(d[18]), "+f"(d[19]), "+f"(d[20]), "+f"(d[21]), "+f"(d[22]), "+f"(d[23]), "+f"(d[24]), "+f"(d[25]), "+f"(d[26]), "+f"(d[27]), "+f"(d[28]), "+f"(d[29]), "+f"(d[30]), "+f"(d[31]), "+f"(d[32]), "+f"(d[33]), "+f"(d[34]), "+f"(d[35]), "+f"(d[36]), "+f"(d[37]), "+f"(d[38]), "+f"(d[39])
    : "l"(da), "l"(db), "r"(scale_d), "n"(TB));
}

__device__ float g_mod[6 * D_];
__device__ __align__(1024) bf16 g_h[S_ * D_];
__device__ __align__(1024) bf16 g_o[S_ * HD_];
__device__ __align__(1024) bf16 g_xch[16 * 2 * 4 * 4 * 128 * 80];
__device__ __align__(1024) bf16 g_w1t[D_ * D_];
__device__ __align__(1024) bf16 g_w2t[D_ * D_];
__device__ __align__(1024) bf16 g_w4t[D_ * F_];
__device__ __align__(32) float g_st1[S_ * 8];
__device__ __align__(32) float g_st2[S_ * 2];
__device__ __align__(32) float g_vec[3 * D_ + F_ + 8];
__device__ unsigned g_flag[1024];
enum { F_XCH = 0, F_XA = 256, F_US = 272, F_X1 = 288, F_G = 304, F_PREP = 320, F_O = 512 };
__device__ __align__(1024) bf16 g_xa[S_ * D_];
__device__ __align__(1024) bf16 g_us[(S_ + 4) * D_];
__device__ __align__(1024) bf16 g_x1[S_ * D_];
__device__ __align__(1024) bf16 g_g[S_ * F_];

__global__ void __launch_bounds__(256) mod_kernel(const bf16* __restrict__ c, const bf16* __restrict__ w_mod) {
  TL_ENTRY(0);
  pdl_launch();
  __shared__ float red[8][32];
  if (blockIdx.x < 14) { const int i = blockIdx.x * 256 + threadIdx.x; if (i < 3 * D_ + F_) g_vec[i] = 0.f; }
  else if (blockIdx.x < 18) g_flag[(blockIdx.x - 14) * 256 + threadIdx.x] = 0u;
  const int t = threadIdx.x, cg = t & 3, r0 = t >> 2;
  const int col0 = blockIdx.x * 32 + cg * 8;
  uint4 w[10];
#pragma unroll
  for (int i = 0; i < 10; i++) w[i] = __ldg(reinterpret_cast<const uint4*>(w_mod + (size_t)(r0 + 64 * i) * (6 * D_) + col0));
  float acc[8];
#pragma unroll
  for (int j = 0; j < 8; j++) acc[j] = 0.f;
#pragma unroll
  for (int i = 0; i < 10; i++) {
    float cv = __bfloat162float(c[r0 + 64 * i]);
    float s = bf_round(cv / (1.f + __expf(-cv)));
    acc[0] = fmaf(s, bf_lo(w[i].x), acc[0]); acc[1] = fmaf(s, bf_hi(w[i].x), acc[1]);
    acc[2] = fmaf(s, bf_lo(w[i].y), acc[2]); acc[3] = fmaf(s, bf_hi(w[i].y), acc[3]);
    acc[4] = fmaf(s, bf_lo(w[i].z), acc[4]); acc[5] = fmaf(s, bf_hi(w[i].z), acc[5]);
    acc[6] = fmaf(s, bf_lo(w[i].w), acc[6]); acc[7] = fmaf(s, bf_hi(w[i].w), acc[7]);
  }
#pragma unroll
  for (int j = 0; j < 8; j++) {
    acc[j] += __shfl_xor_sync(0xffffffffu, acc[j], 4);
    acc[j] += __shfl_xor_sync(0xffffffffu, acc[j], 8);
    acc[j] += __shfl_xor_sync(0xffffffffu, acc[j], 16);
  }
  if ((t & 31) < 4) {
#pragma unroll
    for (int j = 0; j < 8; j++) red[t >> 5][cg * 8 + j] = acc[j];
  }
  __syncthreads();
  if (t < 32) {
    float s = 0.f;
#pragma unroll
    for (int w8 = 0; w8 < 8; w8++) s += red[w8][t];
    const int col = blockIdx.x * 32 + t;
    s = bf_round(s);
    const int part = col / D_;
    if (part == 1 || part == 4) s = bf_round(1.f + s);
    g_mod[col] = s;
    if (t == 0) TL_END(0);
  }
}

__device__ __forceinline__ void row_stats(const float (&v)[20], float& mean, float& rstd) {
  float s = 0.f;
#pragma unroll
  for (int i = 0; i < 20; i++) s += v[i];
  mean = warp_sum(s) * (1.f / D_);
  float q = 0.f;
#pragma unroll
  for (int i = 0; i < 20; i++) { float d = v[i] - mean; q = fmaf(d, d, q); }
  rstd = rsqrtf(warp_sum(q) * (1.f / D_) + LN_EPS);
}
__device__ __forceinline__ void load_row_bf16(const bf16* p, int lane, float (&v)[20]) {
#pragma unroll
  for (int i = 0; i < 5; i++) {
    uint2 u = *reinterpret_cast<const uint2*>(p + (lane + 32 * i) * 4);
    v[4 * i] = bf_lo(u.x); v[4 * i + 1] = bf_hi(u.x); v[4 * i + 2] = bf_lo(u.y); v[4 * i + 3] = bf_hi(u.y);
  }
}
__device__ __forceinline__ void store_row_bf16(bf16* p, int lane, const float (&v)[20]) {
#pragma unroll
  for (int i = 0; i < 5; i++) {
    uint2 u; u.x = pack_bf16(v[4 * i], v[4 * i + 1]); u.y = pack_bf16(v[4 * i + 2], v[4 * i + 3]);
    *reinterpret_cast<uint2*>(p + (lane + 32 * i) * 4) = u;
  }
}
__device__ __forceinline__ void load_row_f32(const float* p, int lane, float (&v)[20]) {
#pragma unroll
  for (int i = 0; i < 5; i++) {
    float4 u = *reinterpret_cast<const float4*>(p + (lane + 32 * i) * 4);
    v[4 * i] = u.x; v[4 * i + 1] = u.y; v[4 * i + 2] = u.z; v[4 * i + 3] = u.w;
  }
}

__global__ void __launch_bounds__(256) ln1_kernel(const bf16* __restrict__ x) {
  TL_ENTRY(1);
  pdl_launch();
  const int lane = threadIdx.x & 31, row = blockIdx.x * 8 + (threadIdx.x >> 5);
  float v[20];
  load_row_bf16(x + (size_t)row * D_, lane, v);
  float mean, rstd;
  row_stats(v, mean, rstd);
  if (lane < 8) g_st1[row * 8 + lane] = 0.f;
  if (lane < 2) g_st2[row * 2 + lane] = 0.f;
  pdl_wait();
  if (threadIdx.x == 0) TL_WAITED(1);
  float sa[20], ca[20];
  load_row_f32(g_mod, lane, sa);
  load_row_f32(g_mod + D_, lane, ca);
#pragma unroll
  for (int i = 0; i < 20; i++) v[i] = fmaf((v[i] - mean) * rstd, ca[i], sa[i]);
  store_row_bf16(g_h + (size_t)row * D_, lane, v);
  if (threadIdx.x == 0) TL_END(1);
}

constexpr int PREP_JOBS = 200 + 200 + 480 + 480;
struct PrepW { const bf16 *w1, *w2, *w3, *w4; };
__device__ __forceinline__ void prep_warp(const PrepW& pw, bf16 (*tile)[72], int lane) {
#pragma unroll 1
  for (int job = blockIdx.x; job < PREP_JOBS; job += gridDim.x) {
    const bf16* src; bf16* dst; int ld = D_, ldd = D_, kt, nt, kind = 1;
    if (job < 200) { src = pw.w1; dst = g_w1t; kt = job / 10; nt = job % 10; kind = 0; }
    else if (job < 400) { src = pw.w2; dst = g_w2t; kt = (job - 200) / 10; nt = (job - 200) % 10; }
    else if (job < 880) { src = pw.w4; dst = g_w4t; ldd = F_; kt = (job - 400) / 10; nt = (job - 400) % 10; }
    else { src = pw.w3; dst = nullptr; ld = F_; kt = (job - 880) / 24; nt = (job - 880) % 24; kind = 2; }
    src += (size_t)(kt * 32 + (lane >> 3)) * ld + nt * 64 + (lane & 7) * 8;
    __syncwarp();
#pragma unroll
    for (int h = 0; h < 2; h++) {
      uint4 v[4];
#pragma unroll
      for (int i = 0; i < 4; i++) v[i] = __ldg(reinterpret_cast<const uint4*>(src + (size_t)(h * 16 + i * 4) * ld));
#pragma unroll
      for (int i = 0; i < 4; i++) *reinterpret_cast<uint4*>(&tile[h * 16 + i * 4 + (lane >> 3)][(lane & 7) * 8]) = v[i];
    }
    __syncwarp();
    const float* pa = g_mod + 4 * D_ + kt * 32;
    const float* pb = g_mod + 3 * D_ + kt * 32;
#pragma unroll 1
    for (int h = 0; h < 2; h++) {
      const int n = lane + 32 * h;
      float sa = 0.f, sb = 0.f, sc = 0.f;
#pragma unroll 1
      for (int c = 0; c < 4; c++) {
        uint32_t u[4];
#pragma unroll
        for (int e = 0; e < 4; e++) {
          const int k = c * 8 + 2 * e;
          float lo = __bfloat162float(tile[k][n]), hi = __bfloat162float(tile[k + 1][n]);
          sc += lo + hi;
          if (kind == 0) {
            const float2 a = __ldcg(reinterpret_cast<const float2*>(pa + k)), b = __ldcg(reinterpret_cast<const float2*>(pb + k));
            sb = fmaf(b.x, lo, fmaf(b.y, hi, sb));
            lo *= a.x; hi *= a.y;
          }
          u[e] = pack_bf16(lo, hi);
          sa += bf_lo(u[e]) + bf_hi(u[e]);
        }
        if (kind != 2) *reinterpret_cast<uint4*>(dst + (size_t)(nt * 64 + n) * ldd + kt * 32 + c * 8) = make_uint4(u[0], u[1], u[2], u[3]);
      }
      if (kind == 0) { atomicAdd(&g_vec[nt * 64 + n], sa); atomicAdd(&g_vec[D_ + nt * 64 + n], sb); atomicAdd(&g_vec[2 * D_ + nt * 64 + n], sc); }
      else if (kind == 2) atomicAdd(&g_vec[3 * D_ + nt * 64 + n], sc);
    }
  }
  __syncwarp();
  if (lane == 0) {
    asm volatile("fence.acq_rel.gpu;" ::: "memory");
    asm volatile("red.relaxed.gpu.global.add.u32 [%0], 1;" :: "l"(g_flag + F_PREP) : "memory");
  }
}

constexpr int A_NSLOT = 9;
constexpr int A_SLOT = 24576;
constexpr int A_NKV = S_ / 64;
constexpr int PREP_CTAS = 128;

struct Ring {
  uint32_t slot, phase;
  __device__ __forceinline__ void adv(int n) { if (++slot == (uint32_t)n) { slot = 0; phase ^= 1; } }
};
constexpr int T_PAR = A_NSLOT * A_SLOT + 384;
constexpr int T_PREP = T_PAR + 3712;
constexpr int T_SMEM = T_PREP + 32 * 72 * 2 + 1024;
enum { P_OGA = 0, P_OA = 80, P_OB = 160, P_VA = 240, P_VB = 320, P_VC = 400, P_A2 = 480, P_B2 = 560, P_GB = 640, P_CS3 = 720, P_SC = 912 };

__device__ __forceinline__ void flag_wait(const unsigned* p, unsigned target) {
  asm volatile(
      "{\n.reg .pred p;\n.reg .u32 n, v;\n"
      "mov.u32 n, 0;\n"
      "SPIN:\n"
      "ld.relaxed.gpu.global.u32 v, [%0];\n"
      "setp.ge.u32 p, v, %1;\n"
      "@p bra DONE;\n"
      "add.u32 n, n, 1;\n"
      "setp.gt.u32 p, n, 4194304;\n"
      "@p trap;\n"
      "bra SPIN;\n"
      "DONE:\n}\n" :: "l"(p), "r"(target) : "memory");
}
__device__ __forceinline__ void fence_async_global() { asm volatile("fence.proxy.async.global;" ::: "memory"); }
__device__ __forceinline__ float lds_f(uint32_t a) { float v; asm volatile("ld.shared.f32 %0, [%1];" : "=f"(v) : "r"(a)); return v; }
__device__ __forceinline__ float2 lds_f2(uint32_t a) { float2 v; asm volatile("ld.shared.v2.f32 {%0, %1}, [%2];" : "=f"(v.x), "=f"(v.y) : "r"(a)); return v; }
__device__ __forceinline__ uint4 ldcg4(const void* p) { return __ldcg(reinterpret_cast<const uint4*>(p)); }

__device__ __forceinline__ void sts_f2(uint32_t a, float x, float y) { asm volatile("st.shared.v2.f32 [%0], {%1, %2};" :: "r"(a), "f"(x), "f"(y) : "memory"); }
__device__ __forceinline__ void sts_u4(uint32_t a, uint4 v) { asm volatile("st.shared.v4.u32 [%0], {%1, %2, %3, %4};" :: "r"(a), "r"(v.x), "r"(v.y), "r"(v.z), "r"(v.w) : "memory"); }
__device__ __forceinline__ void sts_u1(uint32_t a, uint32_t v) { asm volatile("st.shared.u32 [%0], %1;" :: "r"(a), "r"(v) : "memory"); }
__device__ __forceinline__ void fence_async_smem() { asm volatile("fence.proxy.async.shared::cta;" ::: "memory"); }
__device__ __forceinline__ void bulk_store(void* dst, uint32_t src, uint32_t bytes) {
  asm volatile("cp.async.bulk.global.shared::cta.bulk_group [%0], [%1], %2;" :: "l"(dst), "r"(src), "r"(bytes) : "memory");
}
__device__ __forceinline__ void bulk_red_f32(void* dst, uint32_t src, uint32_t bytes) {
  asm volatile("cp.reduce.async.bulk.global.shared::cta.bulk_group.add.f32 [%0], [%1], %2;" :: "l"(dst), "r"(src), "r"(bytes) : "memory");
}
__device__ __forceinline__ void tma_store2d(const CUtensorMap* m, uint32_t src, int c0, int c1) {
  asm volatile("cp.async.bulk.tensor.2d.global.shared::cta.bulk_group [%0, {%2, %3}], [%1];" :: "l"(m), "r"(src), "r"(c0), "r"(c1) : "memory");
}
__device__ __forceinline__ void bulk_done() { asm volatile("cp.async.bulk.commit_group;\ncp.async.bulk.wait_group 0;" ::: "memory"); }
__device__ __forceinline__ void flag_add(unsigned* f) { asm volatile("red.relaxed.gpu.global.add.u32 [%0], 1;" :: "l"(f) : "memory"); }
__device__ __forceinline__ float4 lds_f4(uint32_t a) { return *reinterpret_cast<const float4*>(__cvta_shared_to_generic(a)); }
__device__ __forceinline__ uint4 lds_u4(uint32_t a) { return *reinterpret_cast<const uint4*>(__cvta_shared_to_generic(a)); }
__device__ __forceinline__ void lds8(uint32_t a, float (&v)[8]) {
  const float4 p = lds_f4(a), q = lds_f4(a + 16);
  v[0] = p.x; v[1] = p.y; v[2] = p.z; v[3] = p.w; v[4] = q.x; v[5] = q.y; v[6] = q.z; v[7] = q.w;
}
__device__ __forceinline__ void lds8_bf(uint32_t a, float (&v)[8]) {
  const uint4 u = lds_u4(a);
  v[0] = bf_lo(u.x); v[1] = bf_hi(u.x); v[2] = bf_lo(u.y); v[3] = bf_hi(u.y); v[4] = bf_lo(u.z); v[5] = bf_hi(u.z); v[6] = bf_lo(u.w); v[7] = bf_hi(u.w);
}
__device__ __forceinline__ uint4 pack8(const float (&v)[8]) {
  return make_uint4(pack_bf16(v[0], v[1]), pack_bf16(v[2], v[3]), pack_bf16(v[4], v[5]), pack_bf16(v[6], v[7]));
}
__device__ __forceinline__ void mbar_wait_c(uint32_t a, uint32_t ph) {
  asm volatile("{\n.reg .pred p;\nSPIN:\nmbarrier.try_wait.parity.shared::cta.b64 p, [%0], %1;\n@!p bra SPIN;\n}\n" :: "r"(a), "r"(ph) : "memory");
}
constexpr int ST_P = 80;
constexpr int E_TILE = 128 * 80 * 2;

struct Maps { CUtensorMap h, wq, k, v, o, wo3, wo2, xa, w1t, us, w2t, x1, w3, g, w4t, ex, exa, ex1, sxa, sus, sx1, sout; };
struct PfList { const uint8_t* p[6]; };

constexpr int M_AOFF = 102400, M_NA = 7;

__global__ void __cluster_dims__(2, 1, 1) __launch_bounds__(384, 1)
fused_kernel(const __grid_constant__ Maps tm, const __grid_constant__ PfList pf, const __grid_constant__ PrepW pw, const bf16* __restrict__ x, bf16* __restrict__ out) {
  extern __shared__ uint8_t smem_raw[];
  const uint32_t sb = (smem_u32(smem_raw) + 1023) & ~1023u;
  TL_ENTRY(2);
  const uint32_t bar_full = sb + A_NSLOT * A_SLOT;
  const uint32_t bar_empty = bar_full + 8 * A_NSLOT;
  const uint32_t bar_sig = bar_empty + 8 * A_NSLOT;
  const uint32_t mb_full = bar_sig + 16;
  const uint32_t mb_empty = mb_full + 96;
  const uint32_t par = sb + T_PAR;
  float* parf = reinterpret_cast<float*>(smem_raw + (par - smem_u32(smem_raw)));
  uint32_t rank;
  asm volatile("mov.u32 %0, %%cluster_ctarank;" : "=r"(rank));
  const int cid = blockIdx.x >> 1;
  const int wid = __shfl_sync(0xffffffffu, threadIdx.x >> 5, 0);
  const int wg = wid >> 2;
  const int qtile = (cid & 7) * 2 + rank, hbase = cid >> 3;
  const int o_qt = qtile, o_nh = (cid >> 3) & 1, o_ks = cid >> 4;
  const int o_col = o_nh * 320 + o_ks * 80;
  const int qt = cid >> 2, js = (cid & 3) * 2 + rank;
  if (threadIdx.x == 0) {
    for (int i = 0; i < A_NSLOT; i++) { mbar_init(bar_full + 8 * i, 1); mbar_init(bar_empty + 8 * i, 16); }
    mbar_init(bar_sig, 4); mbar_init(bar_sig + 8, 4);
    for (int i = 0; i < 12; i++) { mbar_init(mb_full + 8 * i, 1); mbar_init(mb_empty + 8 * i, i < 5 ? 8 : 16); }
    asm volatile("fence.mbarrier_init.release.cluster;" ::: "memory");
    prefetch_tmap(&tm.h); prefetch_tmap(&tm.wq); prefetch_tmap(&tm.k); prefetch_tmap(&tm.v);
  }
  __syncthreads();
  cluster_sync();

  if (wg == 0) {
    asm volatile("setmaxnreg.dec.sync.aligned.u32 40;");
    if (wid == 0) {
      Ring r{0, 1};
#define P_ACQ(bytes_) do { mbar_wait(bar_empty + 8 * r.slot, r.phase); mbar_expect_e(bar_full + 8 * r.slot, bytes_); } while (0)
#define P_DST (sb + r.slot * A_SLOT)
#define P_BAR (bar_full + 8 * r.slot)
      uint64_t pol_ef;
      asm volatile("createpolicy.fractional.L2::evict_first.b64 %0, 1.0;" : "=l"(pol_ef));
      pdl_wait();
      TL_WAITED(2);
#pragma unroll 1
      for (int item = 0; item < 4; item++) {
        const int head = hbase + 8 * item;
#pragma unroll 1
        for (int kb = 0; kb < 10; kb++) {
          P_ACQ(16384);
          tma2d(P_DST, &tm.h, P_BAR, kb * 64, qtile * 128);
          r.adv(A_NSLOT);
          P_ACQ(A_SLOT);
          if ((uint32_t)(kb & 1) == rank) tma3d_mc_hint(P_DST, &tm.wq, P_BAR, 0, kb * 64, head * 3, 3, pol_ef);
          r.adv(A_NSLOT);
        }
#pragma unroll 1
        for (int j = 0; j <= A_NKV; j++) {
          if (j < A_NKV) {
            P_ACQ(A_SLOT);
            if (rank == 0) tma3d_mc_hint(P_DST, &tm.k, P_BAR, 0, head * S_ + j * 64, 0, 3, pol_ef);
            r.adv(A_NSLOT);
          }
          if (j > 0) {
            P_ACQ(A_SLOT);
            if (rank == 1) tma3d_mc_hint(P_DST, &tm.v, P_BAR, 0, head * S_ + (j - 1) * 64, 0, 3, pol_ef);
            r.adv(A_NSLOT);
          }
          if (item == 3 && (j & 3) == 0) {
            const int c = (j >> 2) * 128 + blockIdx.x;
            if (c < 980) {
              const int li = c < 480 ? 0 : c < 600 ? 1 : c < 720 ? 2 : c < 880 ? 3 : c < 930 ? 4 : 5;
              const int c0 = c < 480 ? 0 : c < 600 ? 480 : c < 720 ? 600 : c < 880 ? 720 : c < 930 ? 880 : 930;
              l2_prefetch16k(pf.p[li] + (size_t)(c - c0) * 16384);
            }
          }
          if (item == 3) {
            if (j >= 6 && j < 24) {
              const int kb = j - 6;
              l2_prefetch_t2d(&tm.o, ((kb / 6) * 8 + 2 * o_ks + (kb % 6) / 3) * DH_ + (kb % 3) * 64, o_qt * 128);
            }
            if (j >= 24 && j < 30) flag_wait(g_flag + F_O + o_qt * 32 + ((j - 24) >> 1) * 8 + 2 * o_ks + (j & 1), 2);
            if (j == 0 && threadIdx.x == 0) {
              prefetch_tmap(&tm.o); prefetch_tmap(&tm.wo3); prefetch_tmap(&tm.wo2); prefetch_tmap(&tm.xa); prefetch_tmap(&tm.w1t); prefetch_tmap(&tm.us);
              prefetch_tmap(&tm.w2t); prefetch_tmap(&tm.x1); prefetch_tmap(&tm.w3); prefetch_tmap(&tm.g); prefetch_tmap(&tm.w4t);
              prefetch_tmap(&tm.ex); prefetch_tmap(&tm.exa); prefetch_tmap(&tm.ex1);
              prefetch_tmap(&tm.sxa); prefetch_tmap(&tm.sus); prefetch_tmap(&tm.sx1); prefetch_tmap(&tm.sout);
            }
          }
        }
      }
#pragma unroll 1
      for (int kb = 0; kb < 24; kb++) {
        const int head = (kb / 6) * 8 + 2 * o_ks + (kb % 6) / 3;
        const int kcol = head * DH_ + (kb % 3) * 64;
        P_ACQ(24576);
        if (rank == 0) tma3d_mc(P_DST, &tm.wo3, P_BAR, 0, kcol, o_nh * 5, 3);
        r.adv(A_NSLOT);
        P_ACQ(16384);
        if (rank == 1) tma3d_mc(P_DST, &tm.wo2, P_BAR, 0, kcol, o_nh * 5 + 3, 3);
        r.adv(A_NSLOT);
        if (kb == 18 || kb == 21) flag_wait(g_flag + F_O + o_qt * 32 + head, 2);
        if (kb % 3 == 0) fence_async_global();
        P_ACQ(16384);
        tma2d(P_DST, &tm.o, P_BAR, kcol, o_qt * 128);
        r.adv(A_NSLOT);
      }
      P_ACQ(E_TILE);
      tma2d(P_DST, &tm.ex, P_BAR, o_col, o_qt * 128);
      r.adv(A_NSLOT);
      flag_wait(g_flag + F_XCH + (o_qt * 2 + o_nh) * 4 + o_ks, 6);
      fence_async_global();
#pragma unroll 1
      for (int i = 0; i < 3; i++) {
        P_ACQ(E_TILE);
        bulk_load(P_DST, g_xch + (size_t)((((o_qt * 2 + o_nh) * 4 + o_ks) * 4) + ((o_ks + 1 + i) & 3)) * (E_TILE / 2), E_TILE, P_BAR);
        r.adv(A_NSLOT);
      }
      flag_wait(g_flag + F_PREP, PREP_CTAS);
      fence_async_global();
#pragma unroll 1
      for (int i = 0; i < A_NSLOT; i++) { mbar_wait(bar_empty + 8 * r.slot, r.phase); r.adv(A_NSLOT); }
      Ring ra{0, 1};
      uint32_t bpar = 0x1f;
#pragma unroll 1
      for (int ph = 0; ph < 4; ph++) {
        const CUtensorMap* ma = ph == 0 ? &tm.xa : ph == 1 ? &tm.us : ph == 2 ? &tm.x1 : &tm.g;
        const CUtensorMap* mb = ph == 0 ? &tm.w1t : ph == 1 ? &tm.w2t : ph == 2 ? &tm.w3 : &tm.w4t;
        const int nkb = ph == 3 ? 24 : 10;
        const int nbl = ph == 2 ? 10 : nkb / 2;
        const int nel = ph == 1 ? 1 : ph == 3 ? 2 : 0;
        const uint32_t nbs = ph == 2 ? 4 : 5, bsz = ph == 2 ? 24576 : 20480;
        int bl = 0; uint32_t bs = 0;
#pragma unroll 1
        for (int i = 0; i < 5; i++) mbar_wait(mb_empty + 8 * i, (bpar >> i) & 1);
#define T_LOADB() do { mbar_wait(mb_empty + 8 * bs, (bpar >> bs) & 1); bpar ^= 1u << bs; mbar_expect_e(mb_full + 8 * bs, bsz);    \
                       if (bl < nbl) tma3d(sb + bs * bsz, mb, mb_full + 8 * bs, 0, ph == 2 ? bl * 64 : js * 80, ph == 2 ? js * 3 : bl * 2); \
                       else tma2d(sb + bs * bsz, bl == nbl ? &tm.exa : &tm.ex1, mb_full + 8 * bs, js * 80, qt * 128); \
                       bl++; if (++bs == nbs) bs = 0; } while (0)
#pragma unroll 1
        for (uint32_t i = 0; i < nbs; i++) T_LOADB();
        TX(8 + ph * 4);
        const unsigned* fl = g_flag + F_XA + 16 * ph;
        flag_wait(fl + qt, 16);
        if (ph == 1) { if (qt > 0) flag_wait(fl + qt - 1, 16); if (qt < 15) flag_wait(fl + qt + 1, 16); }
        TX(9 + ph * 4);
        fence_async_global();
#pragma unroll 1
        for (int kb = 0; kb < nkb; kb++) {
          mbar_wait(mb_empty + 40 + 8 * ra.slot, ra.phase);
          mbar_expect_e(mb_full + 40 + 8 * ra.slot, 16384);
          tma2d_mc(sb + M_AOFF + ra.slot * 16384 + rank * 8192, ma, mb_full + 40 + 8 * ra.slot, kb * 64, qt * 128 + (int)rank * 64, 3);
          ra.adv(M_NA);
          while (bl < nbl + nel && (kb == nkb - 1 || kb >= (ph == 2 ? bl + 2 : 2 * bl - 3))) T_LOADB();
        }
      }
    } else if (wid < 3) {
      const int w = wid - 1, lane = threadIdx.x & 31;
#pragma unroll 1
      for (int sig = 0; sig < 4; sig++) {
        mbar_wait(bar_sig + 8 * w, sig & 1);
        if (lane == 0) {
          asm volatile("fence.acq_rel.gpu;" ::: "memory");
          flag_add(g_flag + F_O + qtile * 32 + hbase + 8 * sig);
        }
        __syncwarp();
      }
    } else {
      const int lane = threadIdx.x & 31;
      pdl_wait();
      prep_warp(pw, reinterpret_cast<bf16(*)[72]>(smem_raw + (sb + T_PREP - smem_u32(smem_raw))), lane);
      flag_wait(g_flag + F_PREP, PREP_CTAS);
#pragma unroll 1
      for (int i = lane; i < P_SC; i += 32) {
        const int v = i < P_CS3 ? i / 80 : 9, j = i - (i < P_CS3 ? v * 80 : P_CS3);
        const float* src = v == 0 ? g_mod + 2 * D_ + o_col : v == 1 ? g_mod + 4 * D_ + o_col : v == 2 ? g_mod + 3 * D_ + o_col
                         : v < 6 ? g_vec + (v - 3) * D_ + js * 80 : v == 6 ? g_mod + 4 * D_ + js * 80 : v == 7 ? g_mod + 3 * D_ + js * 80
                         : v == 8 ? g_mod + 5 * D_ + js * 80 : g_vec + 3 * D_ + js * 192;
        parf[i] = __ldcg(src + j);
      }
      float sv[5] = {0.f, 0.f, 0.f, 0.f, 0.f};
#pragma unroll 1
      for (int i = lane; i < D_; i += 32) {
        const float a = __ldcg(g_mod + 4 * D_ + i), b = __ldcg(g_mod + 3 * D_ + i);
        sv[0] += a; sv[1] = fmaf(a, a, sv[1]); sv[2] = fmaf(a, b, sv[2]); sv[3] += b; sv[4] = fmaf(b, b, sv[4]);
      }
#pragma unroll 1
      for (int o_ = 16; o_ > 0; o_ >>= 1) {
#pragma unroll
        for (int i = 0; i < 5; i++) sv[i] += __shfl_xor_sync(0xffffffffu, sv[i], o_);
      }
      if (lane == 0) {
#pragma unroll
        for (int i = 0; i < 5; i++) parf[P_SC + i] = sv[i];
      }
      bar_arrive(6, 288);
    }
    __syncwarp();
    cluster_sync();
  } else {
    asm volatile("setmaxnreg.inc.sync.aligned.u32 232;");
    const int w = wg - 1;
    const int lane = threadIdx.x & 31;
    const int warp = wid & 3;
    const int tid = threadIdx.x - 128;
    const uint32_t rel_base = mapa(bar_empty, (lane == 0) ? rank : (rank ^ 1));
    Ring r{0, 0};
#define A_RELEASE(slot_) do { if (lane < 2) mbar_arrive_remote(rel_base + 8 * (slot_)); } while (0)
#define SIGNAL() do { __syncwarp(); if (lane == 0) mbar_arrive(bar_sig + 8 * w); } while (0)
    {
    const float SC = 0.07216878364870322f * 1.4426950408889634f;
    float o[96];
    uint32_t q[48];
    float s[32];
    uint32_t p[16], p2[16];
    if (w == 1) bar_arrive(1, 256);
    float i0 = 0.f, i1 = 0.f;
    bf16* orow = g_o + (size_t)(qtile * 128 + w * 64 + warp * 16 + (lane >> 2)) * HD_ + (hbase - 8) * DH_ + (lane & 3) * 8;
#define O_STORE(g)                                                                                                     \
      {                                                                                                                \
        uint32_t u0 = pack_bf16(o[16 * g + 0] * i0, o[16 * g + 1] * i0), u1 = pack_bf16(o[16 * g + 4] * i0, o[16 * g + 5] * i0);     \
        uint32_t u2 = pack_bf16(o[16 * g + 8] * i0, o[16 * g + 9] * i0), u3 = pack_bf16(o[16 * g + 12] * i0, o[16 * g + 13] * i0);   \
        quad_transpose(u0, u1, u2, u3, lane);                                                                          \
        stg128(orow + g * 32, make_uint4(u0, u1, u2, u3));                                                             \
        uint32_t v0 = pack_bf16(o[16 * g + 2] * i1, o[16 * g + 3] * i1), v1 = pack_bf16(o[16 * g + 6] * i1, o[16 * g + 7] * i1);     \
        uint32_t v2 = pack_bf16(o[16 * g + 10] * i1, o[16 * g + 11] * i1), v3 = pack_bf16(o[16 * g + 14] * i1, o[16 * g + 15] * i1); \
        quad_transpose(v0, v1, v2, v3, lane);                                                                          \
        stg128(orow + (size_t)8 * HD_ + g * 32, make_uint4(v0, v1, v2, v3));                                           \
      }
#pragma unroll 1
    for (int item = 0; item < 4; item++) {
      TSA(item, 0);
      {
        float qa[96];
        uint32_t prevA = 0, prevB = 0;
#pragma unroll
        for (int kb = 0; kb < 10; kb++) {
          const uint32_t sA = r.slot; mbar_wait_c(bar_full + 8 * sA, r.phase); r.adv(A_NSLOT);
          const uint32_t sB = r.slot; mbar_wait_c(bar_full + 8 * sB, r.phase); r.adv(A_NSLOT);
          const uint64_t da = mkdesc(sb + sA * A_SLOT + w * 8192, 16, 1024);
          const uint64_t db = mkdesc(sb + sB * A_SLOT, 8192, 1024);
          wg_fence();
#pragma unroll
          for (int kk = 0; kk < 4; kk++) wgmma_ss_n192<1>(qa, da + kk * 2, db + kk * 128, (kb | kk) != 0);
          wg_commit();
          if (kb < 6 && item > 0) { O_STORE((kb < 6 ? kb : 0)) }
          if (kb == 6 && item > 0) SIGNAL();
          if (kb > 0) { wg_wait<1>(); A_RELEASE(prevA); A_RELEASE(prevB); }
          prevA = sA; prevB = sB;
        }
        wg_wait<0>();
        fence_regs(qa);
        A_RELEASE(prevA); A_RELEASE(prevB);
#pragma unroll
        for (int i = 0; i < 48; i++) q[i] = pack_bf16(qa[2 * i], qa[2 * i + 1]);
      }
      orow += 8 * DH_;

      TSA(item, 1);
      float c0, c1, l0, l1;
      {
        const uint32_t sK = r.slot; mbar_wait_c(bar_full + 8 * sK, r.phase); r.adv(A_NSLOT);
        const uint64_t dk = mkdesc(sb + sK * A_SLOT, 16, 1024);
        bar_sync(1 + w, 256);
        wg_fence();
#pragma unroll
        for (int kk = 0; kk < 12; kk++)
          wgmma_rs_n64<0>(s, q[4 * kk], q[4 * kk + 1], q[4 * kk + 2], q[4 * kk + 3], dk + (kk >> 2) * 512 + (kk & 3) * 2, kk != 0);
        wg_commit();
        bar_arrive(1 + (w ^ 1), 256);
        wg_wait<0>();
        fence_regs(s);
        A_RELEASE(sK);
        float mx0 = fmaxf(s[0], s[1]), mx1 = fmaxf(s[2], s[3]);
#pragma unroll
        for (int i = 1; i < 8; i++) { mx0 = fmaxf(mx0, fmaxf(s[4 * i], s[4 * i + 1])); mx1 = fmaxf(mx1, fmaxf(s[4 * i + 2], s[4 * i + 3])); }
        mx0 = fmaxf(mx0, __shfl_xor_sync(0xffffffffu, mx0, 1)); mx1 = fmaxf(mx1, __shfl_xor_sync(0xffffffffu, mx1, 1));
        mx0 = fmaxf(mx0, __shfl_xor_sync(0xffffffffu, mx0, 2)); mx1 = fmaxf(mx1, __shfl_xor_sync(0xffffffffu, mx1, 2));
        c0 = mx0 * SC; c1 = mx1 * SC;
        l0 = 0.f; l1 = 0.f;
#pragma unroll
        for (int i = 0; i < 8; i++) {
          s[4 * i] = ex2(fmaf(s[4 * i], SC, -c0)); s[4 * i + 1] = ex2(fmaf(s[4 * i + 1], SC, -c0));
          s[4 * i + 2] = ex2(fmaf(s[4 * i + 2], SC, -c1)); s[4 * i + 3] = ex2(fmaf(s[4 * i + 3], SC, -c1));
          l0 += s[4 * i] + s[4 * i + 1]; l1 += s[4 * i + 2] + s[4 * i + 3];
        }
#pragma unroll
        for (int i = 0; i < 16; i++) p[i] = pack_bf16(s[2 * i], s[2 * i + 1]);
      }
      TSA(item, 2);
      uint32_t okn;
      {
        Ring r2 = r; r2.adv(A_NSLOT);
        okn = mbar_try(bar_full + 8 * r.slot, r.phase) & mbar_try(bar_full + 8 * r2.slot, r2.phase);
      }
#define A_STEP(PC, PN, FIRST)                                                                                          \
      {                                                                                                                \
        const uint32_t sK = r.slot, phK = r.phase; r.adv(A_NSLOT);                                                     \
        const uint32_t sV = r.slot, phV = r.phase; r.adv(A_NSLOT);                                                     \
        const uint64_t dk = mkdesc(sb + sK * A_SLOT, 16, 1024);                                                        \
        const uint64_t dv = mkdesc(sb + sV * A_SLOT, 8192, 1024);                                                      \
        if (!okn) { mbar_wait_c(bar_full + 8 * sK, phK); mbar_wait_c(bar_full + 8 * sV, phV); }                            \
        bar_sync(1 + w, 256);                                                                                          \
        wg_fence();                                                                                                    \
        _Pragma("unroll") for (int kk = 0; kk < 12; kk++)                                                              \
          wgmma_rs_n64<0>(s, q[4 * kk], q[4 * kk + 1], q[4 * kk + 2], q[4 * kk + 3], dk + (kk >> 2) * 512 + (kk & 3) * 2, kk != 0); \
        wg_commit();                                                                                                   \
        _Pragma("unroll") for (int kk = 0; kk < 4; kk++)                                                               \
          wgmma_rs_n192<1>(o, PC[4 * kk], PC[4 * kk + 1], PC[4 * kk + 2], PC[4 * kk + 3], dv + kk * 128, !(FIRST) || (kk != 0)); \
        wg_commit();                                                                                                   \
        bar_arrive(1 + (w ^ 1), 256);                                                                                  \
        {                                                                                                              \
          Ring r2 = r; r2.adv(A_NSLOT);                                                                                \
          okn = mbar_try(bar_full + 8 * r.slot, r.phase) & mbar_try(bar_full + 8 * r2.slot, r2.phase);                 \
        }                                                                                                              \
        wg_wait<1>();                                                                                                  \
        fence_regs(s);                                                                                                 \
        A_RELEASE(sK);                                                                                                 \
        float b0 = 0.f, b1 = 0.f;                                                                                      \
        _Pragma("unroll") for (int i = 0; i < 8; i++) {                                                                \
          const float e0 = ex2(fmaf(s[4 * i], SC, -c0)), e1 = ex2(fmaf(s[4 * i + 1], SC, -c0));                        \
          const float e2 = ex2(fmaf(s[4 * i + 2], SC, -c1)), e3 = ex2(fmaf(s[4 * i + 3], SC, -c1));                    \
          b0 += e0 + e1; b1 += e2 + e3;                                                                                \
          PN[2 * i] = pack_bf16(e0, e1); PN[2 * i + 1] = pack_bf16(e2, e3);                                            \
        }                                                                                                              \
        wg_wait<0>();                                                                                                  \
        fence_regs(o);                                                                                                 \
        fence_regs(PC);                                                                                                \
        A_RELEASE(sV);                                                                                                 \
        if (__any_sync(0xffffffffu, !(b0 <= 65536.f) || !(b1 <= 65536.f))) {                                           \
          float mx0 = fmaxf(s[0], s[1]), mx1 = fmaxf(s[2], s[3]);                                                      \
          _Pragma("unroll") for (int i = 1; i < 8; i++) {                                                              \
            mx0 = fmaxf(mx0, fmaxf(s[4 * i], s[4 * i + 1])); mx1 = fmaxf(mx1, fmaxf(s[4 * i + 2], s[4 * i + 3]));     \
          }                                                                                                            \
          mx0 = fmaxf(mx0, __shfl_xor_sync(0xffffffffu, mx0, 1)); mx1 = fmaxf(mx1, __shfl_xor_sync(0xffffffffu, mx1, 1)); \
          mx0 = fmaxf(mx0, __shfl_xor_sync(0xffffffffu, mx0, 2)); mx1 = fmaxf(mx1, __shfl_xor_sync(0xffffffffu, mx1, 2)); \
          const float n0 = fmaxf(c0, mx0 * SC), n1 = fmaxf(c1, mx1 * SC);                                              \
          const float a0 = ex2(c0 - n0), a1 = ex2(c1 - n1);                                                            \
          c0 = n0; c1 = n1;                                                                                            \
          l0 *= a0; l1 *= a1;                                                                                          \
          _Pragma("unroll") for (int i = 0; i < 24; i++) { o[4 * i] *= a0; o[4 * i + 1] *= a0; o[4 * i + 2] *= a1; o[4 * i + 3] *= a1; } \
          b0 = 0.f; b1 = 0.f;                                                                                          \
          _Pragma("unroll") for (int i = 0; i < 8; i++) {                                                              \
            const float e0 = ex2(fmaf(s[4 * i], SC, -c0)), e1 = ex2(fmaf(s[4 * i + 1], SC, -c0));                      \
            const float e2 = ex2(fmaf(s[4 * i + 2], SC, -c1)), e3 = ex2(fmaf(s[4 * i + 3], SC, -c1));                  \
            b0 += e0 + e1; b1 += e2 + e3;                                                                              \
            PN[2 * i] = pack_bf16(e0, e1); PN[2 * i + 1] = pack_bf16(e2, e3);                                          \
          }                                                                                                            \
        }                                                                                                              \
        l0 += b0; l1 += b1;                                                                                            \
      }
      for (int jj = 0; jj < 15; jj++) {
        A_STEP(p, p2, jj == 0)
        A_STEP(p2, p, false)
      }
      A_STEP(p, p2, false)
      TSA(item, 3);
      {
        const uint32_t sV = r.slot; mbar_wait_c(bar_full + 8 * sV, r.phase); r.adv(A_NSLOT);
        const uint64_t dv = mkdesc(sb + sV * A_SLOT, 8192, 1024);
        bar_sync(1 + w, 256);
        wg_fence();
#pragma unroll
        for (int kk = 0; kk < 4; kk++)
          wgmma_rs_n192<1>(o, p2[4 * kk], p2[4 * kk + 1], p2[4 * kk + 2], p2[4 * kk + 3], dv + kk * 128, 1);
        wg_commit();
        bar_arrive(1 + (w ^ 1), 256);
        wg_wait<0>();
        fence_regs(o);
        A_RELEASE(sV);
      }
      TSA(item, 4);
      l0 += __shfl_xor_sync(0xffffffffu, l0, 1); l1 += __shfl_xor_sync(0xffffffffu, l1, 1);
      l0 += __shfl_xor_sync(0xffffffffu, l0, 2); l1 += __shfl_xor_sync(0xffffffffu, l1, 2);
      i0 = __fdividef(1.f, l0); i1 = __fdividef(1.f, l1);
      TSA(item, 5);
    }
#pragma unroll
    for (int g = 0; g < 6; g++) { O_STORE(g) }
    SIGNAL();
    }
    TS(3, 2);
    const uint32_t st_w = (uint32_t)((warp * 16 + (lane >> 2)) * ST_P + (lane & 3) * 2) * 4;
    const uint32_t st_x = (lane & 8) << 2;
    const int er = (tid & 127) >> 1, eh = tid & 1;
    const uint32_t st_r = (uint32_t)(er * ST_P + (eh ^ ((er >> 1) & 1)) * 8) * 4;
    const uint32_t e_r = (uint32_t)((w * 64 + er) * 160 + eh * 16);
    const uint32_t p_r = par + eh * 32;
    const uint32_t stat = sb + T_PREP + w * 2048;
    const bool leader = (tid & 127) == 0;
#define STAGE10(ACC, BASE)                                                                                             \
    _Pragma("unroll") for (int nb = 0; nb < 10; nb++) {                                                                \
      sts_f2(stg + st_w + ((nb * 32) ^ st_x), ACC(BASE + 4 * nb), ACC(BASE + 4 * nb + 1));                                       \
      sts_f2(stg + st_w + ((nb * 32) ^ st_x) + 8 * ST_P * 4, ACC(BASE + 4 * nb + 2), ACC(BASE + 4 * nb + 3));                    \
    }

    {
      float acc1[96], acc2[64];
      uint32_t p0 = 0, p1 = 0, p2 = 0;
#pragma unroll 1
      for (int kb = 0; kb < 24; kb++) {
        const uint32_t s1 = r.slot; mbar_wait_c(bar_full + 8 * s1, r.phase); r.adv(A_NSLOT);
        const uint32_t s2 = r.slot; mbar_wait_c(bar_full + 8 * s2, r.phase); r.adv(A_NSLOT);
        const uint32_t sa = r.slot; mbar_wait_c(bar_full + 8 * sa, r.phase); r.adv(A_NSLOT);
        const uint64_t da = mkdesc(sb + sa * A_SLOT + w * 8192, 16, 1024);
        const uint64_t d1 = mkdesc(sb + s1 * A_SLOT, 8192, 1024), d2 = mkdesc(sb + s2 * A_SLOT, 8192, 1024);
        wg_fence();
#pragma unroll
        for (int kk = 0; kk < 4; kk++) {
          wgmma_ss_n192<1>(acc1, da + kk * 2, d1 + kk * 128, (kb | kk) != 0);
          wgmma_ss_n128<1>(acc2, da + kk * 2, d2 + kk * 128, (kb | kk) != 0);
        }
        wg_commit();
        if (kb > 0) { wg_wait<1>(); A_RELEASE(p0); A_RELEASE(p1); A_RELEASE(p2); }
        p0 = s1; p1 = s2; p2 = sa;
      }
      wg_wait<0>();
      fence_regs(acc1); fence_regs(acc2);
      A_RELEASE(p2);
      bar_sync(6, 288);
      TS(0, 0);
      const uint32_t stg = sb + (w ? p1 : p0) * A_SLOT;
#define OACC(e) (((e) < 96) ? acc1[(e) < 96 ? (e) : 0] : acc2[(e) >= 96 ? (e) - 96 : 0])
#define PACK10(BASE)                                                                                                   \
      _Pragma("unroll") for (int nb = 0; nb < 10; nb++) {                                                              \
        sts_u1(xo + nb * 16, pack_bf16(OACC(BASE + 4 * nb), OACC(BASE + 4 * nb + 1)));                                 \
        sts_u1(xo + nb * 16 + 8 * 160, pack_bf16(OACC(BASE + 4 * nb + 2), OACC(BASE + 4 * nb + 3)));                   \
      }
      const uint32_t f1 = r.slot + 4 >= A_NSLOT ? r.slot + 4 - A_NSLOT : r.slot + 4, f2 = f1 + 1 >= A_NSLOT ? 0 : f1 + 1;
#pragma unroll
      for (int d = 0; d < 4; d++) {
        if (d != o_ks) {
          const int i = (d - o_ks - 1) & 3;
          const uint32_t xo = sb + (i == 0 ? p2 : i == 1 ? f1 : f2) * A_SLOT + (w * 64 + warp * 16 + (lane >> 2)) * 160 + (lane & 3) * 4;
          PACK10(d * 40)
        }
      }
      fence_async_smem();
      bar_sync(3 + w, 128);
      if (leader) {
#pragma unroll 1
        for (int i = 0; i < 3; i++)
          bulk_store(g_xch + (size_t)((((o_qt * 2 + o_nh) * 4 + ((o_ks + 1 + i) & 3)) * 4) + o_ks) * (E_TILE / 2) + w * (E_TILE / 4),
                     sb + (i == 0 ? p2 : i == 1 ? f1 : f2) * A_SLOT + w * (E_TILE / 2), E_TILE / 2);
        bulk_done();
#pragma unroll 1
        for (int i = 0; i < 3; i++) flag_add(g_flag + F_XCH + (o_qt * 2 + o_nh) * 4 + ((o_ks + 1 + i) & 3));
        TX(40 + w);
      }
      if (o_ks == 0) { STAGE10(OACC, 0) } else if (o_ks == 1) { STAGE10(OACC, 40) } else if (o_ks == 2) { STAGE10(OACC, 80) } else { STAGE10(OACC, 120) }
      bar_sync(3 + w, 128);
      const uint32_t sx = r.slot; mbar_wait_c(bar_full + 8 * sx, r.phase); r.adv(A_NSLOT);
      const uint32_t q0 = r.slot; mbar_wait_c(bar_full + 8 * q0, r.phase); r.adv(A_NSLOT);
      const uint32_t q1 = r.slot; mbar_wait_c(bar_full + 8 * q1, r.phase); r.adv(A_NSLOT);
      const uint32_t q2 = r.slot; mbar_wait_c(bar_full + 8 * q2, r.phase); r.adv(A_NSLOT);
      TS(0, 1);
      float st[6] = {0.f, 0.f, 0.f, 0.f, 0.f, 0.f};
      const uint32_t ot = sb + p2 * A_SLOT;
#pragma unroll 1
      for (int c = 0; c < 5; c++) {
        float v[8], t0[8], t1[8], t2[8], xv[8], pg[8], pa_[8], pb_[8];
        lds8(stg + st_r + c * 64, v);
        lds8_bf(sb + q0 * A_SLOT + e_r + c * 32, t0); lds8_bf(sb + q1 * A_SLOT + e_r + c * 32, t1); lds8_bf(sb + q2 * A_SLOT + e_r + c * 32, t2);
        lds8_bf(sb + sx * A_SLOT + e_r + c * 32, xv);
        lds8(p_r + P_OGA * 4 + c * 64, pg); lds8(p_r + P_OA * 4 + c * 64, pa_); lds8(p_r + P_OB * 4 + c * 64, pb_);
#pragma unroll
        for (int e = 0; e < 8; e++) v[e] = fmaf(pg[e], v[e] + ((t0[e] + t1[e]) + t2[e]), xv[e]);
        const uint4 pk = pack8(v);
        sts_u4(ot + e_r + c * 32, pk);
        v[0] = bf_lo(pk.x); v[1] = bf_hi(pk.x); v[2] = bf_lo(pk.y); v[3] = bf_hi(pk.y); v[4] = bf_lo(pk.z); v[5] = bf_hi(pk.z); v[6] = bf_lo(pk.w); v[7] = bf_hi(pk.w);
#pragma unroll
        for (int e = 0; e < 8; e++) {
          const float y = pa_[e] * v[e];
          st[0] += v[e]; st[1] = fmaf(v[e], v[e], st[1]); st[2] += y; st[3] = fmaf(pa_[e], y, st[3]); st[4] = fmaf(y, y, st[4]); st[5] = fmaf(pb_[e], y, st[5]);
        }
      }
#pragma unroll
      for (int i = 0; i < 6; i++) st[i] += __shfl_xor_sync(0xffffffffu, st[i], 1);
      sts_u4(stat + er * 32 + eh * 16, eh ? make_uint4(__float_as_uint(st[4]), __float_as_uint(st[5]), 0u, 0u)
                                          : make_uint4(__float_as_uint(st[0]), __float_as_uint(st[1]), __float_as_uint(st[2]), __float_as_uint(st[3])));
      fence_async_smem();
      bar_sync(3 + w, 128);
      if (leader) {
        tma_store2d(&tm.sxa, ot + w * (E_TILE / 2), o_col, o_qt * 128 + w * 64);
        bulk_red_f32(g_st1 + (size_t)(o_qt * 128 + w * 64) * 8, stat, 2048);
        bulk_done();
        flag_add(g_flag + F_XA + o_qt);
      }
      bar_sync(5, 256);
      A_RELEASE(p0); A_RELEASE(p1); A_RELEASE(sx); A_RELEASE(q0); A_RELEASE(q1); A_RELEASE(q2);
      TS(0, 2);
    }

    Ring ra{0, 0};
    uint32_t bpar = 0;
    const uint32_t rel_a = mapa(mb_empty + 40, (lane == 0) ? rank : (rank ^ 1));
#define B_NEXT(s_) do { s_ = bs; mbar_wait_c(mb_full + 8 * bs, (bpar >> bs) & 1); bpar ^= 1u << bs; if (++bs == nbs) bs = 0; } while (0)
#define A_NEXT(s_) do { s_ = ra.slot; mbar_wait_c(mb_full + 40 + 8 * s_, ra.phase); ra.adv(M_NA); } while (0)
#define B_RELEASE(s_) do { if (lane == 0) mbar_arrive(mb_empty + 8 * (s_)); } while (0)
#define MA_RELEASE(s_) do { if (lane < 2) mbar_arrive_remote(rel_a + 8 * (s_)); } while (0)
    const int grow = qt * 128 + w * 64 + er;
    float mu = 0.f, rs = 0.f;
#pragma unroll 1
    for (int ph = 0; ph < 4; ph++) {
      float acc[96];
      float (&acc80)[40] = *reinterpret_cast<float(*)[40]>(&acc[0]);
      uint32_t pa = 0, pa2 = 0, pb = 0;
      float4 s03 = make_float4(0.f, 0.f, 0.f, 0.f);
      float2 s45 = make_float2(0.f, 0.f);
      const int nit = ph == 3 ? 12 : ph == 2 ? 10 : 5;
      const uint32_t nbs = ph == 2 ? 4 : 5, bsz = ph == 2 ? 24576 : 20480;
      uint32_t bs = 0;
#pragma unroll 1
      for (int it = 0; it < nit; it++) {
        uint32_t sbq, sa, sa2;
        B_NEXT(sbq);
        A_NEXT(sa);
        if (it == 0) TXC(ph);
        const uint64_t da = mkdesc(sb + M_AOFF + sa * 16384 + w * 8192, 16, 1024);
        if (ph == 2) {
          sa2 = sa;
          const uint64_t db = mkdesc(sb + sbq * 24576, 8192, 1024);
          wg_fence();
#pragma unroll
          for (int kk = 0; kk < 4; kk++) wgmma_ss_n192<1>(acc, da + kk * 2, db + kk * 128, (it | kk) != 0);
          wg_commit();
        } else {
          A_NEXT(sa2);
          const uint64_t da2 = mkdesc(sb + M_AOFF + sa2 * 16384 + w * 8192, 16, 1024);
          const uint64_t db = mkdesc(sb + sbq * 20480, 16, 1024);
          wg_fence();
#pragma unroll
          for (int kk = 0; kk < 4; kk++) wgmma_ss_n80<0>(acc80, da + kk * 2, db + kk * 2, (it | kk) != 0);
#pragma unroll
          for (int kk = 0; kk < 4; kk++) wgmma_ss_n80<0>(acc80, da2 + kk * 2, db + 640 + kk * 2, 1);
          wg_commit();
        }
        if (it > 0) { wg_wait<1>(); MA_RELEASE(pa); if (ph != 2) MA_RELEASE(pa2); B_RELEASE(pb); }
        else {
          if (ph == 0) { s03 = __ldcg(reinterpret_cast<const float4*>(g_st1 + (size_t)grow * 8)); s45 = __ldcg(reinterpret_cast<const float2*>(g_st1 + (size_t)grow * 8 + 4)); }
          if (ph == 2) s45 = __ldcg(reinterpret_cast<const float2*>(g_st2 + (size_t)grow * 2));
        }
        pa = sa; pa2 = sa2; pb = sbq;
      }
      wg_wait<0>();
      fence_regs(acc);
      MA_RELEASE(pa); if (ph != 2) MA_RELEASE(pa2);
      bar_sync(5, 256);
      TS(1 + (ph == 3 ? 0 : ph), ph == 3 ? 2 : 0);
      const uint32_t pb1 = pb == 0 ? nbs - 1 : pb - 1, pb2 = pb1 == 0 ? nbs - 1 : pb1 - 1, pb3 = pb2 == 0 ? nbs - 1 : pb2 - 1;
      const uint32_t stg = sb + (w ? pb : pb1) * bsz;
      uint32_t e1 = 0;
#define MACC(e) acc[e]
      if (!(ph & 1)) {
        float c0, c1, c2 = 0.f, c3 = 0.f;
        if (ph == 0) {
          const float4 sc = lds_f4(par + P_SC * 4);
          const float sbb = lds_f(par + (P_SC + 4) * 4);
          mu = s03.x * (1.f / D_);
          rs = rsqrtf(fmaxf(s03.y * (1.f / D_) - mu * mu, 0.f) + LN_EPS);
          const float m2 = (rs * (s03.z - mu * sc.x) + sc.w) * (1.f / D_);
          const float e2 = (rs * rs * (s45.x - 2.f * mu * s03.w + mu * mu * sc.y) + 2.f * rs * (s45.y - mu * sc.z) + sbb) * (1.f / D_);
          c2 = rsqrtf(fmaxf(e2 - m2 * m2, 0.f) + LN_EPS);
          c0 = c2 * rs; c1 = -c0 * mu; c3 = -c2 * m2;
          if (tid < 20) sts_u4(stat + 2048 * 2 + tid * 16, make_uint4(0, 0, 0, 0));
        } else {
          const float m = s45.x * (1.f / D_);
          c0 = rsqrtf(fmaxf(s45.y * (1.f / D_) - m * m, 0.f) + LN_EPS);
          c1 = -c0 * m;
        }
        const int npass = ph == 0 ? 1 : 3, nch = ph == 0 ? 5 : 4;
        const uint32_t ot = ph == 0 ? sb + pb2 * bsz + w * (E_TILE / 2) : sb + (w ? pb2 : pb3) * bsz;
#pragma unroll 1
        for (int ps = 0; ps < npass; ps++) {
          if (ps == 0) { STAGE10(MACC, 0) } else if (ps == 1) { STAGE10(MACC, 32) } else { STAGE10(MACC, 56) }
          bar_sync(3 + w, 128);
          const uint32_t cofs = ps == 2 ? 64 : 0;
          const uint32_t pp = p_r + (ph == 0 ? P_VA : P_CS3 + ps * 64) * 4, pq = p_r + P_VB * 4;
#pragma unroll 1
          for (int c = 0; c < nch; c++) {
            float v[8], t[8], t2[8], t3[8];
            lds8(stg + st_r + cofs + c * 64, v);
            lds8(pp + c * 64, t);
            if (ph == 0) {
              lds8(pq + c * 64, t2); lds8(pq + 320 + c * 64, t3);
#pragma unroll
              for (int e = 0; e < 8; e++) t[e] = fmaf(c1, t[e], fmaf(c2, t2[e], c3 * t3[e]));
            } else {
#pragma unroll
              for (int e = 0; e < 8; e++) t[e] *= c1;
            }
#pragma unroll
            for (int e = 0; e < 8; e++) v[e] = gelu_tanh(fmaf(c0, v[e], t[e]));
            sts_u4(ot + (ph == 0 ? er * 160 + eh * 16 + c * 32 : ps * 8192 + er * 128 + (((2 * c + eh) ^ (er & 7)) << 4)), pack8(v));
          }
          fence_async_smem();
          bar_sync(3 + w, 128);
          if (leader) {
            if (ph == 0) {
              const int grp = js >> 1;
              const int sh = (grp & 2 ? 2 : 1) * (grp & 1 ? -1 : 1);
              tma_store2d(&tm.sus, ot, js * 80, qt * 128 + w * 64 + sh + 2);
              if (w == 0 && qt == (sh > 0 ? 0 : 15)) {
                const int r0 = sh > 0 ? 0 : S_ + sh, n = sh > 0 ? sh : -sh;
                for (int i = 0; i < n; i++) bulk_store(g_us + (size_t)(r0 + i + 2) * D_ + js * 80, stat + 2048 * 2, 160);
              }
            } else {
              tma_store2d(&tm.g, ot + ps * 8192, js * 192 + ps * 64, qt * 128 + w * 64);
            }
          }
        }
      } else {
        STAGE10(MACC, 0)
        uint32_t e2;
        B_NEXT(e1);
        e2 = e1;
        if (ph == 3) B_NEXT(e2);
        bar_sync(3 + w, 128);
        float s1 = 0.f, s2 = 0.f;
        const uint32_t ot = sb + pb2 * bsz;
#pragma unroll 1
        for (int c = 0; c < 5; c++) {
          float v[8], xa[8], x1[8], ta[8], tb[8];
          lds8(stg + st_r + c * 64, v);
          lds8_bf(sb + e1 * 20480 + e_r + c * 32, xa); lds8_bf(sb + e2 * 20480 + e_r + c * 32, x1);
          lds8(p_r + (ph == 1 ? P_A2 : P_GB) * 4 + c * 64, ta); lds8(p_r + P_B2 * 4 + c * 64, tb);
          if (ph == 1) {
#pragma unroll
            for (int e = 0; e < 8; e++) v[e] += fmaf(ta[e] * rs, xa[e] - mu, tb[e]);
          } else {
#pragma unroll
            for (int e = 0; e < 8; e++) v[e] = fmaf(ta[e], v[e] + x1[e], xa[e]);
          }
          const uint4 pk = pack8(v);
          sts_u4(ot + e_r + c * 32, pk);
          v[0] = bf_lo(pk.x); v[1] = bf_hi(pk.x); v[2] = bf_lo(pk.y); v[3] = bf_hi(pk.y); v[4] = bf_lo(pk.z); v[5] = bf_hi(pk.z); v[6] = bf_lo(pk.w); v[7] = bf_hi(pk.w);
#pragma unroll
          for (int e = 0; e < 8; e++) { s1 += v[e]; s2 = fmaf(v[e], v[e], s2); }
        }
        s1 += __shfl_xor_sync(0xffffffffu, s1, 1); s2 += __shfl_xor_sync(0xffffffffu, s2, 1);
        if (eh == 0) sts_f2(stat + er * 8, s1, s2);
        fence_async_smem();
        bar_sync(3 + w, 128);
        if (leader) {
          tma_store2d(ph == 1 ? &tm.sx1 : &tm.sout, ot + w * (E_TILE / 2), js * 80, qt * 128 + w * 64);
          if (ph == 1) bulk_red_f32(g_st2 + (size_t)(qt * 128 + w * 64) * 2, stat, 512);
        }
      }
      if (leader) {
        bulk_done();
        if (ph < 3) flag_add(g_flag + F_US + 16 * ph + qt);
      }
      if (ph < 3) {
        bar_sync(5, 256);
        B_RELEASE(pb);
        if (ph == 1) B_RELEASE(e1);
      }
      TS(1 + (ph == 3 ? 0 : ph), ph == 3 ? 3 : 1);
    }
    if ((threadIdx.x & 127) == 0) TL_END(2);
    cluster_sync();
  }
}

typedef CUresult (*EncFn)(CUtensorMap*, CUtensorMapDataType, cuuint32_t, void*, const cuuint64_t*, const cuuint64_t*,
                          const cuuint32_t*, const cuuint32_t*, CUtensorMapInterleave, CUtensorMapSwizzle,
                          CUtensorMapL2promotion, CUtensorMapFloatOOBfill);
static EncFn g_enc = nullptr;

static CUtensorMap map2d(const void* p, uint64_t rows, uint64_t cols, uint32_t box_rows) {
  CUtensorMap m;
  cuuint64_t gd[2] = {cols, rows}; cuuint64_t gs[1] = {cols * 2};
  cuuint32_t bx[2] = {64, box_rows}; cuuint32_t es[2] = {1, 1};
  g_enc(&m, CU_TENSOR_MAP_DATA_TYPE_BFLOAT16, 2, const_cast<void*>(p), gd, gs, bx, es, CU_TENSOR_MAP_INTERLEAVE_NONE,
        CU_TENSOR_MAP_SWIZZLE_128B, CU_TENSOR_MAP_L2_PROMOTION_L2_256B, CU_TENSOR_MAP_FLOAT_OOB_FILL_NONE);
  return m;
}
static CUtensorMap map3d(const void* p, uint64_t rows, uint64_t cols, uint32_t box_rows, uint32_t nblk) {
  CUtensorMap m;
  cuuint64_t gd[3] = {64, rows, cols / 64}; cuuint64_t gs[2] = {cols * 2, 128};
  cuuint32_t bx[3] = {64, box_rows, nblk}; cuuint32_t es[3] = {1, 1, 1};
  g_enc(&m, CU_TENSOR_MAP_DATA_TYPE_BFLOAT16, 3, const_cast<void*>(p), gd, gs, bx, es, CU_TENSOR_MAP_INTERLEAVE_NONE,
        CU_TENSOR_MAP_SWIZZLE_128B, CU_TENSOR_MAP_L2_PROMOTION_L2_256B, CU_TENSOR_MAP_FLOAT_OOB_FILL_NONE);
  return m;
}

static CUtensorMap map_e(const void* p, uint32_t rows, uint64_t total_rows = S_) {
  CUtensorMap m;
  cuuint64_t gd[2] = {D_, total_rows}; cuuint64_t gs[1] = {D_ * 2};
  cuuint32_t bx[2] = {80, rows}; cuuint32_t es[2] = {1, 1};
  g_enc(&m, CU_TENSOR_MAP_DATA_TYPE_BFLOAT16, 2, const_cast<void*>(p), gd, gs, bx, es, CU_TENSOR_MAP_INTERLEAVE_NONE,
        CU_TENSOR_MAP_SWIZZLE_NONE, CU_TENSOR_MAP_L2_PROMOTION_L2_256B, CU_TENSOR_MAP_FLOAT_OOB_FILL_NONE);
  return m;
}

template <typename... KArgs, typename... Args>
static void launch(void (*kern)(KArgs...), dim3 grid, dim3 block, int smem, bool pdl, Args... args) {
  cudaLaunchConfig_t cfg = {};
  cfg.gridDim = grid; cfg.blockDim = block; cfg.dynamicSmemBytes = smem; cfg.stream = cudaStreamPerThread;
  cudaLaunchAttribute at[1];
  at[0].id = cudaLaunchAttributeProgrammaticStreamSerialization;
  at[0].val.programmaticStreamSerializationAllowed = 1;
  cfg.attrs = at; cfg.numAttrs = pdl ? 1 : 0;
  cudaLaunchKernelEx(&cfg, kern, KArgs(args)...);
}

extern "C" void kernel_launch(void* const* d_in, const int* in_sizes, int n_in, void* d_out, int out_size) {
  const bf16* x = (const bf16*)d_in[0];
  const bf16* kc = (const bf16*)d_in[1];
  const bf16* vc = (const bf16*)d_in[2];
  const bf16* wq = (const bf16*)d_in[3];
  const bf16* wo = (const bf16*)d_in[4];
  const bf16* w1 = (const bf16*)d_in[6];
  const bf16* w2 = (const bf16*)d_in[7];
  const bf16* w3 = (const bf16*)d_in[8];
  const bf16* w4 = (const bf16*)d_in[9];
  const bf16* c = (const bf16*)d_in[10];
  const bf16* wmod = (const bf16*)d_in[11];
  bf16* out = (bf16*)d_out;

  static void *p_h, *p_o, *p_xa, *p_us, *p_x1, *p_g, *p_w1t, *p_w2t, *p_w4t;
  if (!g_enc) {
    void* fn = nullptr; cudaDriverEntryPointQueryResult qr;
    cudaGetDriverEntryPoint("cuTensorMapEncodeTiled", &fn, cudaEnableDefault, &qr);
    g_enc = (EncFn)fn;
    cudaGetSymbolAddress(&p_h, g_h); cudaGetSymbolAddress(&p_o, g_o); cudaGetSymbolAddress(&p_xa, g_xa);
    cudaGetSymbolAddress(&p_us, g_us); cudaGetSymbolAddress(&p_x1, g_x1); cudaGetSymbolAddress(&p_g, g_g);
    cudaGetSymbolAddress(&p_w1t, g_w1t); cudaGetSymbolAddress(&p_w2t, g_w2t); cudaGetSymbolAddress(&p_w4t, g_w4t);
    cudaFuncSetAttribute(fused_kernel, cudaFuncAttributeMaxDynamicSharedMemorySize, T_SMEM);
  }
  Maps tm;
  tm.h = map2d(p_h, S_, D_, 128);
  tm.wq = map3d(wq, D_, HD_, 64, 3);
  tm.k = map3d(kc, (uint64_t)H_ * S_, DH_, 64, 3);
  tm.v = map3d(vc, (uint64_t)H_ * S_, DH_, 64, 3);
  tm.o = map2d(p_o, S_, HD_, 128);
  tm.wo3 = map3d(wo, HD_, D_, 64, 3);
  tm.wo2 = map3d(wo, HD_, D_, 64, 2);
  tm.xa = map2d(p_xa, S_, D_, 64);
  tm.w1t = map3d(p_w1t, D_, D_, 80, 2);
  tm.us = map2d((const bf16*)p_us + 2 * D_, S_, D_, 64);
  tm.w2t = map3d(p_w2t, D_, D_, 80, 2);
  tm.x1 = map2d(p_x1, S_, D_, 64);
  tm.w3 = map3d(w3, D_, F_, 64, 3);
  tm.g = map2d(p_g, S_, F_, 64);
  tm.w4t = map3d(p_w4t, D_, F_, 80, 2);
  tm.ex = map_e(x, 128); tm.exa = map_e(p_xa, 128); tm.ex1 = map_e(p_x1, 128);
  tm.sxa = map_e(p_xa, 64); tm.sus = map_e(p_us, 64, S_ + 4); tm.sx1 = map_e(p_x1, 64); tm.sout = map_e(out, 64);
  PfList pf;
  pf.p[0] = (const uint8_t*)wo; pf.p[1] = (const uint8_t*)w3; pf.p[2] = (const uint8_t*)p_w4t;
  pf.p[3] = (const uint8_t*)x; pf.p[4] = (const uint8_t*)p_w1t; pf.p[5] = (const uint8_t*)p_w2t;

  launch(mod_kernel, dim3(120), dim3(256), 0, false, c, wmod);
  launch(ln1_kernel, dim3(256), dim3(256), 0, true, x);
  launch(fused_kernel, dim3(128), dim3(384), T_SMEM, true, tm, pf, PrepW{w1, w2, w3, w4}, x, out);
}
```

```cpp
#include <cuda_runtime.h>
#include <cuda.h>
#include <cuda_bf16.h>
#include <stdint.h>

typedef __nv_bfloat16 bf16;

constexpr int S_  = 2048;
constexpr int D_  = 640;
constexpr int H_  = 32;
constexpr int DH_ = 192;
constexpr int HD_ = H_ * DH_;
constexpr int F_  = 1536;
constexpr float LN_EPS = 1e-5f;

__device__ __forceinline__ uint32_t smem_u32(const void* p) { return (uint32_t)__cvta_generic_to_shared(p); }
__device__ __forceinline__ void mbar_init(uint32_t a, uint32_t c) { asm volatile("mbarrier.init.shared::cta.b64 [%0], %1;" :: "r"(a), "r"(c) : "memory"); }
__device__ __forceinline__ void mbar_expect(uint32_t a, uint32_t b) { asm volatile("mbarrier.arrive.expect_tx.shared::cta.b64 _, [%0], %1;" :: "r"(a), "r"(b) : "memory"); }
__device__ __forceinline__ void mbar_arrive(uint32_t a) { asm volatile("mbarrier.arrive.shared::cta.b64 _, [%0];" :: "r"(a) : "memory"); }
__device__ __forceinline__ void mbar_arrive_remote(uint32_t ra) { asm volatile("mbarrier.arrive.shared::cluster.b64 _, [%0];" :: "r"(ra) : "memory"); }
__device__ __forceinline__ uint32_t mapa(uint32_t a, uint32_t cta) { uint32_t r; asm volatile("mapa.shared::cluster.u32 %0, %1, %2;" : "=r"(r) : "r"(a), "r"(cta)); return r; }
__device__ __forceinline__ uint32_t mbar_try(uint32_t a, uint32_t ph) {
  uint32_t ok;
  asm volatile("{\n.reg .pred p;\nmbarrier.test_wait.parity.shared::cta.b64 p, [%1], %2;\nselp.u32 %0, 1, 0, p;\n}\n" : "=r"(ok) : "r"(a), "r"(ph) : "memory");
  return ok;
}
__device__ __forceinline__ void mbar_wait(uint32_t a, uint32_t ph) {
  asm volatile(
      "{\n.reg .pred p;\n.reg .u32 n;\n"
      "mov.u32 n, 0;\n"
      "SPIN:\n"
      "mbarrier.try_wait.parity.shared::cta.b64 p, [%0], %1;\n"
      "@p bra DONE;\n"
      "add.u32 n, n, 1;\n"
      "setp.le.u32 p, n, 16777216;\n"
      "@p bra SPIN;\n"
      "trap;\n"
      "DONE:\n}\n" :: "r"(a), "r"(ph) : "memory");
}
#define ELECT_ "{\n.reg .pred p;\nelect.sync _|p, 0xffffffff;\n@p "
__device__ __forceinline__ void mbar_expect_e(uint32_t a, uint32_t b) { asm volatile(ELECT_ "mbarrier.arrive.expect_tx.shared::cta.b64 _, [%0], %1;\n}\n" :: "r"(a), "r"(b) : "memory"); }
__device__ __forceinline__ void tma2d(uint32_t dst, const CUtensorMap* m, uint32_t bar, int c0, int c1) {
  asm volatile(ELECT_ "cp.async.bulk.tensor.2d.shared::cluster.global.mbarrier::complete_tx::bytes [%0], [%1, {%3, %4}], [%2];\n}\n"
               :: "r"(dst), "l"(m), "r"(bar), "r"(c0), "r"(c1) : "memory");
}
__device__ __forceinline__ void tma2d_mc(uint32_t dst, const CUtensorMap* m, uint32_t bar, int c0, int c1, uint16_t mask) {
  asm volatile(ELECT_ "cp.async.bulk.tensor.2d.shared::cluster.global.mbarrier::complete_tx::bytes.multicast::cluster [%0], [%1, {%3, %4}], [%2], %5;\n}\n"
               :: "r"(dst), "l"(m), "r"(bar), "r"(c0), "r"(c1), "h"(mask) : "memory");
}
__device__ __forceinline__ void tma3d(uint32_t dst, const CUtensorMap* m, uint32_t bar, int c0, int c1, int c2) {
  asm volatile(ELECT_ "cp.async.bulk.tensor.3d.shared::cluster.global.mbarrier::complete_tx::bytes [%0], [%1, {%3, %4, %5}], [%2];\n}\n"
               :: "r"(dst), "l"(m), "r"(bar), "r"(c0), "r"(c1), "r"(c2) : "memory");
}
__device__ __forceinline__ void tma3d_mc(uint32_t dst, const CUtensorMap* m, uint32_t bar, int c0, int c1, int c2, uint16_t mask) {
  asm volatile(ELECT_ "cp.async.bulk.tensor.3d.shared::cluster.global.mbarrier::complete_tx::bytes.multicast::cluster [%0], [%1, {%3, %4, %5}], [%2], %6;\n}\n"
               :: "r"(dst), "l"(m), "r"(bar), "r"(c0), "r"(c1), "r"(c2), "h"(mask) : "memory");
}
__device__ __forceinline__ void tma3d_mc_hint(uint32_t dst, const CUtensorMap* m, uint32_t bar, int c0, int c1, int c2, uint16_t mask, uint64_t pol) {
  asm volatile(ELECT_ "cp.async.bulk.tensor.3d.shared::cluster.global.mbarrier::complete_tx::bytes.multicast::cluster.L2::cache_hint [%0], [%1, {%3, %4, %5}], [%2], %6, %7;\n}\n"
               :: "r"(dst), "l"(m), "r"(bar), "r"(c0), "r"(c1), "r"(c2), "h"(mask), "l"(pol) : "memory");
}
__device__ __forceinline__ void bulk_load(uint32_t dst, const void* src, uint32_t bytes, uint32_t bar) {
  asm volatile(ELECT_ "cp.async.bulk.shared::cluster.global.mbarrier::complete_tx::bytes [%0], [%1], %2, [%3];\n}\n"
               :: "r"(dst), "l"(src), "r"(bytes), "r"(bar) : "memory");
}
__device__ __forceinline__ void l2_prefetch16k(const void* p) { asm volatile(ELECT_ "cp.async.bulk.prefetch.L2.global [%0], 16384;\n}\n" :: "l"(p) : "memory"); }
__device__ __forceinline__ void l2_prefetch_t2d(const CUtensorMap* m, int c0, int c1) {
  asm volatile(ELECT_ "cp.async.bulk.prefetch.tensor.2d.L2.global [%0, {%1, %2}];\n}\n" :: "l"(m), "r"(c0), "r"(c1) : "memory");
}
__device__ __forceinline__ void stg128(void* p, uint4 v) {
  asm volatile("st.global.v4.u32 [%0], {%1, %2, %3, %4};" :: "l"(p), "r"(v.x), "r"(v.y), "r"(v.z), "r"(v.w) : "memory");
}
__device__ __forceinline__ void prefetch_tmap(const CUtensorMap* m) { asm volatile("prefetch.tensormap [%0];" :: "l"(m) : "memory"); }
__device__ __forceinline__ void wg_fence() { asm volatile("wgmma.fence.sync.aligned;" ::: "memory"); }
__device__ __forceinline__ void wg_commit() { asm volatile("wgmma.commit_group.sync.aligned;" ::: "memory"); }
template <int N> __device__ __forceinline__ void wg_wait() { asm volatile("wgmma.wait_group.sync.aligned %0;" :: "n"(N) : "memory"); }
template <int N> __device__ __forceinline__ void fence_regs(float (&r)[N]) {
#pragma unroll
  for (int i = 0; i < N; i++) asm volatile("" : "+f"(r[i]) :: "memory");
}
template <int N> __device__ __forceinline__ void fence_regs(uint32_t (&r)[N]) {
#pragma unroll
  for (int i = 0; i < N; i++) asm volatile("" : "+r"(r[i]) :: "memory");
}
__device__ __forceinline__ uint64_t mkdesc(uint32_t addr, uint32_t lbo, uint32_t sbo) {
  return (uint64_t)((addr & 0x3FFFF) >> 4) | ((uint64_t)(lbo >> 4) << 16) | ((uint64_t)(sbo >> 4) << 32) | (1ull << 62);
}
__device__ __forceinline__ void bar_sync(int id, int n) { asm volatile("bar.sync %0, %1;" :: "r"(id), "r"(n) : "memory"); }
__device__ __forceinline__ void bar_arrive(int id, int n) { asm volatile("bar.arrive %0, %1;" :: "r"(id), "r"(n) : "memory"); }
__device__ __forceinline__ void cluster_sync() { asm volatile("barrier.cluster.arrive.aligned;\nbarrier.cluster.wait.aligned;" ::: "memory"); }
__device__ __forceinline__ void pdl_wait() { asm volatile("griddepcontrol.wait;" ::: "memory"); }
__device__ __forceinline__ void pdl_launch() { asm volatile("griddepcontrol.launch_dependents;" ::: "memory"); }
__device__ __forceinline__ float ex2(float x) { float y; asm("ex2.approx.ftz.f32 %0, %1;" : "=f"(y) : "f"(x)); return y; }
__device__ __forceinline__ uint32_t pack_bf16(float lo, float hi) { uint32_t r; asm("cvt.rn.bf16x2.f32 %0, %1, %2;" : "=r"(r) : "f"(hi), "f"(lo)); return r; }
__device__ __forceinline__ float bf_lo(uint32_t u) { return __uint_as_float(u << 16); }
__device__ __forceinline__ float bf_hi(uint32_t u) { return __uint_as_float(u & 0xffff0000u); }
__device__ __forceinline__ float bf_round(float x) { return __bfloat162float(__float2bfloat16_rn(x)); }
__device__ __forceinline__ float tanh_fast(float x) { float y; asm("tanh.approx.f32 %0, %1;" : "=f"(y) : "f"(x)); return y; }
__device__ __forceinline__ float gelu_tanh(float x) {
  float u = x * (0.7978845608028654f + 0.035677408136300125f * x * x);
  float hx = 0.5f * x;
  return fmaf(hx, tanh_fast(u), hx);
}
__device__ __forceinline__ float warp_sum(float v) {
#pragma unroll
  for (int o = 16; o > 0; o >>= 1) v += __shfl_xor_sync(0xffffffffu, v, o);
  return v;
}
__device__ __forceinline__ void quad_transpose(uint32_t& v0, uint32_t& v1, uint32_t& v2, uint32_t& v3, int lane) {
  const bool b0 = lane & 1, b1 = lane & 2;
  uint32_t s0 = b0 ? v0 : v1, s1 = b0 ? v2 : v3;
  s0 = __shfl_xor_sync(0xffffffffu, s0, 1); s1 = __shfl_xor_sync(0xffffffffu, s1, 1);
  if (b0) { v0 = s0; v2 = s1; } else { v1 = s0; v3 = s1; }
  uint32_t t0 = b1 ? v0 : v2, t1 = b1 ? v1 : v3;
  t0 = __shfl_xor_sync(0xffffffffu, t0, 2); t1 = __shfl_xor_sync(0xffffffffu, t1, 2);
  if (b1) { v0 = t0; v1 = t1; } else { v2 = t0; v3 = t1; }
}

#define TX(i)
#define TXC(i)
#define TSA(item, i)
#define TL_ENTRY(k)
#define TL_WAITED(k)
#define TL_END(k)
#define TS(item, i)
template<int TB> __device__ __forceinline__ void wgmma_rs_n64(float (&d)[32], uint32_t a0, uint32_t a1, uint32_t a2, uint32_t a3, uint64_t db, int scale_d) {
  asm volatile("{\n.reg .pred p;\nsetp.ne.b32 p, %37, 0;\n"
    "wgmma.mma_async.sync.aligned.m64n64k16.f32.bf16.bf16 {%0, %1, %2, %3, %4, %5, %6, %7, %8, %9, %10, %11, %12, %13, %14, %15, %16, %17, %18, %19, %20, %21, %22, %23, %24, %25, %26, %27, %28, %29, %30, %31}, {%32, %33, %34, %35}, %36, p, 1, 1, %38;\n}\n"
    : "+f"(d[0]), "+f"(d[1]), "+f"(d[2]), "+f"(d[3]), "+f"(d[4]), "+f"(d[5]), "+f"(d[6]), "+f"(d[7]), "+f"(d[8]), "+f"(d[9]), "+f"(d[10]), "+f"(d[11]), "+f"(d[12]), "+f"(d[13]), "+f"(d[14]), "+f"(d[15]), "+f"(d[16]), "+f"(d[17]), "+f"(d[18]), "+f"(d[19]), "+f"(d[20]), "+f"(d[21]), "+f"(d[22]), "+f"(d[23]), "+f"(d[24]), "+f"(d[25]), "+f"(d[26]), "+f"(d[27]), "+f"(d[28]), "+f"(d[29]), "+f"(d[30]), "+f"(d[31])
    : "r"(a0), "r"(a1), "r"(a2), "r"(a3), "l"(db), "r"(scale_d), "n"(TB));
}
template<int TB> __device__ __forceinline__ void wgmma_rs_n192(float (&d)[96], uint32_t a0, uint32_t a1, uint32_t a2, uint32_t a3, uint64_t db, int scale_d) {
  asm volatile("{\n.reg .pred p;\nsetp.ne.b32 p, %101, 0;\n"
    "wgmma.mma_async.sync.aligned.m64n192k16.f32.bf16.bf16 {%0, %1, %2, %3, %4, %5, %6, %7, %8, %9, %10, %11, %12, %13, %14, %15, %16, %17, %18, %19, %20, %21, %22, %23, %24, %25, %26, %27, %28, %29, %30, %31, %32, %33, %34, %35, %36, %37, %38, %39, %40, %41, %42, %43, %44, %45, %46, %47, %48, %49, %50, %51, %52, %53, %54, %55, %56, %57, %58, %59, %60, %61, %62, %63, %64, %65, %66, %67, %68, %69, %70, %71, %72, %73, %74, %75, %76, %77, %78, %79, %80, %81, %82, %83, %84, %85, %86, %87, %88, %89, %90, %91, %92, %93, %94, %95}, {%96, %97, %98, %99}, %100, p, 1, 1, %102;\n}\n"
    : "+f"(d[0]), "+f"(d[1]), "+f"(d[2]), "+f"(d[3]), "+f"(d[4]), "+f"(d[5]), "+f"(d[6]), "+f"(d[7]), "+f"(d[8]), "+f"(d[9]), "+f"(d[10]), "+f"(d[11]), "+f"(d[12]), "+f"(d[13]), "+f"(d[14]), "+f"(d[15]), "+f"(d[16]), "+f"(d[17]), "+f"(d[18]), "+f"(d[19]), "+f"(d[20]), "+f"(d[21]), "+f"(d[22]), "+f"(d[23]), "+f"(d[24]), "+f"(d[25]), "+f"(d[26]), "+f"(d[27]), "+f"(d[28]), "+f"(d[29]), "+f"(d[30]), "+f"(d[31]), "+f"(d[32]), "+f"(d[33]), "+f"(d[34]), "+f"(d[35]), "+f"(d[36]), "+f"(d[37]), "+f"(d[38]), "+f"(d[39]), "+f"(d[40]), "+f"(d[41]), "+f"(d[42]), "+f"(d[43]), "+f"(d[44]), "+f"(d[45]), "+f"(d[46]), "+f"(d[47]), "+f"(d[48]), "+f"(d[49]), "+f"(d[50]), "+f"(d[51]), "+f"(d[52]), "+f"(d[53]), "+f"(d[54]), "+f"(d[55]), "+f"(d[56]), "+f"(d[57]), "+f"(d[58]), "+f"(d[59]), "+f"(d[60]), "+f"(d[61]), "+f"(d[62]), "+f"(d[63]), "+f"(d[64]), "+f"(d[65]), "+f"(d[66]), "+f"(d[67]), "+f"(d[68]), "+f"(d[69]), "+f"(d[70]), "+f"(d[71]), "+f"(d[72]), "+f"(d[73]), "+f"(d[74]), "+f"(d[75]), "+f"(d[76]), "+f"(d[77]), "+f"(d[78]), "+f"(d[79]), "+f"(d[80]), "+f"(d[81]), "+f"(d[82]), "+f"(d[83]), "+f"(d[84]), "+f"(d[85]), "+f"(d[86]), "+f"(d[87]), "+f"(d[88]), "+f"(d[89]), "+f"(d[90]), "+f"(d[91]), "+f"(d[92]), "+f"(d[93]), "+f"(d[94]), "+f"(d[95])
    : "r"(a0), "r"(a1), "r"(a2), "r"(a3), "l"(db), "r"(scale_d), "n"(TB));
}
template<int TB> __device__ __forceinline__ void wgmma_ss_n128(float (&d)[64], uint64_t da, uint64_t db, int scale_d) {
  asm volatile("{\n.reg .pred p;\nsetp.ne.b32 p, %66, 0;\n"
    "wgmma.mma_async.sync.aligned.m64n128k16.f32.bf16.bf16 {%0, %1, %2, %3, %4, %5, %6, %7, %8, %9, %10, %11, %12, %13, %14, %15, %16, %17, %18, %19, %20, %21, %22, %23, %24, %25, %26, %27, %28, %29, %30, %31, %32, %33, %34, %35, %36, %37, %38, %39, %40, %41, %42, %43, %44, %45, %46, %47, %48, %49, %50, %51, %52, %53, %54, %55, %56, %57, %58, %59, %60, %61, %62, %63}, %64, %65, p, 1, 1, 0, %67;\n}\n"
    : "+f"(d[0]), "+f"(d[1]), "+f"(d[2]), "+f"(d[3]), "+f"(d[4]), "+f"(d[5]), "+f"(d[6]), "+f"(d[7]), "+f"(d[8]), "+f"(d[9]), "+f"(d[10]), "+f"(d[11]), "+f"(d[12]), "+f"(d[13]), "+f"(d[14]), "+f"(d[15]), "+f"(d[16]), "+f"(d[17]), "+f"(d[18]), "+f"(d[19]), "+f"(d[20]), "+f"(d[21]), "+f"(d[22]), "+f"(d[23]), "+f"(d[24]), "+f"(d[25]), "+f"(d[26]), "+f"(d[27]), "+f"(d[28]), "+f"(d[29]), "+f"(d[30]), "+f"(d[31]), "+f"(d[32]), "+f"(d[33]), "+f"(d[34]), "+f"(d[35]), "+f"(d[36]), "+f"(d[37]), "+f"(d[38]), "+f"(d[39]), "+f"(d[40]), "+f"(d[41]), "+f"(d[42]), "+f"(d[43]), "+f"(d[44]), "+f"(d[45]), "+f"(d[46]), "+f"(d[47]), "+f"(d[48]), "+f"(d[49]), "+f"(d[50]), "+f"(d[51]), "+f"(d[52]), "+f"(d[53]), "+f"(d[54]), "+f"(d[55]), "+f"(d[56]), "+f"(d[57]), "+f"(d[58]), "+f"(d[59]), "+f"(d[60]), "+f"(d[61]), "+f"(d[62]), "+f"(d[63])
    : "l"(da), "l"(db), "r"(scale_d), "n"(TB));
}
template<int TB> __device__ __forceinline__ void wgmma_ss_n192(float (&d)[96], uint64_t da, uint64_t db, int scale_d) {
  asm volatile("{\n.reg .pred p;\nsetp.ne.b32 p, %98, 0;\n"
    "wgmma.mma_async.sync.aligned.m64n192k16.f32.bf16.bf16 {%0, %1, %2, %3, %4, %5, %6, %7, %8, %9, %10, %11, %12, %13, %14, %15, %16, %17, %18, %19, %20, %21, %22, %23, %24, %25, %26, %27, %28, %29, %30, %31, %32, %33, %34, %35, %36, %37, %38, %39, %40, %41, %42, %43, %44, %45, %46, %47, %48, %49, %50, %51, %52, %53, %54, %55, %56, %57, %58, %59, %60, %61, %62, %63, %64, %65, %66, %67, %68, %69, %70, %71, %72, %73, %74, %75, %76, %77, %78, %79, %80, %81, %82, %83, %84, %85, %86, %87, %88, %89, %90, %91, %92, %93, %94, %95}, %96, %97, p, 1, 1, 0, %99;\n}\n"
    : "+f"(d[0]), "+f"(d[1]), "+f"(d[2]), "+f"(d[3]), "+f"(d[4]), "+f"(d[5]), "+f"(d[6]), "+f"(d[7]), "+f"(d[8]), "+f"(d[9]), "+f"(d[10]), "+f"(d[11]), "+f"(d[12]), "+f"(d[13]), "+f"(d[14]), "+f"(d[15]), "+f"(d[16]), "+f"(d[17]), "+f"(d[18]), "+f"(d[19]), "+f"(d[20]), "+f"(d[21]), "+f"(d[22]), "+f"(d[23]), "+f"(d[24]), "+f"(d[25]), "+f"(d[26]), "+f"(d[27]), "+f"(d[28]), "+f"(d[29]), "+f"(d[30]), "+f"(d[31]), "+f"(d[32]), "+f"(d[33]), "+f"(d[34]), "+f"(d[35]), "+f"(d[36]), "+f"(d[37]), "+f"(d[38]), "+f"(d[39]), "+f"(d[40]), "+f"(d[41]), "+f"(d[42]), "+f"(d[43]), "+f"(d[44]), "+f"(d[45]), "+f"(d[46]), "+f"(d[47]), "+f"(d[48]), "+f"(d[49]), "+f"(d[50]), "+f"(d[51]), "+f"(d[52]), "+f"(d[53]), "+f"(d[54]), "+f"(d[55]), "+f"(d[56]), "+f"(d[57]), "+f"(d[58]), "+f"(d[59]), "+f"(d[60]), "+f"(d[61]), "+f"(d[62]), "+f"(d[63]), "+f"(d[64]), "+f"(d[65]), "+f"(d[66]), "+f"(d[67]), "+f"(d[68]), "+f"(d[69]), "+f"(d[70]), "+f"(d[71]), "+f"(d[72]), "+f"(d[73]), "+f"(d[74]), "+f"(d[75]), "+f"(d[76]), "+f"(d[77]), "+f"(d[78]), "+f"(d[79]), "+f"(d[80]), "+f"(d[81]), "+f"(d[82]), "+f"(d[83]), "+f"(d[84]), "+f"(d[85]), "+f"(d[86]), "+f"(d[87]), "+f"(d[88]), "+f"(d[89]), "+f"(d[90]), "+f"(d[91]), "+f"(d[92]), "+f"(d[93]), "+f"(d[94]), "+f"(d[95])
    : "l"(da), "l"(db), "r"(scale_d), "n"(TB));
}
template<int TB> __device__ __forceinline__ void wgmma_ss_n80(float (&d)[40], uint64_t da, uint64_t db, int scale_d) {
  asm volatile("{\n.reg .pred p;\nsetp.ne.b32 p, %42, 0;\n"
    "wgmma.mma_async.sync.aligned.m64n80k16.f32.bf16.bf16 {%0, %1, %2, %3, %4, %5, %6, %7, %8, %9, %10, %11, %12, %13, %14, %15, %16, %17, %18, %19, %20, %21, %22, %23, %24, %25, %26, %27, %28, %29, %30, %31, %32, %33, %34, %35, %36, %37, %38, %39}, %40, %41, p, 1, 1, 0, %43;\n}\n"
    : "+f"(d[0]), "+f"(d[1]), "+f"(d[2]), "+f"(d[3]), "+f"(d[4]), "+f"(d[5]), "+f"(d[6]), "+f"(d[7]), "+f"(d[8]), "+f"(d[9]), "+f"(d[10]), "+f"(d[11]), "+f"(d[12]), "+f"(d[13]), "+f"(d[14]), "+f"(d[15]), "+f"(d[16]), "+f"(d[17]), "+f"(d[18]), "+f"(d[19]), "+f"(d[20]), "+f"(d[21]), "+f"(d[22]), "+f"(d[23]), "+f"(d[24]), "+f"(d[25]), "+f"(d[26]), "+f"(d[27]), "+f"(d[28]), "+f"(d[29]), "+f"(d[30]), "+f"(d[31]), "+f"(d[32]), "+f"(d[33]), "+f"(d[34]), "+f"(d[35]), "+f"(d[36]), "+f"(d[37]), "+f"(d[38]), "+f"(d[39])
    : "l"(da), "l"(db), "r"(scale_d), "n"(TB));
}

__device__ float g_mod[6 * D_];
__device__ __align__(1024) bf16 g_h[S_ * D_];
__device__ __align__(1024) bf16 g_o[S_ * HD_];
__device__ __align__(1024) bf16 g_xch[16 * 2 * 4 * 4 * 128 * 80];
__device__ __align__(1024) bf16 g_w1t[D_ * D_];
__device__ __align__(1024) bf16 g_w2t[D_ * D_];
__device__ __align__(1024) bf16 g_w4t[D_ * F_];
__device__ __align__(32) float g_st1[S_ * 8];
__device__ __align__(32) float g_st2[S_ * 2];
__device__ __align__(32) float g_vec[3 * D_ + F_ + 8];
__device__ unsigned g_flag[1024];
enum { F_XCH = 0, F_XA = 256, F_US = 272, F_X1 = 288, F_G = 304, F_PREP = 320, F_O = 512 };
__device__ __align__(1024) bf16 g_xa[S_ * D_];
__device__ __align__(1024) bf16 g_us[(S_ + 4) * D_];
__device__ __align__(1024) bf16 g_x1[S_ * D_];
__device__ __align__(1024) bf16 g_g[S_ * F_];

__global__ void __launch_bounds__(256) mod_kernel(const bf16* __restrict__ c, const bf16* __restrict__ w_mod) {
  TL_ENTRY(0);
  pdl_launch();
  __shared__ float red[8][32];
  if (blockIdx.x < 14) { const int i = blockIdx.x * 256 + threadIdx.x; if (i < 3 * D_ + F_) g_vec[i] = 0.f; }
  else if (blockIdx.x < 18) g_flag[(blockIdx.x - 14) * 256 + threadIdx.x] = 0u;
  const int t = threadIdx.x, cg = t & 3, r0 = t >> 2;
  const int col0 = blockIdx.x * 32 + cg * 8;
  uint4 w[10];
#pragma unroll
  for (int i = 0; i < 10; i++) w[i] = __ldg(reinterpret_cast<const uint4*>(w_mod + (size_t)(r0 + 64 * i) * (6 * D_) + col0));
  float acc[8];
#pragma unroll
  for (int j = 0; j < 8; j++) acc[j] = 0.f;
#pragma unroll
  for (int i = 0; i < 10; i++) {
    float cv = __bfloat162float(c[r0 + 64 * i]);
    float s = bf_round(cv / (1.f + __expf(-cv)));
    acc[0] = fmaf(s, bf_lo(w[i].x), acc[0]); acc[1] = fmaf(s, bf_hi(w[i].x), acc[1]);
    acc[2] = fmaf(s, bf_lo(w[i].y), acc[2]); acc[3] = fmaf(s, bf_hi(w[i].y), acc[3]);
    acc[4] = fmaf(s, bf_lo(w[i].z), acc[4]); acc[5] = fmaf(s, bf_hi(w[i].z), acc[5]);
    acc[6] = fmaf(s, bf_lo(w[i].w), acc[6]); acc[7] = fmaf(s, bf_hi(w[i].w), acc[7]);
  }
#pragma unroll
  for (int j = 0; j < 8; j++) {
    acc[j] += __shfl_xor_sync(0xffffffffu, acc[j], 4);
    acc[j] += __shfl_xor_sync(0xffffffffu, acc[j], 8);
    acc[j] += __shfl_xor_sync(0xffffffffu, acc[j], 16);
  }
  if ((t & 31) < 4) {
#pragma unroll
    for (int j = 0; j < 8; j++) red[t >> 5][cg * 8 + j] = acc[j];
  }
  __syncthreads();
  if (t < 32) {
    float s = 0.f;
#pragma unroll
    for (int w8 = 0; w8 < 8; w8++) s += red[w8][t];
    const int col = blockIdx.x * 32 + t;
    s = bf_round(s);
    const int part = col / D_;
    if (part == 1 || part == 4) s = bf_round(1.f + s);
    g_mod[col] = s;
    if (t == 0) TL_END(0);
  }
}

__device__ __forceinline__ void row_stats(const float (&v)[20], float& mean, float& rstd) {
  float s = 0.f;
#pragma unroll
  for (int i = 0; i < 20; i++) s += v[i];
  mean = warp_sum(s) * (1.f / D_);
  float q = 0.f;
#pragma unroll
  for (int i = 0; i < 20; i++) { float d = v[i] - mean; q = fmaf(d, d, q); }
  rstd = rsqrtf(warp_sum(q) * (1.f / D_) + LN_EPS);
}
__device__ __forceinline__ void load_row_bf16(const bf16* p, int lane, float (&v)[20]) {
#pragma unroll
  for (int i = 0; i < 5; i++) {
    uint2 u = *reinterpret_cast<const uint2*>(p + (lane + 32 * i) * 4);
    v[4 * i] = bf_lo(u.x); v[4 * i + 1] = bf_hi(u.x); v[4 * i + 2] = bf_lo(u.y); v[4 * i + 3] = bf_hi(u.y);
  }
}
__device__ __forceinline__ void store_row_bf16(bf16* p, int lane, const float (&v)[20]) {
#pragma unroll
  for (int i = 0; i < 5; i++) {
    uint2 u; u.x = pack_bf16(v[4 * i], v[4 * i + 1]); u.y = pack_bf16(v[4 * i + 2], v[4 * i + 3]);
    *reinterpret_cast<uint2*>(p + (lane + 32 * i) * 4) = u;
  }
}
__device__ __forceinline__ void load_row_f32(const float* p, int lane, float (&v)[20]) {
#pragma unroll
  for (int i = 0; i < 5; i++) {
    float4 u = *reinterpret_cast<const float4*>(p + (lane + 32 * i) * 4);
    v[4 * i] = u.x; v[4 * i + 1] = u.y; v[4 * i + 2] = u.z; v[4 * i + 3] = u.w;
  }
}

__global__ void __launch_bounds__(256) ln1_kernel(const bf16* __restrict__ x) {
  TL_ENTRY(1);
  pdl_launch();
  const int lane = threadIdx.x & 31, row = blockIdx.x * 8 + (threadIdx.x >> 5);
  float v[20];
  load_row_bf16(x + (size_t)row * D_, lane, v);
  float mean, rstd;
  row_stats(v, mean, rstd);
  if (lane < 8) g_st1[row * 8 + lane] = 0.f;
  if (lane < 2) g_st2[row * 2 + lane] = 0.f;
  pdl_wait();
  if (threadIdx.x == 0) TL_WAITED(1);
  float sa[20], ca[20];
  load_row_f32(g_mod, lane, sa);
  load_row_f32(g_mod + D_, lane, ca);
#pragma unroll
  for (int i = 0; i < 20; i++) v[i] = fmaf((v[i] - mean) * rstd, ca[i], sa[i]);
  store_row_bf16(g_h + (size_t)row * D_, lane, v);
  if (threadIdx.x == 0) TL_END(1);
}

constexpr int PREP_JOBS = 200 + 200 + 480 + 480;
struct PrepW { const bf16 *w1, *w2, *w3, *w4; };
__device__ __forceinline__ void prep_warp(const PrepW& pw, bf16 (*tile)[72], int lane) {
#pragma unroll 1
  for (int job = blockIdx.x; job < PREP_JOBS; job += gridDim.x) {
    const bf16* src; bf16* dst; int ld = D_, ldd = D_, kt, nt, kind = 1;
    if (job < 200) { src = pw.w1; dst = g_w1t; kt = job / 10; nt = job % 10; kind = 0; }
    else if (job < 400) { src = pw.w2; dst = g_w2t; kt = (job - 200) / 10; nt = (job - 200) % 10; }
    else if (job < 880) { src = pw.w4; dst = g_w4t; ldd = F_; kt = (job - 400) / 10; nt = (job - 400) % 10; }
    else { src = pw.w3; dst = nullptr; ld = F_; kt = (job - 880) / 24; nt = (job - 880) % 24; kind = 2; }
    src += (size_t)(kt * 32 + (lane >> 3)) * ld + nt * 64 + (lane & 7) * 8;
    __syncwarp();
#pragma unroll
    for (int h = 0; h < 2; h++) {
      uint4 v[4];
#pragma unroll
      for (int i = 0; i < 4; i++) v[i] = __ldg(reinterpret_cast<const uint4*>(src + (size_t)(h * 16 + i * 4) * ld));
#pragma unroll
      for (int i = 0; i < 4; i++) *reinterpret_cast<uint4*>(&tile[h * 16 + i * 4 + (lane >> 3)][(lane & 7) * 8]) = v[i];
    }
    __syncwarp();
    const float* pa = g_mod + 4 * D_ + kt * 32;
    const float* pb = g_mod + 3 * D_ + kt * 32;
#pragma unroll 1
    for (int h = 0; h < 2; h++) {
      const int n = lane + 32 * h;
      float sa = 0.f, sb = 0.f, sc = 0.f;
#pragma unroll 1
      for (int c = 0; c < 4; c++) {
        uint32_t u[4];
#pragma unroll
        for (int e = 0; e < 4; e++) {
          const int k = c * 8 + 2 * e;
          float lo = __bfloat162float(tile[k][n]), hi = __bfloat162float(tile[k + 1][n]);
          sc += lo + hi;
          if (kind == 0) {
            const float2 a = __ldcg(reinterpret_cast<const float2*>(pa + k)), b = __ldcg(reinterpret_cast<const float2*>(pb + k));
            sb = fmaf(b.x, lo, fmaf(b.y, hi, sb));
            lo *= a.x; hi *= a.y;
          }
          u[e] = pack_bf16(lo, hi);
          sa += bf_lo(u[e]) + bf_hi(u[e]);
        }
        if (kind != 2) *reinterpret_cast<uint4*>(dst + (size_t)(nt * 64 + n) * ldd + kt * 32 + c * 8) = make_uint4(u[0], u[1], u[2], u[3]);
      }
      if (kind == 0) { atomicAdd(&g_vec[nt * 64 + n], sa); atomicAdd(&g_vec[D_ + nt * 64 + n], sb); atomicAdd(&g_vec[2 * D_ + nt * 64 + n], sc); }
      else if (kind == 2) atomicAdd(&g_vec[3 * D_ + nt * 64 + n], sc);
    }
  }
  __syncwarp();
  if (lane == 0) {
    asm volatile("fence.acq_rel.gpu;" ::: "memory");
    asm volatile("red.relaxed.gpu.global.add.u32 [%0], 1;" :: "l"(g_flag + F_PREP) : "memory");
  }
}

constexpr int A_NSLOT = 9;
constexpr int A_SLOT = 24576;
constexpr int A_NKV = S_ / 64;
constexpr int PREP_CTAS = 128;

struct Ring {
  uint32_t slot, phase;
  __device__ __forceinline__ void adv(int n) { if (++slot == (uint32_t)n) { slot = 0; phase ^= 1; } }
};
constexpr int T_PAR = A_NSLOT * A_SLOT + 384;
constexpr int T_PREP = T_PAR + 3712;
constexpr int T_SMEM = T_PREP + 32 * 72 * 2 + 1024;
enum { P_OGA = 0, P_OA = 80, P_OB = 160, P_VA = 240, P_VB = 320, P_VC = 400, P_A2 = 480, P_B2 = 560, P_GB = 640, P_CS3 = 720, P_SC = 912 };

__device__ __forceinline__ void flag_wait(const unsigned* p, unsigned target) {
  asm volatile(
      "{\n.reg .pred p;\n.reg .u32 n, v;\n"
      "mov.u32 n, 0;\n"
      "SPIN:\n"
      "ld.relaxed.gpu.global.u32 v, [%0];\n"
      "setp.ge.u32 p, v, %1;\n"
      "@p bra DONE;\n"
      "add.u32 n, n, 1;\n"
      "setp.gt.u32 p, n, 4194304;\n"
      "@p trap;\n"
      "bra SPIN;\n"
      "DONE:\n}\n" :: "l"(p), "r"(target) : "memory");
}
__device__ __forceinline__ void fence_async_global() { asm volatile("fence.proxy.async.global;" ::: "memory"); }
__device__ __forceinline__ float lds_f(uint32_t a) { float v; asm volatile("ld.shared.f32 %0, [%1];" : "=f"(v) : "r"(a)); return v; }
__device__ __forceinline__ float2 lds_f2(uint32_t a) { float2 v; asm volatile("ld.shared.v2.f32 {%0, %1}, [%2];" : "=f"(v.x), "=f"(v.y) : "r"(a)); return v; }
__device__ __forceinline__ uint4 ldcg4(const void* p) { return __ldcg(reinterpret_cast<const uint4*>(p)); }

__device__ __forceinline__ void sts_f2(uint32_t a, float x, float y) { asm volatile("st.shared.v2.f32 [%0], {%1, %2};" :: "r"(a), "f"(x), "f"(y) : "memory"); }
__device__ __forceinline__ void sts_u4(uint32_t a, uint4 v) { asm volatile("st.shared.v4.u32 [%0], {%1, %2, %3, %4};" :: "r"(a), "r"(v.x), "r"(v.y), "r"(v.z), "r"(v.w) : "memory"); }
__device__ __forceinline__ void sts_u1(uint32_t a, uint32_t v) { asm volatile("st.shared.u32 [%0], %1;" :: "r"(a), "r"(v) : "memory"); }
__device__ __forceinline__ void fence_async_smem() { asm volatile("fence.proxy.async.shared::cta;" ::: "memory"); }
__device__ __forceinline__ void bulk_store(void* dst, uint32_t src, uint32_t bytes) {
  asm volatile("cp.async.bulk.global.shared::cta.bulk_group [%0], [%1], %2;" :: "l"(dst), "r"(src), "r"(bytes) : "memory");
}
__device__ __forceinline__ void bulk_red_f32(void* dst, uint32_t src, uint32_t bytes) {
  asm volatile("cp.reduce.async.bulk.global.shared::cta.bulk_group.add.f32 [%0], [%1], %2;" :: "l"(dst), "r"(src), "r"(bytes) : "memory");
}
__device__ __forceinline__ void tma_store2d(const CUtensorMap* m, uint32_t src, int c0, int c1) {
  asm volatile("cp.async.bulk.tensor.2d.global.shared::cta.bulk_group [%0, {%2, %3}], [%1];" :: "l"(m), "r"(src), "r"(c0), "r"(c1) : "memory");
}
__device__ __forceinline__ void bulk_done() { asm volatile("cp.async.bulk.commit_group;\ncp.async.bulk.wait_group 0;" ::: "memory"); }
__device__ __forceinline__ void flag_add(unsigned* f) { asm volatile("red.relaxed.gpu.global.add.u32 [%0], 1;" :: "l"(f) : "memory"); }
__device__ __forceinline__ float4 lds_f4(uint32_t a) { return *reinterpret_cast<const float4*>(__cvta_shared_to_generic(a)); }
__device__ __forceinline__ uint4 lds_u4(uint32_t a) { return *reinterpret_cast<const uint4*>(__cvta_shared_to_generic(a)); }
__device__ __forceinline__ void lds8(uint32_t a, float (&v)[8]) {
  const float4 p = lds_f4(a), q = lds_f4(a + 16);
  v[0] = p.x; v[1] = p.y; v[2] = p.z; v[3] = p.w; v[4] = q.x; v[5] = q.y; v[6] = q.z; v[7] = q.w;
}
__device__ __forceinline__ void lds8_bf(uint32_t a, float (&v)[8]) {
  const uint4 u = lds_u4(a);
  v[0] = bf_lo(u.x); v[1] = bf_hi(u.x); v[2] = bf_lo(u.y); v[3] = bf_hi(u.y); v[4] = bf_lo(u.z); v[5] = bf_hi(u.z); v[6] = bf_lo(u.w); v[7] = bf_hi(u.w);
}
__device__ __forceinline__ uint4 pack8(const float (&v)[8]) {
  return make_uint4(pack_bf16(v[0], v[1]), pack_bf16(v[2], v[3]), pack_bf16(v[4], v[5]), pack_bf16(v[6], v[7]));
}
__device__ __forceinline__ void mbar_wait_c(uint32_t a, uint32_t ph) {
  asm volatile("{\n.reg .pred p;\nSPIN:\nmbarrier.try_wait.parity.shared::cta.b64 p, [%0], %1;\n@!p bra SPIN;\n}\n" :: "r"(a), "r"(ph) : "memory");
}
constexpr int ST_P = 80;
constexpr int E_TILE = 128 * 80 * 2;

struct Maps { CUtensorMap h, wq, k, v, o, wo3, wo2, xa, w1t, us, w2t, x1, w3, g, w4t, ex, exa, ex1, sxa, sus, sx1, sout; };
struct PfList { const uint8_t* p[6]; };

constexpr int M_AOFF = 102400, M_NA = 7;

__global__ void __cluster_dims__(2, 1, 1) __launch_bounds__(384, 1)
fused_kernel(const __grid_constant__ Maps tm, const __grid_constant__ PfList pf, const __grid_constant__ PrepW pw, const bf16* __restrict__ x, bf16* __restrict__ out) {
  extern __shared__ uint8_t smem_raw[];
  const uint32_t sb = (smem_u32(smem_raw) + 1023) & ~1023u;
  TL_ENTRY(2);
  const uint32_t bar_full = sb + A_NSLOT * A_SLOT;
  const uint32_t bar_empty = bar_full + 8 * A_NSLOT;
  const uint32_t bar_sig = bar_empty + 8 * A_NSLOT;
  const uint32_t mb_full = bar_sig + 16;
  const uint32_t mb_empty = mb_full + 96;
  const uint32_t par = sb + T_PAR;
  float* parf = reinterpret_cast<float*>(smem_raw + (par - smem_u32(smem_raw)));
  uint32_t rank;
  asm volatile("mov.u32 %0, %%cluster_ctarank;" : "=r"(rank));
  const int cid = blockIdx.x >> 1;
  const int wid = __shfl_sync(0xffffffffu, threadIdx.x >> 5, 0);
  const int wg = wid >> 2;
  const int qtile = (cid & 7) * 2 + rank, hbase = cid >> 3;
  const int o_qt = qtile, o_nh = (cid >> 3) & 1, o_ks = cid >> 4;
  const int o_col = o_nh * 320 + o_ks * 80;
  const int qt = cid >> 2, js = (cid & 3) * 2 + rank;
  if (threadIdx.x == 0) {
    for (int i = 0; i < A_NSLOT; i++) { mbar_init(bar_full + 8 * i, 1); mbar_init(bar_empty + 8 * i, 16); }
    mbar_init(bar_sig, 4); mbar_init(bar_sig + 8, 4);
    for (int i = 0; i < 12; i++) { mbar_init(mb_full + 8 * i, 1); mbar_init(mb_empty + 8 * i, i < 5 ? 8 : 16); }
    asm volatile("fence.mbarrier_init.release.cluster;" ::: "memory");
    prefetch_tmap(&tm.h); prefetch_tmap(&tm.wq); prefetch_tmap(&tm.k); prefetch_tmap(&tm.v);
  }
  __syncthreads();
  cluster_sync();

  if (wg == 0) {
    asm volatile("setmaxnreg.dec.sync.aligned.u32 40;");
    if (wid == 0) {
      Ring r{0, 1};
#define P_ACQ(bytes_) do { mbar_wait(bar_empty + 8 * r.slot, r.phase); mbar_expect_e(bar_full + 8 * r.slot, bytes_); } while (0)
#define P_DST (sb + r.slot * A_SLOT)
#define P_BAR (bar_full + 8 * r.slot)
      uint64_t pol_ef;
      asm volatile("createpolicy.fractional.L2::evict_first.b64 %0, 1.0;" : "=l"(pol_ef));
      pdl_wait();
      TL_WAITED(2);
#pragma unroll 1
      for (int item = 0; item < 4; item++) {
        const int head = hbase + 8 * item;
#pragma unroll 1
        for (int kb = 0; kb < 10; kb++) {
          P_ACQ(16384);
          tma2d(P_DST, &tm.h, P_BAR, kb * 64, qtile * 128);
          r.adv(A_NSLOT);
          P_ACQ(A_SLOT);
          if ((uint32_t)(kb & 1) == rank) tma3d_mc_hint(P_DST, &tm.wq, P_BAR, 0, kb * 64, head * 3, 3, pol_ef);
          r.adv(A_NSLOT);
        }
#pragma unroll 1
        for (int j = 0; j <= A_NKV; j++) {
          if (j < A_NKV) {
            P_ACQ(A_SLOT);
            if (rank == 0) tma3d_mc_hint(P_DST, &tm.k, P_BAR, 0, head * S_ + j * 64, 0, 3, pol_ef);
            r.adv(A_NSLOT);
          }
          if (j > 0) {
            P_ACQ(A_SLOT);
            if (rank == 1) tma3d_mc_hint(P_DST, &tm.v, P_BAR, 0, head * S_ + (j - 1) * 64, 0, 3, pol_ef);
            r.adv(A_NSLOT);
          }
          if (item == 3 && (j & 3) == 0) {
            const int c = (j >> 2) * 128 + blockIdx.x;
            if (c < 980) {
              const int li = c < 480 ? 0 : c < 600 ? 1 : c < 720 ? 2 : c < 880 ? 3 : c < 930 ? 4 : 5;
              const int c0 = c < 480 ? 0 : c < 600 ? 480 : c < 720 ? 600 : c < 880 ? 720 : c < 930 ? 880 : 930;
              l2_prefetch16k(pf.p[li] + (size_t)(c - c0) * 16384);
            }
          }
          if (item == 3) {
            if (j >= 6 && j < 24) {
              const int kb = j - 6;
              l2_prefetch_t2d(&tm.o, ((kb / 6) * 8 + 2 * o_ks + (kb % 6) / 3) * DH_ + (kb % 3) * 64, o_qt * 128);
            }
            if (j >= 24 && j < 30) flag_wait(g_flag + F_O + o_qt * 32 + ((j - 24) >> 1) * 8 + 2 * o_ks + (j & 1), 2);
            if (j == 0 && threadIdx.x == 0) {
              prefetch_tmap(&tm.o); prefetch_tmap(&tm.wo3); prefetch_tmap(&tm.wo2); prefetch_tmap(&tm.xa); prefetch_tmap(&tm.w1t); prefetch_tmap(&tm.us);
              prefetch_tmap(&tm.w2t); prefetch_tmap(&tm.x1); prefetch_tmap(&tm.w3); prefetch_tmap(&tm.g); prefetch_tmap(&tm.w4t);
              prefetch_tmap(&tm.ex); prefetch_tmap(&tm.exa); prefetch_tmap(&tm.ex1);
              prefetch_tmap(&tm.sxa); prefetch_tmap(&tm.sus); prefetch_tmap(&tm.sx1); prefetch_tmap(&tm.sout);
            }
          }
        }
      }
#pragma unroll 1
      for (int kb = 0; kb < 24; kb++) {
        const int head = (kb / 6) * 8 + 2 * o_ks + (kb % 6) / 3;
        const int kcol = head * DH_ + (kb % 3) * 64;
        P_ACQ(24576);
        if (rank == 0) tma3d_mc(P_DST, &tm.wo3, P_BAR, 0, kcol, o_nh * 5, 3);
        r.adv(A_NSLOT);
        P_ACQ(16384);
        if (rank == 1) tma3d_mc(P_DST, &tm.wo2, P_BAR, 0, kcol, o_nh * 5 + 3, 3);
        r.adv(A_NSLOT);
        if (kb == 18 || kb == 21) flag_wait(g_flag + F_O + o_qt * 32 + head, 2);
        if (kb % 3 == 0) fence_async_global();
        P_ACQ(16384);
        tma2d(P_DST, &tm.o, P_BAR, kcol, o_qt * 128);
        r.adv(A_NSLOT);
      }
      P_ACQ(E_TILE);
      tma2d(P_DST, &tm.ex, P_BAR, o_col, o_qt * 128);
      r.adv(A_NSLOT);
      flag_wait(g_flag + F_XCH + (o_qt * 2 + o_nh) * 4 + o_ks, 6);
      fence_async_global();
#pragma unroll 1
      for (int i = 0; i < 3; i++) {
        P_ACQ(E_TILE);
        bulk_load(P_DST, g_xch + (size_t)((((o_qt * 2 + o_nh) * 4 + o_ks) * 4) + ((o_ks + 1 + i) & 3)) * (E_TILE / 2), E_TILE, P_BAR);
        r.adv(A_NSLOT);
      }
      flag_wait(g_flag + F_PREP, PREP_CTAS);
      fence_async_global();
#pragma unroll 1
      for (int i = 0; i < A_NSLOT; i++) { mbar_wait(bar_empty + 8 * r.slot, r.phase); r.adv(A_NSLOT); }
      Ring ra{0, 1};
      uint32_t bpar = 0x1f;
#pragma unroll 1
      for (int ph = 0; ph < 4; ph++) {
        const CUtensorMap* ma = ph == 0 ? &tm.xa : ph == 1 ? &tm.us : ph == 2 ? &tm.x1 : &tm.g;
        const CUtensorMap* mb = ph == 0 ? &tm.w1t : ph == 1 ? &tm.w2t : ph == 2 ? &tm.w3 : &tm.w4t;
        const int nkb = ph == 3 ? 24 : 10;
        const int nbl = ph == 2 ? 10 : nkb / 2;
        const int nel = ph == 1 ? 1 : ph == 3 ? 2 : 0;
        const uint32_t nbs = ph == 2 ? 4 : 5, bsz = ph == 2 ? 24576 : 20480;
        int bl = 0; uint32_t bs = 0;
#pragma unroll 1
        for (int i = 0; i < 5; i++) mbar_wait(mb_empty + 8 * i, (bpar >> i) & 1);
#define T_LOADB() do { mbar_wait(mb_empty + 8 * bs, (bpar >> bs) & 1); bpar ^= 1u << bs; mbar_expect_e(mb_full + 8 * bs, bsz);    \
                       if (bl < nbl) tma3d(sb + bs * bsz, mb, mb_full + 8 * bs, 0, ph == 2 ? bl * 64 : js * 80, ph == 2 ? js * 3 : bl * 2); \
                       else tma2d(sb + bs * bsz, bl == nbl ? &tm.exa : &tm.ex1, mb_full + 8 * bs, js * 80, qt * 128); \
                       bl++; if (++bs == nbs) bs = 0; } while (0)
#pragma unroll 1
        for (uint32_t i = 0; i < nbs; i++) T_LOADB();
        TX(8 + ph * 4);
        const unsigned* fl = g_flag + F_XA + 16 * ph;
        flag_wait(fl + qt, 16);
        if (ph == 1) { if (qt > 0) flag_wait(fl + qt - 1, 16); if (qt < 15) flag_wait(fl + qt + 1, 16); }
        TX(9 + ph * 4);
        fence_async_global();
#pragma unroll 1
        for (int kb = 0; kb < nkb; kb++) {
          mbar_wait(mb_empty + 40 + 8 * ra.slot, ra.phase);
          mbar_expect_e(mb_full + 40 + 8 * ra.slot, 16384);
          tma2d_mc(sb + M_AOFF + ra.slot * 16384 + rank * 8192, ma, mb_full + 40 + 8 * ra.slot, kb * 64, qt * 128 + (int)rank * 64, 3);
          ra.adv(M_NA);
          while (bl < nbl + nel && (kb == nkb - 1 || kb >= (ph == 2 ? bl + 2 : 2 * bl - 3))) T_LOADB();
        }
      }
    } else if (wid < 3) {
      const int w = wid - 1, lane = threadIdx.x & 31;
#pragma unroll 1
      for (int sig = 0; sig < 4; sig++) {
        mbar_wait(bar_sig + 8 * w, sig & 1);
        if (lane == 0) {
          asm volatile("fence.acq_rel.gpu;" ::: "memory");
          flag_add(g_flag + F_O + qtile * 32 + hbase + 8 * sig);
        }
        __syncwarp();
      }
    } else {
      const int lane = threadIdx.x & 31;
      pdl_wait();
      prep_warp(pw, reinterpret_cast<bf16(*)[72]>(smem_raw + (sb + T_PREP - smem_u32(smem_raw))), lane);
      flag_wait(g_flag + F_PREP, PREP_CTAS);
#pragma unroll 1
      for (int i = lane; i < P_SC; i += 32) {
        const int v = i < P_CS3 ? i / 80 : 9, j = i - (i < P_CS3 ? v * 80 : P_CS3);
        const float* src = v == 0 ? g_mod + 2 * D_ + o_col : v == 1 ? g_mod + 4 * D_ + o_col : v == 2 ? g_mod + 3 * D_ + o_col
                         : v < 6 ? g_vec + (v - 3) * D_ + js * 80 : v == 6 ? g_mod + 4 * D_ + js * 80 : v == 7 ? g_mod + 3 * D_ + js * 80
                         : v == 8 ? g_mod + 5 * D_ + js * 80 : g_vec + 3 * D_ + js * 192;
        parf[i] = __ldcg(src + j);
      }
      float sv[5] = {0.f, 0.f, 0.f, 0.f, 0.f};
#pragma unroll 1
      for (int i = lane; i < D_; i += 32) {
        const float a = __ldcg(g_mod + 4 * D_ + i), b = __ldcg(g_mod + 3 * D_ + i);
        sv[0] += a; sv[1] = fmaf(a, a, sv[1]); sv[2] = fmaf(a, b, sv[2]); sv[3] += b; sv[4] = fmaf(b, b, sv[4]);
      }
#pragma unroll 1
      for (int o_ = 16; o_ > 0; o_ >>= 1) {
#pragma unroll
        for (int i = 0; i < 5; i++) sv[i] += __shfl_xor_sync(0xffffffffu, sv[i], o_);
      }
      if (lane == 0) {
#pragma unroll
        for (int i = 0; i < 5; i++) parf[P_SC + i] = sv[i];
      }
      bar_arrive(6, 288);
    }
    __syncwarp();
    cluster_sync();
  } else {
    asm volatile("setmaxnreg.inc.sync.aligned.u32 232;");
    const int w = wg - 1;
    const int lane = threadIdx.x & 31;
    const int warp = wid & 3;
    const int tid = threadIdx.x - 128;
    const uint32_t rel_base = mapa(bar_empty, (lane == 0) ? rank : (rank ^ 1));
    Ring r{0, 0};
#define A_RELEASE(slot_) do { if (lane < 2) mbar_arrive_remote(rel_base + 8 * (slot_)); } while (0)
#define SIGNAL() do { __syncwarp(); if (lane == 0) mbar_arrive(bar_sig + 8 * w); } while (0)
    {
    const float SC = 0.07216878364870322f * 1.4426950408889634f;
    float o[96];
    uint32_t q[48];
    float s[32];
    uint32_t p[16], p2[16];
    if (w == 1) bar_arrive(1, 256);
    bf16* orow = g_o + (size_t)(qtile * 128 + w * 64 + warp * 16 + (lane >> 2)) * HD_ + (hbase - 8) * DH_ + (lane & 3) * 8;
#define O_STORE(g)                                                                                                     \
      {                                                                                                                \
        quad_transpose(q[8 * g], q[8 * g + 2], q[8 * g + 4], q[8 * g + 6], lane);                                      \
        stg128(orow + g * 32, make_uint4(q[8 * g], q[8 * g + 2], q[8 * g + 4], q[8 * g + 6]));                         \
        quad_transpose(q[8 * g + 1], q[8 * g + 3], q[8 * g + 5], q[8 * g + 7], lane);                                  \
        stg128(orow + (size_t)8 * HD_ + g * 32, make_uint4(q[8 * g + 1], q[8 * g + 3], q[8 * g + 5], q[8 * g + 7]));   \
      }
#pragma unroll 1
    for (int item = 0; item < 4; item++) {
      TSA(item, 0);
      {
        uint32_t prevA = 0, prevB = 0;
#pragma unroll
        for (int kb = 0; kb < 10; kb++) {
          const uint32_t sA = r.slot; mbar_wait_c(bar_full + 8 * sA, r.phase); r.adv(A_NSLOT);
          const uint32_t sB = r.slot; mbar_wait_c(bar_full + 8 * sB, r.phase); r.adv(A_NSLOT);
          const uint64_t da = mkdesc(sb + sA * A_SLOT + w * 8192, 16, 1024);
          const uint64_t db = mkdesc(sb + sB * A_SLOT, 8192, 1024);
          wg_fence();
#pragma unroll
          for (int kk = 0; kk < 4; kk++) wgmma_ss_n192<1>(o, da + kk * 2, db + kk * 128, (kb | kk) != 0);
          wg_commit();
          if (kb < 6 && item > 0) { O_STORE((kb < 6 ? kb : 0)) }
          if (kb == 6 && item > 0) SIGNAL();
          if (kb > 0) { wg_wait<1>(); A_RELEASE(prevA); A_RELEASE(prevB); }
          prevA = sA; prevB = sB;
        }
        wg_wait<0>();
        fence_regs(o);
        A_RELEASE(prevA); A_RELEASE(prevB);
#pragma unroll
        for (int i = 0; i < 48; i++) q[i] = pack_bf16(o[2 * i], o[2 * i + 1]);
      }
      orow += 8 * DH_;

      TSA(item, 1);
      float c0, c1, l0, l1;
      {
        const uint32_t sK = r.slot; mbar_wait_c(bar_full + 8 * sK, r.phase); r.adv(A_NSLOT);
        const uint64_t dk = mkdesc(sb + sK * A_SLOT, 16, 1024);
        bar_sync(1 + w, 256);
        wg_fence();
#pragma unroll
        for (int kk = 0; kk < 12; kk++)
          wgmma_rs_n64<0>(s, q[4 * kk], q[4 * kk + 1], q[4 * kk + 2], q[4 * kk + 3], dk + (kk >> 2) * 512 + (kk & 3) * 2, kk != 0);
        wg_commit();
        bar_arrive(1 + (w ^ 1), 256);
        wg_wait<0>();
        fence_regs(s);
        A_RELEASE(sK);
        float mx0 = fmaxf(s[0], s[1]), mx1 = fmaxf(s[2], s[3]);
#pragma unroll
        for (int i = 1; i < 8; i++) { mx0 = fmaxf(mx0, fmaxf(s[4 * i], s[4 * i + 1])); mx1 = fmaxf(mx1, fmaxf(s[4 * i + 2], s[4 * i + 3])); }
        mx0 = fmaxf(mx0, __shfl_xor_sync(0xffffffffu, mx0, 1)); mx1 = fmaxf(mx1, __shfl_xor_sync(0xffffffffu, mx1, 1));
        mx0 = fmaxf(mx0, __shfl_xor_sync(0xffffffffu, mx0, 2)); mx1 = fmaxf(mx1, __shfl_xor_sync(0xffffffffu, mx1, 2));
        c0 = mx0 * SC; c1 = mx1 * SC;
        l0 = 0.f; l1 = 0.f;
#pragma unroll
        for (int i = 0; i < 8; i++) {
          s[4 * i] = ex2(fmaf(s[4 * i], SC, -c0)); s[4 * i + 1] = ex2(fmaf(s[4 * i + 1], SC, -c0));
          s[4 * i + 2] = ex2(fmaf(s[4 * i + 2], SC, -c1)); s[4 * i + 3] = ex2(fmaf(s[4 * i + 3], SC, -c1));
          l0 += s[4 * i] + s[4 * i + 1]; l1 += s[4 * i + 2] + s[4 * i + 3];
        }
#pragma unroll
        for (int i = 0; i < 16; i++) p[i] = pack_bf16(s[2 * i], s[2 * i + 1]);
      }
      TSA(item, 2);
      uint32_t okn;
      {
        Ring r2 = r; r2.adv(A_NSLOT);
        okn = mbar_try(bar_full + 8 * r.slot, r.phase) & mbar_try(bar_full + 8 * r2.slot, r2.phase);
      }
#define A_STEP(PC, PN, FIRST)                                                                                          \
      {                                                                                                                \
        const uint32_t sK = r.slot, phK = r.phase; r.adv(A_NSLOT);                                                     \
        const uint32_t sV = r.slot, phV = r.phase; r.adv(A_NSLOT);                                                     \
        const uint64_t dk = mkdesc(sb + sK * A_SLOT, 16, 1024);                                                        \
        const uint64_t dv = mkdesc(sb + sV * A_SLOT, 8192, 1024);                                                      \
        if (!okn) { mbar_wait_c(bar_full + 8 * sK, phK); mbar_wait_c(bar_full + 8 * sV, phV); }                            \
        bar_sync(1 + w, 256);                                                                                          \
        wg_fence();                                                                                                    \
        _Pragma("unroll") for (int kk = 0; kk < 12; kk++)                                                              \
          wgmma_rs_n64<0>(s, q[4 * kk], q[4 * kk + 1], q[4 * kk + 2], q[4 * kk + 3], dk + (kk >> 2) * 512 + (kk & 3) * 2, kk != 0); \
        wg_commit();                                                                                                   \
        _Pragma("unroll") for (int kk = 0; kk < 4; kk++)                                                               \
          wgmma_rs_n192<1>(o, PC[4 * kk], PC[4 * kk + 1], PC[4 * kk + 2], PC[4 * kk + 3], dv + kk * 128, !(FIRST) || (kk != 0)); \
        wg_commit();                                                                                                   \
        bar_arrive(1 + (w ^ 1), 256);                                                                                  \
        {                                                                                                              \
          Ring r2 = r; r2.adv(A_NSLOT);                                                                                \
          okn = mbar_try(bar_full + 8 * r.slot, r.phase) & mbar_try(bar_full + 8 * r2.slot, r2.phase);                 \
        }                                                                                                              \
        wg_wait<1>();                                                                                                  \
        fence_regs(s);                                                                                                 \
        A_RELEASE(sK);                                                                                                 \
        float b0 = 0.f, b1 = 0.f;                                                                                      \
        _Pragma("unroll") for (int i = 0; i < 8; i++) {                                                                \
          const float e0 = ex2(fmaf(s[4 * i], SC, -c0)), e1 = ex2(fmaf(s[4 * i + 1], SC, -c0));                        \
          const float e2 = ex2(fmaf(s[4 * i + 2], SC, -c1)), e3 = ex2(fmaf(s[4 * i + 3], SC, -c1));                    \
          b0 += e0 + e1; b1 += e2 + e3;                                                                                \
          PN[2 * i] = pack_bf16(e0, e1); PN[2 * i + 1] = pack_bf16(e2, e3);                                            \
        }                                                                                                              \
        wg_wait<0>();                                                                                                  \
        fence_regs(o);                                                                                                 \
        fence_regs(PC);                                                                                                \
        A_RELEASE(sV);                                                                                                 \
        if (__any_sync(0xffffffffu, !(b0 <= 65536.f) || !(b1 <= 65536.f))) {                                           \
          float mx0 = fmaxf(s[0], s[1]), mx1 = fmaxf(s[2], s[3]);                                                      \
          _Pragma("unroll") for (int i = 1; i < 8; i++) {                                                              \
            mx0 = fmaxf(mx0, fmaxf(s[4 * i], s[4 * i + 1])); mx1 = fmaxf(mx1, fmaxf(s[4 * i + 2], s[4 * i + 3]));     \
          }                                                                                                            \
          mx0 = fmaxf(mx0, __shfl_xor_sync(0xffffffffu, mx0, 1)); mx1 = fmaxf(mx1, __shfl_xor_sync(0xffffffffu, mx1, 1)); \
          mx0 = fmaxf(mx0, __shfl_xor_sync(0xffffffffu, mx0, 2)); mx1 = fmaxf(mx1, __shfl_xor_sync(0xffffffffu, mx1, 2)); \
          const float n0 = fmaxf(c0, mx0 * SC), n1 = fmaxf(c1, mx1 * SC);                                              \
          const float a0 = ex2(c0 - n0), a1 = ex2(c1 - n1);                                                            \
          c0 = n0; c1 = n1;                                                                                            \
          l0 *= a0; l1 *= a1;                                                                                          \
          _Pragma("unroll") for (int i = 0; i < 24; i++) { o[4 * i] *= a0; o[4 * i + 1] *= a0; o[4 * i + 2] *= a1; o[4 * i + 3] *= a1; } \
          b0 = 0.f; b1 = 0.f;                                                                                          \
          _Pragma("unroll") for (int i = 0; i < 8; i++) {                                                              \
            const float e0 = ex2(fmaf(s[4 * i], SC, -c0)), e1 = ex2(fmaf(s[4 * i + 1], SC, -c0));                      \
            const float e2 = ex2(fmaf(s[4 * i + 2], SC, -c1)), e3 = ex2(fmaf(s[4 * i + 3], SC, -c1));                  \
            b0 += e0 + e1; b1 += e2 + e3;                                                                              \
            PN[2 * i] = pack_bf16(e0, e1); PN[2 * i + 1] = pack_bf16(e2, e3);                                          \
          }                                                                                                            \
        }                                                                                                              \
        l0 += b0; l1 += b1;                                                                                            \
      }
      for (int jj = 0; jj < 15; jj++) {
        A_STEP(p, p2, jj == 0)
        A_STEP(p2, p, false)
      }
      A_STEP(p, p2, false)
      TSA(item, 3);
      {
        const uint32_t sV = r.slot; mbar_wait_c(bar_full + 8 * sV, r.phase); r.adv(A_NSLOT);
        const uint64_t dv = mkdesc(sb + sV * A_SLOT, 8192, 1024);
        bar_sync(1 + w, 256);
        wg_fence();
#pragma unroll
        for (int kk = 0; kk < 4; kk++)
          wgmma_rs_n192<1>(o, p2[4 * kk], p2[4 * kk + 1], p2[4 * kk + 2], p2[4 * kk + 3], dv + kk * 128, 1);
        wg_commit();
        bar_arrive(1 + (w ^ 1), 256);
        wg_wait<0>();
        fence_regs(o);
        A_RELEASE(sV);
      }
      TSA(item, 4);
      l0 += __shfl_xor_sync(0xffffffffu, l0, 1); l1 += __shfl_xor_sync(0xffffffffu, l1, 1);
      l0 += __shfl_xor_sync(0xffffffffu, l0, 2); l1 += __shfl_xor_sync(0xffffffffu, l1, 2);
      const float i0 = __fdividef(1.f, l0), i1 = __fdividef(1.f, l1);
#pragma unroll
      for (int i = 0; i < 24; i++) { q[2 * i] = pack_bf16(o[4 * i] * i0, o[4 * i + 1] * i0); q[2 * i + 1] = pack_bf16(o[4 * i + 2] * i1, o[4 * i + 3] * i1); }
      TSA(item, 5);
    }
#pragma unroll
    for (int g = 0; g < 6; g++) { O_STORE(g) }
    SIGNAL();
    }
    TS(3, 2);
    const uint32_t st_w = (uint32_t)((warp * 16 + (lane >> 2)) * ST_P + (lane & 3) * 2) * 4;
    const uint32_t st_x = (lane & 8) << 2;
    const int er = (tid & 127) >> 1, eh = tid & 1;
    const uint32_t st_r = (uint32_t)(er * ST_P + (eh ^ ((er >> 1) & 1)) * 8) * 4;
    const uint32_t e_r = (uint32_t)((w * 64 + er) * 160 + eh * 16);
    const uint32_t p_r = par + eh * 32;
    const uint32_t stat = sb + T_PREP + w * 2048;
    const bool leader = (tid & 127) == 0;
#define STAGE10(ACC, BASE)                                                                                             \
    _Pragma("unroll") for (int nb = 0; nb < 10; nb++) {                                                                \
      sts_f2(stg + st_w + ((nb * 32) ^ st_x), ACC(BASE + 4 * nb), ACC(BASE + 4 * nb + 1));                                       \
      sts_f2(stg + st_w + ((nb * 32) ^ st_x) + 8 * ST_P * 4, ACC(BASE + 4 * nb + 2), ACC(BASE + 4 * nb + 3));                    \
    }

    {
      float acc1[96], acc2[64];
      uint32_t p0 = 0, p1 = 0, p2 = 0;
#pragma unroll 1
      for (int kb = 0; kb < 24; kb++) {
        const uint32_t s1 = r.slot; mbar_wait_c(bar_full + 8 * s1, r.phase); r.adv(A_NSLOT);
        const uint32_t s2 = r.slot; mbar_wait_c(bar_full + 8 * s2, r.phase); r.adv(A_NSLOT);
        const uint32_t sa = r.slot; mbar_wait_c(bar_full + 8 * sa, r.phase); r.adv(A_NSLOT);
        const uint64_t da = mkdesc(sb + sa * A_SLOT + w * 8192, 16, 1024);
        const uint64_t d1 = mkdesc(sb + s1 * A_SLOT, 8192, 1024), d2 = mkdesc(sb + s2 * A_SLOT, 8192, 1024);
        wg_fence();
#pragma unroll
        for (int kk = 0; kk < 4; kk++) {
          wgmma_ss_n192<1>(acc1, da + kk * 2, d1 + kk * 128, (kb | kk) != 0);
          wgmma_ss_n128<1>(acc2, da + kk * 2, d2 + kk * 128, (kb | kk) != 0);
        }
        wg_commit();
        if (kb > 0) { wg_wait<1>(); A_RELEASE(p0); A_RELEASE(p1); A_RELEASE(p2); }
        p0 = s1; p1 = s2; p2 = sa;
      }
      wg_wait<0>();
      fence_regs(acc1); fence_regs(acc2);
      A_RELEASE(p2);
      bar_sync(6, 288);
      TS(0, 0);
      const uint32_t stg = sb + (w ? p1 : p0) * A_SLOT;
#define OACC(e) (((e) < 96) ? acc1[(e) < 96 ? (e) : 0] : acc2[(e) >= 96 ? (e) - 96 : 0])
#define PACK10(BASE)                                                                                                   \
      _Pragma("unroll") for (int nb = 0; nb < 10; nb++) {                                                              \
        sts_u1(xo + nb * 16, pack_bf16(OACC(BASE + 4 * nb), OACC(BASE + 4 * nb + 1)));                                 \
        sts_u1(xo + nb * 16 + 8 * 160, pack_bf16(OACC(BASE + 4 * nb + 2), OACC(BASE + 4 * nb + 3)));                   \
      }
      const uint32_t f1 = r.slot + 4 >= A_NSLOT ? r.slot + 4 - A_NSLOT : r.slot + 4, f2 = f1 + 1 >= A_NSLOT ? 0 : f1 + 1;
#pragma unroll
      for (int d = 0; d < 4; d++) {
        if (d != o_ks) {
          const int i = (d - o_ks - 1) & 3;
          const uint32_t xo = sb + (i == 0 ? p2 : i == 1 ? f1 : f2) * A_SLOT + (w * 64 + warp * 16 + (lane >> 2)) * 160 + (lane & 3) * 4;
          PACK10(d * 40)
        }
      }
      fence_async_smem();
      bar_sync(3 + w, 128);
      if (leader) {
#pragma unroll 1
        for (int i = 0; i < 3; i++)
          bulk_store(g_xch + (size_t)((((o_qt * 2 + o_nh) * 4 + ((o_ks + 1 + i) & 3)) * 4) + o_ks) * (E_TILE / 2) + w * (E_TILE / 4),
                     sb + (i == 0 ? p2 : i == 1 ? f1 : f2) * A_SLOT + w * (E_TILE / 2), E_TILE / 2);
        bulk_done();
#pragma unroll 1
        for (int i = 0; i < 3; i++) flag_add(g_flag + F_XCH + (o_qt * 2 + o_nh) * 4 + ((o_ks + 1 + i) & 3));
        TX(40 + w);
      }
      if (o_ks == 0) { STAGE10(OACC, 0) } else if (o_ks == 1) { STAGE10(OACC, 40) } else if (o_ks == 2) { STAGE10(OACC, 80) } else { STAGE10(OACC, 120) }
      bar_sync(3 + w, 128);
      const uint32_t sx = r.slot; mbar_wait_c(bar_full + 8 * sx, r.phase); r.adv(A_NSLOT);
      const uint32_t q0 = r.slot; mbar_wait_c(bar_full + 8 * q0, r.phase); r.adv(A_NSLOT);
      const uint32_t q1 = r.slot; mbar_wait_c(bar_full + 8 * q1, r.phase); r.adv(A_NSLOT);
      const uint32_t q2 = r.slot; mbar_wait_c(bar_full + 8 * q2, r.phase); r.adv(A_NSLOT);
      TS(0, 1);
      float st[6] = {0.f, 0.f, 0.f, 0.f, 0.f, 0.f};
      const uint32_t ot = sb + p2 * A_SLOT;
#pragma unroll 1
      for (int c = 0; c < 5; c++) {
        float v[8], t0[8], t1[8], t2[8], xv[8], pg[8], pa_[8], pb_[8];
        lds8(stg + st_r + c * 64, v);
        lds8_bf(sb + q0 * A_SLOT + e_r + c * 32, t0); lds8_bf(sb + q1 * A_SLOT + e_r + c * 32, t1); lds8_bf(sb + q2 * A_SLOT + e_r + c * 32, t2);
        lds8_bf(sb + sx * A_SLOT + e_r + c * 32, xv);
        lds8(p_r + P_OGA * 4 + c * 64, pg); lds8(p_r + P_OA * 4 + c * 64, pa_); lds8(p_r + P_OB * 4 + c * 64, pb_);
#pragma unroll
        for (int e = 0; e < 8; e++) v[e] = fmaf(pg[e], v[e] + ((t0[e] + t1[e]) + t2[e]), xv[e]);
        const uint4 pk = pack8(v);
        sts_u4(ot + e_r + c * 32, pk);
        v[0] = bf_lo(pk.x); v[1] = bf_hi(pk.x); v[2] = bf_lo(pk.y); v[3] = bf_hi(pk.y); v[4] = bf_lo(pk.z); v[5] = bf_hi(pk.z); v[6] = bf_lo(pk.w); v[7] = bf_hi(pk.w);
#pragma unroll
        for (int e = 0; e < 8; e++) {
          const float y = pa_[e] * v[e];
          st[0] += v[e]; st[1] = fmaf(v[e], v[e], st[1]); st[2] += y; st[3] = fmaf(pa_[e], y, st[3]); st[4] = fmaf(y, y, st[4]); st[5] = fmaf(pb_[e], y, st[5]);
        }
      }
#pragma unroll
      for (int i = 0; i < 6; i++) st[i] += __shfl_xor_sync(0xffffffffu, st[i], 1);
      sts_u4(stat + er * 32 + eh * 16, eh ? make_uint4(__float_as_uint(st[4]), __float_as_uint(st[5]), 0u, 0u)
                                          : make_uint4(__float_as_uint(st[0]), __float_as_uint(st[1]), __float_as_uint(st[2]), __float_as_uint(st[3])));
      fence_async_smem();
      bar_sync(3 + w, 128);
      if (leader) {
        tma_store2d(&tm.sxa, ot + w * (E_TILE / 2), o_col, o_qt * 128 + w * 64);
        bulk_red_f32(g_st1 + (size_t)(o_qt * 128 + w * 64) * 8, stat, 2048);
        bulk_done();
        flag_add(g_flag + F_XA + o_qt);
      }
      bar_sync(5, 256);
      A_RELEASE(p0); A_RELEASE(p1); A_RELEASE(sx); A_RELEASE(q0); A_RELEASE(q1); A_RELEASE(q2);
      TS(0, 2);
    }

    Ring ra{0, 0};
    uint32_t bpar = 0;
    const uint32_t rel_a = mapa(mb_empty + 40, (lane == 0) ? rank : (rank ^ 1));
#define B_NEXT(s_) do { s_ = bs; mbar_wait_c(mb_full + 8 * bs, (bpar >> bs) & 1); bpar ^= 1u << bs; if (++bs == nbs) bs = 0; } while (0)
#define A_NEXT(s_) do { s_ = ra.slot; mbar_wait_c(mb_full + 40 + 8 * s_, ra.phase); ra.adv(M_NA); } while (0)
#define B_RELEASE(s_) do { if (lane == 0) mbar_arrive(mb_empty + 8 * (s_)); } while (0)
#define MA_RELEASE(s_) do { if (lane < 2) mbar_arrive_remote(rel_a + 8 * (s_)); } while (0)
    const int grow = qt * 128 + w * 64 + er;
    float mu = 0.f, rs = 0.f;
#pragma unroll 1
    for (int ph = 0; ph < 4; ph++) {
      float acc[96];
      float (&acc80)[40] = *reinterpret_cast<float(*)[40]>(&acc[0]);
      uint32_t pa = 0, pa2 = 0, pb = 0;
      float4 s03 = make_float4(0.f, 0.f, 0.f, 0.f);
      float2 s45 = make_float2(0.f, 0.f);
      const int nit = ph == 3 ? 12 : ph == 2 ? 10 : 5;
      const uint32_t nbs = ph == 2 ? 4 : 5, bsz = ph == 2 ? 24576 : 20480;
      uint32_t bs = 0;
#pragma unroll 1
      for (int it = 0; it < nit; it++) {
        uint32_t sbq, sa, sa2;
        B_NEXT(sbq);
        A_NEXT(sa);
        if (it == 0) TXC(ph);
        const uint64_t da = mkdesc(sb + M_AOFF + sa * 16384 + w * 8192, 16, 1024);
        if (ph == 2) {
          sa2 = sa;
          const uint64_t db = mkdesc(sb + sbq * 24576, 8192, 1024);
          wg_fence();
#pragma unroll
          for (int kk = 0; kk < 4; kk++) wgmma_ss_n192<1>(acc, da + kk * 2, db + kk * 128, (it | kk) != 0);
          wg_commit();
        } else {
          A_NEXT(sa2);
          const uint64_t da2 = mkdesc(sb + M_AOFF + sa2 * 16384 + w * 8192, 16, 1024);
          const uint64_t db = mkdesc(sb + sbq * 20480, 16, 1024);
          wg_fence();
#pragma unroll
          for (int kk = 0; kk < 4; kk++) wgmma_ss_n80<0>(acc80, da + kk * 2, db + kk * 2, (it | kk) != 0);
#pragma unroll
          for (int kk = 0; kk < 4; kk++) wgmma_ss_n80<0>(acc80, da2 + kk * 2, db + 640 + kk * 2, 1);
          wg_commit();
        }
        if (it > 0) { wg_wait<1>(); MA_RELEASE(pa); if (ph != 2) MA_RELEASE(pa2); B_RELEASE(pb); }
        else {
          if (ph == 0) { s03 = __ldcg(reinterpret_cast<const float4*>(g_st1 + (size_t)grow * 8)); s45 = __ldcg(reinterpret_cast<const float2*>(g_st1 + (size_t)grow * 8 + 4)); }
          if (ph == 2) s45 = __ldcg(reinterpret_cast<const float2*>(g_st2 + (size_t)grow * 2));
        }
        pa = sa; pa2 = sa2; pb = sbq;
      }
      wg_wait<0>();
      fence_regs(acc);
      MA_RELEASE(pa); if (ph != 2) MA_RELEASE(pa2);
      bar_sync(5, 256);
      TS(1 + (ph == 3 ? 0 : ph), ph == 3 ? 2 : 0);
      const uint32_t pb1 = pb == 0 ? nbs - 1 : pb - 1, pb2 = pb1 == 0 ? nbs - 1 : pb1 - 1, pb3 = pb2 == 0 ? nbs - 1 : pb2 - 1;
      const uint32_t stg = sb + (w ? pb : pb1) * bsz;
      uint32_t e1 = 0;
#define MACC(e) acc[e]
      if (!(ph & 1)) {
        float c0, c1, c2 = 0.f, c3 = 0.f;
        if (ph == 0) {
          const float4 sc = lds_f4(par + P_SC * 4);
          const float sbb = lds_f(par + (P_SC + 4) * 4);
          mu = s03.x * (1.f / D_);
          rs = rsqrtf(fmaxf(s03.y * (1.f / D_) - mu * mu, 0.f) + LN_EPS);
          const float m2 = (rs * (s03.z - mu * sc.x) + sc.w) * (1.f / D_);
          const float e2 = (rs * rs * (s45.x - 2.f * mu * s03.w + mu * mu * sc.y) + 2.f * rs * (s45.y - mu * sc.z) + sbb) * (1.f / D_);
          c2 = rsqrtf(fmaxf(e2 - m2 * m2, 0.f) + LN_EPS);
          c0 = c2 * rs; c1 = -c0 * mu; c3 = -c2 * m2;
          if (tid < 20) sts_u4(stat + 2048 * 2 + tid * 16, make_uint4(0, 0, 0, 0));
        } else {
          const float m = s45.x * (1.f / D_);
          c0 = rsqrtf(fmaxf(s45.y * (1.f / D_) - m * m, 0.f) + LN_EPS);
          c1 = -c0 * m;
        }
        const int npass = ph == 0 ? 1 : 3, nch = ph == 0 ? 5 : 4;
        const uint32_t ot = ph == 0 ? sb + pb2 * bsz + w * (E_TILE / 2) : sb + (w ? pb2 : pb3) * bsz;
#pragma unroll 1
        for (int ps = 0; ps < npass; ps++) {
          if (ps == 0) { STAGE10(MACC, 0) } else if (ps == 1) { STAGE10(MACC, 32) } else { STAGE10(MACC, 56) }
          bar_sync(3 + w, 128);
          const uint32_t cofs = ps == 2 ? 64 : 0;
          const uint32_t pp = p_r + (ph == 0 ? P_VA : P_CS3 + ps * 64) * 4, pq = p_r + P_VB * 4;
#pragma unroll 1
          for (int c = 0; c < nch; c++) {
            float v[8], t[8], t2[8], t3[8];
            lds8(stg + st_r + cofs + c * 64, v);
            lds8(pp + c * 64, t);
            if (ph == 0) {
              lds8(pq + c * 64, t2); lds8(pq + 320 + c * 64, t3);
#pragma unroll
              for (int e = 0; e < 8; e++) t[e] = fmaf(c1, t[e], fmaf(c2, t2[e], c3 * t3[e]));
            } else {
#pragma unroll
              for (int e = 0; e < 8; e++) t[e] *= c1;
            }
#pragma unroll
            for (int e = 0; e < 8; e++) v[e] = gelu_tanh(fmaf(c0, v[e], t[e]));
            sts_u4(ot + (ph == 0 ? er * 160 + eh * 16 + c * 32 : ps * 8192 + er * 128 + (((2 * c + eh) ^ (er & 7)) << 4)), pack8(v));
          }
          fence_async_smem();
          bar_sync(3 + w, 128);
          if (leader) {
            if (ph == 0) {
              const int grp = js >> 1;
              const int sh = (grp & 2 ? 2 : 1) * (grp & 1 ? -1 : 1);
              tma_store2d(&tm.sus, ot, js * 80, qt * 128 + w * 64 + sh + 2);
              if (w == 0 && qt == (sh > 0 ? 0 : 15)) {
                const int r0 = sh > 0 ? 0 : S_ + sh, n = sh > 0 ? sh : -sh;
                for (int i = 0; i < n; i++) bulk_store(g_us + (size_t)(r0 + i + 2) * D_ + js * 80, stat + 2048 * 2, 160);
              }
            } else {
              tma_store2d(&tm.g, ot + ps * 8192, js * 192 + ps * 64, qt * 128 + w * 64);
            }
          }
        }
      } else {
        STAGE10(MACC, 0)
        uint32_t e2;
        B_NEXT(e1);
        e2 = e1;
        if (ph == 3) B_NEXT(e2);
        bar_sync(3 + w, 128);
        float s1 = 0.f, s2 = 0.f;
        const uint32_t ot = sb + pb2 * bsz;
#pragma unroll 1
        for (int c = 0; c < 5; c++) {
          float v[8], xa[8], x1[8], ta[8], tb[8];
          lds8(stg + st_r + c * 64, v);
          lds8_bf(sb + e1 * 20480 + e_r + c * 32, xa); lds8_bf(sb + e2 * 20480 + e_r + c * 32, x1);
          lds8(p_r + (ph == 1 ? P_A2 : P_GB) * 4 + c * 64, ta); lds8(p_r + P_B2 * 4 + c * 64, tb);
          if (ph == 1) {
#pragma unroll
            for (int e = 0; e < 8; e++) v[e] += fmaf(ta[e] * rs, xa[e] - mu, tb[e]);
          } else {
#pragma unroll
            for (int e = 0; e < 8; e++) v[e] = fmaf(ta[e], v[e] + x1[e], xa[e]);
          }
          const uint4 pk = pack8(v);
          sts_u4(ot + e_r + c * 32, pk);
          v[0] = bf_lo(pk.x); v[1] = bf_hi(pk.x); v[2] = bf_lo(pk.y); v[3] = bf_hi(pk.y); v[4] = bf_lo(pk.z); v[5] = bf_hi(pk.z); v[6] = bf_lo(pk.w); v[7] = bf_hi(pk.w);
#pragma unroll
          for (int e = 0; e < 8; e++) { s1 += v[e]; s2 = fmaf(v[e], v[e], s2); }
        }
        s1 += __shfl_xor_sync(0xffffffffu, s1, 1); s2 += __shfl_xor_sync(0xffffffffu, s2, 1);
        if (eh == 0) sts_f2(stat + er * 8, s1, s2);
        fence_async_smem();
        bar_sync(3 + w, 128);
        if (leader) {
          tma_store2d(ph == 1 ? &tm.sx1 : &tm.sout, ot + w * (E_TILE / 2), js * 80, qt * 128 + w * 64);
          if (ph == 1) bulk_red_f32(g_st2 + (size_t)(qt * 128 + w * 64) * 2, stat, 512);
        }
      }
      if (leader) {
        bulk_done();
        if (ph < 3) flag_add(g_flag + F_US + 16 * ph + qt);
      }
      if (ph < 3) {
        bar_sync(5, 256);
        B_RELEASE(pb);
        if (ph == 1) B_RELEASE(e1);
      }
      TS(1 + (ph == 3 ? 0 : ph), ph == 3 ? 3 : 1);
    }
    if ((threadIdx.x & 127) == 0) TL_END(2);
    cluster_sync();
  }
}

typedef CUresult (*EncFn)(CUtensorMap*, CUtensorMapDataType, cuuint32_t, void*, const cuuint64_t*, const cuuint64_t*,
                          const cuuint32_t*, const cuuint32_t*, CUtensorMapInterleave, CUtensorMapSwizzle,
                          CUtensorMapL2promotion, CUtensorMapFloatOOBfill);
static EncFn g_enc = nullptr;

static CUtensorMap map2d(const void* p, uint64_t rows, uint64_t cols, uint32_t box_rows) {
  CUtensorMap m;
  cuuint64_t gd[2] = {cols, rows}; cuuint64_t gs[1] = {cols * 2};
  cuuint32_t bx[2] = {64, box_rows}; cuuint32_t es[2] = {1, 1};
  g_enc(&m, CU_TENSOR_MAP_DATA_TYPE_BFLOAT16, 2, const_cast<void*>(p), gd, gs, bx, es, CU_TENSOR_MAP_INTERLEAVE_NONE,
        CU_TENSOR_MAP_SWIZZLE_128B, CU_TENSOR_MAP_L2_PROMOTION_L2_256B, CU_TENSOR_MAP_FLOAT_OOB_FILL_NONE);
  return m;
}
static CUtensorMap map3d(const void* p, uint64_t rows, uint64_t cols, uint32_t box_rows, uint32_t nblk) {
  CUtensorMap m;
  cuuint64_t gd[3] = {64, rows, cols / 64}; cuuint64_t gs[2] = {cols * 2, 128};
  cuuint32_t bx[3] = {64, box_rows, nblk}; cuuint32_t es[3] = {1, 1, 1};
  g_enc(&m, CU_TENSOR_MAP_DATA_TYPE_BFLOAT16, 3, const_cast<void*>(p), gd, gs, bx, es, CU_TENSOR_MAP_INTERLEAVE_NONE,
        CU_TENSOR_MAP_SWIZZLE_128B, CU_TENSOR_MAP_L2_PROMOTION_L2_256B, CU_TENSOR_MAP_FLOAT_OOB_FILL_NONE);
  return m;
}

static CUtensorMap map_e(const void* p, uint32_t rows, uint64_t total_rows = S_) {
  CUtensorMap m;
  cuuint64_t gd[2] = {D_, total_rows}; cuuint64_t gs[1] = {D_ * 2};
  cuuint32_t bx[2] = {80, rows}; cuuint32_t es[2] = {1, 1};
  g_enc(&m, CU_TENSOR_MAP_DATA_TYPE_BFLOAT16, 2, const_cast<void*>(p), gd, gs, bx, es, CU_TENSOR_MAP_INTERLEAVE_NONE,
        CU_TENSOR_MAP_SWIZZLE_NONE, CU_TENSOR_MAP_L2_PROMOTION_L2_256B, CU_TENSOR_MAP_FLOAT_OOB_FILL_NONE);
  return m;
}

template <typename... KArgs, typename... Args>
static void launch(void (*kern)(KArgs...), dim3 grid, dim3 block, int smem, bool pdl, Args... args) {
  cudaLaunchConfig_t cfg = {};
  cfg.gridDim = grid; cfg.blockDim = block; cfg.dynamicSmemBytes = smem; cfg.stream = cudaStreamPerThread;
  cudaLaunchAttribute at[1];
  at[0].id = cudaLaunchAttributeProgrammaticStreamSerialization;
  at[0].val.programmaticStreamSerializationAllowed = 1;
  cfg.attrs = at; cfg.numAttrs = pdl ? 1 : 0;
  cudaLaunchKernelEx(&cfg, kern, KArgs(args)...);
}

extern "C" void kernel_launch(void* const* d_in, const int* in_sizes, int n_in, void* d_out, int out_size) {
  const bf16* x = (const bf16*)d_in[0];
  const bf16* kc = (const bf16*)d_in[1];
  const bf16* vc = (const bf16*)d_in[2];
  const bf16* wq = (const bf16*)d_in[3];
  const bf16* wo = (const bf16*)d_in[4];
  const bf16* w1 = (const bf16*)d_in[6];
  const bf16* w2 = (const bf16*)d_in[7];
  const bf16* w3 = (const bf16*)d_in[8];
  const bf16* w4 = (const bf16*)d_in[9];
  const bf16* c = (const bf16*)d_in[10];
  const bf16* wmod = (const bf16*)d_in[11];
  bf16* out = (bf16*)d_out;

  static void *p_h, *p_o, *p_xa, *p_us, *p_x1, *p_g, *p_w1t, *p_w2t, *p_w4t;
  if (!g_enc) {
    void* fn = nullptr; cudaDriverEntryPointQueryResult qr;
    cudaGetDriverEntryPoint("cuTensorMapEncodeTiled", &fn, cudaEnableDefault, &qr);
    g_enc = (EncFn)fn;
    cudaGetSymbolAddress(&p_h, g_h); cudaGetSymbolAddress(&p_o, g_o); cudaGetSymbolAddress(&p_xa, g_xa);
    cudaGetSymbolAddress(&p_us, g_us); cudaGetSymbolAddress(&p_x1, g_x1); cudaGetSymbolAddress(&p_g, g_g);
    cudaGetSymbolAddress(&p_w1t, g_w1t); cudaGetSymbolAddress(&p_w2t, g_w2t); cudaGetSymbolAddress(&p_w4t, g_w4t);
    cudaFuncSetAttribute(fused_kernel, cudaFuncAttributeMaxDynamicSharedMemorySize, T_SMEM);
  }
  Maps tm;
  tm.h = map2d(p_h, S_, D_, 128);
  tm.wq = map3d(wq, D_, HD_, 64, 3);
  tm.k = map3d(kc, (uint64_t)H_ * S_, DH_, 64, 3);
  tm.v = map3d(vc, (uint64_t)H_ * S_, DH_, 64, 3);
  tm.o = map2d(p_o, S_, HD_, 128);
  tm.wo3 = map3d(wo, HD_, D_, 64, 3);
  tm.wo2 = map3d(wo, HD_, D_, 64, 2);
  tm.xa = map2d(p_xa, S_, D_, 64);
  tm.w1t = map3d(p_w1t, D_, D_, 80, 2);
  tm.us = map2d((const bf16*)p_us + 2 * D_, S_, D_, 64);
  tm.w2t = map3d(p_w2t, D_, D_, 80, 2);
  tm.x1 = map2d(p_x1, S_, D_, 64);
  tm.w3 = map3d(w3, D_, F_, 64, 3);
  tm.g = map2d(p_g, S_, F_, 64);
  tm.w4t = map3d(p_w4t, D_, F_, 80, 2);
  tm.ex = map_e(x, 128); tm.exa = map_e(p_xa, 128); tm.ex1 = map_e(p_x1, 128);
  tm.sxa = map_e(p_xa, 64); tm.sus = map_e(p_us, 64, S_ + 4); tm.sx1 = map_e(p_x1, 64); tm.sout = map_e(out, 64);
  PfList pf;
  pf.p[0] = (const uint8_t*)wo; pf.p[1] = (const uint8_t*)w3; pf.p[2] = (const uint8_t*)p_w4t;
  pf.p[3] = (const uint8_t*)x; pf.p[4] = (const uint8_t*)p_w1t; pf.p[5] = (const uint8_t*)p_w2t;

  launch(mod_kernel, dim3(120), dim3(256), 0, false, c, wmod);
  launch(ln1_kernel, dim3(256), dim3(256), 0, true, x);
  launch(fused_kernel, dim3(128), dim3(384), T_SMEM, true, tm, pf, PrepW{w1, w2, w3, w4}, x, out);
}
```

```cpp
#include <cuda_runtime.h>
#include <cuda.h>
#include <cuda_bf16.h>
#include <stdint.h>

typedef __nv_bfloat16 bf16;

constexpr int S_  = 2048;
constexpr int D_  = 640;
constexpr int H_  = 32;
constexpr int DH_ = 192;
constexpr int HD_ = H_ * DH_;
constexpr int F_  = 1536;
constexpr float LN_EPS = 1e-5f;

__device__ __forceinline__ uint32_t smem_u32(const void* p) { return (uint32_t)__cvta_generic_to_shared(p); }
__device__ __forceinline__ void mbar_init(uint32_t a, uint32_t c) { asm volatile("mbarrier.init.shared::cta.b64 [%0], %1;" :: "r"(a), "r"(c) : "memory"); }
__device__ __forceinline__ void mbar_expect(uint32_t a, uint32_t b) { asm volatile("mbarrier.arrive.expect_tx.shared::cta.b64 _, [%0], %1;" :: "r"(a), "r"(b) : "memory"); }
__device__ __forceinline__ void mbar_arrive(uint32_t a) { asm volatile("mbarrier.arrive.shared::cta.b64 _, [%0];" :: "r"(a) : "memory"); }
__device__ __forceinline__ void mbar_arrive_remote(uint32_t ra) { asm volatile("mbarrier.arrive.shared::cluster.b64 _, [%0];" :: "r"(ra) : "memory"); }
__device__ __forceinline__ uint32_t mapa(uint32_t a, uint32_t cta) { uint32_t r; asm volatile("mapa.shared::cluster.u32 %0, %1, %2;" : "=r"(r) : "r"(a), "r"(cta)); return r; }
__device__ __forceinline__ uint32_t mbar_try(uint32_t a, uint32_t ph) {
  uint32_t ok;
  asm volatile("{\n.reg .pred p;\nmbarrier.test_wait.parity.shared::cta.b64 p, [%1], %2;\nselp.u32 %0, 1, 0, p;\n}\n" : "=r"(ok) : "r"(a), "r"(ph) : "memory");
  return ok;
}
__device__ __forceinline__ void mbar_wait(uint32_t a, uint32_t ph) {
  asm volatile(
      "{\n.reg .pred p;\n.reg .u32 n;\n"
      "mov.u32 n, 0;\n"
      "SPIN:\n"
      "mbarrier.try_wait.parity.shared::cta.b64 p, [%0], %1;\n"
      "@p bra DONE;\n"
      "add.u32 n, n, 1;\n"
      "setp.le.u32 p, n, 16777216;\n"
      "@p bra SPIN;\n"
      "trap;\n"
      "DONE:\n}\n" :: "r"(a), "r"(ph) : "memory");
}
#define ELECT_ "{\n.reg .pred p;\nelect.sync _|p, 0xffffffff;\n@p "
__device__ __forceinline__ void mbar_expect_e(uint32_t a, uint32_t b) { asm volatile(ELECT_ "mbarrier.arrive.expect_tx.shared::cta.b64 _, [%0], %1;\n}\n" :: "r"(a), "r"(b) : "memory"); }
__device__ __forceinline__ void tma2d(uint32_t dst, const CUtensorMap* m, uint32_t bar, int c0, int c1) {
  asm volatile(ELECT_ "cp.async.bulk.tensor.2d.shared::cluster.global.mbarrier::complete_tx::bytes [%0], [%1, {%3, %4}], [%2];\n}\n"
               :: "r"(dst), "l"(m), "r"(bar), "r"(c0), "r"(c1) : "memory");
}
__device__ __forceinline__ void tma2d_mc(uint32_t dst, const CUtensorMap* m, uint32_t bar, int c0, int c1, uint16_t mask) {
  asm volatile(ELECT_ "cp.async.bulk.tensor.2d.shared::cluster.global.mbarrier::complete_tx::bytes.multicast::cluster [%0], [%1, {%3, %4}], [%2], %5;\n}\n"
               :: "r"(dst), "l"(m), "r"(bar), "r"(c0), "r"(c1), "h"(mask) : "memory");
}
__device__ __forceinline__ void tma3d(uint32_t dst, const CUtensorMap* m, uint32_t bar, int c0, int c1, int c2) {
  asm volatile(ELECT_ "cp.async.bulk.tensor.3d.shared::cluster.global.mbarrier::complete_tx::bytes [%0], [%1, {%3, %4, %5}], [%2];\n}\n"
               :: "r"(dst), "l"(m), "r"(bar), "r"(c0), "r"(c1), "r"(c2) : "memory");
}
__device__ __forceinline__ void tma3d_mc(uint32_t dst, const CUtensorMap* m, uint32_t bar, int c0, int c1, int c2, uint16_t mask) {
  asm volatile(ELECT_ "cp.async.bulk.tensor.3d.shared::cluster.global.mbarrier::complete_tx::bytes.multicast::cluster [%0], [%1, {%3, %4, %5}], [%2], %6;\n}\n"
               :: "r"(dst), "l"(m), "r"(bar), "r"(c0), "r"(c1), "r"(c2), "h"(mask) : "memory");
}
__device__ __forceinline__ void tma3d_mc_hint(uint32_t dst, const CUtensorMap* m, uint32_t bar, int c0, int c1, int c2, uint16_t mask, uint64_t pol) {
  asm volatile(ELECT_ "cp.async.bulk.tensor.3d.shared::cluster.global.mbarrier::complete_tx::bytes.multicast::cluster.L2::cache_hint [%0], [%1, {%3, %4, %5}], [%2], %6, %7;\n}\n"
               :: "r"(dst), "l"(m), "r"(bar), "r"(c0), "r"(c1), "r"(c2), "h"(mask), "l"(pol) : "memory");
}
__device__ __forceinline__ void bulk_load(uint32_t dst, const void* src, uint32_t bytes, uint32_t bar) {
  asm volatile(ELECT_ "cp.async.bulk.shared::cluster.global.mbarrier::complete_tx::bytes [%0], [%1], %2, [%3];\n}\n"
               :: "r"(dst), "l"(src), "r"(bytes), "r"(bar) : "memory");
}
__device__ __forceinline__ void l2_prefetch16k(const void* p) { asm volatile(ELECT_ "cp.async.bulk.prefetch.L2.global [%0], 16384;\n}\n" :: "l"(p) : "memory"); }
__device__ __forceinline__ void l2_prefetch_t2d(const CUtensorMap* m, int c0, int c1) {
  asm volatile(ELECT_ "cp.async.bulk.prefetch.tensor.2d.L2.global [%0, {%1, %2}];\n}\n" :: "l"(m), "r"(c0), "r"(c1) : "memory");
}
__device__ __forceinline__ void l2_prefetch_t3d(const CUtensorMap* m, int c0, int c1, int c2) {
  asm volatile(ELECT_ "cp.async.bulk.prefetch.tensor.3d.L2.global [%0, {%1, %2, %3}];\n}\n" :: "l"(m), "r"(c0), "r"(c1), "r"(c2) : "memory");
}
__device__ __forceinline__ void stg128(void* p, uint4 v) {
  asm volatile("st.global.v4.u32 [%0], {%1, %2, %3, %4};" :: "l"(p), "r"(v.x), "r"(v.y), "r"(v.z), "r"(v.w) : "memory");
}
__device__ __forceinline__ void prefetch_tmap(const CUtensorMap* m) { asm volatile("prefetch.tensormap [%0];" :: "l"(m) : "memory"); }
__device__ __forceinline__ void wg_fence() { asm volatile("wgmma.fence.sync.aligned;" ::: "memory"); }
__device__ __forceinline__ void wg_commit() { asm volatile("wgmma.commit_group.sync.aligned;" ::: "memory"); }
template <int N> __device__ __forceinline__ void wg_wait() { asm volatile("wgmma.wait_group.sync.aligned %0;" :: "n"(N) : "memory"); }
template <int N> __device__ __forceinline__ void fence_regs(float (&r)[N]) {
#pragma unroll
  for (int i = 0; i < N; i++) asm volatile("" : "+f"(r[i]) :: "memory");
}
template <int N> __device__ __forceinline__ void fence_regs(uint32_t (&r)[N]) {
#pragma unroll
  for (int i = 0; i < N; i++) asm volatile("" : "+r"(r[i]) :: "memory");
}
__device__ __forceinline__ uint64_t mkdesc(uint32_t addr, uint32_t lbo, uint32_t sbo) {
  return (uint64_t)((addr & 0x3FFFF) >> 4) | ((uint64_t)(lbo >> 4) << 16) | ((uint64_t)(sbo >> 4) << 32) | (1ull << 62);
}
__device__ __forceinline__ void bar_sync(int id, int n) { asm volatile("bar.sync %0, %1;" :: "r"(id), "r"(n) : "memory"); }
__device__ __forceinline__ void bar_arrive(int id, int n) { asm volatile("bar.arrive %0, %1;" :: "r"(id), "r"(n) : "memory"); }
__device__ __forceinline__ void cluster_sync() { asm volatile("barrier.cluster.arrive.aligned;\nbarrier.cluster.wait.aligned;" ::: "memory"); }
__device__ __forceinline__ void pdl_wait() { asm volatile("griddepcontrol.wait;" ::: "memory"); }
__device__ __forceinline__ void pdl_launch() { asm volatile("griddepcontrol.launch_dependents;" ::: "memory"); }
__device__ __forceinline__ float ex2(float x) { float y; asm("ex2.approx.ftz.f32 %0, %1;" : "=f"(y) : "f"(x)); return y; }
__device__ __forceinline__ uint32_t pack_bf16(float lo, float hi) { uint32_t r; asm("cvt.rn.bf16x2.f32 %0, %1, %2;" : "=r"(r) : "f"(hi), "f"(lo)); return r; }
__device__ __forceinline__ float bf_lo(uint32_t u) { return __uint_as_float(u << 16); }
__device__ __forceinline__ float bf_hi(uint32_t u) { return __uint_as_float(u & 0xffff0000u); }
__device__ __forceinline__ float bf_round(float x) { return __bfloat162float(__float2bfloat16_rn(x)); }
__device__ __forceinline__ float tanh_fast(float x) { float y; asm("tanh.approx.f32 %0, %1;" : "=f"(y) : "f"(x)); return y; }
__device__ __forceinline__ float gelu_tanh(float x) {
  float u = x * (0.7978845608028654f + 0.035677408136300125f * x * x);
  float hx = 0.5f * x;
  return fmaf(hx, tanh_fast(u), hx);
}
__device__ __forceinline__ float warp_sum(float v) {
#pragma unroll
  for (int o = 16; o > 0; o >>= 1) v += __shfl_xor_sync(0xffffffffu, v, o);
  return v;
}
__device__ __forceinline__ void quad_transpose(uint32_t& v0, uint32_t& v1, uint32_t& v2, uint32_t& v3, int lane) {
  const bool b0 = lane & 1, b1 = lane & 2;
  uint32_t s0 = b0 ? v0 : v1, s1 = b0 ? v2 : v3;
  s0 = __shfl_xor_sync(0xffffffffu, s0, 1); s1 = __shfl_xor_sync(0xffffffffu, s1, 1);
  if (b0) { v0 = s0; v2 = s1; } else { v1 = s0; v3 = s1; }
  uint32_t t0 = b1 ? v0 : v2, t1 = b1 ? v1 : v3;
  t0 = __shfl_xor_sync(0xffffffffu, t0, 2); t1 = __shfl_xor_sync(0xffffffffu, t1, 2);
  if (b1) { v0 = t0; v1 = t1; } else { v2 = t0; v3 = t1; }
}

#define TX(i)
#define TXC(i)
#define TSA(item, i)
#define TL_ENTRY(k)
#define TL_WAITED(k)
#define TL_END(k)
#define TS(item, i)
template<int TB> __device__ __forceinline__ void wgmma_rs_n64(float (&d)[32], uint32_t a0, uint32_t a1, uint32_t a2, uint32_t a3, uint64_t db, int scale_d) {
  asm volatile("{\n.reg .pred p;\nsetp.ne.b32 p, %37, 0;\n"
    "wgmma.mma_async.sync.aligned.m64n64k16.f32.bf16.bf16 {%0, %1, %2, %3, %4, %5, %6, %7, %8, %9, %10, %11, %12, %13, %14, %15, %16, %17, %18, %19, %20, %21, %22, %23, %24, %25, %26, %27, %28, %29, %30, %31}, {%32, %33, %34, %35}, %36, p, 1, 1, %38;\n}\n"
    : "+f"(d[0]), "+f"(d[1]), "+f"(d[2]), "+f"(d[3]), "+f"(d[4]), "+f"(d[5]), "+f"(d[6]), "+f"(d[7]), "+f"(d[8]), "+f"(d[9]), "+f"(d[10]), "+f"(d[11]), "+f"(d[12]), "+f"(d[13]), "+f"(d[14]), "+f"(d[15]), "+f"(d[16]), "+f"(d[17]), "+f"(d[18]), "+f"(d[19]), "+f"(d[20]), "+f"(d[21]), "+f"(d[22]), "+f"(d[23]), "+f"(d[24]), "+f"(d[25]), "+f"(d[26]), "+f"(d[27]), "+f"(d[28]), "+f"(d[29]), "+f"(d[30]), "+f"(d[31])
    : "r"(a0), "r"(a1), "r"(a2), "r"(a3), "l"(db), "r"(scale_d), "n"(TB));
}
template<int TB> __device__ __forceinline__ void wgmma_rs_n192(float (&d)[96], uint32_t a0, uint32_t a1, uint32_t a2, uint32_t a3, uint64_t db, int scale_d) {
  asm volatile("{\n.reg .pred p;\nsetp.ne.b32 p, %101, 0;\n"
    "wgmma.mma_async.sync.aligned.m64n192k16.f32.bf16.bf16 {%0, %1, %2, %3, %4, %5, %6, %7, %8, %9, %10, %11, %12, %13, %14, %15, %16, %17, %18, %19, %20, %21, %22, %23, %24, %25, %26, %27, %28, %29, %30, %31, %32, %33, %34, %35, %36, %37, %38, %39, %40, %41, %42, %43, %44, %45, %46, %47, %48, %49, %50, %51, %52, %53, %54, %55, %56, %57, %58, %59, %60, %61, %62, %63, %64, %65, %66, %67, %68, %69, %70, %71, %72, %73, %74, %75, %76, %77, %78, %79, %80, %81, %82, %83, %84, %85, %86, %87, %88, %89, %90, %91, %92, %93, %94, %95}, {%96, %97, %98, %99}, %100, p, 1, 1, %102;\n}\n"
    : "+f"(d[0]), "+f"(d[1]), "+f"(d[2]), "+f"(d[3]), "+f"(d[4]), "+f"(d[5]), "+f"(d[6]), "+f"(d[7]), "+f"(d[8]), "+f"(d[9]), "+f"(d[10]), "+f"(d[11]), "+f"(d[12]), "+f"(d[13]), "+f"(d[14]), "+f"(d[15]), "+f"(d[16]), "+f"(d[17]), "+f"(d[18]), "+f"(d[19]), "+f"(d[20]), "+f"(d[21]), "+f"(d[22]), "+f"(d[23]), "+f"(d[24]), "+f"(d[25]), "+f"(d[26]), "+f"(d[27]), "+f"(d[28]), "+f"(d[29]), "+f"(d[30]), "+f"(d[31]), "+f"(d[32]), "+f"(d[33]), "+f"(d[34]), "+f"(d[35]), "+f"(d[36]), "+f"(d[37]), "+f"(d[38]), "+f"(d[39]), "+f"(d[40]), "+f"(d[41]), "+f"(d[42]), "+f"(d[43]), "+f"(d[44]), "+f"(d[45]), "+f"(d[46]), "+f"(d[47]), "+f"(d[48]), "+f"(d[49]), "+f"(d[50]), "+f"(d[51]), "+f"(d[52]), "+f"(d[53]), "+f"(d[54]), "+f"(d[55]), "+f"(d[56]), "+f"(d[57]), "+f"(d[58]), "+f"(d[59]), "+f"(d[60]), "+f"(d[61]), "+f"(d[62]), "+f"(d[63]), "+f"(d[64]), "+f"(d[65]), "+f"(d[66]), "+f"(d[67]), "+f"(d[68]), "+f"(d[69]), "+f"(d[70]), "+f"(d[71]), "+f"(d[72]), "+f"(d[73]), "+f"(d[74]), "+f"(d[75]), "+f"(d[76]), "+f"(d[77]), "+f"(d[78]), "+f"(d[79]), "+f"(d[80]), "+f"(d[81]), "+f"(d[82]), "+f"(d[83]), "+f"(d[84]), "+f"(d[85]), "+f"(d[86]), "+f"(d[87]), "+f"(d[88]), "+f"(d[89]), "+f"(d[90]), "+f"(d[91]), "+f"(d[92]), "+f"(d[93]), "+f"(d[94]), "+f"(d[95])
    : "r"(a0), "r"(a1), "r"(a2), "r"(a3), "l"(db), "r"(scale_d), "n"(TB));
}
template<int TB> __device__ __forceinline__ void wgmma_ss_n128(float (&d)[64], uint64_t da, uint64_t db, int scale_d) {
  asm volatile("{\n.reg .pred p;\nsetp.ne.b32 p, %66, 0;\n"
    "wgmma.mma_async.sync.aligned.m64n128k16.f32.bf16.bf16 {%0, %1, %2, %3, %4, %5, %6, %7, %8, %9, %10, %11, %12, %13, %14, %15, %16, %17, %18, %19, %20, %21, %22, %23, %24, %25, %26, %27, %28, %29, %30, %31, %32, %33, %34, %35, %36, %37, %38, %39, %40, %41, %42, %43, %44, %45, %46, %47, %48, %49, %50, %51, %52, %53, %54, %55, %56, %57, %58, %59, %60, %61, %62, %63}, %64, %65, p, 1, 1, 0, %67;\n}\n"
    : "+f"(d[0]), "+f"(d[1]), "+f"(d[2]), "+f"(d[3]), "+f"(d[4]), "+f"(d[5]), "+f"(d[6]), "+f"(d[7]), "+f"(d[8]), "+f"(d[9]), "+f"(d[10]), "+f"(d[11]), "+f"(d[12]), "+f"(d[13]), "+f"(d[14]), "+f"(d[15]), "+f"(d[16]), "+f"(d[17]), "+f"(d[18]), "+f"(d[19]), "+f"(d[20]), "+f"(d[21]), "+f"(d[22]), "+f"(d[23]), "+f"(d[24]), "+f"(d[25]), "+f"(d[26]), "+f"(d[27]), "+f"(d[28]), "+f"(d[29]), "+f"(d[30]), "+f"(d[31]), "+f"(d[32]), "+f"(d[33]), "+f"(d[34]), "+f"(d[35]), "+f"(d[36]), "+f"(d[37]), "+f"(d[38]), "+f"(d[39]), "+f"(d[40]), "+f"(d[41]), "+f"(d[42]), "+f"(d[43]), "+f"(d[44]), "+f"(d[45]), "+f"(d[46]), "+f"(d[47]), "+f"(d[48]), "+f"(d[49]), "+f"(d[50]), "+f"(d[51]), "+f"(d[52]), "+f"(d[53]), "+f"(d[54]), "+f"(d[55]), "+f"(d[56]), "+f"(d[57]), "+f"(d[58]), "+f"(d[59]), "+f"(d[60]), "+f"(d[61]), "+f"(d[62]), "+f"(d[63])
    : "l"(da), "l"(db), "r"(scale_d), "n"(TB));
}
template<int TB> __device__ __forceinline__ void wgmma_ss_n192(float (&d)[96], uint64_t da, uint64_t db, int scale_d) {
  asm volatile("{\n.reg .pred p;\nsetp.ne.b32 p, %98, 0;\n"
    "wgmma.mma_async.sync.aligned.m64n192k16.f32.bf16.bf16 {%0, %1, %2, %3, %4, %5, %6, %7, %8, %9, %10, %11, %12, %13, %14, %15, %16, %17, %18, %19, %20, %21, %22, %23, %24, %25, %26, %27, %28, %29, %30, %31, %32, %33, %34, %35, %36, %37, %38, %39, %40, %41, %42, %43, %44, %45, %46, %47, %48, %49, %50, %51, %52, %53, %54, %55, %56, %57, %58, %59, %60, %61, %62, %63, %64, %65, %66, %67, %68, %69, %70, %71, %72, %73, %74, %75, %76, %77, %78, %79, %80, %81, %82, %83, %84, %85, %86, %87, %88, %89, %90, %91, %92, %93, %94, %95}, %96, %97, p, 1, 1, 0, %99;\n}\n"
    : "+f"(d[0]), "+f"(d[1]), "+f"(d[2]), "+f"(d[3]), "+f"(d[4]), "+f"(d[5]), "+f"(d[6]), "+f"(d[7]), "+f"(d[8]), "+f"(d[9]), "+f"(d[10]), "+f"(d[11]), "+f"(d[12]), "+f"(d[13]), "+f"(d[14]), "+f"(d[15]), "+f"(d[16]), "+f"(d[17]), "+f"(d[18]), "+f"(d[19]), "+f"(d[20]), "+f"(d[21]), "+f"(d[22]), "+f"(d[23]), "+f"(d[24]), "+f"(d[25]), "+f"(d[26]), "+f"(d[27]), "+f"(d[28]), "+f"(d[29]), "+f"(d[30]), "+f"(d[31]), "+f"(d[32]), "+f"(d[33]), "+f"(d[34]), "+f"(d[35]), "+f"(d[36]), "+f"(d[37]), "+f"(d[38]), "+f"(d[39]), "+f"(d[40]), "+f"(d[41]), "+f"(d[42]), "+f"(d[43]), "+f"(d[44]), "+f"(d[45]), "+f"(d[46]), "+f"(d[47]), "+f"(d[48]), "+f"(d[49]), "+f"(d[50]), "+f"(d[51]), "+f"(d[52]), "+f"(d[53]), "+f"(d[54]), "+f"(d[55]), "+f"(d[56]), "+f"(d[57]), "+f"(d[58]), "+f"(d[59]), "+f"(d[60]), "+f"(d[61]), "+f"(d[62]), "+f"(d[63]), "+f"(d[64]), "+f"(d[65]), "+f"(d[66]), "+f"(d[67]), "+f"(d[68]), "+f"(d[69]), "+f"(d[70]), "+f"(d[71]), "+f"(d[72]), "+f"(d[73]), "+f"(d[74]), "+f"(d[75]), "+f"(d[76]), "+f"(d[77]), "+f"(d[78]), "+f"(d[79]), "+f"(d[80]), "+f"(d[81]), "+f"(d[82]), "+f"(d[83]), "+f"(d[84]), "+f"(d[85]), "+f"(d[86]), "+f"(d[87]), "+f"(d[88]), "+f"(d[89]), "+f"(d[90]), "+f"(d[91]), "+f"(d[92]), "+f"(d[93]), "+f"(d[94]), "+f"(d[95])
    : "l"(da), "l"(db), "r"(scale_d), "n"(TB));
}
template<int TB> __device__ __forceinline__ void wgmma_ss_n80(float (&d)[40], uint64_t da, uint64_t db, int scale_d) {
  asm volatile("{\n.reg .pred p;\nsetp.ne.b32 p, %42, 0;\n"
    "wgmma.mma_async.sync.aligned.m64n80k16.f32.bf16.bf16 {%0, %1, %2, %3, %4, %5, %6, %7, %8, %9, %10, %11, %12, %13, %14, %15, %16, %17, %18, %19, %20, %21, %22, %23, %24, %25, %26, %27, %28, %29, %30, %31, %32, %33, %34, %35, %36, %37, %38, %39}, %40, %41, p, 1, 1, 0, %43;\n}\n"
    : "+f"(d[0]), "+f"(d[1]), "+f"(d[2]), "+f"(d[3]), "+f"(d[4]), "+f"(d[5]), "+f"(d[6]), "+f"(d[7]), "+f"(d[8]), "+f"(d[9]), "+f"(d[10]), "+f"(d[11]), "+f"(d[12]), "+f"(d[13]), "+f"(d[14]), "+f"(d[15]), "+f"(d[16]), "+f"(d[17]), "+f"(d[18]), "+f"(d[19]), "+f"(d[20]), "+f"(d[21]), "+f"(d[22]), "+f"(d[23]), "+f"(d[24]), "+f"(d[25]), "+f"(d[26]), "+f"(d[27]), "+f"(d[28]), "+f"(d[29]), "+f"(d[30]), "+f"(d[31]), "+f"(d[32]), "+f"(d[33]), "+f"(d[34]), "+f"(d[35]), "+f"(d[36]), "+f"(d[37]), "+f"(d[38]), "+f"(d[39])
    : "l"(da), "l"(db), "r"(scale_d), "n"(TB));
}

__device__ float g_mod[6 * D_];
__device__ __align__(1024) bf16 g_h[S_ * D_];
__device__ __align__(1024) bf16 g_o[S_ * HD_];
__device__ __align__(1024) bf16 g_xch[16 * 2 * 4 * 4 * 128 * 80];
__device__ __align__(1024) bf16 g_w1t[D_ * D_];
__device__ __align__(1024) bf16 g_w2t[D_ * D_];
__device__ __align__(1024) bf16 g_w4t[D_ * F_];
__device__ __align__(32) float g_st1[S_ * 8];
__device__ __align__(32) float g_st2[S_ * 2];
__device__ __align__(32) float g_vec[3 * D_ + F_ + 8];
__device__ unsigned g_flag[1024];
enum { F_XCH = 0, F_XA = 256, F_US = 272, F_X1 = 288, F_G = 304, F_PREP = 320, F_O = 512 };
__device__ __align__(1024) bf16 g_xa[S_ * D_];
__device__ __align__(1024) bf16 g_us[(S_ + 4) * D_];
__device__ __align__(1024) bf16 g_x1[S_ * D_];
__device__ __align__(1024) bf16 g_g[S_ * F_];

__global__ void __launch_bounds__(256) mod_kernel(const bf16* __restrict__ c, const bf16* __restrict__ w_mod) {
  TL_ENTRY(0);
  pdl_launch();
  __shared__ float red[8][32];
  if (blockIdx.x < 14) { const int i = blockIdx.x * 256 + threadIdx.x; if (i < 3 * D_ + F_) g_vec[i] = 0.f; }
  else if (blockIdx.x < 18) g_flag[(blockIdx.x - 14) * 256 + threadIdx.x] = 0u;
  const int t = threadIdx.x, cg = t & 3, r0 = t >> 2;
  const int col0 = blockIdx.x * 32 + cg * 8;
  uint4 w[10];
#pragma unroll
  for (int i = 0; i < 10; i++) w[i] = __ldg(reinterpret_cast<const uint4*>(w_mod + (size_t)(r0 + 64 * i) * (6 * D_) + col0));
  float acc[8];
#pragma unroll
  for (int j = 0; j < 8; j++) acc[j] = 0.f;
#pragma unroll
  for (int i = 0; i < 10; i++) {
    float cv = __bfloat162float(c[r0 + 64 * i]);
    float s = bf_round(cv / (1.f + __expf(-cv)));
    acc[0] = fmaf(s, bf_lo(w[i].x), acc[0]); acc[1] = fmaf(s, bf_hi(w[i].x), acc[1]);
    acc[2] = fmaf(s, bf_lo(w[i].y), acc[2]); acc[3] = fmaf(s, bf_hi(w[i].y), acc[3]);
    acc[4] = fmaf(s, bf_lo(w[i].z), acc[4]); acc[5] = fmaf(s, bf_hi(w[i].z), acc[5]);
    acc[6] = fmaf(s, bf_lo(w[i].w), acc[6]); acc[7] = fmaf(s, bf_hi(w[i].w), acc[7]);
  }
#pragma unroll
  for (int j = 0; j < 8; j++) {
    acc[j] += __shfl_xor_sync(0xffffffffu, acc[j], 4);
    acc[j] += __shfl_xor_sync(0xffffffffu, acc[j], 8);
    acc[j] += __shfl_xor_sync(0xffffffffu, acc[j], 16);
  }
  if ((t & 31) < 4) {
#pragma unroll
    for (int j = 0; j < 8; j++) red[t >> 5][cg * 8 + j] = acc[j];
  }
  __syncthreads();
  if (t < 32) {
    float s = 0.f;
#pragma unroll
    for (int w8 = 0; w8 < 8; w8++) s += red[w8][t];
    const int col = blockIdx.x * 32 + t;
    s = bf_round(s);
    const int part = col / D_;
    if (part == 1 || part == 4) s = bf_round(1.f + s);
    g_mod[col] = s;
    if (t == 0) TL_END(0);
  }
}

__device__ __forceinline__ void row_stats(const float (&v)[20], float& mean, float& rstd) {
  float s = 0.f;
#pragma unroll
  for (int i = 0; i < 20; i++) s += v[i];
  mean = warp_sum(s) * (1.f / D_);
  float q = 0.f;
#pragma unroll
  for (int i = 0; i < 20; i++) { float d = v[i] - mean; q = fmaf(d, d, q); }
  rstd = rsqrtf(warp_sum(q) * (1.f / D_) + LN_EPS);
}
__device__ __forceinline__ void load_row_bf16(const bf16* p, int lane, float (&v)[20]) {
#pragma unroll
  for (int i = 0; i < 5; i++) {
    uint2 u = *reinterpret_cast<const uint2*>(p + (lane + 32 * i) * 4);
    v[4 * i] = bf_lo(u.x); v[4 * i + 1] = bf_hi(u.x); v[4 * i + 2] = bf_lo(u.y); v[4 * i + 3] = bf_hi(u.y);
  }
}
__device__ __forceinline__ void store_row_bf16(bf16* p, int lane, const float (&v)[20]) {
#pragma unroll
  for (int i = 0; i < 5; i++) {
    uint2 u; u.x = pack_bf16(v[4 * i], v[4 * i + 1]); u.y = pack_bf16(v[4 * i + 2], v[4 * i + 3]);
    *reinterpret_cast<uint2*>(p + (lane + 32 * i) * 4) = u;
  }
}
__device__ __forceinline__ void load_row_f32(const float* p, int lane, float (&v)[20]) {
#pragma unroll
  for (int i = 0; i < 5; i++) {
    float4 u = *reinterpret_cast<const float4*>(p + (lane + 32 * i) * 4);
    v[4 * i] = u.x; v[4 * i + 1] = u.y; v[4 * i + 2] = u.z; v[4 * i + 3] = u.w;
  }
}

__global__ void __launch_bounds__(256) ln1_kernel(const bf16* __restrict__ x) {
  TL_ENTRY(1);
  pdl_launch();
  const int lane = threadIdx.x & 31, row = blockIdx.x * 8 + (threadIdx.x >> 5);
  float v[20];
  load_row_bf16(x + (size_t)row * D_, lane, v);
  float mean, rstd;
  row_stats(v, mean, rstd);
  if (lane < 8) g_st1[row * 8 + lane] = 0.f;
  if (lane < 2) g_st2[row * 2 + lane] = 0.f;
  pdl_wait();
  if (threadIdx.x == 0) TL_WAITED(1);
  float sa[20], ca[20];
  load_row_f32(g_mod, lane, sa);
  load_row_f32(g_mod + D_, lane, ca);
#pragma unroll
  for (int i = 0; i < 20; i++) v[i] = fmaf((v[i] - mean) * rstd, ca[i], sa[i]);
  store_row_bf16(g_h + (size_t)row * D_, lane, v);
  if (threadIdx.x == 0) TL_END(1);
}

constexpr int PREP_JOBS = 200 + 200 + 480 + 480;
struct PrepW { const bf16 *w1, *w2, *w3, *w4; };
__device__ __forceinline__ void prep_warp(const PrepW& pw, bf16 (*tile)[72], int lane) {
#pragma unroll 1
  for (int job = blockIdx.x; job < PREP_JOBS; job += gridDim.x) {
    const bf16* src; bf16* dst; int ld = D_, ldd = D_, kt, nt, kind = 1;
    if (job < 200) { src = pw.w1; dst = g_w1t; kt = job / 10; nt = job % 10; kind = 0; }
    else if (job < 400) { src = pw.w2; dst = g_w2t; kt = (job - 200) / 10; nt = (job - 200) % 10; }
    else if (job < 880) { src = pw.w4; dst = g_w4t; ldd = F_; kt = (job - 400) / 10; nt = (job - 400) % 10; }
    else { src = pw.w3; dst = nullptr; ld = F_; kt = (job - 880) / 24; nt = (job - 880) % 24; kind = 2; }
    src += (size_t)(kt * 32 + (lane >> 3)) * ld + nt * 64 + (lane & 7) * 8;
    __syncwarp();
#pragma unroll
    for (int h = 0; h < 2; h++) {
      uint4 v[4];
#pragma unroll
      for (int i = 0; i < 4; i++) v[i] = __ldg(reinterpret_cast<const uint4*>(src + (size_t)(h * 16 + i * 4) * ld));
#pragma unroll
      for (int i = 0; i < 4; i++) *reinterpret_cast<uint4*>(&tile[h * 16 + i * 4 + (lane >> 3)][(lane & 7) * 8]) = v[i];
    }
    __syncwarp();
    const float* pa = g_mod + 4 * D_ + kt * 32;
    const float* pb = g_mod + 3 * D_ + kt * 32;
#pragma unroll 1
    for (int h = 0; h < 2; h++) {
      const int n = lane + 32 * h;
      float sa = 0.f, sb = 0.f, sc = 0.f;
#pragma unroll 1
      for (int c = 0; c < 4; c++) {
        uint32_t u[4];
#pragma unroll
        for (int e = 0; e < 4; e++) {
          const int k = c * 8 + 2 * e;
          float lo = __bfloat162float(tile[k][n]), hi = __bfloat162float(tile[k + 1][n]);
          sc += lo + hi;
          if (kind == 0) {
            const float2 a = __ldcg(reinterpret_cast<const float2*>(pa + k)), b = __ldcg(reinterpret_cast<const float2*>(pb + k));
            sb = fmaf(b.x, lo, fmaf(b.y, hi, sb));
            lo *= a.x; hi *= a.y;
          }
          u[e] = pack_bf16(lo, hi);
          sa += bf_lo(u[e]) + bf_hi(u[e]);
        }
        if (kind != 2) *reinterpret_cast<uint4*>(dst + (size_t)(nt * 64 + n) * ldd + kt * 32 + c * 8) = make_uint4(u[0], u[1], u[2], u[3]);
      }
      if (kind == 0) { atomicAdd(&g_vec[nt * 64 + n], sa); atomicAdd(&g_vec[D_ + nt * 64 + n], sb); atomicAdd(&g_vec[2 * D_ + nt * 64 + n], sc); }
      else if (kind == 2) atomicAdd(&g_vec[3 * D_ + nt * 64 + n], sc);
    }
  }
  __syncwarp();
  if (lane == 0) {
    asm volatile("fence.acq_rel.gpu;" ::: "memory");
    asm volatile("red.relaxed.gpu.global.add.u32 [%0], 1;" :: "l"(g_flag + F_PREP) : "memory");
  }
}

constexpr int A_NSLOT = 9;
constexpr int A_SLOT = 24576;
constexpr int A_NKV = S_ / 64;
constexpr int PREP_CTAS = 128;

struct Ring {
  uint32_t slot, phase;
  __device__ __forceinline__ void adv(int n) { if (++slot == (uint32_t)n) { slot = 0; phase ^= 1; } }
};
constexpr int T_PAR = A_NSLOT * A_SLOT + 384;
constexpr int T_PREP = T_PAR + 3712;
constexpr int T_SMEM = T_PREP + 32 * 72 * 2 + 1024;
enum { P_OGA = 0, P_OA = 80, P_OB = 160, P_VA = 240, P_VB = 320, P_VC = 400, P_A2 = 480, P_B2 = 560, P_GB = 640, P_CS3 = 720, P_SC = 912 };

__device__ __forceinline__ void flag_wait(const unsigned* p, unsigned target) {
  asm volatile(
      "{\n.reg .pred p;\n.reg .u32 n, v;\n"
      "mov.u32 n, 0;\n"
      "SPIN:\n"
      "ld.relaxed.gpu.global.u32 v, [%0];\n"
      "setp.ge.u32 p, v, %1;\n"
      "@p bra DONE;\n"
      "add.u32 n, n, 1;\n"
      "setp.gt.u32 p, n, 4194304;\n"
      "@p trap;\n"
      "bra SPIN;\n"
      "DONE:\n}\n" :: "l"(p), "r"(target) : "memory");
}
__device__ __forceinline__ void fence_async_global() { asm volatile("fence.proxy.async.global;" ::: "memory"); }
__device__ __forceinline__ float lds_f(uint32_t a) { float v; asm volatile("ld.shared.f32 %0, [%1];" : "=f"(v) : "r"(a)); return v; }
__device__ __forceinline__ float2 lds_f2(uint32_t a) { float2 v; asm volatile("ld.shared.v2.f32 {%0, %1}, [%2];" : "=f"(v.x), "=f"(v.y) : "r"(a)); return v; }
__device__ __forceinline__ uint4 ldcg4(const void* p) { return __ldcg(reinterpret_cast<const uint4*>(p)); }

__device__ __forceinline__ void sts_f2(uint32_t a, float x, float y) { asm volatile("st.shared.v2.f32 [%0], {%1, %2};" :: "r"(a), "f"(x), "f"(y) : "memory"); }
__device__ __forceinline__ void sts_u4(uint32_t a, uint4 v) { asm volatile("st.shared.v4.u32 [%0], {%1, %2, %3, %4};" :: "r"(a), "r"(v.x), "r"(v.y), "r"(v.z), "r"(v.w) : "memory"); }
__device__ __forceinline__ void sts_u1(uint32_t a, uint32_t v) { asm volatile("st.shared.u32 [%0], %1;" :: "r"(a), "r"(v) : "memory"); }
__device__ __forceinline__ void fence_async_smem() { asm volatile("fence.proxy.async.shared::cta;" ::: "memory"); }
__device__ __forceinline__ void bulk_store(void* dst, uint32_t src, uint32_t bytes) {
  asm volatile("cp.async.bulk.global.shared::cta.bulk_group [%0], [%1], %2;" :: "l"(dst), "r"(src), "r"(bytes) : "memory");
}
__device__ __forceinline__ void bulk_red_f32(void* dst, uint32_t src, uint32_t bytes) {
  asm volatile("cp.reduce.async.bulk.global.shared::cta.bulk_group.add.f32 [%0], [%1], %2;" :: "l"(dst), "r"(src), "r"(bytes) : "memory");
}
__device__ __forceinline__ void tma_store2d(const CUtensorMap* m, uint32_t src, int c0, int c1) {
  asm volatile("cp.async.bulk.tensor.2d.global.shared::cta.bulk_group [%0, {%2, %3}], [%1];" :: "l"(m), "r"(src), "r"(c0), "r"(c1) : "memory");
}
__device__ __forceinline__ void bulk_done() { asm volatile("cp.async.bulk.commit_group;\ncp.async.bulk.wait_group 0;" ::: "memory"); }
__device__ __forceinline__ void flag_add(unsigned* f) { asm volatile("red.relaxed.gpu.global.add.u32 [%0], 1;" :: "l"(f) : "memory"); }
__device__ __forceinline__ float4 lds_f4(uint32_t a) { return *reinterpret_cast<const float4*>(__cvta_shared_to_generic(a)); }
__device__ __forceinline__ uint4 lds_u4(uint32_t a) { return *reinterpret_cast<const uint4*>(__cvta_shared_to_generic(a)); }
__device__ __forceinline__ void lds8(uint32_t a, float (&v)[8]) {
  const float4 p = lds_f4(a), q = lds_f4(a + 16);
  v[0] = p.x; v[1] = p.y; v[2] = p.z; v[3] = p.w; v[4] = q.x; v[5] = q.y; v[6] = q.z; v[7] = q.w;
}
__device__ __forceinline__ void lds8_bf(uint32_t a, float (&v)[8]) {
  const uint4 u = lds_u4(a);
  v[0] = bf_lo(u.x); v[1] = bf_hi(u.x); v[2] = bf_lo(u.y); v[3] = bf_hi(u.y); v[4] = bf_lo(u.z); v[5] = bf_hi(u.z); v[6] = bf_lo(u.w); v[7] = bf_hi(u.w);
}
__device__ __forceinline__ uint4 pack8(const float (&v)[8]) {
  return make_uint4(pack_bf16(v[0], v[1]), pack_bf16(v[2], v[3]), pack_bf16(v[4], v[5]), pack_bf16(v[6], v[7]));
}
__device__ __forceinline__ void mbar_wait_c(uint32_t a, uint32_t ph) {
  asm volatile("{\n.reg .pred p;\nSPIN:\nmbarrier.try_wait.parity.shared::cta.b64 p, [%0], %1;\n@!p bra SPIN;\n}\n" :: "r"(a), "r"(ph) : "memory");
}
constexpr int ST_P = 80;
constexpr int E_TILE = 128 * 80 * 2;

struct Maps { CUtensorMap h, wq, k, v, o, wo3, wo2, xa, w1t, us, w2t, x1, w3, g, w4t, ex, exa, ex1, sxa, sus, sx1, sout; };
struct PfList { const uint8_t* p[6]; };

constexpr int M_AOFF = 102400, M_NA = 7;

__global__ void __cluster_dims__(2, 1, 1) __launch_bounds__(384, 1)
fused_kernel(const __grid_constant__ Maps tm, const __grid_constant__ PfList pf, const __grid_constant__ PrepW pw, const bf16* __restrict__ x, bf16* __restrict__ out) {
  extern __shared__ uint8_t smem_raw[];
  const uint32_t sb = (smem_u32(smem_raw) + 1023) & ~1023u;
  TL_ENTRY(2);
  const uint32_t bar_full = sb + A_NSLOT * A_SLOT;
  const uint32_t bar_empty = bar_full + 8 * A_NSLOT;
  const uint32_t bar_sig = bar_empty + 8 * A_NSLOT;
  const uint32_t mb_full = bar_sig + 16;
  const uint32_t mb_empty = mb_full + 96;
  const uint32_t par = sb + T_PAR;
  float* parf = reinterpret_cast<float*>(smem_raw + (par - smem_u32(smem_raw)));
  uint32_t rank;
  asm volatile("mov.u32 %0, %%cluster_ctarank;" : "=r"(rank));
  const int cid = blockIdx.x >> 1;
  const int wid = __shfl_sync(0xffffffffu, threadIdx.x >> 5, 0);
  const int wg = wid >> 2;
  const int qtile = (cid & 7) * 2 + rank, hbase = cid >> 3;
  const int o_qt = qtile, o_nh = (cid >> 3) & 1, o_ks = cid >> 4;
  const int o_col = o_nh * 320 + o_ks * 80;
  const int qt = cid >> 2, js = (cid & 3) * 2 + rank;
  if (threadIdx.x == 0) {
    for (int i = 0; i < A_NSLOT; i++) { mbar_init(bar_full + 8 * i, 1); mbar_init(bar_empty + 8 * i, 16); }
    mbar_init(bar_sig, 4); mbar_init(bar_sig + 8, 4);
    for (int i = 0; i < 12; i++) { mbar_init(mb_full + 8 * i, 1); mbar_init(mb_empty + 8 * i, i < 5 ? 8 : 16); }
    asm volatile("fence.mbarrier_init.release.cluster;" ::: "memory");
    prefetch_tmap(&tm.h); prefetch_tmap(&tm.wq); prefetch_tmap(&tm.k); prefetch_tmap(&tm.v);
  }
  __syncthreads();
  cluster_sync();

  if (wg == 0) {
    asm volatile("setmaxnreg.dec.sync.aligned.u32 40;");
    if (wid == 0) {
      Ring r{0, 1};
#define P_ACQ(bytes_) do { mbar_wait(bar_empty + 8 * r.slot, r.phase); mbar_expect_e(bar_full + 8 * r.slot, bytes_); } while (0)
#define P_DST (sb + r.slot * A_SLOT)
#define P_BAR (bar_full + 8 * r.slot)
      uint64_t pol_ef;
      asm volatile("createpolicy.fractional.L2::evict_first.b64 %0, 1.0;" : "=l"(pol_ef));
      if (qtile < 10) l2_prefetch_t3d(&tm.wq, 0, qtile * 64, hbase * 3);
      else l2_prefetch_t3d((qtile & 1) ? &tm.v : &tm.k, 0, hbase * S_ + ((qtile - 10) >> 1) * 64, 0);
      pdl_wait();
      TL_WAITED(2);
#pragma unroll 1
      for (int item = 0; item < 4; item++) {
        const int head = hbase + 8 * item;
#pragma unroll 1
        for (int kb = 0; kb < 10; kb++) {
          P_ACQ(16384);
          tma2d(P_DST, &tm.h, P_BAR, kb * 64, qtile * 128);
          r.adv(A_NSLOT);
          P_ACQ(A_SLOT);
          if ((uint32_t)(kb & 1) == rank) tma3d_mc_hint(P_DST, &tm.wq, P_BAR, 0, kb * 64, head * 3, 3, pol_ef);
          r.adv(A_NSLOT);
        }
#pragma unroll 1
        for (int j = 0; j <= A_NKV; j++) {
          if (j < A_NKV) {
            P_ACQ(A_SLOT);
            if (rank == 0) tma3d_mc_hint(P_DST, &tm.k, P_BAR, 0, head * S_ + j * 64, 0, 3, pol_ef);
            r.adv(A_NSLOT);
          }
          if (j > 0) {
            P_ACQ(A_SLOT);
            if (rank == 1) tma3d_mc_hint(P_DST, &tm.v, P_BAR, 0, head * S_ + (j - 1) * 64, 0, 3, pol_ef);
            r.adv(A_NSLOT);
          }
          if (item < 3 && j == 16 && qtile < 10) l2_prefetch_t3d(&tm.wq, 0, qtile * 64, (head + 8) * 3);
          if (item == 3 && (j & 3) == 0) {
            const int c = (j >> 2) * 128 + blockIdx.x;
            if (c < 980) {
              const int li = c < 480 ? 0 : c < 600 ? 1 : c < 720 ? 2 : c < 880 ? 3 : c < 930 ? 4 : 5;
              const int c0 = c < 480 ? 0 : c < 600 ? 480 : c < 720 ? 600 : c < 880 ? 720 : c < 930 ? 880 : 930;
              l2_prefetch16k(pf.p[li] + (size_t)(c - c0) * 16384);
            }
          }
          if (item == 3) {
            if (j >= 6 && j < 24) {
              const int kb = j - 6;
              l2_prefetch_t2d(&tm.o, ((kb / 6) * 8 + 2 * o_ks + (kb % 6) / 3) * DH_ + (kb % 3) * 64, o_qt * 128);
            }
            if (j >= 24 && j < 30) flag_wait(g_flag + F_O + o_qt * 32 + ((j - 24) >> 1) * 8 + 2 * o_ks + (j & 1), 2);
            if (j == 0 && threadIdx.x == 0) {
              prefetch_tmap(&tm.o); prefetch_tmap(&tm.wo3); prefetch_tmap(&tm.wo2); prefetch_tmap(&tm.xa); prefetch_tmap(&tm.w1t); prefetch_tmap(&tm.us);
              prefetch_tmap(&tm.w2t); prefetch_tmap(&tm.x1); prefetch_tmap(&tm.w3); prefetch_tmap(&tm.g); prefetch_tmap(&tm.w4t);
              prefetch_tmap(&tm.ex); prefetch_tmap(&tm.exa); prefetch_tmap(&tm.ex1);
              prefetch_tmap(&tm.sxa); prefetch_tmap(&tm.sus); prefetch_tmap(&tm.sx1); prefetch_tmap(&tm.sout);
            }
          }
        }
      }
#pragma unroll 1
      for (int kb = 0; kb < 24; kb++) {
        const int head = (kb / 6) * 8 + 2 * o_ks + (kb % 6) / 3;
        const int kcol = head * DH_ + (kb % 3) * 64;
        P_ACQ(24576);
        if (rank == 0) tma3d_mc(P_DST, &tm.wo3, P_BAR, 0, kcol, o_nh * 5, 3);
        r.adv(A_NSLOT);
        P_ACQ(16384);
        if (rank == 1) tma3d_mc(P_DST, &tm.wo2, P_BAR, 0, kcol, o_nh * 5 + 3, 3);
        r.adv(A_NSLOT);
        if (kb == 18 || kb == 21) flag_wait(g_flag + F_O + o_qt * 32 + head, 2);
        if (kb % 3 == 0) fence_async_global();
        P_ACQ(16384);
        tma2d(P_DST, &tm.o, P_BAR, kcol, o_qt * 128);
        r.adv(A_NSLOT);
      }
      P_ACQ(E_TILE);
      tma2d(P_DST, &tm.ex, P_BAR, o_col, o_qt * 128);
      r.adv(A_NSLOT);
      flag_wait(g_flag + F_XCH + (o_qt * 2 + o_nh) * 4 + o_ks, 6);
      fence_async_global();
#pragma unroll 1
      for (int i = 0; i < 3; i++) {
        P_ACQ(E_TILE);
        bulk_load(P_DST, g_xch + (size_t)((((o_qt * 2 + o_nh) * 4 + o_ks) * 4) + ((o_ks + 1 + i) & 3)) * (E_TILE / 2), E_TILE, P_BAR);
        r.adv(A_NSLOT);
      }
      flag_wait(g_flag + F_PREP, PREP_CTAS);
      fence_async_global();
#pragma unroll 1
      for (int i = 0; i < A_NSLOT; i++) { mbar_wait(bar_empty + 8 * r.slot, r.phase); r.adv(A_NSLOT); }
      Ring ra{0, 1};
      uint32_t bpar = 0x1f;
#pragma unroll 1
      for (int ph = 0; ph < 4; ph++) {
        const CUtensorMap* ma = ph == 0 ? &tm.xa : ph == 1 ? &tm.us : ph == 2 ? &tm.x1 : &tm.g;
        const CUtensorMap* mb = ph == 0 ? &tm.w1t : ph == 1 ? &tm.w2t : ph == 2 ? &tm.w3 : &tm.w4t;
        const int nkb = ph == 3 ? 24 : 10;
        const int nbl = ph == 2 ? 10 : nkb / 2;
        const int nel = ph == 1 ? 1 : ph == 3 ? 2 : 0;
        const uint32_t nbs = ph == 2 ? 4 : 5, bsz = ph == 2 ? 24576 : 20480;
        int bl = 0; uint32_t bs = 0;
#pragma unroll 1
        for (int i = 0; i < 5; i++) mbar_wait(mb_empty + 8 * i, (bpar >> i) & 1);
#define T_LOADB() do { mbar_wait(mb_empty + 8 * bs, (bpar >> bs) & 1); bpar ^= 1u << bs; mbar_expect_e(mb_full + 8 * bs, bsz);    \
                       if (bl < nbl) tma3d(sb + bs * bsz, mb, mb_full + 8 * bs, 0, ph == 2 ? bl * 64 : js * 80, ph == 2 ? js * 3 : bl * 2); \
                       else tma2d(sb + bs * bsz, bl == nbl ? &tm.exa : &tm.ex1, mb_full + 8 * bs, js * 80, qt * 128); \
                       bl++; if (++bs == nbs) bs = 0; } while (0)
#pragma unroll 1
        for (uint32_t i = 0; i < nbs; i++) T_LOADB();
        TX(8 + ph * 4);
        const unsigned* fl = g_flag + F_XA + 16 * ph;
        flag_wait(fl + qt, 16);
        if (ph == 1) { if (qt > 0) flag_wait(fl + qt - 1, 16); if (qt < 15) flag_wait(fl + qt + 1, 16); }
        TX(9 + ph * 4);
        fence_async_global();
#pragma unroll 1
        for (int kb = 0; kb < nkb; kb++) {
          mbar_wait(mb_empty + 40 + 8 * ra.slot, ra.phase);
          mbar_expect_e(mb_full + 40 + 8 * ra.slot, 16384);
          tma2d_mc(sb + M_AOFF + ra.slot * 16384 + rank * 8192, ma, mb_full + 40 + 8 * ra.slot, kb * 64, qt * 128 + (int)rank * 64, 3);
          ra.adv(M_NA);
          while (bl < nbl + nel && (kb == nkb - 1 || kb >= (ph == 2 ? bl + 2 : 2 * bl - 3))) T_LOADB();
        }
      }
    } else if (wid < 3) {
      const int w = wid - 1, lane = threadIdx.x & 31;
#pragma unroll 1
      for (int sig = 0; sig < 4; sig++) {
        mbar_wait(bar_sig + 8 * w, sig & 1);
        if (lane == 0) {
          asm volatile("fence.acq_rel.gpu;" ::: "memory");
          flag_add(g_flag + F_O + qtile * 32 + hbase + 8 * sig);
        }
        __syncwarp();
      }
    } else {
      const int lane = threadIdx.x & 31;
      pdl_wait();
      prep_warp(pw, reinterpret_cast<bf16(*)[72]>(smem_raw + (sb + T_PREP - smem_u32(smem_raw))), lane);
      flag_wait(g_flag + F_PREP, PREP_CTAS);
#pragma unroll 1
      for (int i = lane; i < P_SC; i += 32) {
        const int v = i < P_CS3 ? i / 80 : 9, j = i - (i < P_CS3 ? v * 80 : P_CS3);
        const float* src = v == 0 ? g_mod + 2 * D_ + o_col : v == 1 ? g_mod + 4 * D_ + o_col : v == 2 ? g_mod + 3 * D_ + o_col
                         : v < 6 ? g_vec + (v - 3) * D_ + js * 80 : v == 6 ? g_mod + 4 * D_ + js * 80 : v == 7 ? g_mod + 3 * D_ + js * 80
                         : v == 8 ? g_mod + 5 * D_ + js * 80 : g_vec + 3 * D_ + js * 192;
        parf[i] = __ldcg(src + j);
      }
      float sv[5] = {0.f, 0.f, 0.f, 0.f, 0.f};
#pragma unroll 1
      for (int i = lane; i < D_; i += 32) {
        const float a = __ldcg(g_mod + 4 * D_ + i), b = __ldcg(g_mod + 3 * D_ + i);
        sv[0] += a; sv[1] = fmaf(a, a, sv[1]); sv[2] = fmaf(a, b, sv[2]); sv[3] += b; sv[4] = fmaf(b, b, sv[4]);
      }
#pragma unroll 1
      for (int o_ = 16; o_ > 0; o_ >>= 1) {
#pragma unroll
        for (int i = 0; i < 5; i++) sv[i] += __shfl_xor_sync(0xffffffffu, sv[i], o_);
      }
      if (lane == 0) {
#pragma unroll
        for (int i = 0; i < 5; i++) parf[P_SC + i] = sv[i];
      }
      bar_arrive(6, 288);
    }
    __syncwarp();
    cluster_sync();
  } else {
    asm volatile("setmaxnreg.inc.sync.aligned.u32 232;");
    const int w = wg - 1;
    const int lane = threadIdx.x & 31;
    const int warp = wid & 3;
    const int tid = threadIdx.x - 128;
    const uint32_t rel_base = mapa(bar_empty, (lane == 0) ? rank : (rank ^ 1));
    Ring r{0, 0};
#define A_RELEASE(slot_) do { if (lane < 2) mbar_arrive_remote(rel_base + 8 * (slot_)); } while (0)
#define SIGNAL() do { __syncwarp(); if (lane == 0) mbar_arrive(bar_sig + 8 * w); } while (0)
    {
    const float SC = 0.07216878364870322f * 1.4426950408889634f;
    float o[96];
    uint32_t q[48];
    float s[32];
    uint32_t p[16], p2[16];
    if (w == 1) bar_arrive(1, 256);
    bf16* orow = g_o + (size_t)(qtile * 128 + w * 64 + warp * 16 + (lane >> 2)) * HD_ + (hbase - 8) * DH_ + (lane & 3) * 8;
#define O_STORE(g)                                                                                                     \
      {                                                                                                                \
        quad_transpose(q[8 * g], q[8 * g + 2], q[8 * g + 4], q[8 * g + 6], lane);                                      \
        stg128(orow + g * 32, make_uint4(q[8 * g], q[8 * g + 2], q[8 * g + 4], q[8 * g + 6]));                         \
        quad_transpose(q[8 * g + 1], q[8 * g + 3], q[8 * g + 5], q[8 * g + 7], lane);                                  \
        stg128(orow + (size_t)8 * HD_ + g * 32, make_uint4(q[8 * g + 1], q[8 * g + 3], q[8 * g + 5], q[8 * g + 7]));   \
      }
#pragma unroll 1
    for (int item = 0; item < 4; item++) {
      TSA(item, 0);
      {
        uint32_t prevA = 0, prevB = 0;
#pragma unroll
        for (int kb = 0; kb < 10; kb++) {
          const uint32_t sA = r.slot; mbar_wait_c(bar_full + 8 * sA, r.phase); r.adv(A_NSLOT);
          const uint32_t sB = r.slot; mbar_wait_c(bar_full + 8 * sB, r.phase); r.adv(A_NSLOT);
          const uint64_t da = mkdesc(sb + sA * A_SLOT + w * 8192, 16, 1024);
          const uint64_t db = mkdesc(sb + sB * A_SLOT, 8192, 1024);
          if (w == 0 ? kb != 1 : kb != 9) bar_sync(1 + w, 256);
          wg_fence();
#pragma unroll
          for (int kk = 0; kk < 4; kk++) wgmma_ss_n192<1>(o, da + kk * 2, db + kk * 128, (kb | kk) != 0);
          wg_commit();
          if (w == 0 ? kb != 0 : kb != 8) bar_arrive(1 + (w ^ 1), 256);
          if (kb < 6 && item > 0) { O_STORE((kb < 6 ? kb : 0)) }
          if (kb == 6 && item > 0) SIGNAL();
          if (kb > 0) { wg_wait<1>(); A_RELEASE(prevA); A_RELEASE(prevB); }
          prevA = sA; prevB = sB;
        }
        wg_wait<0>();
        fence_regs(o);
        A_RELEASE(prevA); A_RELEASE(prevB);
#pragma unroll
        for (int i = 0; i < 48; i++) q[i] = pack_bf16(o[2 * i], o[2 * i + 1]);
      }
      orow += 8 * DH_;

      TSA(item, 1);
      float c0, c1, l0, l1;
      {
        const uint32_t sK = r.slot; mbar_wait_c(bar_full + 8 * sK, r.phase); r.adv(A_NSLOT);
        const uint64_t dk = mkdesc(sb + sK * A_SLOT, 16, 1024);
        bar_sync(1 + w, 256);
        wg_fence();
#pragma unroll
        for (int kk = 0; kk < 12; kk++)
          wgmma_rs_n64<0>(s, q[4 * kk], q[4 * kk + 1], q[4 * kk + 2], q[4 * kk + 3], dk + (kk >> 2) * 512 + (kk & 3) * 2, kk != 0);
        wg_commit();
        bar_arrive(1 + (w ^ 1), 256);
        wg_wait<0>();
        fence_regs(s);
        A_RELEASE(sK);
        float mx0 = fmaxf(s[0], s[1]), mx1 = fmaxf(s[2], s[3]);
#pragma unroll
        for (int i = 1; i < 8; i++) { mx0 = fmaxf(mx0, fmaxf(s[4 * i], s[4 * i + 1])); mx1 = fmaxf(mx1, fmaxf(s[4 * i + 2], s[4 * i + 3])); }
        mx0 = fmaxf(mx0, __shfl_xor_sync(0xffffffffu, mx0, 1)); mx1 = fmaxf(mx1, __shfl_xor_sync(0xffffffffu, mx1, 1));
        mx0 = fmaxf(mx0, __shfl_xor_sync(0xffffffffu, mx0, 2)); mx1 = fmaxf(mx1, __shfl_xor_sync(0xffffffffu, mx1, 2));
        c0 = mx0 * SC; c1 = mx1 * SC;
        l0 = 0.f; l1 = 0.f;
#pragma unroll
        for (int i = 0; i < 8; i++) {
          s[4 * i] = ex2(fmaf(s[4 * i], SC, -c0)); s[4 * i + 1] = ex2(fmaf(s[4 * i + 1], SC, -c0));
          s[4 * i + 2] = ex2(fmaf(s[4 * i + 2], SC, -c1)); s[4 * i + 3] = ex2(fmaf(s[4 * i + 3], SC, -c1));
          l0 += s[4 * i] + s[4 * i + 1]; l1 += s[4 * i + 2] + s[4 * i + 3];
        }
#pragma unroll
        for (int i = 0; i < 16; i++) p[i] = pack_bf16(s[2 * i], s[2 * i + 1]);
      }
      TSA(item, 2);
      uint32_t okn;
      {
        Ring r2 = r; r2.adv(A_NSLOT);
        okn = mbar_try(bar_full + 8 * r.slot, r.phase) & mbar_try(bar_full + 8 * r2.slot, r2.phase);
      }
#define A_STEP(PC, PN, FIRST)                                                                                          \
      {                                                                                                                \
        const uint32_t sK = r.slot, phK = r.phase; r.adv(A_NSLOT);                                                     \
        const uint32_t sV = r.slot, phV = r.phase; r.adv(A_NSLOT);                                                     \
        const uint64_t dk = mkdesc(sb + sK * A_SLOT, 16, 1024);                                                        \
        const uint64_t dv = mkdesc(sb + sV * A_SLOT, 8192, 1024);                                                      \
        if (!okn) { mbar_wait_c(bar_full + 8 * sK, phK); mbar_wait_c(bar_full + 8 * sV, phV); }                            \
        bar_sync(1 + w, 256);                                                                                          \
        wg_fence();                                                                                                    \
        _Pragma("unroll") for (int kk = 0; kk < 12; kk++)                                                              \
          wgmma_rs_n64<0>(s, q[4 * kk], q[4 * kk + 1], q[4 * kk + 2], q[4 * kk + 3], dk + (kk >> 2) * 512 + (kk & 3) * 2, kk != 0); \
        wg_commit();                                                                                                   \
        _Pragma("unroll") for (int kk = 0; kk < 4; kk++)                                                               \
          wgmma_rs_n192<1>(o, PC[4 * kk], PC[4 * kk + 1], PC[4 * kk + 2], PC[4 * kk + 3], dv + kk * 128, !(FIRST) || (kk != 0)); \
        wg_commit();                                                                                                   \
        bar_arrive(1 + (w ^ 1), 256);                                                                                  \
        {                                                                                                              \
          Ring r2 = r; r2.adv(A_NSLOT);                                                                                \
          okn = mbar_try(bar_full + 8 * r.slot, r.phase) & mbar_try(bar_full + 8 * r2.slot, r2.phase);                 \
        }                                                                                                              \
        wg_wait<1>();                                                                                                  \
        fence_regs(s);                                                                                                 \
        A_RELEASE(sK);                                                                                                 \
        float b0 = 0.f, b1 = 0.f;                                                                                      \
        _Pragma("unroll") for (int i = 0; i < 8; i++) {                                                                \
          const float e0 = ex2(fmaf(s[4 * i], SC, -c0)), e1 = ex2(fmaf(s[4 * i + 1], SC, -c0));                        \
          const float e2 = ex2(fmaf(s[4 * i + 2], SC, -c1)), e3 = ex2(fmaf(s[4 * i + 3], SC, -c1));                    \
          b0 += e0 + e1; b1 += e2 + e3;                                                                                \
          PN[2 * i] = pack_bf16(e0, e1); PN[2 * i + 1] = pack_bf16(e2, e3);                                            \
        }                                                                                                              \
        wg_wait<0>();                                                                                                  \
        fence_regs(o);                                                                                                 \
        fence_regs(PC);                                                                                                \
        A_RELEASE(sV);                                                                                                 \
        if (__any_sync(0xffffffffu, !(b0 <= 65536.f) || !(b1 <= 65536.f))) {                                           \
          float mx0 = fmaxf(s[0], s[1]), mx1 = fmaxf(s[2], s[3]);                                                      \
          _Pragma("unroll") for (int i = 1; i < 8; i++) {                                                              \
            mx0 = fmaxf(mx0, fmaxf(s[4 * i], s[4 * i + 1])); mx1 = fmaxf(mx1, fmaxf(s[4 * i + 2], s[4 * i + 3]));     \
          }                                                                                                            \
          mx0 = fmaxf(mx0, __shfl_xor_sync(0xffffffffu, mx0, 1)); mx1 = fmaxf(mx1, __shfl_xor_sync(0xffffffffu, mx1, 1)); \
          mx0 = fmaxf(mx0, __shfl_xor_sync(0xffffffffu, mx0, 2)); mx1 = fmaxf(mx1, __shfl_xor_sync(0xffffffffu, mx1, 2)); \
          const float n0 = fmaxf(c0, mx0 * SC), n1 = fmaxf(c1, mx1 * SC);                                              \
          const float a0 = ex2(c0 - n0), a1 = ex2(c1 - n1);                                                            \
          c0 = n0; c1 = n1;                                                                                            \
          l0 *= a0; l1 *= a1;                                                                                          \
          _Pragma("unroll") for (int i = 0; i < 24; i++) { o[4 * i] *= a0; o[4 * i + 1] *= a0; o[4 * i + 2] *= a1; o[4 * i + 3] *= a1; } \
          b0 = 0.f; b1 = 0.f;                                                                                          \
          _Pragma("unroll") for (int i = 0; i < 8; i++) {                                                              \
            const float e0 = ex2(fmaf(s[4 * i], SC, -c0)), e1 = ex2(fmaf(s[4 * i + 1], SC, -c0));                      \
            const float e2 = ex2(fmaf(s[4 * i + 2], SC, -c1)), e3 = ex2(fmaf(s[4 * i + 3], SC, -c1));                  \
            b0 += e0 + e1; b1 += e2 + e3;                                                                              \
            PN[2 * i] = pack_bf16(e0, e1); PN[2 * i + 1] = pack_bf16(e2, e3);                                          \
          }                                                                                                            \
        }                                                                                                              \
        l0 += b0; l1 += b1;                                                                                            \
      }
      for (int jj = 0; jj < 15; jj++) {
        A_STEP(p, p2, jj == 0)
        A_STEP(p2, p, false)
      }
      A_STEP(p, p2, false)
      TSA(item, 3);
      {
        const uint32_t sV = r.slot; mbar_wait_c(bar_full + 8 * sV, r.phase); r.adv(A_NSLOT);
        const uint64_t dv = mkdesc(sb + sV * A_SLOT, 8192, 1024);
        bar_sync(1 + w, 256);
        wg_fence();
#pragma unroll
        for (int kk = 0; kk < 4; kk++)
          wgmma_rs_n192<1>(o, p2[4 * kk], p2[4 * kk + 1], p2[4 * kk + 2], p2[4 * kk + 3], dv + kk * 128, 1);
        wg_commit();
        bar_arrive(1 + (w ^ 1), 256);
        wg_wait<0>();
        fence_regs(o);
        A_RELEASE(sV);
      }
      TSA(item, 4);
      l0 += __shfl_xor_sync(0xffffffffu, l0, 1); l1 += __shfl_xor_sync(0xffffffffu, l1, 1);
      l0 += __shfl_xor_sync(0xffffffffu, l0, 2); l1 += __shfl_xor_sync(0xffffffffu, l1, 2);
      const float i0 = __fdividef(1.f, l0), i1 = __fdividef(1.f, l1);
#pragma unroll
      for (int i = 0; i < 24; i++) { q[2 * i] = pack_bf16(o[4 * i] * i0, o[4 * i + 1] * i0); q[2 * i + 1] = pack_bf16(o[4 * i + 2] * i1, o[4 * i + 3] * i1); }
      TSA(item, 5);
    }
#pragma unroll
    for (int g = 0; g < 6; g++) { O_STORE(g) }
    SIGNAL();
    }
    TS(3, 2);
    const uint32_t st_w = (uint32_t)((warp * 16 + (lane >> 2)) * ST_P + (lane & 3) * 2) * 4;
    const uint32_t st_x = (lane & 8) << 2;
    const int er = (tid & 127) >> 1, eh = tid & 1;
    const uint32_t st_r = (uint32_t)(er * ST_P + (eh ^ ((er >> 1) & 1)) * 8) * 4;
    const uint32_t e_r = (uint32_t)((w * 64 + er) * 160 + eh * 16);
    const uint32_t p_r = par + eh * 32;
    const uint32_t stat = sb + T_PREP + w * 2048;
    const bool leader = (tid & 127) == 0;
#define STAGE10(ACC, BASE)                                                                                             \
    _Pragma("unroll") for (int nb = 0; nb < 10; nb++) {                                                                \
      sts_f2(stg + st_w + ((nb * 32) ^ st_x), ACC(BASE + 4 * nb), ACC(BASE + 4 * nb + 1));                                       \
      sts_f2(stg + st_w + ((nb * 32) ^ st_x) + 8 * ST_P * 4, ACC(BASE + 4 * nb + 2), ACC(BASE + 4 * nb + 3));                    \
    }

    {
      float acc1[96], acc2[64];
      uint32_t p0 = 0, p1 = 0, p2 = 0;
#pragma unroll 1
      for (int kb = 0; kb < 24; kb++) {
        const uint32_t s1 = r.slot; mbar_wait_c(bar_full + 8 * s1, r.phase); r.adv(A_NSLOT);
        const uint32_t s2 = r.slot; mbar_wait_c(bar_full + 8 * s2, r.phase); r.adv(A_NSLOT);
        const uint32_t sa = r.slot; mbar_wait_c(bar_full + 8 * sa, r.phase); r.adv(A_NSLOT);
        const uint64_t da = mkdesc(sb + sa * A_SLOT + w * 8192, 16, 1024);
        const uint64_t d1 = mkdesc(sb + s1 * A_SLOT, 8192, 1024), d2 = mkdesc(sb + s2 * A_SLOT, 8192, 1024);
        wg_fence();
#pragma unroll
        for (int kk = 0; kk < 4; kk++) {
          wgmma_ss_n192<1>(acc1, da + kk * 2, d1 + kk * 128, (kb | kk) != 0);
          wgmma_ss_n128<1>(acc2, da + kk * 2, d2 + kk * 128, (kb | kk) != 0);
        }
        wg_commit();
        if (kb > 0) { wg_wait<1>(); A_RELEASE(p0); A_RELEASE(p1); A_RELEASE(p2); }
        p0 = s1; p1 = s2; p2 = sa;
      }
      wg_wait<0>();
      fence_regs(acc1); fence_regs(acc2);
      A_RELEASE(p2);
      bar_sync(6, 288);
      TS(0, 0);
      const uint32_t stg = sb + (w ? p1 : p0) * A_SLOT;
#define OACC(e) (((e) < 96) ? acc1[(e) < 96 ? (e) : 0] : acc2[(e) >= 96 ? (e) - 96 : 0])
#define PACK10(BASE)                                                                                                   \
      _Pragma("unroll") for (int nb = 0; nb < 10; nb++) {                                                              \
        sts_u1(xo + nb * 16, pack_bf16(OACC(BASE + 4 * nb), OACC(BASE + 4 * nb + 1)));                                 \
        sts_u1(xo + nb * 16 + 8 * 160, pack_bf16(OACC(BASE + 4 * nb + 2), OACC(BASE + 4 * nb + 3)));                   \
      }
      const uint32_t f1 = r.slot + 4 >= A_NSLOT ? r.slot + 4 - A_NSLOT : r.slot + 4, f2 = f1 + 1 >= A_NSLOT ? 0 : f1 + 1;
#pragma unroll
      for (int d = 0; d < 4; d++) {
        if (d != o_ks) {
          const int i = (d - o_ks - 1) & 3;
          const uint32_t xo = sb + (i == 0 ? p2 : i == 1 ? f1 : f2) * A_SLOT + (w * 64 + warp * 16 + (lane >> 2)) * 160 + (lane & 3) * 4;
          PACK10(d * 40)
        }
      }
      fence_async_smem();
      bar_sync(3 + w, 128);
      if (leader) {
#pragma unroll 1
        for (int i = 0; i < 3; i++)
          bulk_store(g_xch + (size_t)((((o_qt * 2 + o_nh) * 4 + ((o_ks + 1 + i) & 3)) * 4) + o_ks) * (E_TILE / 2) + w * (E_TILE / 4),
                     sb + (i == 0 ? p2 : i == 1 ? f1 : f2) * A_SLOT + w * (E_TILE / 2), E_TILE / 2);
        bulk_done();
#pragma unroll 1
        for (int i = 0; i < 3; i++) flag_add(g_flag + F_XCH + (o_qt * 2 + o_nh) * 4 + ((o_ks + 1 + i) & 3));
        TX(40 + w);
      }
      if (o_ks == 0) { STAGE10(OACC, 0) } else if (o_ks == 1) { STAGE10(OACC, 40) } else if (o_ks == 2) { STAGE10(OACC, 80) } else { STAGE10(OACC, 120) }
      bar_sync(3 + w, 128);
      const uint32_t sx = r.slot; mbar_wait_c(bar_full + 8 * sx, r.phase); r.adv(A_NSLOT);
      const uint32_t q0 = r.slot; mbar_wait_c(bar_full + 8 * q0, r.phase); r.adv(A_NSLOT);
      const uint32_t q1 = r.slot; mbar_wait_c(bar_full + 8 * q1, r.phase); r.adv(A_NSLOT);
      const uint32_t q2 = r.slot; mbar_wait_c(bar_full + 8 * q2, r.phase); r.adv(A_NSLOT);
      TS(0, 1);
      float st[6] = {0.f, 0.f, 0.f, 0.f, 0.f, 0.f};
      const uint32_t ot = sb + p2 * A_SLOT;
#pragma unroll 1
      for (int c = 0; c < 5; c++) {
        float v[8], t0[8], t1[8], t2[8], xv[8], pg[8], pa_[8], pb_[8];
        lds8(stg + st_r + c * 64, v);
        lds8_bf(sb + q0 * A_SLOT + e_r + c * 32, t0); lds8_bf(sb + q1 * A_SLOT + e_r + c * 32, t1); lds8_bf(sb + q2 * A_SLOT + e_r + c * 32, t2);
        lds8_bf(sb + sx * A_SLOT + e_r + c * 32, xv);
        lds8(p_r + P_OGA * 4 + c * 64, pg); lds8(p_r + P_OA * 4 + c * 64, pa_); lds8(p_r + P_OB * 4 + c * 64, pb_);
#pragma unroll
        for (int e = 0; e < 8; e++) v[e] = fmaf(pg[e], v[e] + ((t0[e] + t1[e]) + t2[e]), xv[e]);
        const uint4 pk = pack8(v);
        sts_u4(ot + e_r + c * 32, pk);
        v[0] = bf_lo(pk.x); v[1] = bf_hi(pk.x); v[2] = bf_lo(pk.y); v[3] = bf_hi(pk.y); v[4] = bf_lo(pk.z); v[5] = bf_hi(pk.z); v[6] = bf_lo(pk.w); v[7] = bf_hi(pk.w);
#pragma unroll
        for (int e = 0; e < 8; e++) {
          const float y = pa_[e] * v[e];
          st[0] += v[e]; st[1] = fmaf(v[e], v[e], st[1]); st[2] += y; st[3] = fmaf(pa_[e], y, st[3]); st[4] = fmaf(y, y, st[4]); st[5] = fmaf(pb_[e], y, st[5]);
        }
      }
#pragma unroll
      for (int i = 0; i < 6; i++) st[i] += __shfl_xor_sync(0xffffffffu, st[i], 1);
      sts_u4(stat + er * 32 + eh * 16, eh ? make_uint4(__float_as_uint(st[4]), __float_as_uint(st[5]), 0u, 0u)
                                          : make_uint4(__float_as_uint(st[0]), __float_as_uint(st[1]), __float_as_uint(st[2]), __float_as_uint(st[3])));
      fence_async_smem();
      bar_sync(3 + w, 128);
      if (leader) {
        tma_store2d(&tm.sxa, ot + w * (E_TILE / 2), o_col, o_qt * 128 + w * 64);
        bulk_red_f32(g_st1 + (size_t)(o_qt * 128 + w * 64) * 8, stat, 2048);
        bulk_done();
        flag_add(g_flag + F_XA + o_qt);
      }
      bar_sync(5, 256);
      A_RELEASE(p0); A_RELEASE(p1); A_RELEASE(sx); A_RELEASE(q0); A_RELEASE(q1); A_RELEASE(q2);
      TS(0, 2);
    }

    Ring ra{0, 0};
    uint32_t bpar = 0;
    const uint32_t rel_a = mapa(mb_empty + 40, (lane == 0) ? rank : (rank ^ 1));
#define B_NEXT(s_) do { s_ = bs; mbar_wait_c(mb_full + 8 * bs, (bpar >> bs) & 1); bpar ^= 1u << bs; if (++bs == nbs) bs = 0; } while (0)
#define A_NEXT(s_) do { s_ = ra.slot; mbar_wait_c(mb_full + 40 + 8 * s_, ra.phase); ra.adv(M_NA); } while (0)
#define B_RELEASE(s_) do { if (lane == 0) mbar_arrive(mb_empty + 8 * (s_)); } while (0)
#define MA_RELEASE(s_) do { if (lane < 2) mbar_arrive_remote(rel_a + 8 * (s_)); } while (0)
    const int grow = qt * 128 + w * 64 + er;
    float mu = 0.f, rs = 0.f;
#pragma unroll 1
    for (int ph = 0; ph < 4; ph++) {
      float acc[96];
      float (&acc80)[40] = *reinterpret_cast<float(*)[40]>(&acc[0]);
      uint32_t pa = 0, pa2 = 0, pb = 0;
      float4 s03 = make_float4(0.f, 0.f, 0.f, 0.f);
      float2 s45 = make_float2(0.f, 0.f);
      const int nit = ph == 3 ? 12 : ph == 2 ? 10 : 5;
      const uint32_t nbs = ph == 2 ? 4 : 5, bsz = ph == 2 ? 24576 : 20480;
      uint32_t bs = 0;
#pragma unroll 1
      for (int it = 0; it < nit; it++) {
        uint32_t sbq, sa, sa2;
        B_NEXT(sbq);
        A_NEXT(sa);
        if (it == 0) TXC(ph);
        const uint64_t da = mkdesc(sb + M_AOFF + sa * 16384 + w * 8192, 16, 1024);
        if (ph == 2) {
          sa2 = sa;
          const uint64_t db = mkdesc(sb + sbq * 24576, 8192, 1024);
          wg_fence();
#pragma unroll
          for (int kk = 0; kk < 4; kk++) wgmma_ss_n192<1>(acc, da + kk * 2, db + kk * 128, (it | kk) != 0);
          wg_commit();
        } else {
          A_NEXT(sa2);
          const uint64_t da2 = mkdesc(sb + M_AOFF + sa2 * 16384 + w * 8192, 16, 1024);
          const uint64_t db = mkdesc(sb + sbq * 20480, 16, 1024);
          wg_fence();
#pragma unroll
          for (int kk = 0; kk < 4; kk++) wgmma_ss_n80<0>(acc80, da + kk * 2, db + kk * 2, (it | kk) != 0);
#pragma unroll
          for (int kk = 0; kk < 4; kk++) wgmma_ss_n80<0>(acc80, da2 + kk * 2, db + 640 + kk * 2, 1);
          wg_commit();
        }
        if (it > 0) { wg_wait<1>(); MA_RELEASE(pa); if (ph != 2) MA_RELEASE(pa2); B_RELEASE(pb); }
        else {
          if (ph == 0) { s03 = __ldcg(reinterpret_cast<const float4*>(g_st1 + (size_t)grow * 8)); s45 = __ldcg(reinterpret_cast<const float2*>(g_st1 + (size_t)grow * 8 + 4)); }
          if (ph == 2) s45 = __ldcg(reinterpret_cast<const float2*>(g_st2 + (size_t)grow * 2));
        }
        pa = sa; pa2 = sa2; pb = sbq;
      }
      wg_wait<0>();
      fence_regs(acc);
      MA_RELEASE(pa); if (ph != 2) MA_RELEASE(pa2);
      bar_sync(5, 256);
      TS(1 + (ph == 3 ? 0 : ph), ph == 3 ? 2 : 0);
      const uint32_t pb1 = pb == 0 ? nbs - 1 : pb - 1, pb2 = pb1 == 0 ? nbs - 1 : pb1 - 1, pb3 = pb2 == 0 ? nbs - 1 : pb2 - 1;
      const uint32_t stg = sb + (w ? pb : pb1) * bsz;
      uint32_t e1 = 0;
#define MACC(e) acc[e]
      if (!(ph & 1)) {
        float c0, c1, c2 = 0.f, c3 = 0.f;
        if (ph == 0) {
          const float4 sc = lds_f4(par + P_SC * 4);
          const float sbb = lds_f(par + (P_SC + 4) * 4);
          mu = s03.x * (1.f / D_);
          rs = rsqrtf(fmaxf(s03.y * (1.f / D_) - mu * mu, 0.f) + LN_EPS);
          const float m2 = (rs * (s03.z - mu * sc.x) + sc.w) * (1.f / D_);
          const float e2 = (rs * rs * (s45.x - 2.f * mu * s03.w + mu * mu * sc.y) + 2.f * rs * (s45.y - mu * sc.z) + sbb) * (1.f / D_);
          c2 = rsqrtf(fmaxf(e2 - m2 * m2, 0.f) + LN_EPS);
          c0 = c2 * rs; c1 = -c0 * mu; c3 = -c2 * m2;
          if (tid < 20) sts_u4(stat + 2048 * 2 + tid * 16, make_uint4(0, 0, 0, 0));
        } else {
          const float m = s45.x * (1.f / D_);
          c0 = rsqrtf(fmaxf(s45.y * (1.f / D_) - m * m, 0.f) + LN_EPS);
          c1 = -c0 * m;
        }
        const int npass = ph == 0 ? 1 : 3, nch = ph == 0 ? 5 : 4;
        const uint32_t ot = ph == 0 ? sb + pb2 * bsz + w * (E_TILE / 2) : sb + (w ? pb2 : pb3) * bsz;
#pragma unroll 1
        for (int ps = 0; ps < npass; ps++) {
          if (ps == 0) { STAGE10(MACC, 0) } else if (ps == 1) { STAGE10(MACC, 32) } else { STAGE10(MACC, 56) }
          bar_sync(3 + w, 128);
          const uint32_t cofs = ps == 2 ? 64 : 0;
          const uint32_t pp = p_r + (ph == 0 ? P_VA : P_CS3 + ps * 64) * 4, pq = p_r + P_VB * 4;
#pragma unroll 1
          for (int c = 0; c < nch; c++) {
            float v[8], t[8], t2[8], t3[8];
            lds8(stg + st_r + cofs + c * 64, v);
            lds8(pp + c * 64, t);
            if (ph == 0) {
              lds8(pq + c * 64, t2); lds8(pq + 320 + c * 64, t3);
#pragma unroll
              for (int e = 0; e < 8; e++) t[e] = fmaf(c1, t[e], fmaf(c2, t2[e], c3 * t3[e]));
            } else {
#pragma unroll
              for (int e = 0; e < 8; e++) t[e] *= c1;
            }
#pragma unroll
            for (int e = 0; e < 8; e++) v[e] = gelu_tanh(fmaf(c0, v[e], t[e]));
            sts_u4(ot + (ph == 0 ? er * 160 + eh * 16 + c * 32 : ps * 8192 + er * 128 + (((2 * c + eh) ^ (er & 7)) << 4)), pack8(v));
          }
          fence_async_smem();
          bar_sync(3 + w, 128);
          if (leader) {
            if (ph == 0) {
              const int grp = js >> 1;
              const int sh = (grp & 2 ? 2 : 1) * (grp & 1 ? -1 : 1);
              tma_store2d(&tm.sus, ot, js * 80, qt * 128 + w * 64 + sh + 2);
              if (w == 0 && qt == (sh > 0 ? 0 : 15)) {
                const int r0 = sh > 0 ? 0 : S_ + sh, n = sh > 0 ? sh : -sh;
                for (int i = 0; i < n; i++) bulk_store(g_us + (size_t)(r0 + i + 2) * D_ + js * 80, stat + 2048 * 2, 160);
              }
            } else {
              tma_store2d(&tm.g, ot + ps * 8192, js * 192 + ps * 64, qt * 128 + w * 64);
            }
          }
        }
      } else {
        STAGE10(MACC, 0)
        uint32_t e2;
        B_NEXT(e1);
        e2 = e1;
        if (ph == 3) B_NEXT(e2);
        bar_sync(3 + w, 128);
        float s1 = 0.f, s2 = 0.f;
        const uint32_t ot = sb + pb2 * bsz;
#pragma unroll 1
        for (int c = 0; c < 5; c++) {
          float v[8], xa[8], x1[8], ta[8], tb[8];
          lds8(stg + st_r + c * 64, v);
          lds8_bf(sb + e1 * 20480 + e_r + c * 32, xa); lds8_bf(sb + e2 * 20480 + e_r + c * 32, x1);
          lds8(p_r + (ph == 1 ? P_A2 : P_GB) * 4 + c * 64, ta); lds8(p_r + P_B2 * 4 + c * 64, tb);
          if (ph == 1) {
#pragma unroll
            for (int e = 0; e < 8; e++) v[e] += fmaf(ta[e] * rs, xa[e] - mu, tb[e]);
          } else {
#pragma unroll
            for (int e = 0; e < 8; e++) v[e] = fmaf(ta[e], v[e] + x1[e], xa[e]);
          }
          const uint4 pk = pack8(v);
          sts_u4(ot + e_r + c * 32, pk);
          v[0] = bf_lo(pk.x); v[1] = bf_hi(pk.x); v[2] = bf_lo(pk.y); v[3] = bf_hi(pk.y); v[4] = bf_lo(pk.z); v[5] = bf_hi(pk.z); v[6] = bf_lo(pk.w); v[7] = bf_hi(pk.w);
#pragma unroll
          for (int e = 0; e < 8; e++) { s1 += v[e]; s2 = fmaf(v[e], v[e], s2); }
        }
        s1 += __shfl_xor_sync(0xffffffffu, s1, 1); s2 += __shfl_xor_sync(0xffffffffu, s2, 1);
        if (eh == 0) sts_f2(stat + er * 8, s1, s2);
        fence_async_smem();
        bar_sync(3 + w, 128);
        if (leader) {
          tma_store2d(ph == 1 ? &tm.sx1 : &tm.sout, ot + w * (E_TILE / 2), js * 80, qt * 128 + w * 64);
          if (ph == 1) bulk_red_f32(g_st2 + (size_t)(qt * 128 + w * 64) * 2, stat, 512);
        }
      }
      if (leader) {
        bulk_done();
        if (ph < 3) flag_add(g_flag + F_US + 16 * ph + qt);
      }
      if (ph < 3) {
        bar_sync(5, 256);
        B_RELEASE(pb);
        if (ph == 1) B_RELEASE(e1);
      }
      TS(1 + (ph == 3 ? 0 : ph), ph == 3 ? 3 : 1);
    }
    if ((threadIdx.x & 127) == 0) TL_END(2);
    cluster_sync();
  }
}

typedef CUresult (*EncFn)(CUtensorMap*, CUtensorMapDataType, cuuint32_t, void*, const cuuint64_t*, const cuuint64_t*,
                          const cuuint32_t*, const cuuint32_t*, CUtensorMapInterleave, CUtensorMapSwizzle,
                          CUtensorMapL2promotion, CUtensorMapFloatOOBfill);
static EncFn g_enc = nullptr;

static CUtensorMap map2d(const void* p, uint64_t rows, uint64_t cols, uint32_t box_rows) {
  CUtensorMap m;
  cuuint64_t gd[2] = {cols, rows}; cuuint64_t gs[1] = {cols * 2};
  cuuint32_t bx[2] = {64, box_rows}; cuuint32_t es[2] = {1, 1};
  g_enc(&m, CU_TENSOR_MAP_DATA_TYPE_BFLOAT16, 2, const_cast<void*>(p), gd, gs, bx, es, CU_TENSOR_MAP_INTERLEAVE_NONE,
        CU_TENSOR_MAP_SWIZZLE_128B, CU_TENSOR_MAP_L2_PROMOTION_L2_256B, CU_TENSOR_MAP_FLOAT_OOB_FILL_NONE);
  return m;
}
static CUtensorMap map3d(const void* p, uint64_t rows, uint64_t cols, uint32_t box_rows, uint32_t nblk) {
  CUtensorMap m;
  cuuint64_t gd[3] = {64, rows, cols / 64}; cuuint64_t gs[2] = {cols * 2, 128};
  cuuint32_t bx[3] = {64, box_rows, nblk}; cuuint32_t es[3] = {1, 1, 1};
  g_enc(&m, CU_TENSOR_MAP_DATA_TYPE_BFLOAT16, 3, const_cast<void*>(p), gd, gs, bx, es, CU_TENSOR_MAP_INTERLEAVE_NONE,
        CU_TENSOR_MAP_SWIZZLE_128B, CU_TENSOR_MAP_L2_PROMOTION_L2_256B, CU_TENSOR_MAP_FLOAT_OOB_FILL_NONE);
  return m;
}

static CUtensorMap map_e(const void* p, uint32_t rows, uint64_t total_rows = S_) {
  CUtensorMap m;
  cuuint64_t gd[2] = {D_, total_rows}; cuuint64_t gs[1] = {D_ * 2};
  cuuint32_t bx[2] = {80, rows}; cuuint32_t es[2] = {1, 1};
  g_enc(&m, CU_TENSOR_MAP_DATA_TYPE_BFLOAT16, 2, const_cast<void*>(p), gd, gs, bx, es, CU_TENSOR_MAP_INTERLEAVE_NONE,
        CU_TENSOR_MAP_SWIZZLE_NONE, CU_TENSOR_MAP_L2_PROMOTION_L2_256B, CU_TENSOR_MAP_FLOAT_OOB_FILL_NONE);
  return m;
}

template <typename... KArgs, typename... Args>
static void launch(void (*kern)(KArgs...), dim3 grid, dim3 block, int smem, bool pdl, Args... args) {
  cudaLaunchConfig_t cfg = {};
  cfg.gridDim = grid; cfg.blockDim = block; cfg.dynamicSmemBytes = smem; cfg.stream = cudaStreamPerThread;
  cudaLaunchAttribute at[1];
  at[0].id = cudaLaunchAttributeProgrammaticStreamSerialization;
  at[0].val.programmaticStreamSerializationAllowed = 1;
  cfg.attrs = at; cfg.numAttrs = pdl ? 1 : 0;
  cudaLaunchKernelEx(&cfg, kern, KArgs(args)...);
}

extern "C" void kernel_launch(void* const* d_in, const int* in_sizes, int n_in, void* d_out, int out_size) {
  const bf16* x = (const bf16*)d_in[0];
  const bf16* kc = (const bf16*)d_in[1];
  const bf16* vc = (const bf16*)d_in[2];
  const bf16* wq = (const bf16*)d_in[3];
  const bf16* wo = (const bf16*)d_in[4];
  const bf16* w1 = (const bf16*)d_in[6];
  const bf16* w2 = (const bf16*)d_in[7];
  const bf16* w3 = (const bf16*)d_in[8];
  const bf16* w4 = (const bf16*)d_in[9];
  const bf16* c = (const bf16*)d_in[10];
  const bf16* wmod = (const bf16*)d_in[11];
  bf16* out = (bf16*)d_out;

  static void *p_h, *p_o, *p_xa, *p_us, *p_x1, *p_g, *p_w1t, *p_w2t, *p_w4t;
  if (!g_enc) {
    void* fn = nullptr; cudaDriverEntryPointQueryResult qr;
    cudaGetDriverEntryPoint("cuTensorMapEncodeTiled", &fn, cudaEnableDefault, &qr);
    g_enc = (EncFn)fn;
    cudaGetSymbolAddress(&p_h, g_h); cudaGetSymbolAddress(&p_o, g_o); cudaGetSymbolAddress(&p_xa, g_xa);
    cudaGetSymbolAddress(&p_us, g_us); cudaGetSymbolAddress(&p_x1, g_x1); cudaGetSymbolAddress(&p_g, g_g);
    cudaGetSymbolAddress(&p_w1t, g_w1t); cudaGetSymbolAddress(&p_w2t, g_w2t); cudaGetSymbolAddress(&p_w4t, g_w4t);
    cudaFuncSetAttribute(fused_kernel, cudaFuncAttributeMaxDynamicSharedMemorySize, T_SMEM);
  }
  Maps tm;
  tm.h = map2d(p_h, S_, D_, 128);
  tm.wq = map3d(wq, D_, HD_, 64, 3);
  tm.k = map3d(kc, (uint64_t)H_ * S_, DH_, 64, 3);
  tm.v = map3d(vc, (uint64_t)H_ * S_, DH_, 64, 3);
  tm.o = map2d(p_o, S_, HD_, 128);
  tm.wo3 = map3d(wo, HD_, D_, 64, 3);
  tm.wo2 = map3d(wo, HD_, D_, 64, 2);
  tm.xa = map2d(p_xa, S_, D_, 64);
  tm.w1t = map3d(p_w1t, D_, D_, 80, 2);
  tm.us = map2d((const bf16*)p_us + 2 * D_, S_, D_, 64);
  tm.w2t = map3d(p_w2t, D_, D_, 80, 2);
  tm.x1 = map2d(p_x1, S_, D_, 64);
  tm.w3 = map3d(w3, D_, F_, 64, 3);
  tm.g = map2d(p_g, S_, F_, 64);
  tm.w4t = map3d(p_w4t, D_, F_, 80, 2);
  tm.ex = map_e(x, 128); tm.exa = map_e(p_xa, 128); tm.ex1 = map_e(p_x1, 128);
  tm.sxa = map_e(p_xa, 64); tm.sus = map_e(p_us, 64, S_ + 4); tm.sx1 = map_e(p_x1, 64); tm.sout = map_e(out, 64);
  PfList pf;
  pf.p[0] = (const uint8_t*)wo; pf.p[1] = (const uint8_t*)w3; pf.p[2] = (const uint8_t*)p_w4t;
  pf.p[3] = (const uint8_t*)x; pf.p[4] = (const uint8_t*)p_w1t; pf.p[5] = (const uint8_t*)p_w2t;

  launch(mod_kernel, dim3(120), dim3(256), 0, false, c, wmod);
  launch(ln1_kernel, dim3(256), dim3(256), 0, true, x);
  launch(fused_kernel, dim3(128), dim3(384), T_SMEM, true, tm, pf, PrepW{w1, w2, w3, w4}, x, out);
}
```

```cpp
#include <cuda_runtime.h>
#include <cuda.h>
#include <cuda_bf16.h>
#include <stdint.h>

typedef __nv_bfloat16 bf16;

constexpr int S_  = 2048;
constexpr int D_  = 640;
constexpr int H_  = 32;
constexpr int DH_ = 192;
constexpr int HD_ = H_ * DH_;
constexpr int F_  = 1536;
constexpr float LN_EPS = 1e-5f;

__device__ __forceinline__ uint32_t smem_u32(const void* p) { return (uint32_t)__cvta_generic_to_shared(p); }
__device__ __forceinline__ void mbar_init(uint32_t a, uint32_t c) { asm volatile("mbarrier.init.shared::cta.b64 [%0], %1;" :: "r"(a), "r"(c) : "memory"); }
__device__ __forceinline__ void mbar_expect(uint32_t a, uint32_t b) { asm volatile("mbarrier.arrive.expect_tx.shared::cta.b64 _, [%0], %1;" :: "r"(a), "r"(b) : "memory"); }
__device__ __forceinline__ void mbar_arrive(uint32_t a) { asm volatile("mbarrier.arrive.shared::cta.b64 _, [%0];" :: "r"(a) : "memory"); }
__device__ __forceinline__ void mbar_arrive_remote(uint32_t ra) { asm volatile("mbarrier.arrive.shared::cluster.b64 _, [%0];" :: "r"(ra) : "memory"); }
__device__ __forceinline__ uint32_t mapa(uint32_t a, uint32_t cta) { uint32_t r; asm volatile("mapa.shared::cluster.u32 %0, %1, %2;" : "=r"(r) : "r"(a), "r"(cta)); return r; }
__device__ __forceinline__ uint32_t mbar_try(uint32_t a, uint32_t ph) {
  uint32_t ok;
  asm volatile("{\n.reg .pred p;\nmbarrier.test_wait.parity.shared::cta.b64 p, [%1], %2;\nselp.u32 %0, 1, 0, p;\n}\n" : "=r"(ok) : "r"(a), "r"(ph) : "memory");
  return ok;
}
__device__ __forceinline__ void mbar_wait(uint32_t a, uint32_t ph) {
  asm volatile(
      "{\n.reg .pred p;\n.reg .u32 n;\n"
      "mov.u32 n, 0;\n"
      "SPIN:\n"
      "mbarrier.try_wait.parity.shared::cta.b64 p, [%0], %1;\n"
      "@p bra DONE;\n"
      "add.u32 n, n, 1;\n"
      "setp.le.u32 p, n, 16777216;\n"
      "@p bra SPIN;\n"
      "trap;\n"
      "DONE:\n}\n" :: "r"(a), "r"(ph) : "memory");
}
#define ELECT_ "{\n.reg .pred p;\nelect.sync _|p, 0xffffffff;\n@p "
__device__ __forceinline__ void mbar_expect_e(uint32_t a, uint32_t b) { asm volatile(ELECT_ "mbarrier.arrive.expect_tx.shared::cta.b64 _, [%0], %1;\n}\n" :: "r"(a), "r"(b) : "memory"); }
__device__ __forceinline__ void tma2d(uint32_t dst, const CUtensorMap* m, uint32_t bar, int c0, int c1) {
  asm volatile(ELECT_ "cp.async.bulk.tensor.2d.shared::cluster.global.mbarrier::complete_tx::bytes [%0], [%1, {%3, %4}], [%2];\n}\n"
               :: "r"(dst), "l"(m), "r"(bar), "r"(c0), "r"(c1) : "memory");
}
__device__ __forceinline__ void tma2d_mc(uint32_t dst, const CUtensorMap* m, uint32_t bar, int c0, int c1, uint16_t mask) {
  asm volatile(ELECT_ "cp.async.bulk.tensor.2d.shared::cluster.global.mbarrier::complete_tx::bytes.multicast::cluster [%0], [%1, {%3, %4}], [%2], %5;\n}\n"
               :: "r"(dst), "l"(m), "r"(bar), "r"(c0), "r"(c1), "h"(mask) : "memory");
}
__device__ __forceinline__ void tma3d(uint32_t dst, const CUtensorMap* m, uint32_t bar, int c0, int c1, int c2) {
  asm volatile(ELECT_ "cp.async.bulk.tensor.3d.shared::cluster.global.mbarrier::complete_tx::bytes [%0], [%1, {%3, %4, %5}], [%2];\n}\n"
               :: "r"(dst), "l"(m), "r"(bar), "r"(c0), "r"(c1), "r"(c2) : "memory");
}
__device__ __forceinline__ void tma3d_mc(uint32_t dst, const CUtensorMap* m, uint32_t bar, int c0, int c1, int c2, uint16_t mask) {
  asm volatile(ELECT_ "cp.async.bulk.tensor.3d.shared::cluster.global.mbarrier::complete_tx::bytes.multicast::cluster [%0], [%1, {%3, %4, %5}], [%2], %6;\n}\n"
               :: "r"(dst), "l"(m), "r"(bar), "r"(c0), "r"(c1), "r"(c2), "h"(mask) : "memory");
}
__device__ __forceinline__ void tma3d_mc_hint(uint32_t dst, const CUtensorMap* m, uint32_t bar, int c0, int c1, int c2, uint16_t mask, uint64_t pol) {
  asm volatile(ELECT_ "cp.async.bulk.tensor.3d.shared::cluster.global.mbarrier::complete_tx::bytes.multicast::cluster.L2::cache_hint [%0], [%1, {%3, %4, %5}], [%2], %6, %7;\n}\n"
               :: "r"(dst), "l"(m), "r"(bar), "r"(c0), "r"(c1), "r"(c2), "h"(mask), "l"(pol) : "memory");
}
__device__ __forceinline__ void bulk_load(uint32_t dst, const void* src, uint32_t bytes, uint32_t bar) {
  asm volatile(ELECT_ "cp.async.bulk.shared::cluster.global.mbarrier::complete_tx::bytes [%0], [%1], %2, [%3];\n}\n"
               :: "r"(dst), "l"(src), "r"(bytes), "r"(bar) : "memory");
}
__device__ __forceinline__ void l2_prefetch16k(const void* p) { asm volatile(ELECT_ "cp.async.bulk.prefetch.L2.global [%0], 16384;\n}\n" :: "l"(p) : "memory"); }
__device__ __forceinline__ void l2_prefetch_t2d(const CUtensorMap* m, int c0, int c1) {
  asm volatile(ELECT_ "cp.async.bulk.prefetch.tensor.2d.L2.global [%0, {%1, %2}];\n}\n" :: "l"(m), "r"(c0), "r"(c1) : "memory");
}
__device__ __forceinline__ void l2_prefetch_t3d(const CUtensorMap* m, int c0, int c1, int c2) {
  asm volatile(ELECT_ "cp.async.bulk.prefetch.tensor.3d.L2.global [%0, {%1, %2, %3}];\n}\n" :: "l"(m), "r"(c0), "r"(c1), "r"(c2) : "memory");
}
__device__ __forceinline__ void stg128(void* p, uint4 v) {
  asm volatile("st.global.v4.u32 [%0], {%1, %2, %3, %4};" :: "l"(p), "r"(v.x), "r"(v.y), "r"(v.z), "r"(v.w) : "memory");
}
__device__ __forceinline__ void prefetch_tmap(const CUtensorMap* m) { asm volatile("prefetch.tensormap [%0];" :: "l"(m) : "memory"); }
__device__ __forceinline__ void wg_fence() { asm volatile("wgmma.fence.sync.aligned;" ::: "memory"); }
__device__ __forceinline__ void wg_commit() { asm volatile("wgmma.commit_group.sync.aligned;" ::: "memory"); }
template <int N> __device__ __forceinline__ void wg_wait() { asm volatile("wgmma.wait_group.sync.aligned %0;" :: "n"(N) : "memory"); }
template <int N> __device__ __forceinline__ void fence_regs(float (&r)[N]) {
#pragma unroll
  for (int i = 0; i < N; i++) asm volatile("" : "+f"(r[i]) :: "memory");
}
template <int N> __device__ __forceinline__ void fence_regs(uint32_t (&r)[N]) {
#pragma unroll
  for (int i = 0; i < N; i++) asm volatile("" : "+r"(r[i]) :: "memory");
}
__device__ __forceinline__ uint64_t mkdesc(uint32_t addr, uint32_t lbo, uint32_t sbo) {
  return (uint64_t)((addr & 0x3FFFF) >> 4) | ((uint64_t)(lbo >> 4) << 16) | ((uint64_t)(sbo >> 4) << 32) | (1ull << 62);
}
__device__ __forceinline__ void bar_sync(int id, int n) { asm volatile("bar.sync %0, %1;" :: "r"(id), "r"(n) : "memory"); }
__device__ __forceinline__ void bar_arrive(int id, int n) { asm volatile("bar.arrive %0, %1;" :: "r"(id), "r"(n) : "memory"); }
__device__ __forceinline__ void cluster_sync() { asm volatile("barrier.cluster.arrive.aligned;\nbarrier.cluster.wait.aligned;" ::: "memory"); }
__device__ __forceinline__ void pdl_wait() { asm volatile("griddepcontrol.wait;" ::: "memory"); }
__device__ __forceinline__ void pdl_launch() { asm volatile("griddepcontrol.launch_dependents;" ::: "memory"); }
__device__ __forceinline__ float ex2(float x) { float y; asm("ex2.approx.ftz.f32 %0, %1;" : "=f"(y) : "f"(x)); return y; }
__device__ __forceinline__ uint32_t pack_bf16(float lo, float hi) { uint32_t r; asm("cvt.rn.bf16x2.f32 %0, %1, %2;" : "=r"(r) : "f"(hi), "f"(lo)); return r; }
__device__ __forceinline__ float bf_lo(uint32_t u) { return __uint_as_float(u << 16); }
__device__ __forceinline__ float bf_hi(uint32_t u) { return __uint_as_float(u & 0xffff0000u); }
__device__ __forceinline__ float bf_round(float x) { return __bfloat162float(__float2bfloat16_rn(x)); }
__device__ __forceinline__ float tanh_fast(float x) { float y; asm("tanh.approx.f32 %0, %1;" : "=f"(y) : "f"(x)); return y; }
__device__ __forceinline__ float gelu_tanh(float x) {
  float u = x * (0.7978845608028654f + 0.035677408136300125f * x * x);
  float hx = 0.5f * x;
  return fmaf(hx, tanh_fast(u), hx);
}
__device__ __forceinline__ float warp_sum(float v) {
#pragma unroll
  for (int o = 16; o > 0; o >>= 1) v += __shfl_xor_sync(0xffffffffu, v, o);
  return v;
}
__device__ __forceinline__ void quad_transpose(uint32_t& v0, uint32_t& v1, uint32_t& v2, uint32_t& v3, int lane) {
  const bool b0 = lane & 1, b1 = lane & 2;
  uint32_t s0 = b0 ? v0 : v1, s1 = b0 ? v2 : v3;
  s0 = __shfl_xor_sync(0xffffffffu, s0, 1); s1 = __shfl_xor_sync(0xffffffffu, s1, 1);
  if (b0) { v0 = s0; v2 = s1; } else { v1 = s0; v3 = s1; }
  uint32_t t0 = b1 ? v0 : v2, t1 = b1 ? v1 : v3;
  t0 = __shfl_xor_sync(0xffffffffu, t0, 2); t1 = __shfl_xor_sync(0xffffffffu, t1, 2);
  if (b1) { v0 = t0; v1 = t1; } else { v2 = t0; v3 = t1; }
}

#define TX(i)
#define TXC(i)
#define TSA(item, i)
#define TL_ENTRY(k)
#define TL_WAITED(k)
#define TL_END(k)
#define TS(item, i)
template<int TB> __device__ __forceinline__ void wgmma_rs_n64(float (&d)[32], uint32_t a0, uint32_t a1, uint32_t a2, uint32_t a3, uint64_t db, int scale_d) {
  asm volatile("{\n.reg .pred p;\nsetp.ne.b32 p, %37, 0;\n"
    "wgmma.mma_async.sync.aligned.m64n64k16.f32.bf16.bf16 {%0, %1, %2, %3, %4, %5, %6, %7, %8, %9, %10, %11, %12, %13, %14, %15, %16, %17, %18, %19, %20, %21, %22, %23, %24, %25, %26, %27, %28, %29, %30, %31}, {%32, %33, %34, %35}, %36, p, 1, 1, %38;\n}\n"
    : "+f"(d[0]), "+f"(d[1]), "+f"(d[2]), "+f"(d[3]), "+f"(d[4]), "+f"(d[5]), "+f"(d[6]), "+f"(d[7]), "+f"(d[8]), "+f"(d[9]), "+f"(d[10]), "+f"(d[11]), "+f"(d[12]), "+f"(d[13]), "+f"(d[14]), "+f"(d[15]), "+f"(d[16]), "+f"(d[17]), "+f"(d[18]), "+f"(d[19]), "+f"(d[20]), "+f"(d[21]), "+f"(d[22]), "+f"(d[23]), "+f"(d[24]), "+f"(d[25]), "+f"(d[26]), "+f"(d[27]), "+f"(d[28]), "+f"(d[29]), "+f"(d[30]), "+f"(d[31])
    : "r"(a0), "r"(a1), "r"(a2), "r"(a3), "l"(db), "r"(scale_d), "n"(TB));
}
template<int TB> __device__ __forceinline__ void wgmma_rs_n192(float (&d)[96], uint32_t a0, uint32_t a1, uint32_t a2, uint32_t a3, uint64_t db, int scale_d) {
  asm volatile("{\n.reg .pred p;\nsetp.ne.b32 p, %101, 0;\n"
    "wgmma.mma_async.sync.aligned.m64n192k16.f32.bf16.bf16 {%0, %1, %2, %3, %4, %5, %6, %7, %8, %9, %10, %11, %12, %13, %14, %15, %16, %17, %18, %19, %20, %21, %22, %23, %24, %25, %26, %27, %28, %29, %30, %31, %32, %33, %34, %35, %36, %37, %38, %39, %40, %41, %42, %43, %44, %45, %46, %47, %48, %49, %50, %51, %52, %53, %54, %55, %56, %57, %58, %59, %60, %61, %62, %63, %64, %65, %66, %67, %68, %69, %70, %71, %72, %73, %74, %75, %76, %77, %78, %79, %80, %81, %82, %83, %84, %85, %86, %87, %88, %89, %90, %91, %92, %93, %94, %95}, {%96, %97, %98, %99}, %100, p, 1, 1, %102;\n}\n"
    : "+f"(d[0]), "+f"(d[1]), "+f"(d[2]), "+f"(d[3]), "+f"(d[4]), "+f"(d[5]), "+f"(d[6]), "+f"(d[7]), "+f"(d[8]), "+f"(d[9]), "+f"(d[10]), "+f"(d[11]), "+f"(d[12]), "+f"(d[13]), "+f"(d[14]), "+f"(d[15]), "+f"(d[16]), "+f"(d[17]), "+f"(d[18]), "+f"(d[19]), "+f"(d[20]), "+f"(d[21]), "+f"(d[22]), "+f"(d[23]), "+f"(d[24]), "+f"(d[25]), "+f"(d[26]), "+f"(d[27]), "+f"(d[28]), "+f"(d[29]), "+f"(d[30]), "+f"(d[31]), "+f"(d[32]), "+f"(d[33]), "+f"(d[34]), "+f"(d[35]), "+f"(d[36]), "+f"(d[37]), "+f"(d[38]), "+f"(d[39]), "+f"(d[40]), "+f"(d[41]), "+f"(d[42]), "+f"(d[43]), "+f"(d[44]), "+f"(d[45]), "+f"(d[46]), "+f"(d[47]), "+f"(d[48]), "+f"(d[49]), "+f"(d[50]), "+f"(d[51]), "+f"(d[52]), "+f"(d[53]), "+f"(d[54]), "+f"(d[55]), "+f"(d[56]), "+f"(d[57]), "+f"(d[58]), "+f"(d[59]), "+f"(d[60]), "+f"(d[61]), "+f"(d[62]), "+f"(d[63]), "+f"(d[64]), "+f"(d[65]), "+f"(d[66]), "+f"(d[67]), "+f"(d[68]), "+f"(d[69]), "+f"(d[70]), "+f"(d[71]), "+f"(d[72]), "+f"(d[73]), "+f"(d[74]), "+f"(d[75]), "+f"(d[76]), "+f"(d[77]), "+f"(d[78]), "+f"(d[79]), "+f"(d[80]), "+f"(d[81]), "+f"(d[82]), "+f"(d[83]), "+f"(d[84]), "+f"(d[85]), "+f"(d[86]), "+f"(d[87]), "+f"(d[88]), "+f"(d[89]), "+f"(d[90]), "+f"(d[91]), "+f"(d[92]), "+f"(d[93]), "+f"(d[94]), "+f"(d[95])
    : "r"(a0), "r"(a1), "r"(a2), "r"(a3), "l"(db), "r"(scale_d), "n"(TB));
}
template<int TB> __device__ __forceinline__ void wgmma_ss_n128(float (&d)[64], uint64_t da, uint64_t db, int scale_d) {
  asm volatile("{\n.reg .pred p;\nsetp.ne.b32 p, %66, 0;\n"
    "wgmma.mma_async.sync.aligned.m64n128k16.f32.bf16.bf16 {%0, %1, %2, %3, %4, %5, %6, %7, %8, %9, %10, %11, %12, %13, %14, %15, %16, %17, %18, %19, %20, %21, %22, %23, %24, %25, %26, %27, %28, %29, %30, %31, %32, %33, %34, %35, %36, %37, %38, %39, %40, %41, %42, %43, %44, %45, %46, %47, %48, %49, %50, %51, %52, %53, %54, %55, %56, %57, %58, %59, %60, %61, %62, %63}, %64, %65, p, 1, 1, 0, %67;\n}\n"
    : "+f"(d[0]), "+f"(d[1]), "+f"(d[2]), "+f"(d[3]), "+f"(d[4]), "+f"(d[5]), "+f"(d[6]), "+f"(d[7]), "+f"(d[8]), "+f"(d[9]), "+f"(d[10]), "+f"(d[11]), "+f"(d[12]), "+f"(d[13]), "+f"(d[14]), "+f"(d[15]), "+f"(d[16]), "+f"(d[17]), "+f"(d[18]), "+f"(d[19]), "+f"(d[20]), "+f"(d[21]), "+f"(d[22]), "+f"(d[23]), "+f"(d[24]), "+f"(d[25]), "+f"(d[26]), "+f"(d[27]), "+f"(d[28]), "+f"(d[29]), "+f"(d[30]), "+f"(d[31]), "+f"(d[32]), "+f"(d[33]), "+f"(d[34]), "+f"(d[35]), "+f"(d[36]), "+f"(d[37]), "+f"(d[38]), "+f"(d[39]), "+f"(d[40]), "+f"(d[41]), "+f"(d[42]), "+f"(d[43]), "+f"(d[44]), "+f"(d[45]), "+f"(d[46]), "+f"(d[47]), "+f"(d[48]), "+f"(d[49]), "+f"(d[50]), "+f"(d[51]), "+f"(d[52]), "+f"(d[53]), "+f"(d[54]), "+f"(d[55]), "+f"(d[56]), "+f"(d[57]), "+f"(d[58]), "+f"(d[59]), "+f"(d[60]), "+f"(d[61]), "+f"(d[62]), "+f"(d[63])
    : "l"(da), "l"(db), "r"(scale_d), "n"(TB));
}
template<int TB> __device__ __forceinline__ void wgmma_ss_n192(float (&d)[96], uint64_t da, uint64_t db, int scale_d) {
  asm volatile("{\n.reg .pred p;\nsetp.ne.b32 p, %98, 0;\n"
    "wgmma.mma_async.sync.aligned.m64n192k16.f32.bf16.bf16 {%0, %1, %2, %3, %4, %5, %6, %7, %8, %9, %10, %11, %12, %13, %14, %15, %16, %17, %18, %19, %20, %21, %22, %23, %24, %25, %26, %27, %28, %29, %30, %31, %32, %33, %34, %35, %36, %37, %38, %39, %40, %41, %42, %43, %44, %45, %46, %47, %48, %49, %50, %51, %52, %53, %54, %55, %56, %57, %58, %59, %60, %61, %62, %63, %64, %65, %66, %67, %68, %69, %70, %71, %72, %73, %74, %75, %76, %77, %78, %79, %80, %81, %82, %83, %84, %85, %86, %87, %88, %89, %90, %91, %92, %93, %94, %95}, %96, %97, p, 1, 1, 0, %99;\n}\n"
    : "+f"(d[0]), "+f"(d[1]), "+f"(d[2]), "+f"(d[3]), "+f"(d[4]), "+f"(d[5]), "+f"(d[6]), "+f"(d[7]), "+f"(d[8]), "+f"(d[9]), "+f"(d[10]), "+f"(d[11]), "+f"(d[12]), "+f"(d[13]), "+f"(d[14]), "+f"(d[15]), "+f"(d[16]), "+f"(d[17]), "+f"(d[18]), "+f"(d[19]), "+f"(d[20]), "+f"(d[21]), "+f"(d[22]), "+f"(d[23]), "+f"(d[24]), "+f"(d[25]), "+f"(d[26]), "+f"(d[27]), "+f"(d[28]), "+f"(d[29]), "+f"(d[30]), "+f"(d[31]), "+f"(d[32]), "+f"(d[33]), "+f"(d[34]), "+f"(d[35]), "+f"(d[36]), "+f"(d[37]), "+f"(d[38]), "+f"(d[39]), "+f"(d[40]), "+f"(d[41]), "+f"(d[42]), "+f"(d[43]), "+f"(d[44]), "+f"(d[45]), "+f"(d[46]), "+f"(d[47]), "+f"(d[48]), "+f"(d[49]), "+f"(d[50]), "+f"(d[51]), "+f"(d[52]), "+f"(d[53]), "+f"(d[54]), "+f"(d[55]), "+f"(d[56]), "+f"(d[57]), "+f"(d[58]), "+f"(d[59]), "+f"(d[60]), "+f"(d[61]), "+f"(d[62]), "+f"(d[63]), "+f"(d[64]), "+f"(d[65]), "+f"(d[66]), "+f"(d[67]), "+f"(d[68]), "+f"(d[69]), "+f"(d[70]), "+f"(d[71]), "+f"(d[72]), "+f"(d[73]), "+f"(d[74]), "+f"(d[75]), "+f"(d[76]), "+f"(d[77]), "+f"(d[78]), "+f"(d[79]), "+f"(d[80]), "+f"(d[81]), "+f"(d[82]), "+f"(d[83]), "+f"(d[84]), "+f"(d[85]), "+f"(d[86]), "+f"(d[87]), "+f"(d[88]), "+f"(d[89]), "+f"(d[90]), "+f"(d[91]), "+f"(d[92]), "+f"(d[93]), "+f"(d[94]), "+f"(d[95])
    : "l"(da), "l"(db), "r"(scale_d), "n"(TB));
}
template<int TB> __device__ __forceinline__ void wgmma_ss_n80(float (&d)[40], uint64_t da, uint64_t db, int scale_d) {
  asm volatile("{\n.reg .pred p;\nsetp.ne.b32 p, %42, 0;\n"
    "wgmma.mma_async.sync.aligned.m64n80k16.f32.bf16.bf16 {%0, %1, %2, %3, %4, %5, %6, %7, %8, %9, %10, %11, %12, %13, %14, %15, %16, %17, %18, %19, %20, %21, %22, %23, %24, %25, %26, %27, %28, %29, %30, %31, %32, %33, %34, %35, %36, %37, %38, %39}, %40, %41, p, 1, 1, 0, %43;\n}\n"
    : "+f"(d[0]), "+f"(d[1]), "+f"(d[2]), "+f"(d[3]), "+f"(d[4]), "+f"(d[5]), "+f"(d[6]), "+f"(d[7]), "+f"(d[8]), "+f"(d[9]), "+f"(d[10]), "+f"(d[11]), "+f"(d[12]), "+f"(d[13]), "+f"(d[14]), "+f"(d[15]), "+f"(d[16]), "+f"(d[17]), "+f"(d[18]), "+f"(d[19]), "+f"(d[20]), "+f"(d[21]), "+f"(d[22]), "+f"(d[23]), "+f"(d[24]), "+f"(d[25]), "+f"(d[26]), "+f"(d[27]), "+f"(d[28]), "+f"(d[29]), "+f"(d[30]), "+f"(d[31]), "+f"(d[32]), "+f"(d[33]), "+f"(d[34]), "+f"(d[35]), "+f"(d[36]), "+f"(d[37]), "+f"(d[38]), "+f"(d[39])
    : "l"(da), "l"(db), "r"(scale_d), "n"(TB));
}

__device__ float g_mod[6 * D_];
__device__ __align__(1024) bf16 g_h[S_ * D_];
__device__ __align__(1024) uint4 g_qs[128 * 3 * 12 * 256];
__device__ __align__(1024) bf16 g_o[S_ * HD_];
__device__ __align__(1024) bf16 g_xch[16 * 2 * 4 * 4 * 128 * 80];
__device__ __align__(1024) bf16 g_w1t[D_ * D_];
__device__ __align__(1024) bf16 g_w2t[D_ * D_];
__device__ __align__(1024) bf16 g_w4t[D_ * F_];
__device__ __align__(32) float g_st1[S_ * 8];
__device__ __align__(32) float g_st2[S_ * 2];
__device__ __align__(32) float g_vec[3 * D_ + F_ + 8];
__device__ unsigned g_flag[1024];
enum { F_XCH = 0, F_XA = 256, F_US = 272, F_X1 = 288, F_G = 304, F_PREP = 320, F_O = 512 };
__device__ __align__(1024) bf16 g_xa[S_ * D_];
__device__ __align__(1024) bf16 g_us[(S_ + 4) * D_];
__device__ __align__(1024) bf16 g_x1[S_ * D_];
__device__ __align__(1024) bf16 g_g[S_ * F_];

__global__ void __launch_bounds__(256) mod_kernel(const bf16* __restrict__ c, const bf16* __restrict__ w_mod) {
  TL_ENTRY(0);
  pdl_launch();
  __shared__ float red[8][32];
  if (blockIdx.x < 14) { const int i = blockIdx.x * 256 + threadIdx.x; if (i < 3 * D_ + F_) g_vec[i] = 0.f; }
  else if (blockIdx.x < 18) g_flag[(blockIdx.x - 14) * 256 + threadIdx.x] = 0u;
  const int t = threadIdx.x, cg = t & 3, r0 = t >> 2;
  const int col0 = blockIdx.x * 32 + cg * 8;
  uint4 w[10];
#pragma unroll
  for (int i = 0; i < 10; i++) w[i] = __ldg(reinterpret_cast<const uint4*>(w_mod + (size_t)(r0 + 64 * i) * (6 * D_) + col0));
  float acc[8];
#pragma unroll
  for (int j = 0; j < 8; j++) acc[j] = 0.f;
#pragma unroll
  for (int i = 0; i < 10; i++) {
    float cv = __bfloat162float(c[r0 + 64 * i]);
    float s = bf_round(cv / (1.f + __expf(-cv)));
    acc[0] = fmaf(s, bf_lo(w[i].x), acc[0]); acc[1] = fmaf(s, bf_hi(w[i].x), acc[1]);
    acc[2] = fmaf(s, bf_lo(w[i].y), acc[2]); acc[3] = fmaf(s, bf_hi(w[i].y), acc[3]);
    acc[4] = fmaf(s, bf_lo(w[i].z), acc[4]); acc[5] = fmaf(s, bf_hi(w[i].z), acc[5]);
    acc[6] = fmaf(s, bf_lo(w[i].w), acc[6]); acc[7] = fmaf(s, bf_hi(w[i].w), acc[7]);
  }
#pragma unroll
  for (int j = 0; j < 8; j++) {
    acc[j] += __shfl_xor_sync(0xffffffffu, acc[j], 4);
    acc[j] += __shfl_xor_sync(0xffffffffu, acc[j], 8);
    acc[j] += __shfl_xor_sync(0xffffffffu, acc[j], 16);
  }
  if ((t & 31) < 4) {
#pragma unroll
    for (int j = 0; j < 8; j++) red[t >> 5][cg * 8 + j] = acc[j];
  }
  __syncthreads();
  if (t < 32) {
    float s = 0.f;
#pragma unroll
    for (int w8 = 0; w8 < 8; w8++) s += red[w8][t];
    const int col = blockIdx.x * 32 + t;
    s = bf_round(s);
    const int part = col / D_;
    if (part == 1 || part == 4) s = bf_round(1.f + s);
    g_mod[col] = s;
    if (t == 0) TL_END(0);
  }
}

__device__ __forceinline__ void row_stats(const float (&v)[20], float& mean, float& rstd) {
  float s = 0.f;
#pragma unroll
  for (int i = 0; i < 20; i++) s += v[i];
  mean = warp_sum(s) * (1.f / D_);
  float q = 0.f;
#pragma unroll
  for (int i = 0; i < 20; i++) { float d = v[i] - mean; q = fmaf(d, d, q); }
  rstd = rsqrtf(warp_sum(q) * (1.f / D_) + LN_EPS);
}
__device__ __forceinline__ void load_row_bf16(const bf16* p, int lane, float (&v)[20]) {
#pragma unroll
  for (int i = 0; i < 5; i++) {
    uint2 u = *reinterpret_cast<const uint2*>(p + (lane + 32 * i) * 4);
    v[4 * i] = bf_lo(u.x); v[4 * i + 1] = bf_hi(u.x); v[4 * i + 2] = bf_lo(u.y); v[4 * i + 3] = bf_hi(u.y);
  }
}
__device__ __forceinline__ void store_row_bf16(bf16* p, int lane, const float (&v)[20]) {
#pragma unroll
  for (int i = 0; i < 5; i++) {
    uint2 u; u.x = pack_bf16(v[4 * i], v[4 * i + 1]); u.y = pack_bf16(v[4 * i + 2], v[4 * i + 3]);
    *reinterpret_cast<uint2*>(p + (lane + 32 * i) * 4) = u;
  }
}
__device__ __forceinline__ void load_row_f32(const float* p, int lane, float (&v)[20]) {
#pragma unroll
  for (int i = 0; i < 5; i++) {
    float4 u = *reinterpret_cast<const float4*>(p + (lane + 32 * i) * 4);
    v[4 * i] = u.x; v[4 * i + 1] = u.y; v[4 * i + 2] = u.z; v[4 * i + 3] = u.w;
  }
}

__global__ void __launch_bounds__(256) ln1_kernel(const bf16* __restrict__ x) {
  TL_ENTRY(1);
  pdl_launch();
  const int lane = threadIdx.x & 31, row = blockIdx.x * 8 + (threadIdx.x >> 5);
  float v[20];
  load_row_bf16(x + (size_t)row * D_, lane, v);
  float mean, rstd;
  row_stats(v, mean, rstd);
  if (lane < 8) g_st1[row * 8 + lane] = 0.f;
  if (lane < 2) g_st2[row * 2 + lane] = 0.f;
  pdl_wait();
  if (threadIdx.x == 0) TL_WAITED(1);
  float sa[20], ca[20];
  load_row_f32(g_mod, lane, sa);
  load_row_f32(g_mod + D_, lane, ca);
#pragma unroll
  for (int i = 0; i < 20; i++) v[i] = fmaf((v[i] - mean) * rstd, ca[i], sa[i]);
  store_row_bf16(g_h + (size_t)row * D_, lane, v);
  if (threadIdx.x == 0) TL_END(1);
}

constexpr int PREP_JOBS = 200 + 200 + 480 + 480;
struct PrepW { const bf16 *w1, *w2, *w3, *w4; };
__device__ __forceinline__ void prep_warp(const PrepW& pw, bf16 (*tile)[72], int lane) {
#pragma unroll 1
  for (int job = blockIdx.x; job < PREP_JOBS; job += gridDim.x) {
    const bf16* src; bf16* dst; int ld = D_, ldd = D_, kt, nt, kind = 1;
    if (job < 200) { src = pw.w1; dst = g_w1t; kt = job / 10; nt = job % 10; kind = 0; }
    else if (job < 400) { src = pw.w2; dst = g_w2t; kt = (job - 200) / 10; nt = (job - 200) % 10; }
    else if (job < 880) { src = pw.w4; dst = g_w4t; ldd = F_; kt = (job - 400) / 10; nt = (job - 400) % 10; }
    else { src = pw.w3; dst = nullptr; ld = F_; kt = (job - 880) / 24; nt = (job - 880) % 24; kind = 2; }
    src += (size_t)(kt * 32 + (lane >> 3)) * ld + nt * 64 + (lane & 7) * 8;
    __syncwarp();
#pragma unroll
    for (int h = 0; h < 2; h++) {
      uint4 v[4];
#pragma unroll
      for (int i = 0; i < 4; i++) v[i] = __ldg(reinterpret_cast<const uint4*>(src + (size_t)(h * 16 + i * 4) * ld));
#pragma unroll
      for (int i = 0; i < 4; i++) *reinterpret_cast<uint4*>(&tile[h * 16 + i * 4 + (lane >> 3)][(lane & 7) * 8]) = v[i];
    }
    __syncwarp();
    const float* pa = g_mod + 4 * D_ + kt * 32;
    const float* pb = g_mod + 3 * D_ + kt * 32;
#pragma unroll 1
    for (int h = 0; h < 2; h++) {
      const int n = lane + 32 * h;
      float sa = 0.f, sb = 0.f, sc = 0.f;
#pragma unroll 1
      for (int c = 0; c < 4; c++) {
        uint32_t u[4];
#pragma unroll
        for (int e = 0; e < 4; e++) {
          const int k = c * 8 + 2 * e;
          float lo = __bfloat162float(tile[k][n]), hi = __bfloat162float(tile[k + 1][n]);
          sc += lo + hi;
          if (kind == 0) {
            const float2 a = __ldcg(reinterpret_cast<const float2*>(pa + k)), b = __ldcg(reinterpret_cast<const float2*>(pb + k));
            sb = fmaf(b.x, lo, fmaf(b.y, hi, sb));
            lo *= a.x; hi *= a.y;
          }
          u[e] = pack_bf16(lo, hi);
          sa += bf_lo(u[e]) + bf_hi(u[e]);
        }
        if (kind != 2) *reinterpret_cast<uint4*>(dst + (size_t)(nt * 64 + n) * ldd + kt * 32 + c * 8) = make_uint4(u[0], u[1], u[2], u[3]);
      }
      if (kind == 0) { atomicAdd(&g_vec[nt * 64 + n], sa); atomicAdd(&g_vec[D_ + nt * 64 + n], sb); atomicAdd(&g_vec[2 * D_ + nt * 64 + n], sc); }
      else if (kind == 2) atomicAdd(&g_vec[3 * D_ + nt * 64 + n], sc);
    }
  }
  __syncwarp();
  if (lane == 0) {
    asm volatile("fence.acq_rel.gpu;" ::: "memory");
    asm volatile("red.relaxed.gpu.global.add.u32 [%0], 1;" :: "l"(g_flag + F_PREP) : "memory");
  }
}

constexpr int A_NSLOT = 9;
constexpr int A_SLOT = 24576;
constexpr int A_NKV = S_ / 64;
constexpr int PREP_CTAS = 128;

struct Ring {
  uint32_t slot, phase;
  __device__ __forceinline__ void adv(int n) { if (++slot == (uint32_t)n) { slot = 0; phase ^= 1; } }
};
constexpr int T_PAR = A_NSLOT * A_SLOT + 384;
constexpr int T_PREP = T_PAR + 3712;
constexpr int T_SMEM = T_PREP + 32 * 72 * 2 + 1024;
enum { P_OGA = 0, P_OA = 80, P_OB = 160, P_VA = 240, P_VB = 320, P_VC = 400, P_A2 = 480, P_B2 = 560, P_GB = 640, P_CS3 = 720, P_SC = 912 };

__device__ __forceinline__ void flag_wait(const unsigned* p, unsigned target) {
  asm volatile(
      "{\n.reg .pred p;\n.reg .u32 n, v;\n"
      "mov.u32 n, 0;\n"
      "SPIN:\n"
      "ld.relaxed.gpu.global.u32 v, [%0];\n"
      "setp.ge.u32 p, v, %1;\n"
      "@p bra DONE;\n"
      "add.u32 n, n, 1;\n"
      "setp.gt.u32 p, n, 4194304;\n"
      "@p trap;\n"
      "bra SPIN;\n"
      "DONE:\n}\n" :: "l"(p), "r"(target) : "memory");
}
__device__ __forceinline__ void fence_async_global() { asm volatile("fence.proxy.async.global;" ::: "memory"); }
__device__ __forceinline__ float lds_f(uint32_t a) { float v; asm volatile("ld.shared.f32 %0, [%1];" : "=f"(v) : "r"(a)); return v; }
__device__ __forceinline__ float2 lds_f2(uint32_t a) { float2 v; asm volatile("ld.shared.v2.f32 {%0, %1}, [%2];" : "=f"(v.x), "=f"(v.y) : "r"(a)); return v; }
__device__ __forceinline__ uint4 ldcg4(const void* p) { return __ldcg(reinterpret_cast<const uint4*>(p)); }

__device__ __forceinline__ void sts_f2(uint32_t a, float x, float y) { asm volatile("st.shared.v2.f32 [%0], {%1, %2};" :: "r"(a), "f"(x), "f"(y) : "memory"); }
__device__ __forceinline__ void sts_u4(uint32_t a, uint4 v) { asm volatile("st.shared.v4.u32 [%0], {%1, %2, %3, %4};" :: "r"(a), "r"(v.x), "r"(v.y), "r"(v.z), "r"(v.w) : "memory"); }
__device__ __forceinline__ void sts_u1(uint32_t a, uint32_t v) { asm volatile("st.shared.u32 [%0], %1;" :: "r"(a), "r"(v) : "memory"); }
__device__ __forceinline__ void fence_async_smem() { asm volatile("fence.proxy.async.shared::cta;" ::: "memory"); }
__device__ __forceinline__ void bulk_store(void* dst, uint32_t src, uint32_t bytes) {
  asm volatile("cp.async.bulk.global.shared::cta.bulk_group [%0], [%1], %2;" :: "l"(dst), "r"(src), "r"(bytes) : "memory");
}
__device__ __forceinline__ void bulk_red_f32(void* dst, uint32_t src, uint32_t bytes) {
  asm volatile("cp.reduce.async.bulk.global.shared::cta.bulk_group.add.f32 [%0], [%1], %2;" :: "l"(dst), "r"(src), "r"(bytes) : "memory");
}
__device__ __forceinline__ void tma_store2d(const CUtensorMap* m, uint32_t src, int c0, int c1) {
  asm volatile("cp.async.bulk.tensor.2d.global.shared::cta.bulk_group [%0, {%2, %3}], [%1];" :: "l"(m), "r"(src), "r"(c0), "r"(c1) : "memory");
}
__device__ __forceinline__ void bulk_done() { asm volatile("cp.async.bulk.commit_group;\ncp.async.bulk.wait_group 0;" ::: "memory"); }
__device__ __forceinline__ void flag_add(unsigned* f) { asm volatile("red.relaxed.gpu.global.add.u32 [%0], 1;" :: "l"(f) : "memory"); }
__device__ __forceinline__ float4 lds_f4(uint32_t a) { return *reinterpret_cast<const float4*>(__cvta_shared_to_generic(a)); }
__device__ __forceinline__ uint4 lds_u4(uint32_t a) { return *reinterpret_cast<const uint4*>(__cvta_shared_to_generic(a)); }
__device__ __forceinline__ void lds8(uint32_t a, float (&v)[8]) {
  const float4 p = lds_f4(a), q = lds_f4(a + 16);
  v[0] = p.x; v[1] = p.y; v[2] = p.z; v[3] = p.w; v[4] = q.x; v[5] = q.y; v[6] = q.z; v[7] = q.w;
}
__device__ __forceinline__ void lds8_bf(uint32_t a, float (&v)[8]) {
  const uint4 u = lds_u4(a);
  v[0] = bf_lo(u.x); v[1] = bf_hi(u.x); v[2] = bf_lo(u.y); v[3] = bf_hi(u.y); v[4] = bf_lo(u.z); v[5] = bf_hi(u.z); v[6] = bf_lo(u.w); v[7] = bf_hi(u.w);
}
__device__ __forceinline__ uint4 pack8(const float (&v)[8]) {
  return make_uint4(pack_bf16(v[0], v[1]), pack_bf16(v[2], v[3]), pack_bf16(v[4], v[5]), pack_bf16(v[6], v[7]));
}
__device__ __forceinline__ void mbar_wait_c(uint32_t a, uint32_t ph) {
  asm volatile("{\n.reg .pred p;\nSPIN:\nmbarrier.try_wait.parity.shared::cta.b64 p, [%0], %1;\n@!p bra SPIN;\n}\n" :: "r"(a), "r"(ph) : "memory");
}
constexpr int ST_P = 80;
constexpr int E_TILE = 128 * 80 * 2;

struct Maps { CUtensorMap h, wq, k, v, o, wo3, wo2, xa, w1t, us, w2t, x1, w3, g, w4t, ex, exa, ex1, sxa, sus, sx1, sout; };
struct PfList { const uint8_t* p[6]; };

constexpr int M_AOFF = 102400, M_NA = 7;

__global__ void __cluster_dims__(2, 1, 1) __launch_bounds__(384, 1)
fused_kernel(const __grid_constant__ Maps tm, const __grid_constant__ PfList pf, const __grid_constant__ PrepW pw, const bf16* __restrict__ x, bf16* __restrict__ out) {
  extern __shared__ uint8_t smem_raw[];
  const uint32_t sb = (smem_u32(smem_raw) + 1023) & ~1023u;
  TL_ENTRY(2);
  const uint32_t bar_full = sb + A_NSLOT * A_SLOT;
  const uint32_t bar_empty = bar_full + 8 * A_NSLOT;
  const uint32_t bar_sig = bar_empty + 8 * A_NSLOT;
  const uint32_t mb_full = bar_sig + 16;
  const uint32_t mb_empty = mb_full + 96;
  const uint32_t par = sb + T_PAR;
  float* parf = reinterpret_cast<float*>(smem_raw + (par - smem_u32(smem_raw)));
  uint32_t rank;
  asm volatile("mov.u32 %0, %%cluster_ctarank;" : "=r"(rank));
  const int cid = blockIdx.x >> 1;
  const int wid = __shfl_sync(0xffffffffu, threadIdx.x >> 5, 0);
  const int wg = wid >> 2;
  const int qtile = (cid & 7) * 2 + rank, hbase = cid >> 3;
  const int o_qt = qtile, o_nh = (cid >> 3) & 1, o_ks = cid >> 4;
  const int o_col = o_nh * 320 + o_ks * 80;
  const int qt = cid >> 2, js = (cid & 3) * 2 + rank;
  if (threadIdx.x == 0) {
    for (int i = 0; i < A_NSLOT; i++) { mbar_init(bar_full + 8 * i, 1); mbar_init(bar_empty + 8 * i, 16); }
    mbar_init(bar_sig, 4); mbar_init(bar_sig + 8, 4);
    for (int i = 0; i < 12; i++) { mbar_init(mb_full + 8 * i, 1); mbar_init(mb_empty + 8 * i, i < 5 ? 8 : 16); }
    asm volatile("fence.mbarrier_init.release.cluster;" ::: "memory");
    prefetch_tmap(&tm.h); prefetch_tmap(&tm.wq); prefetch_tmap(&tm.k); prefetch_tmap(&tm.v);
  }
  __syncthreads();
  cluster_sync();

  if (wg == 0) {
    asm volatile("setmaxnreg.dec.sync.aligned.u32 24;");
    if (wid == 0) {
      Ring r{0, 1};
#define P_ACQ(bytes_) do { mbar_wait(bar_empty + 8 * r.slot, r.phase); mbar_expect_e(bar_full + 8 * r.slot, bytes_); } while (0)
#define P_DST (sb + r.slot * A_SLOT)
#define P_BAR (bar_full + 8 * r.slot)
      uint64_t pol_ef;
      asm volatile("createpolicy.fractional.L2::evict_first.b64 %0, 1.0;" : "=l"(pol_ef));
#pragma unroll 1
      for (int t = qtile; t < 40; t += 16) {
        const int hs = t < 20 ? 1 + (t & 1) : (t & 1) * 3;
        l2_prefetch_t3d(&tm.wq, 0, ((t % 20) >> 1) * 64, (hbase + 8 * hs) * 3);
      }
      pdl_wait();
      TL_WAITED(2);
#pragma unroll 1
      for (int t = 0; t < 20; t++) {
        const int kb = t % 10;
        P_ACQ(16384);
        tma2d(P_DST, &tm.h, P_BAR, kb * 64, qtile * 128);
        r.adv(A_NSLOT);
        P_ACQ(A_SLOT);
        if (rank == 0) tma3d_mc_hint(P_DST, &tm.wq, P_BAR, 0, kb * 64, (hbase + (t < 10 ? 8 : 0)) * 3, 3, pol_ef);
        r.adv(A_NSLOT);
        P_ACQ(A_SLOT);
        if (rank == 1) tma3d_mc_hint(P_DST, &tm.wq, P_BAR, 0, kb * 64, (hbase + (t < 10 ? 16 : 24)) * 3, 3, pol_ef);
        r.adv(A_NSLOT);
      }
#pragma unroll 1
      for (int item = 0; item < 4; item++) {
        const int head = hbase + 8 * item;
#pragma unroll 1
        for (int j = 0; j <= A_NKV; j++) {
          if (j < A_NKV) {
            P_ACQ(A_SLOT);
            if (rank == 0) tma3d_mc_hint(P_DST, &tm.k, P_BAR, 0, head * S_ + j * 64, 0, 3, pol_ef);
            r.adv(A_NSLOT);
          }
          if (j > 0) {
            P_ACQ(A_SLOT);
            if (rank == 1) tma3d_mc_hint(P_DST, &tm.v, P_BAR, 0, head * S_ + (j - 1) * 64, 0, 3, pol_ef);
            r.adv(A_NSLOT);
          }
          if (item < 3 && j >= 20 && j < 23) l2_prefetch16k(g_qs + ((size_t)(blockIdx.x * 3 + item) * 12 + (j - 20) * 4) * 256);
          if (item == 3 && (j & 3) == 0) {
            const int c = (j >> 2) * 128 + blockIdx.x;
            if (c < 980) {
              const int li = c < 480 ? 0 : c < 600 ? 1 : c < 720 ? 2 : c < 880 ? 3 : c < 930 ? 4 : 5;
              const int c0 = c < 480 ? 0 : c < 600 ? 480 : c < 720 ? 600 : c < 880 ? 720 : c < 930 ? 880 : 930;
              l2_prefetch16k(pf.p[li] + (size_t)(c - c0) * 16384);
            }
          }
          if (item == 3) {
            if (j >= 6 && j < 24) {
              const int kb = j - 6;
              l2_prefetch_t2d(&tm.o, ((kb / 6) * 8 + 2 * o_ks + (kb % 6) / 3) * DH_ + (kb % 3) * 64, o_qt * 128);
            }
            if (j >= 24 && j < 30) flag_wait(g_flag + F_O + o_qt * 32 + ((j - 24) >> 1) * 8 + 2 * o_ks + (j & 1), 2);
            if (j == 0 && threadIdx.x == 0) {
              prefetch_tmap(&tm.o); prefetch_tmap(&tm.wo3); prefetch_tmap(&tm.wo2); prefetch_tmap(&tm.xa); prefetch_tmap(&tm.w1t); prefetch_tmap(&tm.us);
              prefetch_tmap(&tm.w2t); prefetch_tmap(&tm.x1); prefetch_tmap(&tm.w3); prefetch_tmap(&tm.g); prefetch_tmap(&tm.w4t);
              prefetch_tmap(&tm.ex); prefetch_tmap(&tm.exa); prefetch_tmap(&tm.ex1);
              prefetch_tmap(&tm.sxa); prefetch_tmap(&tm.sus); prefetch_tmap(&tm.sx1); prefetch_tmap(&tm.sout);
            }
          }
        }
      }
#pragma unroll 1
      for (int kb = 0; kb < 24; kb++) {
        const int head = (kb / 6) * 8 + 2 * o_ks + (kb % 6) / 3;
        const int kcol = head * DH_ + (kb % 3) * 64;
        P_ACQ(24576);
        if (rank == 0) tma3d_mc(P_DST, &tm.wo3, P_BAR, 0, kcol, o_nh * 5, 3);
        r.adv(A_NSLOT);
        P_ACQ(16384);
        if (rank == 1) tma3d_mc(P_DST, &tm.wo2, P_BAR, 0, kcol, o_nh * 5 + 3, 3);
        r.adv(A_NSLOT);
        if (kb == 18 || kb == 21) flag_wait(g_flag + F_O + o_qt * 32 + head, 2);
        if (kb % 3 == 0) fence_async_global();
        P_ACQ(16384);
        tma2d(P_DST, &tm.o, P_BAR, kcol, o_qt * 128);
        r.adv(A_NSLOT);
      }
      P_ACQ(E_TILE);
      tma2d(P_DST, &tm.ex, P_BAR, o_col, o_qt * 128);
      r.adv(A_NSLOT);
      flag_wait(g_flag + F_XCH + (o_qt * 2 + o_nh) * 4 + o_ks, 6);
      fence_async_global();
#pragma unroll 1
      for (int i = 0; i < 3; i++) {
        P_ACQ(E_TILE);
        bulk_load(P_DST, g_xch + (size_t)((((o_qt * 2 + o_nh) * 4 + o_ks) * 4) + ((o_ks + 1 + i) & 3)) * (E_TILE / 2), E_TILE, P_BAR);
        r.adv(A_NSLOT);
      }
      flag_wait(g_flag + F_PREP, PREP_CTAS);
      fence_async_global();
#pragma unroll 1
      for (int i = 0; i < A_NSLOT; i++) { mbar_wait(bar_empty + 8 * r.slot, r.phase); r.adv(A_NSLOT); }
      Ring ra{0, 1};
      uint32_t bpar = 0x1f;
#pragma unroll 1
      for (int ph = 0; ph < 4; ph++) {
        const CUtensorMap* ma = ph == 0 ? &tm.xa : ph == 1 ? &tm.us : ph == 2 ? &tm.x1 : &tm.g;
        const CUtensorMap* mb = ph == 0 ? &tm.w1t : ph == 1 ? &tm.w2t : ph == 2 ? &tm.w3 : &tm.w4t;
        const int nkb = ph == 3 ? 24 : 10;
        const int nbl = ph == 2 ? 10 : nkb / 2;
        const int nel = ph == 1 ? 1 : ph == 3 ? 2 : 0;
        const uint32_t nbs = ph == 2 ? 4 : 5, bsz = ph == 2 ? 24576 : 20480;
        int bl = 0; uint32_t bs = 0;
#pragma unroll 1
        for (int i = 0; i < 5; i++) mbar_wait(mb_empty + 8 * i, (bpar >> i) & 1);
#define T_LOADB() do { mbar_wait(mb_empty + 8 * bs, (bpar >> bs) & 1); bpar ^= 1u << bs; mbar_expect_e(mb_full + 8 * bs, bsz);    \
                       if (bl < nbl) tma3d(sb + bs * bsz, mb, mb_full + 8 * bs, 0, ph == 2 ? bl * 64 : js * 80, ph == 2 ? js * 3 : bl * 2); \
                       else tma2d(sb + bs * bsz, bl == nbl ? &tm.exa : &tm.ex1, mb_full + 8 * bs, js * 80, qt * 128); \
                       bl++; if (++bs == nbs) bs = 0; } while (0)
#pragma unroll 1
        for (uint32_t i = 0; i < nbs; i++) T_LOADB();
        TX(8 + ph * 4);
        const unsigned* fl = g_flag + F_XA + 16 * ph;
        flag_wait(fl + qt, 16);
        if (ph == 1) { if (qt > 0) flag_wait(fl + qt - 1, 16); if (qt < 15) flag_wait(fl + qt + 1, 16); }
        TX(9 + ph * 4);
        fence_async_global();
#pragma unroll 1
        for (int kb = 0; kb < nkb; kb++) {
          mbar_wait(mb_empty + 40 + 8 * ra.slot, ra.phase);
          mbar_expect_e(mb_full + 40 + 8 * ra.slot, 16384);
          tma2d_mc(sb + M_AOFF + ra.slot * 16384 + rank * 8192, ma, mb_full + 40 + 8 * ra.slot, kb * 64, qt * 128 + (int)rank * 64, 3);
          ra.adv(M_NA);
          while (bl < nbl + nel && (kb == nkb - 1 || kb >= (ph == 2 ? bl + 2 : 2 * bl - 3))) T_LOADB();
        }
      }
    } else if (wid < 3) {
      const int w = wid - 1, lane = threadIdx.x & 31;
#pragma unroll 1
      for (int sig = 0; sig < 4; sig++) {
        mbar_wait(bar_sig + 8 * w, sig & 1);
        if (lane == 0) {
          asm volatile("fence.acq_rel.gpu;" ::: "memory");
          flag_add(g_flag + F_O + qtile * 32 + hbase + 8 * sig);
        }
        __syncwarp();
      }
    } else {
      const int lane = threadIdx.x & 31;
      pdl_wait();
      prep_warp(pw, reinterpret_cast<bf16(*)[72]>(smem_raw + (sb + T_PREP - smem_u32(smem_raw))), lane);
      flag_wait(g_flag + F_PREP, PREP_CTAS);
#pragma unroll 1
      for (int i = lane; i < P_SC; i += 32) {
        const int v = i < P_CS3 ? i / 80 : 9, j = i - (i < P_CS3 ? v * 80 : P_CS3);
        const float* src = v == 0 ? g_mod + 2 * D_ + o_col : v == 1 ? g_mod + 4 * D_ + o_col : v == 2 ? g_mod + 3 * D_ + o_col
                         : v < 6 ? g_vec + (v - 3) * D_ + js * 80 : v == 6 ? g_mod + 4 * D_ + js * 80 : v == 7 ? g_mod + 3 * D_ + js * 80
                         : v == 8 ? g_mod + 5 * D_ + js * 80 : g_vec + 3 * D_ + js * 192;
        parf[i] = __ldcg(src + j);
      }
      float sv[5] = {0.f, 0.f, 0.f, 0.f, 0.f};
#pragma unroll 1
      for (int i = lane; i < D_; i += 32) {
        const float a = __ldcg(g_mod + 4 * D_ + i), b = __ldcg(g_mod + 3 * D_ + i);
        sv[0] += a; sv[1] = fmaf(a, a, sv[1]); sv[2] = fmaf(a, b, sv[2]); sv[3] += b; sv[4] = fmaf(b, b, sv[4]);
      }
#pragma unroll 1
      for (int o_ = 16; o_ > 0; o_ >>= 1) {
#pragma unroll
        for (int i = 0; i < 5; i++) sv[i] += __shfl_xor_sync(0xffffffffu, sv[i], o_);
      }
      if (lane == 0) {
#pragma unroll
        for (int i = 0; i < 5; i++) parf[P_SC + i] = sv[i];
      }
      bar_arrive(6, 288);
    }
    __syncwarp();
    cluster_sync();
  } else {
    asm volatile("setmaxnreg.inc.sync.aligned.u32 240;");
    const int w = wg - 1;
    const int lane = threadIdx.x & 31;
    const int warp = wid & 3;
    const int tid = threadIdx.x - 128;
    const uint32_t rel_base = mapa(bar_empty, (lane == 0) ? rank : (rank ^ 1));
    Ring r{0, 0};
#define A_RELEASE(slot_) do { if (lane < 2) mbar_arrive_remote(rel_base + 8 * (slot_)); } while (0)
#define SIGNAL() do { __syncwarp(); if (lane == 0) mbar_arrive(bar_sig + 8 * w); } while (0)
    {
    const float SC = 0.07216878364870322f * 1.4426950408889634f;
    float o[96];
    uint32_t q[48];
    float s[32];
    uint32_t p[16], p2[16];
    if (w == 1) bar_arrive(1, 256);
#define QS_PTR(i_) (g_qs + ((size_t)(blockIdx.x * 3 + (i_)) * 12) * 256 + (threadIdx.x - 128))
#define OROW_PTR(it_) (g_o + (size_t)(qtile * 128 + ((threadIdx.x - 128) >> 5) * 16 + ((threadIdx.x & 31) >> 2)) * HD_ + (hbase + 8 * (it_)) * DH_ + (threadIdx.x & 3) * 8)
    TSA(0, 0);
    {
      float qb[96];
#pragma unroll 1
      for (int pass = 0; pass < 2; pass++) {
        uint32_t p0 = 0, p1 = 0, p2_ = 0;
#pragma unroll 1
        for (int kb = 0; kb < 10; kb++) {
          const uint32_t sA = r.slot; mbar_wait_c(bar_full + 8 * sA, r.phase); r.adv(A_NSLOT);
          const uint32_t sB = r.slot; mbar_wait_c(bar_full + 8 * sB, r.phase); r.adv(A_NSLOT);
          const uint32_t sC = r.slot; mbar_wait_c(bar_full + 8 * sC, r.phase); r.adv(A_NSLOT);
          const uint64_t da = mkdesc(sb + sA * A_SLOT + w * 8192, 16, 1024);
          const uint64_t db = mkdesc(sb + sB * A_SLOT, 8192, 1024), dc = mkdesc(sb + sC * A_SLOT, 8192, 1024);
          wg_fence();
#pragma unroll
          for (int kk = 0; kk < 4; kk++) {
            wgmma_ss_n192<1>(o, da + kk * 2, db + kk * 128, (kb | kk) != 0);
            wgmma_ss_n192<1>(qb, da + kk * 2, dc + kk * 128, (kb | kk) != 0);
          }
          wg_commit();
          if (kb > 0) { wg_wait<1>(); A_RELEASE(p0); A_RELEASE(p1); A_RELEASE(p2_); }
          p0 = sA; p1 = sB; p2_ = sC;
        }
        wg_wait<0>();
        fence_regs(o); fence_regs(qb);
        A_RELEASE(p0); A_RELEASE(p1); A_RELEASE(p2_);
#pragma unroll
        for (int i = 0; i < 12; i++)
          stg128(QS_PTR(pass + 1) + i * 256, make_uint4(pack_bf16(qb[8 * i], qb[8 * i + 1]), pack_bf16(qb[8 * i + 2], qb[8 * i + 3]),
                                                               pack_bf16(qb[8 * i + 4], qb[8 * i + 5]), pack_bf16(qb[8 * i + 6], qb[8 * i + 7])));
        if (pass == 0) {
#pragma unroll
          for (int i = 0; i < 12; i++)
            stg128(QS_PTR(0) + i * 256, make_uint4(pack_bf16(o[8 * i], o[8 * i + 1]), pack_bf16(o[8 * i + 2], o[8 * i + 3]),
                                            pack_bf16(o[8 * i + 4], o[8 * i + 5]), pack_bf16(o[8 * i + 6], o[8 * i + 7])));
        }
      }
#pragma unroll
      for (int i = 0; i < 48; i++) q[i] = pack_bf16(o[2 * i], o[2 * i + 1]);
    }
    uint32_t ob[48];
#pragma unroll
    for (int i = 0; i < 48; i++) asm volatile("" : "=r"(ob[i]));
#define O_STORE(g)                                                                                                     \
      {                                                                                                                \
        quad_transpose(ob[8 * g], ob[8 * g + 2], ob[8 * g + 4], ob[8 * g + 6], lane);                                  \
        stg128(orow + g * 32, make_uint4(ob[8 * g], ob[8 * g + 2], ob[8 * g + 4], ob[8 * g + 6]));                     \
        quad_transpose(ob[8 * g + 1], ob[8 * g + 3], ob[8 * g + 5], ob[8 * g + 7], lane);                              \
        stg128(orow + (size_t)8 * HD_ + g * 32, make_uint4(ob[8 * g + 1], ob[8 * g + 3], ob[8 * g + 5], ob[8 * g + 7])); \
      }
#pragma unroll 1
    for (int item = 0; item < 4; item++) {
      if (item > 0) TSA(item, 0);
      TSA(item, 1);
      float c0, c1, l0, l1;
      {
        const uint32_t sK = r.slot; mbar_wait_c(bar_full + 8 * sK, r.phase); r.adv(A_NSLOT);
        const uint64_t dk = mkdesc(sb + sK * A_SLOT, 16, 1024);
        bar_sync(1 + w, 256);
        wg_fence();
#pragma unroll
        for (int kk = 0; kk < 12; kk++)
          wgmma_rs_n64<0>(s, q[4 * kk], q[4 * kk + 1], q[4 * kk + 2], q[4 * kk + 3], dk + (kk >> 2) * 512 + (kk & 3) * 2, kk != 0);
        wg_commit();
        bar_arrive(1 + (w ^ 1), 256);
        if (item > 0) {
          bf16* orow = OROW_PTR(item - 1);
#pragma unroll
          for (int g = 0; g < 6; g++) { O_STORE(g) }
          SIGNAL();
        }
        wg_wait<0>();
        fence_regs(s);
        A_RELEASE(sK);
        float mx0 = fmaxf(s[0], s[1]), mx1 = fmaxf(s[2], s[3]);
#pragma unroll
        for (int i = 1; i < 8; i++) { mx0 = fmaxf(mx0, fmaxf(s[4 * i], s[4 * i + 1])); mx1 = fmaxf(mx1, fmaxf(s[4 * i + 2], s[4 * i + 3])); }
        mx0 = fmaxf(mx0, __shfl_xor_sync(0xffffffffu, mx0, 1)); mx1 = fmaxf(mx1, __shfl_xor_sync(0xffffffffu, mx1, 1));
        mx0 = fmaxf(mx0, __shfl_xor_sync(0xffffffffu, mx0, 2)); mx1 = fmaxf(mx1, __shfl_xor_sync(0xffffffffu, mx1, 2));
        c0 = mx0 * SC; c1 = mx1 * SC;
        l0 = 0.f; l1 = 0.f;
#pragma unroll
        for (int i = 0; i < 8; i++) {
          s[4 * i] = ex2(fmaf(s[4 * i], SC, -c0)); s[4 * i + 1] = ex2(fmaf(s[4 * i + 1], SC, -c0));
          s[4 * i + 2] = ex2(fmaf(s[4 * i + 2], SC, -c1)); s[4 * i + 3] = ex2(fmaf(s[4 * i + 3], SC, -c1));
          l0 += s[4 * i] + s[4 * i + 1]; l1 += s[4 * i + 2] + s[4 * i + 3];
        }
#pragma unroll
        for (int i = 0; i < 16; i++) p[i] = pack_bf16(s[2 * i], s[2 * i + 1]);
      }
      TSA(item, 2);
#pragma unroll
      for (int i = 0; i < 96; i++) asm volatile("" : "=f"(o[i]));
      uint32_t okn;
      {
        Ring r2 = r; r2.adv(A_NSLOT);
        okn = mbar_try(bar_full + 8 * r.slot, r.phase) & mbar_try(bar_full + 8 * r2.slot, r2.phase);
      }
#define A_STEP(PC, PN, FIRST, LAST)                                                                                          \
      {                                                                                                                \
        const uint32_t sK = r.slot, phK = r.phase; r.adv(A_NSLOT);                                                     \
        const uint32_t sV = r.slot, phV = r.phase; r.adv(A_NSLOT);                                                     \
        const uint64_t dk = mkdesc(sb + sK * A_SLOT, 16, 1024);                                                        \
        const uint64_t dv = mkdesc(sb + sV * A_SLOT, 8192, 1024);                                                      \
        if (!okn) { mbar_wait_c(bar_full + 8 * sK, phK); mbar_wait_c(bar_full + 8 * sV, phV); }                            \
        bar_sync(1 + w, 256);                                                                                          \
        wg_fence();                                                                                                    \
        _Pragma("unroll") for (int kk = 0; kk < 12; kk++)                                                              \
          wgmma_rs_n64<0>(s, q[4 * kk], q[4 * kk + 1], q[4 * kk + 2], q[4 * kk + 3], dk + (kk >> 2) * 512 + (kk & 3) * 2, kk != 0); \
        wg_commit();                                                                                                   \
        _Pragma("unroll") for (int kk = 0; kk < 4; kk++)                                                               \
          wgmma_rs_n192<1>(o, PC[4 * kk], PC[4 * kk + 1], PC[4 * kk + 2], PC[4 * kk + 3], dv + kk * 128, !(FIRST) || (kk != 0)); \
        wg_commit();                                                                                                   \
        bar_arrive(1 + (w ^ 1), 256);                                                                                  \
        {                                                                                                              \
          Ring r2 = r; r2.adv(A_NSLOT);                                                                                \
          okn = mbar_try(bar_full + 8 * r.slot, r.phase) & mbar_try(bar_full + 8 * r2.slot, r2.phase);                 \
        }                                                                                                              \
        wg_wait<1>();                                                                                                  \
        fence_regs(s);                                                                                                 \
        A_RELEASE(sK);                                                                                                 \
        if (LAST) {                                         \
          _Pragma("unroll") for (int i = 0; i < 12; i++)                                                               \
            asm volatile("ld.global.cg.v4.u32 {%0, %1, %2, %3}, [%4];" : "=r"(q[4 * i]), "=r"(q[4 * i + 1]), "=r"(q[4 * i + 2]), "=r"(q[4 * i + 3]) : "l"(QS_PTR(item < 3 ? item : 2) + i * 256) : "memory"); \
        }                                                                                                              \
        float b0 = 0.f, b1 = 0.f;                                                                                      \
        _Pragma("unroll") for (int i = 0; i < 8; i++) {                                                                \
          const float e0 = ex2(fmaf(s[4 * i], SC, -c0)), e1 = ex2(fmaf(s[4 * i + 1], SC, -c0));                        \
          const float e2 = ex2(fmaf(s[4 * i + 2], SC, -c1)), e3 = ex2(fmaf(s[4 * i + 3], SC, -c1));                    \
          b0 += e0 + e1; b1 += e2 + e3;                                                                                \
          PN[2 * i] = pack_bf16(e0, e1); PN[2 * i + 1] = pack_bf16(e2, e3);                                            \
        }                                                                                                              \
        wg_wait<0>();                                                                                                  \
        fence_regs(o);                                                                                                 \
        fence_regs(PC);                                                                                                \
        A_RELEASE(sV);                                                                                                 \
        if (__any_sync(0xffffffffu, !(b0 <= 65536.f) || !(b1 <= 65536.f))) {                                           \
          float mx0 = fmaxf(s[0], s[1]), mx1 = fmaxf(s[2], s[3]);                                                      \
          _Pragma("unroll") for (int i = 1; i < 8; i++) {                                                              \
            mx0 = fmaxf(mx0, fmaxf(s[4 * i], s[4 * i + 1])); mx1 = fmaxf(mx1, fmaxf(s[4 * i + 2], s[4 * i + 3]));     \
          }                                                                                                            \
          mx0 = fmaxf(mx0, __shfl_xor_sync(0xffffffffu, mx0, 1)); mx1 = fmaxf(mx1, __shfl_xor_sync(0xffffffffu, mx1, 1)); \
          mx0 = fmaxf(mx0, __shfl_xor_sync(0xffffffffu, mx0, 2)); mx1 = fmaxf(mx1, __shfl_xor_sync(0xffffffffu, mx1, 2)); \
          const float n0 = fmaxf(c0, mx0 * SC), n1 = fmaxf(c1, mx1 * SC);                                              \
          const float a0 = ex2(c0 - n0), a1 = ex2(c1 - n1);                                                            \
          c0 = n0; c1 = n1;                                                                                            \
          l0 *= a0; l1 *= a1;                                                                                          \
          _Pragma("unroll") for (int i = 0; i < 24; i++) { o[4 * i] *= a0; o[4 * i + 1] *= a0; o[4 * i + 2] *= a1; o[4 * i + 3] *= a1; } \
          b0 = 0.f; b1 = 0.f;                                                                                          \
          _Pragma("unroll") for (int i = 0; i < 8; i++) {                                                              \
            const float e0 = ex2(fmaf(s[4 * i], SC, -c0)), e1 = ex2(fmaf(s[4 * i + 1], SC, -c0));                      \
            const float e2 = ex2(fmaf(s[4 * i + 2], SC, -c1)), e3 = ex2(fmaf(s[4 * i + 3], SC, -c1));                  \
            b0 += e0 + e1; b1 += e2 + e3;                                                                              \
            PN[2 * i] = pack_bf16(e0, e1); PN[2 * i + 1] = pack_bf16(e2, e3);                                          \
          }                                                                                                            \
        }                                                                                                              \
        l0 += b0; l1 += b1;                                                                                            \
      }
      for (int jj = 0; jj < 15; jj++) {
        A_STEP(p, p2, jj == 0, false)
        A_STEP(p2, p, false, false)
      }
      A_STEP(p, p2, false, true)
      TSA(item, 3);
      {
        const uint32_t sV = r.slot; mbar_wait_c(bar_full + 8 * sV, r.phase); r.adv(A_NSLOT);
        const uint64_t dv = mkdesc(sb + sV * A_SLOT, 8192, 1024);
        bar_sync(1 + w, 256);
        wg_fence();
#pragma unroll
        for (int kk = 0; kk < 4; kk++)
          wgmma_rs_n192<1>(o, p2[4 * kk], p2[4 * kk + 1], p2[4 * kk + 2], p2[4 * kk + 3], dv + kk * 128, 1);
        wg_commit();
        bar_arrive(1 + (w ^ 1), 256);
        wg_wait<0>();
        fence_regs(o);
        A_RELEASE(sV);
      }
      TSA(item, 4);
      l0 += __shfl_xor_sync(0xffffffffu, l0, 1); l1 += __shfl_xor_sync(0xffffffffu, l1, 1);
      l0 += __shfl_xor_sync(0xffffffffu, l0, 2); l1 += __shfl_xor_sync(0xffffffffu, l1, 2);
      const float i0 = __fdividef(1.f, l0), i1 = __fdividef(1.f, l1);
#pragma unroll
      for (int i = 0; i < 24; i++) { ob[2 * i] = pack_bf16(o[4 * i] * i0, o[4 * i + 1] * i0); ob[2 * i + 1] = pack_bf16(o[4 * i + 2] * i1, o[4 * i + 3] * i1); }
      TSA(item, 5);
    }
    bf16* orow = OROW_PTR(3);
#pragma unroll
    for (int g = 0; g < 6; g++) { O_STORE(g) }
    SIGNAL();
    }
    TS(3, 2);
    const uint32_t st_w = (uint32_t)((warp * 16 + (lane >> 2)) * ST_P + (lane & 3) * 2) * 4;
    const uint32_t st_x = (lane & 8) << 2;
    const int er = (tid & 127) >> 1, eh = tid & 1;
    const uint32_t st_r = (uint32_t)(er * ST_P + (eh ^ ((er >> 1) & 1)) * 8) * 4;
    const uint32_t e_r = (uint32_t)((w * 64 + er) * 160 + eh * 16);
    const uint32_t p_r = par + eh * 32;
    const uint32_t stat = sb + T_PREP + w * 2048;
    const bool leader = (tid & 127) == 0;
#define STAGE10(ACC, BASE)                                                                                             \
    _Pragma("unroll") for (int nb = 0; nb < 10; nb++) {                                                                \
      sts_f2(stg + st_w + ((nb * 32) ^ st_x), ACC(BASE + 4 * nb), ACC(BASE + 4 * nb + 1));                                       \
      sts_f2(stg + st_w + ((nb * 32) ^ st_x) + 8 * ST_P * 4, ACC(BASE + 4 * nb + 2), ACC(BASE + 4 * nb + 3));                    \
    }

    {
      float acc1[96], acc2[64];
      uint32_t p0 = 0, p1 = 0, p2 = 0;
#pragma unroll 1
      for (int kb = 0; kb < 24; kb++) {
        const uint32_t s1 = r.slot; mbar_wait_c(bar_full + 8 * s1, r.phase); r.adv(A_NSLOT);
        const uint32_t s2 = r.slot; mbar_wait_c(bar_full + 8 * s2, r.phase); r.adv(A_NSLOT);
        const uint32_t sa = r.slot; mbar_wait_c(bar_full + 8 * sa, r.phase); r.adv(A_NSLOT);
        const uint64_t da = mkdesc(sb + sa * A_SLOT + w * 8192, 16, 1024);
        const uint64_t d1 = mkdesc(sb + s1 * A_SLOT, 8192, 1024), d2 = mkdesc(sb + s2 * A_SLOT, 8192, 1024);
        wg_fence();
#pragma unroll
        for (int kk = 0; kk < 4; kk++) {
          wgmma_ss_n192<1>(acc1, da + kk * 2, d1 + kk * 128, (kb | kk) != 0);
          wgmma_ss_n128<1>(acc2, da + kk * 2, d2 + kk * 128, (kb | kk) != 0);
        }
        wg_commit();
        if (kb > 0) { wg_wait<1>(); A_RELEASE(p0); A_RELEASE(p1); A_RELEASE(p2); }
        p0 = s1; p1 = s2; p2 = sa;
      }
      wg_wait<0>();
      fence_regs(acc1); fence_regs(acc2);
      A_RELEASE(p2);
      bar_sync(6, 288);
      TS(0, 0);
      const uint32_t stg = sb + (w ? p1 : p0) * A_SLOT;
#define OACC(e) (((e) < 96) ? acc1[(e) < 96 ? (e) : 0] : acc2[(e) >= 96 ? (e) - 96 : 0])
#define PACK10(BASE)                                                                                                   \
      _Pragma("unroll") for (int nb = 0; nb < 10; nb++) {                                                              \
        sts_u1(xo + nb * 16, pack_bf16(OACC(BASE + 4 * nb), OACC(BASE + 4 * nb + 1)));                                 \
        sts_u1(xo + nb * 16 + 8 * 160, pack_bf16(OACC(BASE + 4 * nb + 2), OACC(BASE + 4 * nb + 3)));                   \
      }
      const uint32_t f1 = r.slot + 4 >= A_NSLOT ? r.slot + 4 - A_NSLOT : r.slot + 4, f2 = f1 + 1 >= A_NSLOT ? 0 : f1 + 1;
#pragma unroll
      for (int d = 0; d < 4; d++) {
        if (d != o_ks) {
          const int i = (d - o_ks - 1) & 3;
          const uint32_t xo = sb + (i == 0 ? p2 : i == 1 ? f1 : f2) * A_SLOT + (w * 64 + warp * 16 + (lane >> 2)) * 160 + (lane & 3) * 4;
          PACK10(d * 40)
        }
      }
      fence_async_smem();
      bar_sync(3 + w, 128);
      if (leader) {
#pragma unroll 1
        for (int i = 0; i < 3; i++)
          bulk_store(g_xch + (size_t)((((o_qt * 2 + o_nh) * 4 + ((o_ks + 1 + i) & 3)) * 4) + o_ks) * (E_TILE / 2) + w * (E_TILE / 4),
                     sb + (i == 0 ? p2 : i == 1 ? f1 : f2) * A_SLOT + w * (E_TILE / 2), E_TILE / 2);
        bulk_done();
#pragma unroll 1
        for (int i = 0; i < 3; i++) flag_add(g_flag + F_XCH + (o_qt * 2 + o_nh) * 4 + ((o_ks + 1 + i) & 3));
        TX(40 + w);
      }
      if (o_ks == 0) { STAGE10(OACC, 0) } else if (o_ks == 1) { STAGE10(OACC, 40) } else if (o_ks == 2) { STAGE10(OACC, 80) } else { STAGE10(OACC, 120) }
      bar_sync(3 + w, 128);
      const uint32_t sx = r.slot; mbar_wait_c(bar_full + 8 * sx, r.phase); r.adv(A_NSLOT);
      const uint32_t q0 = r.slot; mbar_wait_c(bar_full + 8 * q0, r.phase); r.adv(A_NSLOT);
      const uint32_t q1 = r.slot; mbar_wait_c(bar_full + 8 * q1, r.phase); r.adv(A_NSLOT);
      const uint32_t q2 = r.slot; mbar_wait_c(bar_full + 8 * q2, r.phase); r.adv(A_NSLOT);
      TS(0, 1);
      float st[6] = {0.f, 0.f, 0.f, 0.f, 0.f, 0.f};
      const uint32_t ot = sb + p2 * A_SLOT;
#pragma unroll 1
      for (int c = 0; c < 5; c++) {
        float v[8], t0[8], t1[8], t2[8], xv[8], pg[8], pa_[8], pb_[8];
        lds8(stg + st_r + c * 64, v);
        lds8_bf(sb + q0 * A_SLOT + e_r + c * 32, t0); lds8_bf(sb + q1 * A_SLOT + e_r + c * 32, t1); lds8_bf(sb + q2 * A_SLOT + e_r + c * 32, t2);
        lds8_bf(sb + sx * A_SLOT + e_r + c * 32, xv);
        lds8(p_r + P_OGA * 4 + c * 64, pg); lds8(p_r + P_OA * 4 + c * 64, pa_); lds8(p_r + P_OB * 4 + c * 64, pb_);
#pragma unroll
        for (int e = 0; e < 8; e++) v[e] = fmaf(pg[e], v[e] + ((t0[e] + t1[e]) + t2[e]), xv[e]);
        const uint4 pk = pack8(v);
        sts_u4(ot + e_r + c * 32, pk);
        v[0] = bf_lo(pk.x); v[1] = bf_hi(pk.x); v[2] = bf_lo(pk.y); v[3] = bf_hi(pk.y); v[4] = bf_lo(pk.z); v[5] = bf_hi(pk.z); v[6] = bf_lo(pk.w); v[7] = bf_hi(pk.w);
#pragma unroll
        for (int e = 0; e < 8; e++) {
          const float y = pa_[e] * v[e];
          st[0] += v[e]; st[1] = fmaf(v[e], v[e], st[1]); st[2] += y; st[3] = fmaf(pa_[e], y, st[3]); st[4] = fmaf(y, y, st[4]); st[5] = fmaf(pb_[e], y, st[5]);
        }
      }
#pragma unroll
      for (int i = 0; i < 6; i++) st[i] += __shfl_xor_sync(0xffffffffu, st[i], 1);
      sts_u4(stat + er * 32 + eh * 16, eh ? make_uint4(__float_as_uint(st[4]), __float_as_uint(st[5]), 0u, 0u)
                                          : make_uint4(__float_as_uint(st[0]), __float_as_uint(st[1]), __float_as_uint(st[2]), __float_as_uint(st[3])));
      fence_async_smem();
      bar_sync(3 + w, 128);
      if (leader) {
        tma_store2d(&tm.sxa, ot + w * (E_TILE / 2), o_col, o_qt * 128 + w * 64);
        bulk_red_f32(g_st1 + (size_t)(o_qt * 128 + w * 64) * 8, stat, 2048);
        bulk_done();
        flag_add(g_flag + F_XA + o_qt);
      }
      bar_sync(5, 256);
      A_RELEASE(p0); A_RELEASE(p1); A_RELEASE(sx); A_RELEASE(q0); A_RELEASE(q1); A_RELEASE(q2);
      TS(0, 2);
    }

    Ring ra{0, 0};
    uint32_t bpar = 0;
    const uint32_t rel_a = mapa(mb_empty + 40, (lane == 0) ? rank : (rank ^ 1));
#define B_NEXT(s_) do { s_ = bs; mbar_wait_c(mb_full + 8 * bs, (bpar >> bs) & 1); bpar ^= 1u << bs; if (++bs == nbs) bs = 0; } while (0)
#define A_NEXT(s_) do { s_ = ra.slot; mbar_wait_c(mb_full + 40 + 8 * s_, ra.phase); ra.adv(M_NA); } while (0)
#define B_RELEASE(s_) do { if (lane == 0) mbar_arrive(mb_empty + 8 * (s_)); } while (0)
#define MA_RELEASE(s_) do { if (lane < 2) mbar_arrive_remote(rel_a + 8 * (s_)); } while (0)
    const int grow = qt * 128 + w * 64 + er;
    float mu = 0.f, rs = 0.f;
#pragma unroll 1
    for (int ph = 0; ph < 4; ph++) {
      float acc[96];
      float (&acc80)[40] = *reinterpret_cast<float(*)[40]>(&acc[0]);
      uint32_t pa = 0, pa2 = 0, pb = 0;
      float4 s03 = make_float4(0.f, 0.f, 0.f, 0.f);
      float2 s45 = make_float2(0.f, 0.f);
      const int nit = ph == 3 ? 12 : ph == 2 ? 10 : 5;
      const uint32_t nbs = ph == 2 ? 4 : 5, bsz = ph == 2 ? 24576 : 20480;
      uint32_t bs = 0;
#pragma unroll 1
      for (int it = 0; it < nit; it++) {
        uint32_t sbq, sa, sa2;
        B_NEXT(sbq);
        A_NEXT(sa);
        if (it == 0) TXC(ph);
        const uint64_t da = mkdesc(sb + M_AOFF + sa * 16384 + w * 8192, 16, 1024);
        if (ph == 2) {
          sa2 = sa;
          const uint64_t db = mkdesc(sb + sbq * 24576, 8192, 1024);
          wg_fence();
#pragma unroll
          for (int kk = 0; kk < 4; kk++) wgmma_ss_n192<1>(acc, da + kk * 2, db + kk * 128, (it | kk) != 0);
          wg_commit();
        } else {
          A_NEXT(sa2);
          const uint64_t da2 = mkdesc(sb + M_AOFF + sa2 * 16384 + w * 8192, 16, 1024);
          const uint64_t db = mkdesc(sb + sbq * 20480, 16, 1024);
          wg_fence();
#pragma unroll
          for (int kk = 0; kk < 4; kk++) wgmma_ss_n80<0>(acc80, da + kk * 2, db + kk * 2, (it | kk) != 0);
#pragma unroll
          for (int kk = 0; kk < 4; kk++) wgmma_ss_n80<0>(acc80, da2 + kk * 2, db + 640 + kk * 2, 1);
          wg_commit();
        }
        if (it > 0) { wg_wait<1>(); MA_RELEASE(pa); if (ph != 2) MA_RELEASE(pa2); B_RELEASE(pb); }
        else {
          if (ph == 0) { s03 = __ldcg(reinterpret_cast<const float4*>(g_st1 + (size_t)grow * 8)); s45 = __ldcg(reinterpret_cast<const float2*>(g_st1 + (size_t)grow * 8 + 4)); }
          if (ph == 2) s45 = __ldcg(reinterpret_cast<const float2*>(g_st2 + (size_t)grow * 2));
        }
        pa = sa; pa2 = sa2; pb = sbq;
      }
      wg_wait<0>();
      fence_regs(acc);
      MA_RELEASE(pa); if (ph != 2) MA_RELEASE(pa2);
      bar_sync(5, 256);
      TS(1 + (ph == 3 ? 0 : ph), ph == 3 ? 2 : 0);
      const uint32_t pb1 = pb == 0 ? nbs - 1 : pb - 1, pb2 = pb1 == 0 ? nbs - 1 : pb1 - 1, pb3 = pb2 == 0 ? nbs - 1 : pb2 - 1;
      const uint32_t stg = sb + (w ? pb : pb1) * bsz;
      uint32_t e1 = 0;
#define MACC(e) acc[e]
      if (!(ph & 1)) {
        float c0, c1, c2 = 0.f, c3 = 0.f;
        if (ph == 0) {
          const float4 sc = lds_f4(par + P_SC * 4);
          const float sbb = lds_f(par + (P_SC + 4) * 4);
          mu = s03.x * (1.f / D_);
          rs = rsqrtf(fmaxf(s03.y * (1.f / D_) - mu * mu, 0.f) + LN_EPS);
          const float m2 = (rs * (s03.z - mu * sc.x) + sc.w) * (1.f / D_);
          const float e2 = (rs * rs * (s45.x - 2.f * mu * s03.w + mu * mu * sc.y) + 2.f * rs * (s45.y - mu * sc.z) + sbb) * (1.f / D_);
          c2 = rsqrtf(fmaxf(e2 - m2 * m2, 0.f) + LN_EPS);
          c0 = c2 * rs; c1 = -c0 * mu; c3 = -c2 * m2;
          if (tid < 20) sts_u4(stat + 2048 * 2 + tid * 16, make_uint4(0, 0, 0, 0));
        } else {
          const float m = s45.x * (1.f / D_);
          c0 = rsqrtf(fmaxf(s45.y * (1.f / D_) - m * m, 0.f) + LN_EPS);
          c1 = -c0 * m;
        }
        const int npass = ph == 0 ? 1 : 3, nch = ph == 0 ? 5 : 4;
        const uint32_t ot = ph == 0 ? sb + pb2 * bsz + w * (E_TILE / 2) : sb + (w ? pb2 : pb3) * bsz;
#pragma unroll 1
        for (int ps = 0; ps < npass; ps++) {
          if (ps == 0) { STAGE10(MACC, 0) } else if (ps == 1) { STAGE10(MACC, 32) } else { STAGE10(MACC, 56) }
          bar_sync(3 + w, 128);
          const uint32_t cofs = ps == 2 ? 64 : 0;
          const uint32_t pp = p_r + (ph == 0 ? P_VA : P_CS3 + ps * 64) * 4, pq = p_r + P_VB * 4;
#pragma unroll 1
          for (int c = 0; c < nch; c++) {
            float v[8], t[8], t2[8], t3[8];
            lds8(stg + st_r + cofs + c * 64, v);
            lds8(pp + c * 64, t);
            if (ph == 0) {
              lds8(pq + c * 64, t2); lds8(pq + 320 + c * 64, t3);
#pragma unroll
              for (int e = 0; e < 8; e++) t[e] = fmaf(c1, t[e], fmaf(c2, t2[e], c3 * t3[e]));
            } else {
#pragma unroll
              for (int e = 0; e < 8; e++) t[e] *= c1;
            }
#pragma unroll
            for (int e = 0; e < 8; e++) v[e] = gelu_tanh(fmaf(c0, v[e], t[e]));
            sts_u4(ot + (ph == 0 ? er * 160 + eh * 16 + c * 32 : ps * 8192 + er * 128 + (((2 * c + eh) ^ (er & 7)) << 4)), pack8(v));
          }
          fence_async_smem();
          bar_sync(3 + w, 128);
          if (leader) {
            if (ph == 0) {
              const int grp = js >> 1;
              const int sh = (grp & 2 ? 2 : 1) * (grp & 1 ? -1 : 1);
              tma_store2d(&tm.sus, ot, js * 80, qt * 128 + w * 64 + sh + 2);
              if (w == 0 && qt == (sh > 0 ? 0 : 15)) {
                const int r0 = sh > 0 ? 0 : S_ + sh, n = sh > 0 ? sh : -sh;
                for (int i = 0; i < n; i++) bulk_store(g_us + (size_t)(r0 + i + 2) * D_ + js * 80, stat + 2048 * 2, 160);
              }
            } else {
              tma_store2d(&tm.g, ot + ps * 8192, js * 192 + ps * 64, qt * 128 + w * 64);
            }
          }
        }
      } else {
        STAGE10(MACC, 0)
        uint32_t e2;
        B_NEXT(e1);
        e2 = e1;
        if (ph == 3) B_NEXT(e2);
        bar_sync(3 + w, 128);
        float s1 = 0.f, s2 = 0.f;
        const uint32_t ot = sb + pb2 * bsz;
#pragma unroll 1
        for (int c = 0; c < 5; c++) {
          float v[8], xa[8], x1[8], ta[8], tb[8];
          lds8(stg + st_r + c * 64, v);
          lds8_bf(sb + e1 * 20480 + e_r + c * 32, xa); lds8_bf(sb + e2 * 20480 + e_r + c * 32, x1);
          lds8(p_r + (ph == 1 ? P_A2 : P_GB) * 4 + c * 64, ta); lds8(p_r + P_B2 * 4 + c * 64, tb);
          if (ph == 1) {
#pragma unroll
            for (int e = 0; e < 8; e++) v[e] += fmaf(ta[e] * rs, xa[e] - mu, tb[e]);
          } else {
#pragma unroll
            for (int e = 0; e < 8; e++) v[e] = fmaf(ta[e], v[e] + x1[e], xa[e]);
          }
          const uint4 pk = pack8(v);
          sts_u4(ot + e_r + c * 32, pk);
          v[0] = bf_lo(pk.x); v[1] = bf_hi(pk.x); v[2] = bf_lo(pk.y); v[3] = bf_hi(pk.y); v[4] = bf_lo(pk.z); v[5] = bf_hi(pk.z); v[6] = bf_lo(pk.w); v[7] = bf_hi(pk.w);
#pragma unroll
          for (int e = 0; e < 8; e++) { s1 += v[e]; s2 = fmaf(v[e], v[e], s2); }
        }
        s1 += __shfl_xor_sync(0xffffffffu, s1, 1); s2 += __shfl_xor_sync(0xffffffffu, s2, 1);
        if (eh == 0) sts_f2(stat + er * 8, s1, s2);
        fence_async_smem();
        bar_sync(3 + w, 128);
        if (leader) {
          tma_store2d(ph == 1 ? &tm.sx1 : &tm.sout, ot + w * (E_TILE / 2), js * 80, qt * 128 + w * 64);
          if (ph == 1) bulk_red_f32(g_st2 + (size_t)(qt * 128 + w * 64) * 2, stat, 512);
        }
      }
      if (leader) {
        bulk_done();
        if (ph < 3) flag_add(g_flag + F_US + 16 * ph + qt);
      }
      if (ph < 3) {
        bar_sync(5, 256);
        B_RELEASE(pb);
        if (ph == 1) B_RELEASE(e1);
      }
      TS(1 + (ph == 3 ? 0 : ph), ph == 3 ? 3 : 1);
    }
    if ((threadIdx.x & 127) == 0) TL_END(2);
    cluster_sync();
  }
}

typedef CUresult (*EncFn)(CUtensorMap*, CUtensorMapDataType, cuuint32_t, void*, const cuuint64_t*, const cuuint64_t*,
                          const cuuint32_t*, const cuuint32_t*, CUtensorMapInterleave, CUtensorMapSwizzle,
                          CUtensorMapL2promotion, CUtensorMapFloatOOBfill);
static EncFn g_enc = nullptr;

static CUtensorMap map2d(const void* p, uint64_t rows, uint64_t cols, uint32_t box_rows) {
  CUtensorMap m;
  cuuint64_t gd[2] = {cols, rows}; cuuint64_t gs[1] = {cols * 2};
  cuuint32_t bx[2] = {64, box_rows}; cuuint32_t es[2] = {1, 1};
  g_enc(&m, CU_TENSOR_MAP_DATA_TYPE_BFLOAT16, 2, const_cast<void*>(p), gd, gs, bx, es, CU_TENSOR_MAP_INTERLEAVE_NONE,
        CU_TENSOR_MAP_SWIZZLE_128B, CU_TENSOR_MAP_L2_PROMOTION_L2_256B, CU_TENSOR_MAP_FLOAT_OOB_FILL_NONE);
  return m;
}
static CUtensorMap map3d(const void* p, uint64_t rows, uint64_t cols, uint32_t box_rows, uint32_t nblk) {
  CUtensorMap m;
  cuuint64_t gd[3] = {64, rows, cols / 64}; cuuint64_t gs[2] = {cols * 2, 128};
  cuuint32_t bx[3] = {64, box_rows, nblk}; cuuint32_t es[3] = {1, 1, 1};
  g_enc(&m, CU_TENSOR_MAP_DATA_TYPE_BFLOAT16, 3, const_cast<void*>(p), gd, gs, bx, es, CU_TENSOR_MAP_INTERLEAVE_NONE,
        CU_TENSOR_MAP_SWIZZLE_128B, CU_TENSOR_MAP_L2_PROMOTION_L2_256B, CU_TENSOR_MAP_FLOAT_OOB_FILL_NONE);
  return m;
}

static CUtensorMap map_e(const void* p, uint32_t rows, uint64_t total_rows = S_) {
  CUtensorMap m;
  cuuint64_t gd[2] = {D_, total_rows}; cuuint64_t gs[1] = {D_ * 2};
  cuuint32_t bx[2] = {80, rows}; cuuint32_t es[2] = {1, 1};
  g_enc(&m, CU_TENSOR_MAP_DATA_TYPE_BFLOAT16, 2, const_cast<void*>(p), gd, gs, bx, es, CU_TENSOR_MAP_INTERLEAVE_NONE,
        CU_TENSOR_MAP_SWIZZLE_NONE, CU_TENSOR_MAP_L2_PROMOTION_L2_256B, CU_TENSOR_MAP_FLOAT_OOB_FILL_NONE);
  return m;
}

template <typename... KArgs, typename... Args>
static void launch(void (*kern)(KArgs...), dim3 grid, dim3 block, int smem, bool pdl, Args... args) {
  cudaLaunchConfig_t cfg = {};
  cfg.gridDim = grid; cfg.blockDim = block; cfg.dynamicSmemBytes = smem; cfg.stream = cudaStreamPerThread;
  cudaLaunchAttribute at[1];
  at[0].id = cudaLaunchAttributeProgrammaticStreamSerialization;
  at[0].val.programmaticStreamSerializationAllowed = 1;
  cfg.attrs = at; cfg.numAttrs = pdl ? 1 : 0;
  cudaLaunchKernelEx(&cfg, kern, KArgs(args)...);
}

extern "C" void kernel_launch(void* const* d_in, const int* in_sizes, int n_in, void* d_out, int out_size) {
  const bf16* x = (const bf16*)d_in[0];
  const bf16* kc = (const bf16*)d_in[1];
  const bf16* vc = (const bf16*)d_in[2];
  const bf16* wq = (const bf16*)d_in[3];
  const bf16* wo = (const bf16*)d_in[4];
  const bf16* w1 = (const bf16*)d_in[6];
  const bf16* w2 = (const bf16*)d_in[7];
  const bf16* w3 = (const bf16*)d_in[8];
  const bf16* w4 = (const bf16*)d_in[9];
  const bf16* c = (const bf16*)d_in[10];
  const bf16* wmod = (const bf16*)d_in[11];
  bf16* out = (bf16*)d_out;

  static void *p_h, *p_o, *p_xa, *p_us, *p_x1, *p_g, *p_w1t, *p_w2t, *p_w4t;
  if (!g_enc) {
    void* fn = nullptr; cudaDriverEntryPointQueryResult qr;
    cudaGetDriverEntryPoint("cuTensorMapEncodeTiled", &fn, cudaEnableDefault, &qr);
    g_enc = (EncFn)fn;
    cudaGetSymbolAddress(&p_h, g_h); cudaGetSymbolAddress(&p_o, g_o); cudaGetSymbolAddress(&p_xa, g_xa);
    cudaGetSymbolAddress(&p_us, g_us); cudaGetSymbolAddress(&p_x1, g_x1); cudaGetSymbolAddress(&p_g, g_g);
    cudaGetSymbolAddress(&p_w1t, g_w1t); cudaGetSymbolAddress(&p_w2t, g_w2t); cudaGetSymbolAddress(&p_w4t, g_w4t);
    cudaFuncSetAttribute(fused_kernel, cudaFuncAttributeMaxDynamicSharedMemorySize, T_SMEM);
  }
  Maps tm;
  tm.h = map2d(p_h, S_, D_, 128);
  tm.wq = map3d(wq, D_, HD_, 64, 3);
  tm.k = map3d(kc, (uint64_t)H_ * S_, DH_, 64, 3);
  tm.v = map3d(vc, (uint64_t)H_ * S_, DH_, 64, 3);
  tm.o = map2d(p_o, S_, HD_, 128);
  tm.wo3 = map3d(wo, HD_, D_, 64, 3);
  tm.wo2 = map3d(wo, HD_, D_, 64, 2);
  tm.xa = map2d(p_xa, S_, D_, 64);
  tm.w1t = map3d(p_w1t, D_, D_, 80, 2);
  tm.us = map2d((const bf16*)p_us + 2 * D_, S_, D_, 64);
  tm.w2t = map3d(p_w2t, D_, D_, 80, 2);
  tm.x1 = map2d(p_x1, S_, D_, 64);
  tm.w3 = map3d(w3, D_, F_, 64, 3);
  tm.g = map2d(p_g, S_, F_, 64);
  tm.w4t = map3d(p_w4t, D_, F_, 80, 2);
  tm.ex = map_e(x, 128); tm.exa = map_e(p_xa, 128); tm.ex1 = map_e(p_x1, 128);
  tm.sxa = map_e(p_xa, 64); tm.sus = map_e(p_us, 64, S_ + 4); tm.sx1 = map_e(p_x1, 64); tm.sout = map_e(out, 64);
  PfList pf;
  pf.p[0] = (const uint8_t*)wo; pf.p[1] = (const uint8_t*)w3; pf.p[2] = (const uint8_t*)p_w4t;
  pf.p[3] = (const uint8_t*)x; pf.p[4] = (const uint8_t*)p_w1t; pf.p[5] = (const uint8_t*)p_w2t;

  launch(mod_kernel, dim3(120), dim3(256), 0, false, c, wmod);
  launch(ln1_kernel, dim3(256), dim3(256), 0, true, x);
  launch(fused_kernel, dim3(128), dim3(384), T_SMEM, true, tm, pf, PrepW{w1, w2, w3, w4}, x, out);
}
```

```cpp
#include <cuda_runtime.h>
#include <cuda.h>
#include <cuda_bf16.h>
#include <stdint.h>

typedef __nv_bfloat16 bf16;

constexpr int S_  = 2048;
constexpr int D_  = 640;
constexpr int H_  = 32;
constexpr int DH_ = 192;
constexpr int HD_ = H_ * DH_;
constexpr int F_  = 1536;
constexpr float LN_EPS = 1e-5f;

__device__ __forceinline__ uint32_t smem_u32(const void* p) { return (uint32_t)__cvta_generic_to_shared(p); }
__device__ __forceinline__ void mbar_init(uint32_t a, uint32_t c) { asm volatile("mbarrier.init.shared::cta.b64 [%0], %1;" :: "r"(a), "r"(c) : "memory"); }
__device__ __forceinline__ void mbar_expect(uint32_t a, uint32_t b) { asm volatile("mbarrier.arrive.expect_tx.shared::cta.b64 _, [%0], %1;" :: "r"(a), "r"(b) : "memory"); }
__device__ __forceinline__ void mbar_arrive(uint32_t a) { asm volatile("mbarrier.arrive.shared::cta.b64 _, [%0];" :: "r"(a) : "memory"); }
__device__ __forceinline__ void mbar_arrive_remote(uint32_t ra) { asm volatile("mbarrier.arrive.shared::cluster.b64 _, [%0];" :: "r"(ra) : "memory"); }
__device__ __forceinline__ uint32_t mapa(uint32_t a, uint32_t cta) { uint32_t r; asm volatile("mapa.shared::cluster.u32 %0, %1, %2;" : "=r"(r) : "r"(a), "r"(cta)); return r; }
__device__ __forceinline__ uint32_t mbar_try(uint32_t a, uint32_t ph) {
  uint32_t ok;
  asm volatile("{\n.reg .pred p;\nmbarrier.test_wait.parity.shared::cta.b64 p, [%1], %2;\nselp.u32 %0, 1, 0, p;\n}\n" : "=r"(ok) : "r"(a), "r"(ph) : "memory");
  return ok;
}
__device__ __forceinline__ void mbar_wait(uint32_t a, uint32_t ph) {
  asm volatile(
      "{\n.reg .pred p;\n.reg .u32 n;\n"
      "mov.u32 n, 0;\n"
      "SPIN:\n"
      "mbarrier.try_wait.parity.shared::cta.b64 p, [%0], %1;\n"
      "@p bra DONE;\n"
      "add.u32 n, n, 1;\n"
      "setp.le.u32 p, n, 16777216;\n"
      "@p bra SPIN;\n"
      "trap;\n"
      "DONE:\n}\n" :: "r"(a), "r"(ph) : "memory");
}
#define ELECT_ "{\n.reg .pred p;\nelect.sync _|p, 0xffffffff;\n@p "
__device__ __forceinline__ void mbar_expect_e(uint32_t a, uint32_t b) { asm volatile(ELECT_ "mbarrier.arrive.expect_tx.shared::cta.b64 _, [%0], %1;\n}\n" :: "r"(a), "r"(b) : "memory"); }
__device__ __forceinline__ void tma2d(uint32_t dst, const CUtensorMap* m, uint32_t bar, int c0, int c1) {
  asm volatile(ELECT_ "cp.async.bulk.tensor.2d.shared::cluster.global.mbarrier::complete_tx::bytes [%0], [%1, {%3, %4}], [%2];\n}\n"
               :: "r"(dst), "l"(m), "r"(bar), "r"(c0), "r"(c1) : "memory");
}
__device__ __forceinline__ void tma2d_mc(uint32_t dst, const CUtensorMap* m, uint32_t bar, int c0, int c1, uint16_t mask) {
  asm volatile(ELECT_ "cp.async.bulk.tensor.2d.shared::cluster.global.mbarrier::complete_tx::bytes.multicast::cluster [%0], [%1, {%3, %4}], [%2], %5;\n}\n"
               :: "r"(dst), "l"(m), "r"(bar), "r"(c0), "r"(c1), "h"(mask) : "memory");
}
__device__ __forceinline__ void tma3d(uint32_t dst, const CUtensorMap* m, uint32_t bar, int c0, int c1, int c2) {
  asm volatile(ELECT_ "cp.async.bulk.tensor.3d.shared::cluster.global.mbarrier::complete_tx::bytes [%0], [%1, {%3, %4, %5}], [%2];\n}\n"
               :: "r"(dst), "l"(m), "r"(bar), "r"(c0), "r"(c1), "r"(c2) : "memory");
}
__device__ __forceinline__ void tma3d_mc(uint32_t dst, const CUtensorMap* m, uint32_t bar, int c0, int c1, int c2, uint16_t mask) {
  asm volatile(ELECT_ "cp.async.bulk.tensor.3d.shared::cluster.global.mbarrier::complete_tx::bytes.multicast::cluster [%0], [%1, {%3, %4, %5}], [%2], %6;\n}\n"
               :: "r"(dst), "l"(m), "r"(bar), "r"(c0), "r"(c1), "r"(c2), "h"(mask) : "memory");
}
__device__ __forceinline__ void tma3d_mc_hint(uint32_t dst, const CUtensorMap* m, uint32_t bar, int c0, int c1, int c2, uint16_t mask, uint64_t pol) {
  asm volatile(ELECT_ "cp.async.bulk.tensor.3d.shared::cluster.global.mbarrier::complete_tx::bytes.multicast::cluster.L2::cache_hint [%0], [%1, {%3, %4, %5}], [%2], %6, %7;\n}\n"
               :: "r"(dst), "l"(m), "r"(bar), "r"(c0), "r"(c1), "r"(c2), "h"(mask), "l"(pol) : "memory");
}
__device__ __forceinline__ void bulk_load(uint32_t dst, const void* src, uint32_t bytes, uint32_t bar) {
  asm volatile(ELECT_ "cp.async.bulk.shared::cluster.global.mbarrier::complete_tx::bytes [%0], [%1], %2, [%3];\n}\n"
               :: "r"(dst), "l"(src), "r"(bytes), "r"(bar) : "memory");
}
__device__ __forceinline__ void l2_prefetch16k(const void* p) { asm volatile(ELECT_ "cp.async.bulk.prefetch.L2.global [%0], 16384;\n}\n" :: "l"(p) : "memory"); }
__device__ __forceinline__ void l2_prefetch_t2d(const CUtensorMap* m, int c0, int c1) {
  asm volatile(ELECT_ "cp.async.bulk.prefetch.tensor.2d.L2.global [%0, {%1, %2}];\n}\n" :: "l"(m), "r"(c0), "r"(c1) : "memory");
}
__device__ __forceinline__ void l2_prefetch_t3d(const CUtensorMap* m, int c0, int c1, int c2) {
  asm volatile(ELECT_ "cp.async.bulk.prefetch.tensor.3d.L2.global [%0, {%1, %2, %3}];\n}\n" :: "l"(m), "r"(c0), "r"(c1), "r"(c2) : "memory");
}
__device__ __forceinline__ void stg128(void* p, uint4 v) {
  asm volatile("st.global.v4.u32 [%0], {%1, %2, %3, %4};" :: "l"(p), "r"(v.x), "r"(v.y), "r"(v.z), "r"(v.w) : "memory");
}
__device__ __forceinline__ void prefetch_tmap(const CUtensorMap* m) { asm volatile("prefetch.tensormap [%0];" :: "l"(m) : "memory"); }
__device__ __forceinline__ void wg_fence() { asm volatile("wgmma.fence.sync.aligned;" ::: "memory"); }
__device__ __forceinline__ void wg_commit() { asm volatile("wgmma.commit_group.sync.aligned;" ::: "memory"); }
template <int N> __device__ __forceinline__ void wg_wait() { asm volatile("wgmma.wait_group.sync.aligned %0;" :: "n"(N) : "memory"); }
template <int N> __device__ __forceinline__ void fence_regs(float (&r)[N]) {
#pragma unroll
  for (int i = 0; i < N; i++) asm volatile("" : "+f"(r[i]) :: "memory");
}
template <int N> __device__ __forceinline__ void fence_regs(uint32_t (&r)[N]) {
#pragma unroll
  for (int i = 0; i < N; i++) asm volatile("" : "+r"(r[i]) :: "memory");
}
__device__ __forceinline__ uint64_t mkdesc(uint32_t addr, uint32_t lbo, uint32_t sbo) {
  return (uint64_t)((addr & 0x3FFFF) >> 4) | ((uint64_t)(lbo >> 4) << 16) | ((uint64_t)(sbo >> 4) << 32) | (1ull << 62);
}
__device__ __forceinline__ void bar_sync(int id, int n) { asm volatile("bar.sync %0, %1;" :: "r"(id), "r"(n) : "memory"); }
__device__ __forceinline__ void bar_arrive(int id, int n) { asm volatile("bar.arrive %0, %1;" :: "r"(id), "r"(n) : "memory"); }
__device__ __forceinline__ void cluster_sync() { asm volatile("barrier.cluster.arrive.aligned;\nbarrier.cluster.wait.aligned;" ::: "memory"); }
__device__ __forceinline__ void pdl_wait() { asm volatile("griddepcontrol.wait;" ::: "memory"); }
__device__ __forceinline__ void pdl_launch() { asm volatile("griddepcontrol.launch_dependents;" ::: "memory"); }
__device__ __forceinline__ float ex2(float x) { float y; asm("ex2.approx.ftz.f32 %0, %1;" : "=f"(y) : "f"(x)); return y; }
__device__ __forceinline__ uint32_t pack_bf16(float lo, float hi) { uint32_t r; asm("cvt.rn.bf16x2.f32 %0, %1, %2;" : "=r"(r) : "f"(hi), "f"(lo)); return r; }
__device__ __forceinline__ float bf_lo(uint32_t u) { return __uint_as_float(u << 16); }
__device__ __forceinline__ float bf_hi(uint32_t u) { return __uint_as_float(u & 0xffff0000u); }
__device__ __forceinline__ float bf_round(float x) { return __bfloat162float(__float2bfloat16_rn(x)); }
__device__ __forceinline__ float tanh_fast(float x) { float y; asm("tanh.approx.f32 %0, %1;" : "=f"(y) : "f"(x)); return y; }
__device__ __forceinline__ float gelu_tanh(float x) {
  float u = x * (0.7978845608028654f + 0.035677408136300125f * x * x);
  float hx = 0.5f * x;
  return fmaf(hx, tanh_fast(u), hx);
}
__device__ __forceinline__ float warp_sum(float v) {
#pragma unroll
  for (int o = 16; o > 0; o >>= 1) v += __shfl_xor_sync(0xffffffffu, v, o);
  return v;
}
__device__ __forceinline__ void quad_transpose(uint32_t& v0, uint32_t& v1, uint32_t& v2, uint32_t& v3, int lane) {
  const bool b0 = lane & 1, b1 = lane & 2;
  uint32_t s0 = b0 ? v0 : v1, s1 = b0 ? v2 : v3;
  s0 = __shfl_xor_sync(0xffffffffu, s0, 1); s1 = __shfl_xor_sync(0xffffffffu, s1, 1);
  if (b0) { v0 = s0; v2 = s1; } else { v1 = s0; v3 = s1; }
  uint32_t t0 = b1 ? v0 : v2, t1 = b1 ? v1 : v3;
  t0 = __shfl_xor_sync(0xffffffffu, t0, 2); t1 = __shfl_xor_sync(0xffffffffu, t1, 2);
  if (b1) { v0 = t0; v1 = t1; } else { v2 = t0; v3 = t1; }
}

#define TX(i)
#define TXC(i)
#define TSA(item, i)
#define TL_ENTRY(k)
#define TL_WAITED(k)
#define TL_END(k)
#define TS(item, i)
template<int TB> __device__ __forceinline__ void wgmma_rs_n64(float (&d)[32], uint32_t a0, uint32_t a1, uint32_t a2, uint32_t a3, uint64_t db, int scale_d) {
  asm volatile("{\n.reg .pred p;\nsetp.ne.b32 p, %37, 0;\n"
    "wgmma.mma_async.sync.aligned.m64n64k16.f32.bf16.bf16 {%0, %1, %2, %3, %4, %5, %6, %7, %8, %9, %10, %11, %12, %13, %14, %15, %16, %17, %18, %19, %20, %21, %22, %23, %24, %25, %26, %27, %28, %29, %30, %31}, {%32, %33, %34, %35}, %36, p, 1, 1, %38;\n}\n"
    : "+f"(d[0]), "+f"(d[1]), "+f"(d[2]), "+f"(d[3]), "+f"(d[4]), "+f"(d[5]), "+f"(d[6]), "+f"(d[7]), "+f"(d[8]), "+f"(d[9]), "+f"(d[10]), "+f"(d[11]), "+f"(d[12]), "+f"(d[13]), "+f"(d[14]), "+f"(d[15]), "+f"(d[16]), "+f"(d[17]), "+f"(d[18]), "+f"(d[19]), "+f"(d[20]), "+f"(d[21]), "+f"(d[22]), "+f"(d[23]), "+f"(d[24]), "+f"(d[25]), "+f"(d[26]), "+f"(d[27]), "+f"(d[28]), "+f"(d[29]), "+f"(d[30]), "+f"(d[31])
    : "r"(a0), "r"(a1), "r"(a2), "r"(a3), "l"(db), "r"(scale_d), "n"(TB));
}
template<int TB> __device__ __forceinline__ void wgmma_rs_n192(float (&d)[96], uint32_t a0, uint32_t a1, uint32_t a2, uint32_t a3, uint64_t db, int scale_d) {
  asm volatile("{\n.reg .pred p;\nsetp.ne.b32 p, %101, 0;\n"
    "wgmma.mma_async.sync.aligned.m64n192k16.f32.bf16.bf16 {%0, %1, %2, %3, %4, %5, %6, %7, %8, %9, %10, %11, %12, %13, %14, %15, %16, %17, %18, %19, %20, %21, %22, %23, %24, %25, %26, %27, %28, %29, %30, %31, %32, %33, %34, %35, %36, %37, %38, %39, %40, %41, %42, %43, %44, %45, %46, %47, %48, %49, %50, %51, %52, %53, %54, %55, %56, %57, %58, %59, %60, %61, %62, %63, %64, %65, %66, %67, %68, %69, %70, %71, %72, %73, %74, %75, %76, %77, %78, %79, %80, %81, %82, %83, %84, %85, %86, %87, %88, %89, %90, %91, %92, %93, %94, %95}, {%96, %97, %98, %99}, %100, p, 1, 1, %102;\n}\n"
    : "+f"(d[0]), "+f"(d[1]), "+f"(d[2]), "+f"(d[3]), "+f"(d[4]), "+f"(d[5]), "+f"(d[6]), "+f"(d[7]), "+f"(d[8]), "+f"(d[9]), "+f"(d[10]), "+f"(d[11]), "+f"(d[12]), "+f"(d[13]), "+f"(d[14]), "+f"(d[15]), "+f"(d[16]), "+f"(d[17]), "+f"(d[18]), "+f"(d[19]), "+f"(d[20]), "+f"(d[21]), "+f"(d[22]), "+f"(d[23]), "+f"(d[24]), "+f"(d[25]), "+f"(d[26]), "+f"(d[27]), "+f"(d[28]), "+f"(d[29]), "+f"(d[30]), "+f"(d[31]), "+f"(d[32]), "+f"(d[33]), "+f"(d[34]), "+f"(d[35]), "+f"(d[36]), "+f"(d[37]), "+f"(d[38]), "+f"(d[39]), "+f"(d[40]), "+f"(d[41]), "+f"(d[42]), "+f"(d[43]), "+f"(d[44]), "+f"(d[45]), "+f"(d[46]), "+f"(d[47]), "+f"(d[48]), "+f"(d[49]), "+f"(d[50]), "+f"(d[51]), "+f"(d[52]), "+f"(d[53]), "+f"(d[54]), "+f"(d[55]), "+f"(d[56]), "+f"(d[57]), "+f"(d[58]), "+f"(d[59]), "+f"(d[60]), "+f"(d[61]), "+f"(d[62]), "+f"(d[63]), "+f"(d[64]), "+f"(d[65]), "+f"(d[66]), "+f"(d[67]), "+f"(d[68]), "+f"(d[69]), "+f"(d[70]), "+f"(d[71]), "+f"(d[72]), "+f"(d[73]), "+f"(d[74]), "+f"(d[75]), "+f"(d[76]), "+f"(d[77]), "+f"(d[78]), "+f"(d[79]), "+f"(d[80]), "+f"(d[81]), "+f"(d[82]), "+f"(d[83]), "+f"(d[84]), "+f"(d[85]), "+f"(d[86]), "+f"(d[87]), "+f"(d[88]), "+f"(d[89]), "+f"(d[90]), "+f"(d[91]), "+f"(d[92]), "+f"(d[93]), "+f"(d[94]), "+f"(d[95])
    : "r"(a0), "r"(a1), "r"(a2), "r"(a3), "l"(db), "r"(scale_d), "n"(TB));
}
template<int TB> __device__ __forceinline__ void wgmma_ss_n128(float (&d)[64], uint64_t da, uint64_t db, int scale_d) {
  asm volatile("{\n.reg .pred p;\nsetp.ne.b32 p, %66, 0;\n"
    "wgmma.mma_async.sync.aligned.m64n128k16.f32.bf16.bf16 {%0, %1, %2, %3, %4, %5, %6, %7, %8, %9, %10, %11, %12, %13, %14, %15, %16, %17, %18, %19, %20, %21, %22, %23, %24, %25, %26, %27, %28, %29, %30, %31, %32, %33, %34, %35, %36, %37, %38, %39, %40, %41, %42, %43, %44, %45, %46, %47, %48, %49, %50, %51, %52, %53, %54, %55, %56, %57, %58, %59, %60, %61, %62, %63}, %64, %65, p, 1, 1, 0, %67;\n}\n"
    : "+f"(d[0]), "+f"(d[1]), "+f"(d[2]), "+f"(d[3]), "+f"(d[4]), "+f"(d[5]), "+f"(d[6]), "+f"(d[7]), "+f"(d[8]), "+f"(d[9]), "+f"(d[10]), "+f"(d[11]), "+f"(d[12]), "+f"(d[13]), "+f"(d[14]), "+f"(d[15]), "+f"(d[16]), "+f"(d[17]), "+f"(d[18]), "+f"(d[19]), "+f"(d[20]), "+f"(d[21]), "+f"(d[22]), "+f"(d[23]), "+f"(d[24]), "+f"(d[25]), "+f"(d[26]), "+f"(d[27]), "+f"(d[28]), "+f"(d[29]), "+f"(d[30]), "+f"(d[31]), "+f"(d[32]), "+f"(d[33]), "+f"(d[34]), "+f"(d[35]), "+f"(d[36]), "+f"(d[37]), "+f"(d[38]), "+f"(d[39]), "+f"(d[40]), "+f"(d[41]), "+f"(d[42]), "+f"(d[43]), "+f"(d[44]), "+f"(d[45]), "+f"(d[46]), "+f"(d[47]), "+f"(d[48]), "+f"(d[49]), "+f"(d[50]), "+f"(d[51]), "+f"(d[52]), "+f"(d[53]), "+f"(d[54]), "+f"(d[55]), "+f"(d[56]), "+f"(d[57]), "+f"(d[58]), "+f"(d[59]), "+f"(d[60]), "+f"(d[61]), "+f"(d[62]), "+f"(d[63])
    : "l"(da), "l"(db), "r"(scale_d), "n"(TB));
}
template<int TB> __device__ __forceinline__ void wgmma_ss_n192(float (&d)[96], uint64_t da, uint64_t db, int scale_d) {
  asm volatile("{\n.reg .pred p;\nsetp.ne.b32 p, %98, 0;\n"
    "wgmma.mma_async.sync.aligned.m64n192k16.f32.bf16.bf16 {%0, %1, %2, %3, %4, %5, %6, %7, %8, %9, %10, %11, %12, %13, %14, %15, %16, %17, %18, %19, %20, %21, %22, %23, %24, %25, %26, %27, %28, %29, %30, %31, %32, %33, %34, %35, %36, %37, %38, %39, %40, %41, %42, %43, %44, %45, %46, %47, %48, %49, %50, %51, %52, %53, %54, %55, %56, %57, %58, %59, %60, %61, %62, %63, %64, %65, %66, %67, %68, %69, %70, %71, %72, %73, %74, %75, %76, %77, %78, %79, %80, %81, %82, %83, %84, %85, %86, %87, %88, %89, %90, %91, %92, %93, %94, %95}, %96, %97, p, 1, 1, 0, %99;\n}\n"
    : "+f"(d[0]), "+f"(d[1]), "+f"(d[2]), "+f"(d[3]), "+f"(d[4]), "+f"(d[5]), "+f"(d[6]), "+f"(d[7]), "+f"(d[8]), "+f"(d[9]), "+f"(d[10]), "+f"(d[11]), "+f"(d[12]), "+f"(d[13]), "+f"(d[14]), "+f"(d[15]), "+f"(d[16]), "+f"(d[17]), "+f"(d[18]), "+f"(d[19]), "+f"(d[20]), "+f"(d[21]), "+f"(d[22]), "+f"(d[23]), "+f"(d[24]), "+f"(d[25]), "+f"(d[26]), "+f"(d[27]), "+f"(d[28]), "+f"(d[29]), "+f"(d[30]), "+f"(d[31]), "+f"(d[32]), "+f"(d[33]), "+f"(d[34]), "+f"(d[35]), "+f"(d[36]), "+f"(d[37]), "+f"(d[38]), "+f"(d[39]), "+f"(d[40]), "+f"(d[41]), "+f"(d[42]), "+f"(d[43]), "+f"(d[44]), "+f"(d[45]), "+f"(d[46]), "+f"(d[47]), "+f"(d[48]), "+f"(d[49]), "+f"(d[50]), "+f"(d[51]), "+f"(d[52]), "+f"(d[53]), "+f"(d[54]), "+f"(d[55]), "+f"(d[56]), "+f"(d[57]), "+f"(d[58]), "+f"(d[59]), "+f"(d[60]), "+f"(d[61]), "+f"(d[62]), "+f"(d[63]), "+f"(d[64]), "+f"(d[65]), "+f"(d[66]), "+f"(d[67]), "+f"(d[68]), "+f"(d[69]), "+f"(d[70]), "+f"(d[71]), "+f"(d[72]), "+f"(d[73]), "+f"(d[74]), "+f"(d[75]), "+f"(d[76]), "+f"(d[77]), "+f"(d[78]), "+f"(d[79]), "+f"(d[80]), "+f"(d[81]), "+f"(d[82]), "+f"(d[83]), "+f"(d[84]), "+f"(d[85]), "+f"(d[86]), "+f"(d[87]), "+f"(d[88]), "+f"(d[89]), "+f"(d[90]), "+f"(d[91]), "+f"(d[92]), "+f"(d[93]), "+f"(d[94]), "+f"(d[95])
    : "l"(da), "l"(db), "r"(scale_d), "n"(TB));
}
template<int TB> __device__ __forceinline__ void wgmma_ss_n80(float (&d)[40], uint64_t da, uint64_t db, int scale_d) {
  asm volatile("{\n.reg .pred p;\nsetp.ne.b32 p, %42, 0;\n"
    "wgmma.mma_async.sync.aligned.m64n80k16.f32.bf16.bf16 {%0, %1, %2, %3, %4, %5, %6, %7, %8, %9, %10, %11, %12, %13, %14, %15, %16, %17, %18, %19, %20, %21, %22, %23, %24, %25, %26, %27, %28, %29, %30, %31, %32, %33, %34, %35, %36, %37, %38, %39}, %40, %41, p, 1, 1, 0, %43;\n}\n"
    : "+f"(d[0]), "+f"(d[1]), "+f"(d[2]), "+f"(d[3]), "+f"(d[4]), "+f"(d[5]), "+f"(d[6]), "+f"(d[7]), "+f"(d[8]), "+f"(d[9]), "+f"(d[10]), "+f"(d[11]), "+f"(d[12]), "+f"(d[13]), "+f"(d[14]), "+f"(d[15]), "+f"(d[16]), "+f"(d[17]), "+f"(d[18]), "+f"(d[19]), "+f"(d[20]), "+f"(d[21]), "+f"(d[22]), "+f"(d[23]), "+f"(d[24]), "+f"(d[25]), "+f"(d[26]), "+f"(d[27]), "+f"(d[28]), "+f"(d[29]), "+f"(d[30]), "+f"(d[31]), "+f"(d[32]), "+f"(d[33]), "+f"(d[34]), "+f"(d[35]), "+f"(d[36]), "+f"(d[37]), "+f"(d[38]), "+f"(d[39])
    : "l"(da), "l"(db), "r"(scale_d), "n"(TB));
}

__device__ float g_mod[6 * D_];
__device__ __align__(1024) bf16 g_h[S_ * D_];
__device__ __align__(1024) bf16 g_o[S_ * HD_];
__device__ __align__(1024) bf16 g_xch[16 * 2 * 4 * 4 * 128 * 80];
__device__ __align__(1024) bf16 g_w1t[D_ * D_];
__device__ __align__(1024) bf16 g_w2t[D_ * D_];
__device__ __align__(1024) bf16 g_w4t[D_ * F_];
__device__ __align__(32) float g_st1[S_ * 8];
__device__ __align__(32) float g_st2[S_ * 2];
__device__ __align__(32) float g_vec[3 * D_ + F_ + 8];
__device__ unsigned g_flag[1024];
enum { F_XCH = 0, F_XA = 256, F_US = 272, F_X1 = 288, F_G = 304, F_PREP = 320, F_MOD = 321, F_MOD2 = 322, F_DONE = 323, F_H = 336, F_O = 512 };
__device__ __align__(1024) bf16 g_xa[S_ * D_];
__device__ __align__(1024) bf16 g_us[(S_ + 4) * D_];
__device__ __align__(1024) bf16 g_x1[S_ * D_];
__device__ __align__(1024) bf16 g_g[S_ * F_];

__device__ __forceinline__ void row_stats(const float (&v)[20], float& mean, float& rstd) {
  float s = 0.f;
#pragma unroll
  for (int i = 0; i < 20; i++) s += v[i];
  mean = warp_sum(s) * (1.f / D_);
  float q = 0.f;
#pragma unroll
  for (int i = 0; i < 20; i++) { float d = v[i] - mean; q = fmaf(d, d, q); }
  rstd = rsqrtf(warp_sum(q) * (1.f / D_) + LN_EPS);
}
__device__ __forceinline__ void load_row_bf16(const bf16* p, int lane, float (&v)[20]) {
#pragma unroll
  for (int i = 0; i < 5; i++) {
    uint2 u = *reinterpret_cast<const uint2*>(p + (lane + 32 * i) * 4);
    v[4 * i] = bf_lo(u.x); v[4 * i + 1] = bf_hi(u.x); v[4 * i + 2] = bf_lo(u.y); v[4 * i + 3] = bf_hi(u.y);
  }
}
__device__ __forceinline__ void store_row_bf16(bf16* p, int lane, const float (&v)[20]) {
#pragma unroll
  for (int i = 0; i < 5; i++) {
    uint2 u; u.x = pack_bf16(v[4 * i], v[4 * i + 1]); u.y = pack_bf16(v[4 * i + 2], v[4 * i + 3]);
    *reinterpret_cast<uint2*>(p + (lane + 32 * i) * 4) = u;
  }
}
__device__ __forceinline__ void load_row_f32(const float* p, int lane, float (&v)[20]) {
#pragma unroll
  for (int i = 0; i < 5; i++) {
    float4 u = *reinterpret_cast<const float4*>(p + (lane + 32 * i) * 4);
    v[4 * i] = u.x; v[4 * i + 1] = u.y; v[4 * i + 2] = u.z; v[4 * i + 3] = u.w;
  }
}

constexpr int PREP_JOBS = 200 + 200 + 480 + 480;
struct PrepW { const bf16 *w1, *w2, *w3, *w4, *c, *wmod; };
__device__ __forceinline__ void prep_warp(const PrepW& pw, bf16 (*tile)[72], int lane) {
#pragma unroll 1
  for (int job = blockIdx.x; job < PREP_JOBS; job += gridDim.x) {
    const bf16* src; bf16* dst; int ld = D_, ldd = D_, kt, nt, kind = 1;
    if (job < 200) { src = pw.w1; dst = g_w1t; kt = job / 10; nt = job % 10; kind = 0; }
    else if (job < 400) { src = pw.w2; dst = g_w2t; kt = (job - 200) / 10; nt = (job - 200) % 10; }
    else if (job < 880) { src = pw.w4; dst = g_w4t; ldd = F_; kt = (job - 400) / 10; nt = (job - 400) % 10; }
    else { src = pw.w3; dst = nullptr; ld = F_; kt = (job - 880) / 24; nt = (job - 880) % 24; kind = 2; }
    src += (size_t)(kt * 32 + (lane >> 3)) * ld + nt * 64 + (lane & 7) * 8;
    __syncwarp();
#pragma unroll
    for (int h = 0; h < 2; h++) {
      uint4 v[4];
#pragma unroll
      for (int i = 0; i < 4; i++) v[i] = __ldg(reinterpret_cast<const uint4*>(src + (size_t)(h * 16 + i * 4) * ld));
#pragma unroll
      for (int i = 0; i < 4; i++) *reinterpret_cast<uint4*>(&tile[h * 16 + i * 4 + (lane >> 3)][(lane & 7) * 8]) = v[i];
    }
    __syncwarp();
    const float* pa = g_mod + 4 * D_ + kt * 32;
    const float* pb = g_mod + 3 * D_ + kt * 32;
#pragma unroll 1
    for (int h = 0; h < 2; h++) {
      const int n = lane + 32 * h;
      float sa = 0.f, sb = 0.f, sc = 0.f;
#pragma unroll 1
      for (int c = 0; c < 4; c++) {
        uint32_t u[4];
#pragma unroll
        for (int e = 0; e < 4; e++) {
          const int k = c * 8 + 2 * e;
          float lo = __bfloat162float(tile[k][n]), hi = __bfloat162float(tile[k + 1][n]);
          sc += lo + hi;
          if (kind == 0) {
            const float2 a = __ldcg(reinterpret_cast<const float2*>(pa + k)), b = __ldcg(reinterpret_cast<const float2*>(pb + k));
            sb = fmaf(b.x, lo, fmaf(b.y, hi, sb));
            lo *= a.x; hi *= a.y;
          }
          u[e] = pack_bf16(lo, hi);
          sa += bf_lo(u[e]) + bf_hi(u[e]);
        }
        if (kind != 2) *reinterpret_cast<uint4*>(dst + (size_t)(nt * 64 + n) * ldd + kt * 32 + c * 8) = make_uint4(u[0], u[1], u[2], u[3]);
      }
      if (kind == 0) { atomicAdd(&g_vec[nt * 64 + n], sa); atomicAdd(&g_vec[D_ + nt * 64 + n], sb); atomicAdd(&g_vec[2 * D_ + nt * 64 + n], sc); }
      else if (kind == 2) atomicAdd(&g_vec[3 * D_ + nt * 64 + n], sc);
    }
  }
  __syncwarp();
  if (lane == 0) {
    asm volatile("fence.acq_rel.gpu;" ::: "memory");
    asm volatile("red.relaxed.gpu.global.add.u32 [%0], 1;" :: "l"(g_flag + F_PREP) : "memory");
  }
}

constexpr int A_NSLOT = 9;
constexpr int A_SLOT = 24576;
constexpr int A_NKV = S_ / 64;
constexpr int PREP_CTAS = 128;

struct Ring {
  uint32_t slot, phase;
  __device__ __forceinline__ void adv(int n) { if (++slot == (uint32_t)n) { slot = 0; phase ^= 1; } }
};
constexpr int T_PAR = A_NSLOT * A_SLOT + 384;
constexpr int T_PREP = T_PAR + 3712;
constexpr int T_SMEM = T_PREP + 32 * 72 * 2 + 1024;
enum { P_OGA = 0, P_OA = 80, P_OB = 160, P_VA = 240, P_VB = 320, P_VC = 400, P_A2 = 480, P_B2 = 560, P_GB = 640, P_CS3 = 720, P_SC = 912 };

__device__ __forceinline__ void flag_wait(const unsigned* p, unsigned target) {
  asm volatile(
      "{\n.reg .pred p;\n.reg .u32 n, v;\n"
      "mov.u32 n, 0;\n"
      "SPIN:\n"
      "ld.relaxed.gpu.global.u32 v, [%0];\n"
      "setp.ge.u32 p, v, %1;\n"
      "@p bra DONE;\n"
      "add.u32 n, n, 1;\n"
      "setp.gt.u32 p, n, 4194304;\n"
      "@p trap;\n"
      "bra SPIN;\n"
      "DONE:\n}\n" :: "l"(p), "r"(target) : "memory");
}
__device__ __forceinline__ void fence_async_global() { asm volatile("fence.proxy.async.global;" ::: "memory"); }
__device__ __forceinline__ float lds_f(uint32_t a) { float v; asm volatile("ld.shared.f32 %0, [%1];" : "=f"(v) : "r"(a)); return v; }
__device__ __forceinline__ float2 lds_f2(uint32_t a) { float2 v; asm volatile("ld.shared.v2.f32 {%0, %1}, [%2];" : "=f"(v.x), "=f"(v.y) : "r"(a)); return v; }
__device__ __forceinline__ uint4 ldcg4(const void* p) { return __ldcg(reinterpret_cast<const uint4*>(p)); }

__device__ __forceinline__ void sts_f2(uint32_t a, float x, float y) { asm volatile("st.shared.v2.f32 [%0], {%1, %2};" :: "r"(a), "f"(x), "f"(y) : "memory"); }
__device__ __forceinline__ void sts_u4(uint32_t a, uint4 v) { asm volatile("st.shared.v4.u32 [%0], {%1, %2, %3, %4};" :: "r"(a), "r"(v.x), "r"(v.y), "r"(v.z), "r"(v.w) : "memory"); }
__device__ __forceinline__ void sts_u1(uint32_t a, uint32_t v) { asm volatile("st.shared.u32 [%0], %1;" :: "r"(a), "r"(v) : "memory"); }
__device__ __forceinline__ void fence_async_smem() { asm volatile("fence.proxy.async.shared::cta;" ::: "memory"); }
__device__ __forceinline__ void bulk_store(void* dst, uint32_t src, uint32_t bytes) {
  asm volatile("cp.async.bulk.global.shared::cta.bulk_group [%0], [%1], %2;" :: "l"(dst), "r"(src), "r"(bytes) : "memory");
}
__device__ __forceinline__ void bulk_red_f32(void* dst, uint32_t src, uint32_t bytes) {
  asm volatile("cp.reduce.async.bulk.global.shared::cta.bulk_group.add.f32 [%0], [%1], %2;" :: "l"(dst), "r"(src), "r"(bytes) : "memory");
}
__device__ __forceinline__ void tma_store2d(const CUtensorMap* m, uint32_t src, int c0, int c1) {
  asm volatile("cp.async.bulk.tensor.2d.global.shared::cta.bulk_group [%0, {%2, %3}], [%1];" :: "l"(m), "r"(src), "r"(c0), "r"(c1) : "memory");
}
__device__ __forceinline__ void bulk_done() { asm volatile("cp.async.bulk.commit_group;\ncp.async.bulk.wait_group 0;" ::: "memory"); }
__device__ __forceinline__ void flag_add(unsigned* f) { asm volatile("red.relaxed.gpu.global.add.u32 [%0], 1;" :: "l"(f) : "memory"); }
__device__ __forceinline__ float4 lds_f4(uint32_t a) { return *reinterpret_cast<const float4*>(__cvta_shared_to_generic(a)); }
__device__ __forceinline__ uint4 lds_u4(uint32_t a) { return *reinterpret_cast<const uint4*>(__cvta_shared_to_generic(a)); }
__device__ __forceinline__ void lds8(uint32_t a, float (&v)[8]) {
  const float4 p = lds_f4(a), q = lds_f4(a + 16);
  v[0] = p.x; v[1] = p.y; v[2] = p.z; v[3] = p.w; v[4] = q.x; v[5] = q.y; v[6] = q.z; v[7] = q.w;
}
__device__ __forceinline__ void lds8_bf(uint32_t a, float (&v)[8]) {
  const uint4 u = lds_u4(a);
  v[0] = bf_lo(u.x); v[1] = bf_hi(u.x); v[2] = bf_lo(u.y); v[3] = bf_hi(u.y); v[4] = bf_lo(u.z); v[5] = bf_hi(u.z); v[6] = bf_lo(u.w); v[7] = bf_hi(u.w);
}
__device__ __forceinline__ uint4 pack8(const float (&v)[8]) {
  return make_uint4(pack_bf16(v[0], v[1]), pack_bf16(v[2], v[3]), pack_bf16(v[4], v[5]), pack_bf16(v[6], v[7]));
}
__device__ __forceinline__ void mbar_wait_c(uint32_t a, uint32_t ph) {
  asm volatile("{\n.reg .pred p;\nSPIN:\nmbarrier.try_wait.parity.shared::cta.b64 p, [%0], %1;\n@!p bra SPIN;\n}\n" :: "r"(a), "r"(ph) : "memory");
}
constexpr int ST_P = 80;
constexpr int E_TILE = 128 * 80 * 2;

struct Maps { CUtensorMap h, wq, k, v, o, wo3, wo2, xa, w1t, us, w2t, x1, w3, g, w4t, ex, exa, ex1, sxa, sus, sx1, sout; };
struct PfList { const uint8_t* p[6]; };

constexpr int M_AOFF = 102400, M_NA = 7;

__global__ void __cluster_dims__(2, 1, 1) __launch_bounds__(384, 1)
fused_kernel(const __grid_constant__ Maps tm, const __grid_constant__ PfList pf, const __grid_constant__ PrepW pw, const bf16* __restrict__ x, bf16* __restrict__ out) {
  extern __shared__ uint8_t smem_raw[];
  const uint32_t sb = (smem_u32(smem_raw) + 1023) & ~1023u;
  TL_ENTRY(2);
  const uint32_t bar_full = sb + A_NSLOT * A_SLOT;
  const uint32_t bar_empty = bar_full + 8 * A_NSLOT;
  const uint32_t bar_sig = bar_empty + 8 * A_NSLOT;
  const uint32_t mb_full = bar_sig + 16;
  const uint32_t mb_empty = mb_full + 96;
  const uint32_t par = sb + T_PAR;
  float* parf = reinterpret_cast<float*>(smem_raw + (par - smem_u32(smem_raw)));
  uint32_t rank;
  asm volatile("mov.u32 %0, %%cluster_ctarank;" : "=r"(rank));
  const int cid = blockIdx.x >> 1;
  const int wid = __shfl_sync(0xffffffffu, threadIdx.x >> 5, 0);
  const int wg = wid >> 2;
  const int qtile = (cid & 7) * 2 + rank, hbase = cid >> 3;
  const int o_qt = qtile, o_nh = (cid >> 3) & 1, o_ks = cid >> 4;
  const int o_col = o_nh * 320 + o_ks * 80;
  const int qt = cid >> 2, js = (cid & 3) * 2 + rank;
  if (threadIdx.x == 0) {
    for (int i = 0; i < A_NSLOT; i++) { mbar_init(bar_full + 8 * i, 1); mbar_init(bar_empty + 8 * i, 16); }
    mbar_init(bar_sig, 4); mbar_init(bar_sig + 8, 4);
    for (int i = 0; i < 12; i++) { mbar_init(mb_full + 8 * i, 1); mbar_init(mb_empty + 8 * i, i < 5 ? 8 : 16); }
    asm volatile("fence.mbarrier_init.release.cluster;" ::: "memory");
    prefetch_tmap(&tm.h); prefetch_tmap(&tm.wq); prefetch_tmap(&tm.k); prefetch_tmap(&tm.v);
  }
  __syncthreads();
  cluster_sync();

  if (wg == 0) {
    asm volatile("setmaxnreg.dec.sync.aligned.u32 40;");
    if (wid == 0) {
      Ring r{0, 1};
#define P_ACQ(bytes_) do { mbar_wait(bar_empty + 8 * r.slot, r.phase); mbar_expect_e(bar_full + 8 * r.slot, bytes_); } while (0)
#define P_DST (sb + r.slot * A_SLOT)
#define P_BAR (bar_full + 8 * r.slot)
      uint64_t pol_ef;
      asm volatile("createpolicy.fractional.L2::evict_first.b64 %0, 1.0;" : "=l"(pol_ef));
      if (qtile < 10) l2_prefetch_t3d(&tm.wq, 0, qtile * 64, hbase * 3);
      else l2_prefetch_t3d((qtile & 1) ? &tm.v : &tm.k, 0, hbase * S_ + ((qtile - 10) >> 1) * 64, 0);
      flag_wait(g_flag + F_H + qtile, 8);
      fence_async_global();
      TL_WAITED(2);
#pragma unroll 1
      for (int item = 0; item < 4; item++) {
        const int head = hbase + 8 * item;
#pragma unroll 1
        for (int kb = 0; kb < 10; kb++) {
          P_ACQ(16384);
          tma2d(P_DST, &tm.h, P_BAR, kb * 64, qtile * 128);
          r.adv(A_NSLOT);
          P_ACQ(A_SLOT);
          if ((uint32_t)(kb & 1) == rank) tma3d_mc_hint(P_DST, &tm.wq, P_BAR, 0, kb * 64, head * 3, 3, pol_ef);
          r.adv(A_NSLOT);
        }
#pragma unroll 1
        for (int j = 0; j <= A_NKV; j++) {
          if (j < A_NKV) {
            P_ACQ(A_SLOT);
            if (rank == 0) tma3d_mc_hint(P_DST, &tm.k, P_BAR, 0, head * S_ + j * 64, 0, 3, pol_ef);
            r.adv(A_NSLOT);
          }
          if (j > 0) {
            P_ACQ(A_SLOT);
            if (rank == 1) tma3d_mc_hint(P_DST, &tm.v, P_BAR, 0, head * S_ + (j - 1) * 64, 0, 3, pol_ef);
            r.adv(A_NSLOT);
          }
          if (item < 3 && j == 16 && qtile < 10) l2_prefetch_t3d(&tm.wq, 0, qtile * 64, (head + 8) * 3);
          if (item == 3 && (j & 3) == 0) {
            const int c = (j >> 2) * 128 + blockIdx.x;
            if (c < 980) {
              const int li = c < 480 ? 0 : c < 600 ? 1 : c < 720 ? 2 : c < 880 ? 3 : c < 930 ? 4 : 5;
              const int c0 = c < 480 ? 0 : c < 600 ? 480 : c < 720 ? 600 : c < 880 ? 720 : c < 930 ? 880 : 930;
              l2_prefetch16k(pf.p[li] + (size_t)(c - c0) * 16384);
            }
          }
          if (item == 3) {
            if (j >= 6 && j < 24) {
              const int kb = j - 6;
              l2_prefetch_t2d(&tm.o, ((kb / 6) * 8 + 2 * o_ks + (kb % 6) / 3) * DH_ + (kb % 3) * 64, o_qt * 128);
            }
            if (j >= 24 && j < 30) flag_wait(g_flag + F_O + o_qt * 32 + ((j - 24) >> 1) * 8 + 2 * o_ks + (j & 1), 2);
            if (j == 0 && threadIdx.x == 0) {
              prefetch_tmap(&tm.o); prefetch_tmap(&tm.wo3); prefetch_tmap(&tm.wo2); prefetch_tmap(&tm.xa); prefetch_tmap(&tm.w1t); prefetch_tmap(&tm.us);
              prefetch_tmap(&tm.w2t); prefetch_tmap(&tm.x1); prefetch_tmap(&tm.w3); prefetch_tmap(&tm.g); prefetch_tmap(&tm.w4t);
              prefetch_tmap(&tm.ex); prefetch_tmap(&tm.exa); prefetch_tmap(&tm.ex1);
              prefetch_tmap(&tm.sxa); prefetch_tmap(&tm.sus); prefetch_tmap(&tm.sx1); prefetch_tmap(&tm.sout);
            }
          }
        }
      }
#pragma unroll 1
      for (int kb = 0; kb < 24; kb++) {
        const int head = (kb / 6) * 8 + 2 * o_ks + (kb % 6) / 3;
        const int kcol = head * DH_ + (kb % 3) * 64;
        P_ACQ(24576);
        if (rank == 0) tma3d_mc(P_DST, &tm.wo3, P_BAR, 0, kcol, o_nh * 5, 3);
        r.adv(A_NSLOT);
        P_ACQ(16384);
        if (rank == 1) tma3d_mc(P_DST, &tm.wo2, P_BAR, 0, kcol, o_nh * 5 + 3, 3);
        r.adv(A_NSLOT);
        if (kb == 18 || kb == 21) flag_wait(g_flag + F_O + o_qt * 32 + head, 2);
        if (kb % 3 == 0) fence_async_global();
        P_ACQ(16384);
        tma2d(P_DST, &tm.o, P_BAR, kcol, o_qt * 128);
        r.adv(A_NSLOT);
      }
      P_ACQ(E_TILE);
      tma2d(P_DST, &tm.ex, P_BAR, o_col, o_qt * 128);
      r.adv(A_NSLOT);
      flag_wait(g_flag + F_XCH + (o_qt * 2 + o_nh) * 4 + o_ks, 6);
      fence_async_global();
#pragma unroll 1
      for (int i = 0; i < 3; i++) {
        P_ACQ(E_TILE);
        bulk_load(P_DST, g_xch + (size_t)((((o_qt * 2 + o_nh) * 4 + o_ks) * 4) + ((o_ks + 1 + i) & 3)) * (E_TILE / 2), E_TILE, P_BAR);
        r.adv(A_NSLOT);
      }
      flag_wait(g_flag + F_PREP, PREP_CTAS);
      fence_async_global();
#pragma unroll 1
      for (int i = 0; i < A_NSLOT; i++) { mbar_wait(bar_empty + 8 * r.slot, r.phase); r.adv(A_NSLOT); }
      Ring ra{0, 1};
      uint32_t bpar = 0x1f;
#pragma unroll 1
      for (int ph = 0; ph < 4; ph++) {
        const CUtensorMap* ma = ph == 0 ? &tm.xa : ph == 1 ? &tm.us : ph == 2 ? &tm.x1 : &tm.g;
        const CUtensorMap* mb = ph == 0 ? &tm.w1t : ph == 1 ? &tm.w2t : ph == 2 ? &tm.w3 : &tm.w4t;
        const int nkb = ph == 3 ? 24 : 10;
        const int nbl = ph == 2 ? 10 : nkb / 2;
        const int nel = ph == 1 ? 1 : ph == 3 ? 2 : 0;
        const uint32_t nbs = ph == 2 ? 4 : 5, bsz = ph == 2 ? 24576 : 20480;
        int bl = 0; uint32_t bs = 0;
#pragma unroll 1
        for (int i = 0; i < 5; i++) mbar_wait(mb_empty + 8 * i, (bpar >> i) & 1);
#define T_LOADB() do { mbar_wait(mb_empty + 8 * bs, (bpar >> bs) & 1); bpar ^= 1u << bs; mbar_expect_e(mb_full + 8 * bs, bsz);    \
                       if (bl < nbl) tma3d(sb + bs * bsz, mb, mb_full + 8 * bs, 0, ph == 2 ? bl * 64 : js * 80, ph == 2 ? js * 3 : bl * 2); \
                       else tma2d(sb + bs * bsz, bl == nbl ? &tm.exa : &tm.ex1, mb_full + 8 * bs, js * 80, qt * 128); \
                       bl++; if (++bs == nbs) bs = 0; } while (0)
#pragma unroll 1
        for (uint32_t i = 0; i < nbs; i++) T_LOADB();
        TX(8 + ph * 4);
        const unsigned* fl = g_flag + F_XA + 16 * ph;
        flag_wait(fl + qt, 16);
        if (ph == 1) { if (qt > 0) flag_wait(fl + qt - 1, 16); if (qt < 15) flag_wait(fl + qt + 1, 16); }
        TX(9 + ph * 4);
        fence_async_global();
#pragma unroll 1
        for (int kb = 0; kb < nkb; kb++) {
          mbar_wait(mb_empty + 40 + 8 * ra.slot, ra.phase);
          mbar_expect_e(mb_full + 40 + 8 * ra.slot, 16384);
          tma2d_mc(sb + M_AOFF + ra.slot * 16384 + rank * 8192, ma, mb_full + 40 + 8 * ra.slot, kb * 64, qt * 128 + (int)rank * 64, 3);
          ra.adv(M_NA);
          while (bl < nbl + nel && (kb == nkb - 1 || kb >= (ph == 2 ? bl + 2 : 2 * bl - 3))) T_LOADB();
        }
      }
    } else if (wid < 3) {
      const int w = wid - 1, lane = threadIdx.x & 31;
#pragma unroll 1
      for (int sig = 0; sig < 4; sig++) {
        mbar_wait(bar_sig + 8 * w, sig & 1);
        if (lane == 0) {
          asm volatile("fence.acq_rel.gpu;" ::: "memory");
          flag_add(g_flag + F_O + qtile * 32 + hbase + 8 * sig);
        }
        __syncwarp();
      }
    } else {
      const int lane = threadIdx.x & 31;
      flag_wait(g_flag + F_MOD2, 128);
      prep_warp(pw, reinterpret_cast<bf16(*)[72]>(smem_raw + (sb + T_PREP - smem_u32(smem_raw))), lane);
      flag_wait(g_flag + F_PREP, PREP_CTAS);
#pragma unroll 1
      for (int i = lane; i < P_SC; i += 32) {
        const int v = i < P_CS3 ? i / 80 : 9, j = i - (i < P_CS3 ? v * 80 : P_CS3);
        const float* src = v == 0 ? g_mod + 2 * D_ + o_col : v == 1 ? g_mod + 4 * D_ + o_col : v == 2 ? g_mod + 3 * D_ + o_col
                         : v < 6 ? g_vec + (v - 3) * D_ + js * 80 : v == 6 ? g_mod + 4 * D_ + js * 80 : v == 7 ? g_mod + 3 * D_ + js * 80
                         : v == 8 ? g_mod + 5 * D_ + js * 80 : g_vec + 3 * D_ + js * 192;
        parf[i] = __ldcg(src + j);
      }
      float sv[5] = {0.f, 0.f, 0.f, 0.f, 0.f};
#pragma unroll 1
      for (int i = lane; i < D_; i += 32) {
        const float a = __ldcg(g_mod + 4 * D_ + i), b = __ldcg(g_mod + 3 * D_ + i);
        sv[0] += a; sv[1] = fmaf(a, a, sv[1]); sv[2] = fmaf(a, b, sv[2]); sv[3] += b; sv[4] = fmaf(b, b, sv[4]);
      }
#pragma unroll 1
      for (int o_ = 16; o_ > 0; o_ >>= 1) {
#pragma unroll
        for (int i = 0; i < 5; i++) sv[i] += __shfl_xor_sync(0xffffffffu, sv[i], o_);
      }
      if (lane == 0) {
#pragma unroll
        for (int i = 0; i < 5; i++) parf[P_SC + i] = sv[i];
      }
      bar_arrive(6, 288);
    }
    __syncwarp();
    cluster_sync();
  } else {
    asm volatile("setmaxnreg.inc.sync.aligned.u32 232;");
    const int w = wg - 1;
    const int lane = threadIdx.x & 31;
    const int warp = wid & 3;
    const int tid = threadIdx.x - 128;
    const uint32_t rel_base = mapa(bar_empty, (lane == 0) ? rank : (rank ^ 1));
    Ring r{0, 0};
#define A_RELEASE(slot_) do { if (lane < 2) mbar_arrive_remote(rel_base + 8 * (slot_)); } while (0)
#define SIGNAL() do { __syncwarp(); if (lane == 0) mbar_arrive(bar_sig + 8 * w); } while (0)
    {
      const int row = blockIdx.x * 16 + (tid >> 5) * 2;
      float v0[20], v1[20];
      load_row_bf16(x + (size_t)row * D_, lane, v0);
      load_row_bf16(x + (size_t)(row + 1) * D_, lane, v1);
      if (blockIdx.x < 120) {
        const int cg = tid & 3, r0 = tid >> 2;
        const bf16* wp = pw.wmod + (size_t)r0 * (6 * D_) + blockIdx.x * 32 + cg * 8;
        uint4 wv[10];
        float cv[10];
#pragma unroll
        for (int i = 0; i < 10; i++) { wv[i] = __ldg(reinterpret_cast<const uint4*>(wp + (size_t)64 * i * (6 * D_))); cv[i] = __bfloat162float(pw.c[r0 + 64 * i]); }
        float acc[8];
#pragma unroll
        for (int j = 0; j < 8; j++) acc[j] = 0.f;
#pragma unroll
        for (int i = 0; i < 10; i++) {
          const float sv = bf_round(__fdividef(cv[i], 1.f + __expf(-cv[i])));
          acc[0] = fmaf(sv, bf_lo(wv[i].x), acc[0]); acc[1] = fmaf(sv, bf_hi(wv[i].x), acc[1]);
          acc[2] = fmaf(sv, bf_lo(wv[i].y), acc[2]); acc[3] = fmaf(sv, bf_hi(wv[i].y), acc[3]);
          acc[4] = fmaf(sv, bf_lo(wv[i].z), acc[4]); acc[5] = fmaf(sv, bf_hi(wv[i].z), acc[5]);
          acc[6] = fmaf(sv, bf_lo(wv[i].w), acc[6]); acc[7] = fmaf(sv, bf_hi(wv[i].w), acc[7]);
        }
#pragma unroll 1
        for (int o_ = 4; o_ < 32; o_ <<= 1) {
#pragma unroll
          for (int j = 0; j < 8; j++) acc[j] += __shfl_xor_sync(0xffffffffu, acc[j], o_);
        }
        if (lane < 4) {
          *reinterpret_cast<float4*>(parf + (tid >> 5) * 32 + cg * 8) = make_float4(acc[0], acc[1], acc[2], acc[3]);
          *reinterpret_cast<float4*>(parf + (tid >> 5) * 32 + cg * 8 + 4) = make_float4(acc[4], acc[5], acc[6], acc[7]);
        }
      }
      if (tid < 128) g_st1[blockIdx.x * 128 + tid] = 0.f;
      else if (tid < 160) g_st2[blockIdx.x * 32 + tid - 128] = 0.f;
      else if (tid < 187) g_vec[blockIdx.x * 27 + tid - 160] = 0.f;
      bar_sync(5, 256);
      if (tid < 32) {
        if (blockIdx.x < 120) {
          float sm_ = 0.f;
#pragma unroll
          for (int w8 = 0; w8 < 8; w8++) sm_ += parf[w8 * 32 + tid];
          sm_ = bf_round(sm_);
          const int part = blockIdx.x / 20;
          if (part == 1 || part == 4) sm_ = bf_round(1.f + sm_);
          g_mod[blockIdx.x * 32 + tid] = sm_;
        }
        __syncwarp();
        if (tid == 0) {
          asm volatile("fence.acq_rel.gpu;" ::: "memory");
          if (blockIdx.x < 40) flag_add(g_flag + F_MOD);
          flag_add(g_flag + F_MOD2);
        }
      }
      float m0, r0_, m1, r1_;
      row_stats(v0, m0, r0_);
      row_stats(v1, m1, r1_);
      flag_wait(g_flag + F_MOD, 40);
#pragma unroll
      for (int i = 0; i < 5; i++) {
        const float4 sa = __ldcg(reinterpret_cast<const float4*>(g_mod + (lane + 32 * i) * 4));
        const float4 ca = __ldcg(reinterpret_cast<const float4*>(g_mod + D_ + (lane + 32 * i) * 4));
        v0[4 * i] = fmaf((v0[4 * i] - m0) * r0_, ca.x, sa.x); v0[4 * i + 1] = fmaf((v0[4 * i + 1] - m0) * r0_, ca.y, sa.y);
        v0[4 * i + 2] = fmaf((v0[4 * i + 2] - m0) * r0_, ca.z, sa.z); v0[4 * i + 3] = fmaf((v0[4 * i + 3] - m0) * r0_, ca.w, sa.w);
        v1[4 * i] = fmaf((v1[4 * i] - m1) * r1_, ca.x, sa.x); v1[4 * i + 1] = fmaf((v1[4 * i + 1] - m1) * r1_, ca.y, sa.y);
        v1[4 * i + 2] = fmaf((v1[4 * i + 2] - m1) * r1_, ca.z, sa.z); v1[4 * i + 3] = fmaf((v1[4 * i + 3] - m1) * r1_, ca.w, sa.w);
      }
      store_row_bf16(g_h + (size_t)row * D_, lane, v0);
      store_row_bf16(g_h + (size_t)(row + 1) * D_, lane, v1);
      bar_sync(5, 256);
      if (tid == 0) {
        asm volatile("fence.acq_rel.gpu;" ::: "memory");
        flag_add(g_flag + F_H + (blockIdx.x >> 3));
      }
      __syncwarp();
    }
    {
    const float SC = 0.07216878364870322f * 1.4426950408889634f;
    float o[96];
    uint32_t q[48];
    float s[32];
    uint32_t p[16], p2[16];
    if (w == 1) bar_arrive(1, 256);
    bf16* orow = g_o + (size_t)(qtile * 128 + w * 64 + warp * 16 + (lane >> 2)) * HD_ + (hbase - 8) * DH_ + (lane & 3) * 8;
#define O_STORE(g)                                                                                                     \
      {                                                                                                                \
        quad_transpose(q[8 * g], q[8 * g + 2], q[8 * g + 4], q[8 * g + 6], lane);                                      \
        stg128(orow + g * 32, make_uint4(q[8 * g], q[8 * g + 2], q[8 * g + 4], q[8 * g + 6]));                         \
        quad_transpose(q[8 * g + 1], q[8 * g + 3], q[8 * g + 5], q[8 * g + 7], lane);                                  \
        stg128(orow + (size_t)8 * HD_ + g * 32, make_uint4(q[8 * g + 1], q[8 * g + 3], q[8 * g + 5], q[8 * g + 7]));   \
      }
#pragma unroll 1
    for (int item = 0; item < 4; item++) {
      TSA(item, 0);
      {
        uint32_t prevA = 0, prevB = 0;
#pragma unroll
        for (int kb = 0; kb < 10; kb++) {
          const uint32_t sA = r.slot; mbar_wait_c(bar_full + 8 * sA, r.phase); r.adv(A_NSLOT);
          const uint32_t sB = r.slot; mbar_wait_c(bar_full + 8 * sB, r.phase); r.adv(A_NSLOT);
          const uint64_t da = mkdesc(sb + sA * A_SLOT + w * 8192, 16, 1024);
          const uint64_t db = mkdesc(sb + sB * A_SLOT, 8192, 1024);
          wg_fence();
#pragma unroll
          for (int kk = 0; kk < 4; kk++) wgmma_ss_n192<1>(o, da + kk * 2, db + kk * 128, (kb | kk) != 0);
          wg_commit();
          if (kb < 6 && item > 0) { O_STORE((kb < 6 ? kb : 0)) }
          if (kb == 6 && item > 0) SIGNAL();
          if (kb > 0) { wg_wait<1>(); A_RELEASE(prevA); A_RELEASE(prevB); }
          prevA = sA; prevB = sB;
        }
        wg_wait<0>();
        fence_regs(o);
        A_RELEASE(prevA); A_RELEASE(prevB);
#pragma unroll
        for (int i = 0; i < 48; i++) q[i] = pack_bf16(o[2 * i], o[2 * i + 1]);
      }
      orow += 8 * DH_;

      TSA(item, 1);
      float c0, c1, l0, l1;
      {
        const uint32_t sK = r.slot; mbar_wait_c(bar_full + 8 * sK, r.phase); r.adv(A_NSLOT);
        const uint64_t dk = mkdesc(sb + sK * A_SLOT, 16, 1024);
        bar_sync(1 + w, 256);
        wg_fence();
#pragma unroll
        for (int kk = 0; kk < 12; kk++)
          wgmma_rs_n64<0>(s, q[4 * kk], q[4 * kk + 1], q[4 * kk + 2], q[4 * kk + 3], dk + (kk >> 2) * 512 + (kk & 3) * 2, kk != 0);
        wg_commit();
        bar_arrive(1 + (w ^ 1), 256);
        wg_wait<0>();
        fence_regs(s);
        A_RELEASE(sK);
        float mx0 = fmaxf(s[0], s[1]), mx1 = fmaxf(s[2], s[3]);
#pragma unroll
        for (int i = 1; i < 8; i++) { mx0 = fmaxf(mx0, fmaxf(s[4 * i], s[4 * i + 1])); mx1 = fmaxf(mx1, fmaxf(s[4 * i + 2], s[4 * i + 3])); }
        mx0 = fmaxf(mx0, __shfl_xor_sync(0xffffffffu, mx0, 1)); mx1 = fmaxf(mx1, __shfl_xor_sync(0xffffffffu, mx1, 1));
        mx0 = fmaxf(mx0, __shfl_xor_sync(0xffffffffu, mx0, 2)); mx1 = fmaxf(mx1, __shfl_xor_sync(0xffffffffu, mx1, 2));
        c0 = mx0 * SC; c1 = mx1 * SC;
        l0 = 0.f; l1 = 0.f;
#pragma unroll
        for (int i = 0; i < 8; i++) {
          s[4 * i] = ex2(fmaf(s[4 * i], SC, -c0)); s[4 * i + 1] = ex2(fmaf(s[4 * i + 1], SC, -c0));
          s[4 * i + 2] = ex2(fmaf(s[4 * i + 2], SC, -c1)); s[4 * i + 3] = ex2(fmaf(s[4 * i + 3], SC, -c1));
          l0 += s[4 * i] + s[4 * i + 1]; l1 += s[4 * i + 2] + s[4 * i + 3];
        }
#pragma unroll
        for (int i = 0; i < 16; i++) p[i] = pack_bf16(s[2 * i], s[2 * i + 1]);
      }
      TSA(item, 2);
      uint32_t okn;
      {
        Ring r2 = r; r2.adv(A_NSLOT);
        okn = mbar_try(bar_full + 8 * r.slot, r.phase) & mbar_try(bar_full + 8 * r2.slot, r2.phase);
      }
#define A_STEP(PC, PN, FIRST)                                                                                          \
      {                                                                                                                \
        const uint32_t sK = r.slot, phK = r.phase; r.adv(A_NSLOT);                                                     \
        const uint32_t sV = r.slot, phV = r.phase; r.adv(A_NSLOT);                                                     \
        const uint64_t dk = mkdesc(sb + sK * A_SLOT, 16, 1024);                                                        \
        const uint64_t dv = mkdesc(sb + sV * A_SLOT, 8192, 1024);                                                      \
        if (!okn) { mbar_wait_c(bar_full + 8 * sK, phK); mbar_wait_c(bar_full + 8 * sV, phV); }                            \
        bar_sync(1 + w, 256);                                                                                          \
        wg_fence();                                                                                                    \
        _Pragma("unroll") for (int kk = 0; kk < 12; kk++)                                                              \
          wgmma_rs_n64<0>(s, q[4 * kk], q[4 * kk + 1], q[4 * kk + 2], q[4 * kk + 3], dk + (kk >> 2) * 512 + (kk & 3) * 2, kk != 0); \
        wg_commit();                                                                                                   \
        _Pragma("unroll") for (int kk = 0; kk < 4; kk++)                                                               \
          wgmma_rs_n192<1>(o, PC[4 * kk], PC[4 * kk + 1], PC[4 * kk + 2], PC[4 * kk + 3], dv + kk * 128, !(FIRST) || (kk != 0)); \
        wg_commit();                                                                                                   \
        bar_arrive(1 + (w ^ 1), 256);                                                                                  \
        {                                                                                                              \
          Ring r2 = r; r2.adv(A_NSLOT);                                                                                \
          okn = mbar_try(bar_full + 8 * r.slot, r.phase) & mbar_try(bar_full + 8 * r2.slot, r2.phase);                 \
        }                                                                                                              \
        wg_wait<1>();                                                                                                  \
        fence_regs(s);                                                                                                 \
        A_RELEASE(sK);                                                                                                 \
        float b0 = 0.f, b1 = 0.f;                                                                                      \
        _Pragma("unroll") for (int i = 0; i < 8; i++) {                                                                \
          const float e0 = ex2(fmaf(s[4 * i], SC, -c0)), e1 = ex2(fmaf(s[4 * i + 1], SC, -c0));                        \
          const float e2 = ex2(fmaf(s[4 * i + 2], SC, -c1)), e3 = ex2(fmaf(s[4 * i + 3], SC, -c1));                    \
          b0 += e0 + e1; b1 += e2 + e3;                                                                                \
          PN[2 * i] = pack_bf16(e0, e1); PN[2 * i + 1] = pack_bf16(e2, e3);                                            \
        }                                                                                                              \
        wg_wait<0>();                                                                                                  \
        fence_regs(o);                                                                                                 \
        fence_regs(PC);                                                                                                \
        A_RELEASE(sV);                                                                                                 \
        if (__any_sync(0xffffffffu, !(b0 <= 65536.f) || !(b1 <= 65536.f))) {                                           \
          float mx0 = fmaxf(s[0], s[1]), mx1 = fmaxf(s[2], s[3]);                                                      \
          _Pragma("unroll") for (int i = 1; i < 8; i++) {                                                              \
            mx0 = fmaxf(mx0, fmaxf(s[4 * i], s[4 * i + 1])); mx1 = fmaxf(mx1, fmaxf(s[4 * i + 2], s[4 * i + 3]));     \
          }                                                                                                            \
          mx0 = fmaxf(mx0, __shfl_xor_sync(0xffffffffu, mx0, 1)); mx1 = fmaxf(mx1, __shfl_xor_sync(0xffffffffu, mx1, 1)); \
          mx0 = fmaxf(mx0, __shfl_xor_sync(0xffffffffu, mx0, 2)); mx1 = fmaxf(mx1, __shfl_xor_sync(0xffffffffu, mx1, 2)); \
          const float n0 = fmaxf(c0, mx0 * SC), n1 = fmaxf(c1, mx1 * SC);                                              \
          const float a0 = ex2(c0 - n0), a1 = ex2(c1 - n1);                                                            \
          c0 = n0; c1 = n1;                                                                                            \
          l0 *= a0; l1 *= a1;                                                                                          \
          _Pragma("unroll") for (int i = 0; i < 24; i++) { o[4 * i] *= a0; o[4 * i + 1] *= a0; o[4 * i + 2] *= a1; o[4 * i + 3] *= a1; } \
          b0 = 0.f; b1 = 0.f;                                                                                          \
          _Pragma("unroll") for (int i = 0; i < 8; i++) {                                                              \
            const float e0 = ex2(fmaf(s[4 * i], SC, -c0)), e1 = ex2(fmaf(s[4 * i + 1], SC, -c0));                      \
            const float e2 = ex2(fmaf(s[4 * i + 2], SC, -c1)), e3 = ex2(fmaf(s[4 * i + 3], SC, -c1));                  \
            b0 += e0 + e1; b1 += e2 + e3;                                                                              \
            PN[2 * i] = pack_bf16(e0, e1); PN[2 * i + 1] = pack_bf16(e2, e3);                                          \
          }                                                                                                            \
        }                                                                                                              \
        l0 += b0; l1 += b1;                                                                                            \
      }
      for (int jj = 0; jj < 15; jj++) {
        A_STEP(p, p2, jj == 0)
        A_STEP(p2, p, false)
      }
      A_STEP(p, p2, false)
      TSA(item, 3);
      {
        const uint32_t sV = r.slot; mbar_wait_c(bar_full + 8 * sV, r.phase); r.adv(A_NSLOT);
        const uint64_t dv = mkdesc(sb + sV * A_SLOT, 8192, 1024);
        bar_sync(1 + w, 256);
        wg_fence();
#pragma unroll
        for (int kk = 0; kk < 4; kk++)
          wgmma_rs_n192<1>(o, p2[4 * kk], p2[4 * kk + 1], p2[4 * kk + 2], p2[4 * kk + 3], dv + kk * 128, 1);
        wg_commit();
        bar_arrive(1 + (w ^ 1), 256);
        wg_wait<0>();
        fence_regs(o);
        A_RELEASE(sV);
      }
      TSA(item, 4);
      l0 += __shfl_xor_sync(0xffffffffu, l0, 1); l1 += __shfl_xor_sync(0xffffffffu, l1, 1);
      l0 += __shfl_xor_sync(0xffffffffu, l0, 2); l1 += __shfl_xor_sync(0xffffffffu, l1, 2);
      const float i0 = __fdividef(1.f, l0), i1 = __fdividef(1.f, l1);
#pragma unroll
      for (int i = 0; i < 24; i++) { q[2 * i] = pack_bf16(o[4 * i] * i0, o[4 * i + 1] * i0); q[2 * i + 1] = pack_bf16(o[4 * i + 2] * i1, o[4 * i + 3] * i1); }
      TSA(item, 5);
    }
#pragma unroll
    for (int g = 0; g < 6; g++) { O_STORE(g) }
    SIGNAL();
    }
    TS(3, 2);
    const uint32_t st_w = (uint32_t)((warp * 16 + (lane >> 2)) * ST_P + (lane & 3) * 2) * 4;
    const uint32_t st_x = (lane & 8) << 2;
    const int er = (tid & 127) >> 1, eh = tid & 1;
    const uint32_t st_r = (uint32_t)(er * ST_P + (eh ^ ((er >> 1) & 1)) * 8) * 4;
    const uint32_t e_r = (uint32_t)((w * 64 + er) * 160 + eh * 16);
    const uint32_t p_r = par + eh * 32;
    const uint32_t stat = sb + T_PREP + w * 2048;
    const bool leader = (tid & 127) == 0;
#define STAGE10(ACC, BASE)                                                                                             \
    _Pragma("unroll") for (int nb = 0; nb < 10; nb++) {                                                                \
      sts_f2(stg + st_w + ((nb * 32) ^ st_x), ACC(BASE + 4 * nb), ACC(BASE + 4 * nb + 1));                                       \
      sts_f2(stg + st_w + ((nb * 32) ^ st_x) + 8 * ST_P * 4, ACC(BASE + 4 * nb + 2), ACC(BASE + 4 * nb + 3));                    \
    }

    {
      float acc1[96], acc2[64];
      uint32_t p0 = 0, p1 = 0, p2 = 0;
#pragma unroll 1
      for (int kb = 0; kb < 24; kb++) {
        const uint32_t s1 = r.slot; mbar_wait_c(bar_full + 8 * s1, r.phase); r.adv(A_NSLOT);
        const uint32_t s2 = r.slot; mbar_wait_c(bar_full + 8 * s2, r.phase); r.adv(A_NSLOT);
        const uint32_t sa = r.slot; mbar_wait_c(bar_full + 8 * sa, r.phase); r.adv(A_NSLOT);
        const uint64_t da = mkdesc(sb + sa * A_SLOT + w * 8192, 16, 1024);
        const uint64_t d1 = mkdesc(sb + s1 * A_SLOT, 8192, 1024), d2 = mkdesc(sb + s2 * A_SLOT, 8192, 1024);
        wg_fence();
#pragma unroll
        for (int kk = 0; kk < 4; kk++) {
          wgmma_ss_n192<1>(acc1, da + kk * 2, d1 + kk * 128, (kb | kk) != 0);
          wgmma_ss_n128<1>(acc2, da + kk * 2, d2 + kk * 128, (kb | kk) != 0);
        }
        wg_commit();
        if (kb > 0) { wg_wait<1>(); A_RELEASE(p0); A_RELEASE(p1); A_RELEASE(p2); }
        p0 = s1; p1 = s2; p2 = sa;
      }
      wg_wait<0>();
      fence_regs(acc1); fence_regs(acc2);
      A_RELEASE(p2);
      bar_sync(6, 288);
      TS(0, 0);
      const uint32_t stg = sb + (w ? p1 : p0) * A_SLOT;
#define OACC(e) (((e) < 96) ? acc1[(e) < 96 ? (e) : 0] : acc2[(e) >= 96 ? (e) - 96 : 0])
#define PACK10(BASE)                                                                                                   \
      _Pragma("unroll") for (int nb = 0; nb < 10; nb++) {                                                              \
        sts_u1(xo + nb * 16, pack_bf16(OACC(BASE + 4 * nb), OACC(BASE + 4 * nb + 1)));                                 \
        sts_u1(xo + nb * 16 + 8 * 160, pack_bf16(OACC(BASE + 4 * nb + 2), OACC(BASE + 4 * nb + 3)));                   \
      }
      const uint32_t f1 = r.slot + 4 >= A_NSLOT ? r.slot + 4 - A_NSLOT : r.slot + 4, f2 = f1 + 1 >= A_NSLOT ? 0 : f1 + 1;
#pragma unroll
      for (int d = 0; d < 4; d++) {
        if (d != o_ks) {
          const int i = (d - o_ks - 1) & 3;
          const uint32_t xo = sb + (i == 0 ? p2 : i == 1 ? f1 : f2) * A_SLOT + (w * 64 + warp * 16 + (lane >> 2)) * 160 + (lane & 3) * 4;
          PACK10(d * 40)
        }
      }
      fence_async_smem();
      bar_sync(3 + w, 128);
      if (leader) {
#pragma unroll 1
        for (int i = 0; i < 3; i++)
          bulk_store(g_xch + (size_t)((((o_qt * 2 + o_nh) * 4 + ((o_ks + 1 + i) & 3)) * 4) + o_ks) * (E_TILE / 2) + w * (E_TILE / 4),
                     sb + (i == 0 ? p2 : i == 1 ? f1 : f2) * A_SLOT + w * (E_TILE / 2), E_TILE / 2);
        bulk_done();
#pragma unroll 1
        for (int i = 0; i < 3; i++) flag_add(g_flag + F_XCH + (o_qt * 2 + o_nh) * 4 + ((o_ks + 1 + i) & 3));
        TX(40 + w);
      }
      if (o_ks == 0) { STAGE10(OACC, 0) } else if (o_ks == 1) { STAGE10(OACC, 40) } else if (o_ks == 2) { STAGE10(OACC, 80) } else { STAGE10(OACC, 120) }
      bar_sync(3 + w, 128);
      const uint32_t sx = r.slot; mbar_wait_c(bar_full + 8 * sx, r.phase); r.adv(A_NSLOT);
      const uint32_t q0 = r.slot; mbar_wait_c(bar_full + 8 * q0, r.phase); r.adv(A_NSLOT);
      const uint32_t q1 = r.slot; mbar_wait_c(bar_full + 8 * q1, r.phase); r.adv(A_NSLOT);
      const uint32_t q2 = r.slot; mbar_wait_c(bar_full + 8 * q2, r.phase); r.adv(A_NSLOT);
      TS(0, 1);
      float st[6] = {0.f, 0.f, 0.f, 0.f, 0.f, 0.f};
      const uint32_t ot = sb + p2 * A_SLOT;
#pragma unroll 1
      for (int c = 0; c < 5; c++) {
        float v[8], t0[8], t1[8], t2[8], xv[8], pg[8], pa_[8], pb_[8];
        lds8(stg + st_r + c * 64, v);
        lds8_bf(sb + q0 * A_SLOT + e_r + c * 32, t0); lds8_bf(sb + q1 * A_SLOT + e_r + c * 32, t1); lds8_bf(sb + q2 * A_SLOT + e_r + c * 32, t2);
        lds8_bf(sb + sx * A_SLOT + e_r + c * 32, xv);
        lds8(p_r + P_OGA * 4 + c * 64, pg); lds8(p_r + P_OA * 4 + c * 64, pa_); lds8(p_r + P_OB * 4 + c * 64, pb_);
#pragma unroll
        for (int e = 0; e < 8; e++) v[e] = fmaf(pg[e], v[e] + ((t0[e] + t1[e]) + t2[e]), xv[e]);
        const uint4 pk = pack8(v);
        sts_u4(ot + e_r + c * 32, pk);
        v[0] = bf_lo(pk.x); v[1] = bf_hi(pk.x); v[2] = bf_lo(pk.y); v[3] = bf_hi(pk.y); v[4] = bf_lo(pk.z); v[5] = bf_hi(pk.z); v[6] = bf_lo(pk.w); v[7] = bf_hi(pk.w);
#pragma unroll
        for (int e = 0; e < 8; e++) {
          const float y = pa_[e] * v[e];
          st[0] += v[e]; st[1] = fmaf(v[e], v[e], st[1]); st[2] += y; st[3] = fmaf(pa_[e], y, st[3]); st[4] = fmaf(y, y, st[4]); st[5] = fmaf(pb_[e], y, st[5]);
        }
      }
#pragma unroll
      for (int i = 0; i < 6; i++) st[i] += __shfl_xor_sync(0xffffffffu, st[i], 1);
      sts_u4(stat + er * 32 + eh * 16, eh ? make_uint4(__float_as_uint(st[4]), __float_as_uint(st[5]), 0u, 0u)
                                          : make_uint4(__float_as_uint(st[0]), __float_as_uint(st[1]), __float_as_uint(st[2]), __float_as_uint(st[3])));
      fence_async_smem();
      bar_sync(3 + w, 128);
      if (leader) {
        tma_store2d(&tm.sxa, ot + w * (E_TILE / 2), o_col, o_qt * 128 + w * 64);
        bulk_red_f32(g_st1 + (size_t)(o_qt * 128 + w * 64) * 8, stat, 2048);
        bulk_done();
        flag_add(g_flag + F_XA + o_qt);
      }
      bar_sync(5, 256);
      A_RELEASE(p0); A_RELEASE(p1); A_RELEASE(sx); A_RELEASE(q0); A_RELEASE(q1); A_RELEASE(q2);
      TS(0, 2);
    }

    Ring ra{0, 0};
    uint32_t bpar = 0;
    const uint32_t rel_a = mapa(mb_empty + 40, (lane == 0) ? rank : (rank ^ 1));
#define B_NEXT(s_) do { s_ = bs; mbar_wait_c(mb_full + 8 * bs, (bpar >> bs) & 1); bpar ^= 1u << bs; if (++bs == nbs) bs = 0; } while (0)
#define A_NEXT(s_) do { s_ = ra.slot; mbar_wait_c(mb_full + 40 + 8 * s_, ra.phase); ra.adv(M_NA); } while (0)
#define B_RELEASE(s_) do { if (lane == 0) mbar_arrive(mb_empty + 8 * (s_)); } while (0)
#define MA_RELEASE(s_) do { if (lane < 2) mbar_arrive_remote(rel_a + 8 * (s_)); } while (0)
    const int grow = qt * 128 + w * 64 + er;
    float mu = 0.f, rs = 0.f;
#pragma unroll 1
    for (int ph = 0; ph < 4; ph++) {
      float acc[96];
      float (&acc80)[40] = *reinterpret_cast<float(*)[40]>(&acc[0]);
      uint32_t pa = 0, pa2 = 0, pb = 0;
      float4 s03 = make_float4(0.f, 0.f, 0.f, 0.f);
      float2 s45 = make_float2(0.f, 0.f);
      const int nit = ph == 3 ? 12 : ph == 2 ? 10 : 5;
      const uint32_t nbs = ph == 2 ? 4 : 5, bsz = ph == 2 ? 24576 : 20480;
      uint32_t bs = 0;
#pragma unroll 1
      for (int it = 0; it < nit; it++) {
        uint32_t sbq, sa, sa2;
        B_NEXT(sbq);
        A_NEXT(sa);
        if (it == 0) TXC(ph);
        const uint64_t da = mkdesc(sb + M_AOFF + sa * 16384 + w * 8192, 16, 1024);
        if (ph == 2) {
          sa2 = sa;
          const uint64_t db = mkdesc(sb + sbq * 24576, 8192, 1024);
          wg_fence();
#pragma unroll
          for (int kk = 0; kk < 4; kk++) wgmma_ss_n192<1>(acc, da + kk * 2, db + kk * 128, (it | kk) != 0);
          wg_commit();
        } else {
          A_NEXT(sa2);
          const uint64_t da2 = mkdesc(sb + M_AOFF + sa2 * 16384 + w * 8192, 16, 1024);
          const uint64_t db = mkdesc(sb + sbq * 20480, 16, 1024);
          wg_fence();
#pragma unroll
          for (int kk = 0; kk < 4; kk++) wgmma_ss_n80<0>(acc80, da + kk * 2, db + kk * 2, (it | kk) != 0);
#pragma unroll
          for (int kk = 0; kk < 4; kk++) wgmma_ss_n80<0>(acc80, da2 + kk * 2, db + 640 + kk * 2, 1);
          wg_commit();
        }
        if (it > 0) { wg_wait<1>(); MA_RELEASE(pa); if (ph != 2) MA_RELEASE(pa2); B_RELEASE(pb); }
        else {
          if (ph == 0) { s03 = __ldcg(reinterpret_cast<const float4*>(g_st1 + (size_t)grow * 8)); s45 = __ldcg(reinterpret_cast<const float2*>(g_st1 + (size_t)grow * 8 + 4)); }
          if (ph == 2) s45 = __ldcg(reinterpret_cast<const float2*>(g_st2 + (size_t)grow * 2));
        }
        pa = sa; pa2 = sa2; pb = sbq;
      }
      wg_wait<0>();
      fence_regs(acc);
      MA_RELEASE(pa); if (ph != 2) MA_RELEASE(pa2);
      bar_sync(5, 256);
      TS(1 + (ph == 3 ? 0 : ph), ph == 3 ? 2 : 0);
      const uint32_t pb1 = pb == 0 ? nbs - 1 : pb - 1, pb2 = pb1 == 0 ? nbs - 1 : pb1 - 1, pb3 = pb2 == 0 ? nbs - 1 : pb2 - 1;
      const uint32_t stg = sb + (w ? pb : pb1) * bsz;
      uint32_t e1 = 0;
#define MACC(e) acc[e]
      if (!(ph & 1)) {
        float c0, c1, c2 = 0.f, c3 = 0.f;
        if (ph == 0) {
          const float4 sc = lds_f4(par + P_SC * 4);
          const float sbb = lds_f(par + (P_SC + 4) * 4);
          mu = s03.x * (1.f / D_);
          rs = rsqrtf(fmaxf(s03.y * (1.f / D_) - mu * mu, 0.f) + LN_EPS);
          const float m2 = (rs * (s03.z - mu * sc.x) + sc.w) * (1.f / D_);
          const float e2 = (rs * rs * (s45.x - 2.f * mu * s03.w + mu * mu * sc.y) + 2.f * rs * (s45.y - mu * sc.z) + sbb) * (1.f / D_);
          c2 = rsqrtf(fmaxf(e2 - m2 * m2, 0.f) + LN_EPS);
          c0 = c2 * rs; c1 = -c0 * mu; c3 = -c2 * m2;
          if (tid < 20) sts_u4(stat + 2048 * 2 + tid * 16, make_uint4(0, 0, 0, 0));
        } else {
          const float m = s45.x * (1.f / D_);
          c0 = rsqrtf(fmaxf(s45.y * (1.f / D_) - m * m, 0.f) + LN_EPS);
          c1 = -c0 * m;
        }
        const int npass = ph == 0 ? 1 : 3, nch = ph == 0 ? 5 : 4;
        const uint32_t ot = ph == 0 ? sb + pb2 * bsz + w * (E_TILE / 2) : sb + (w ? pb2 : pb3) * bsz;
#pragma unroll 1
        for (int ps = 0; ps < npass; ps++) {
          if (ps == 0) { STAGE10(MACC, 0) } else if (ps == 1) { STAGE10(MACC, 32) } else { STAGE10(MACC, 56) }
          bar_sync(3 + w, 128);
          const uint32_t cofs = ps == 2 ? 64 : 0;
          const uint32_t pp = p_r + (ph == 0 ? P_VA : P_CS3 + ps * 64) * 4, pq = p_r + P_VB * 4;
#pragma unroll 1
          for (int c = 0; c < nch; c++) {
            float v[8], t[8], t2[8], t3[8];
            lds8(stg + st_r + cofs + c * 64, v);
            lds8(pp + c * 64, t);
            if (ph == 0) {
              lds8(pq + c * 64, t2); lds8(pq + 320 + c * 64, t3);
#pragma unroll
              for (int e = 0; e < 8; e++) t[e] = fmaf(c1, t[e], fmaf(c2, t2[e], c3 * t3[e]));
            } else {
#pragma unroll
              for (int e = 0; e < 8; e++) t[e] *= c1;
            }
#pragma unroll
            for (int e = 0; e < 8; e++) v[e] = gelu_tanh(fmaf(c0, v[e], t[e]));
            sts_u4(ot + (ph == 0 ? er * 160 + eh * 16 + c * 32 : ps * 8192 + er * 128 + (((2 * c + eh) ^ (er & 7)) << 4)), pack8(v));
          }
          fence_async_smem();
          bar_sync(3 + w, 128);
          if (leader) {
            if (ph == 0) {
              const int grp = js >> 1;
              const int sh = (grp & 2 ? 2 : 1) * (grp & 1 ? -1 : 1);
              tma_store2d(&tm.sus, ot, js * 80, qt * 128 + w * 64 + sh + 2);
              if (w == 0 && qt == (sh > 0 ? 0 : 15)) {
                const int r0 = sh > 0 ? 0 : S_ + sh, n = sh > 0 ? sh : -sh;
                for (int i = 0; i < n; i++) bulk_store(g_us + (size_t)(r0 + i + 2) * D_ + js * 80, stat + 2048 * 2, 160);
              }
            } else {
              tma_store2d(&tm.g, ot + ps * 8192, js * 192 + ps * 64, qt * 128 + w * 64);
            }
          }
        }
      } else {
        STAGE10(MACC, 0)
        uint32_t e2;
        B_NEXT(e1);
        e2 = e1;
        if (ph == 3) B_NEXT(e2);
        bar_sync(3 + w, 128);
        float s1 = 0.f, s2 = 0.f;
        const uint32_t ot = sb + pb2 * bsz;
#pragma unroll 1
        for (int c = 0; c < 5; c++) {
          float v[8], xa[8], x1[8], ta[8], tb[8];
          lds8(stg + st_r + c * 64, v);
          lds8_bf(sb + e1 * 20480 + e_r + c * 32, xa); lds8_bf(sb + e2 * 20480 + e_r + c * 32, x1);
          lds8(p_r + (ph == 1 ? P_A2 : P_GB) * 4 + c * 64, ta); lds8(p_r + P_B2 * 4 + c * 64, tb);
          if (ph == 1) {
#pragma unroll
            for (int e = 0; e < 8; e++) v[e] += fmaf(ta[e] * rs, xa[e] - mu, tb[e]);
          } else {
#pragma unroll
            for (int e = 0; e < 8; e++) v[e] = fmaf(ta[e], v[e] + x1[e], xa[e]);
          }
          const uint4 pk = pack8(v);
          sts_u4(ot + e_r + c * 32, pk);
          v[0] = bf_lo(pk.x); v[1] = bf_hi(pk.x); v[2] = bf_lo(pk.y); v[3] = bf_hi(pk.y); v[4] = bf_lo(pk.z); v[5] = bf_hi(pk.z); v[6] = bf_lo(pk.w); v[7] = bf_hi(pk.w);
#pragma unroll
          for (int e = 0; e < 8; e++) { s1 += v[e]; s2 = fmaf(v[e], v[e], s2); }
        }
        s1 += __shfl_xor_sync(0xffffffffu, s1, 1); s2 += __shfl_xor_sync(0xffffffffu, s2, 1);
        if (eh == 0) sts_f2(stat + er * 8, s1, s2);
        fence_async_smem();
        bar_sync(3 + w, 128);
        if (leader) {
          tma_store2d(ph == 1 ? &tm.sx1 : &tm.sout, ot + w * (E_TILE / 2), js * 80, qt * 128 + w * 64);
          if (ph == 1) bulk_red_f32(g_st2 + (size_t)(qt * 128 + w * 64) * 2, stat, 512);
        }
      }
      if (leader) {
        bulk_done();
        if (ph < 3) flag_add(g_flag + F_US + 16 * ph + qt);
      }
      if (ph < 3) {
        bar_sync(5, 256);
        B_RELEASE(pb);
        if (ph == 1) B_RELEASE(e1);
      }
      TS(1 + (ph == 3 ? 0 : ph), ph == 3 ? 3 : 1);
    }
    if ((threadIdx.x & 127) == 0) TL_END(2);
    cluster_sync();
    if (wid == 4) {
      unsigned n = 0;
      if (lane == 0) n = atomicAdd(g_flag + F_DONE, 1u);
      n = __shfl_sync(0xffffffffu, n, 0);
      if (n == 127) {
#pragma unroll 1
        for (int i = lane; i < 1024; i += 32) g_flag[i] = 0u;
      }
    }
  }
}

typedef CUresult (*EncFn)(CUtensorMap*, CUtensorMapDataType, cuuint32_t, void*, const cuuint64_t*, const cuuint64_t*,
                          const cuuint32_t*, const cuuint32_t*, CUtensorMapInterleave, CUtensorMapSwizzle,
                          CUtensorMapL2promotion, CUtensorMapFloatOOBfill);
static EncFn g_enc = nullptr;

static CUtensorMap map2d(const void* p, uint64_t rows, uint64_t cols, uint32_t box_rows) {
  CUtensorMap m;
  cuuint64_t gd[2] = {cols, rows}; cuuint64_t gs[1] = {cols * 2};
  cuuint32_t bx[2] = {64, box_rows}; cuuint32_t es[2] = {1, 1};
  g_enc(&m, CU_TENSOR_MAP_DATA_TYPE_BFLOAT16, 2, const_cast<void*>(p), gd, gs, bx, es, CU_TENSOR_MAP_INTERLEAVE_NONE,
        CU_TENSOR_MAP_SWIZZLE_128B, CU_TENSOR_MAP_L2_PROMOTION_L2_256B, CU_TENSOR_MAP_FLOAT_OOB_FILL_NONE);
  return m;
}
static CUtensorMap map3d(const void* p, uint64_t rows, uint64_t cols, uint32_t box_rows, uint32_t nblk) {
  CUtensorMap m;
  cuuint64_t gd[3] = {64, rows, cols / 64}; cuuint64_t gs[2] = {cols * 2, 128};
  cuuint32_t bx[3] = {64, box_rows, nblk}; cuuint32_t es[3] = {1, 1, 1};
  g_enc(&m, CU_TENSOR_MAP_DATA_TYPE_BFLOAT16, 3, const_cast<void*>(p), gd, gs, bx, es, CU_TENSOR_MAP_INTERLEAVE_NONE,
        CU_TENSOR_MAP_SWIZZLE_128B, CU_TENSOR_MAP_L2_PROMOTION_L2_256B, CU_TENSOR_MAP_FLOAT_OOB_FILL_NONE);
  return m;
}

static CUtensorMap map_e(const void* p, uint32_t rows, uint64_t total_rows = S_) {
  CUtensorMap m;
  cuuint64_t gd[2] = {D_, total_rows}; cuuint64_t gs[1] = {D_ * 2};
  cuuint32_t bx[2] = {80, rows}; cuuint32_t es[2] = {1, 1};
  g_enc(&m, CU_TENSOR_MAP_DATA_TYPE_BFLOAT16, 2, const_cast<void*>(p), gd, gs, bx, es, CU_TENSOR_MAP_INTERLEAVE_NONE,
        CU_TENSOR_MAP_SWIZZLE_NONE, CU_TENSOR_MAP_L2_PROMOTION_L2_256B, CU_TENSOR_MAP_FLOAT_OOB_FILL_NONE);
  return m;
}

template <typename... KArgs, typename... Args>
static void launch(void (*kern)(KArgs...), dim3 grid, dim3 block, int smem, bool pdl, Args... args) {
  cudaLaunchConfig_t cfg = {};
  cfg.gridDim = grid; cfg.blockDim = block; cfg.dynamicSmemBytes = smem; cfg.stream = cudaStreamPerThread;
  cudaLaunchAttribute at[1];
  at[0].id = cudaLaunchAttributeProgrammaticStreamSerialization;
  at[0].val.programmaticStreamSerializationAllowed = 1;
  cfg.attrs = at; cfg.numAttrs = pdl ? 1 : 0;
  cudaLaunchKernelEx(&cfg, kern, KArgs(args)...);
}

extern "C" void kernel_launch(void* const* d_in, const int* in_sizes, int n_in, void* d_out, int out_size) {
  const bf16* x = (const bf16*)d_in[0];
  const bf16* kc = (const bf16*)d_in[1];
  const bf16* vc = (const bf16*)d_in[2];
  const bf16* wq = (const bf16*)d_in[3];
  const bf16* wo = (const bf16*)d_in[4];
  const bf16* w1 = (const bf16*)d_in[6];
  const bf16* w2 = (const bf16*)d_in[7];
  const bf16* w3 = (const bf16*)d_in[8];
  const bf16* w4 = (const bf16*)d_in[9];
  const bf16* c = (const bf16*)d_in[10];
  const bf16* wmod = (const bf16*)d_in[11];
  bf16* out = (bf16*)d_out;

  static void *p_h, *p_o, *p_xa, *p_us, *p_x1, *p_g, *p_w1t, *p_w2t, *p_w4t;
  if (!g_enc) {
    void* fn = nullptr; cudaDriverEntryPointQueryResult qr;
    cudaGetDriverEntryPoint("cuTensorMapEncodeTiled", &fn, cudaEnableDefault, &qr);
    g_enc = (EncFn)fn;
    cudaGetSymbolAddress(&p_h, g_h); cudaGetSymbolAddress(&p_o, g_o); cudaGetSymbolAddress(&p_xa, g_xa);
    cudaGetSymbolAddress(&p_us, g_us); cudaGetSymbolAddress(&p_x1, g_x1); cudaGetSymbolAddress(&p_g, g_g);
    cudaGetSymbolAddress(&p_w1t, g_w1t); cudaGetSymbolAddress(&p_w2t, g_w2t); cudaGetSymbolAddress(&p_w4t, g_w4t);
    cudaFuncSetAttribute(fused_kernel, cudaFuncAttributeMaxDynamicSharedMemorySize, T_SMEM);
  }
  Maps tm;
  tm.h = map2d(p_h, S_, D_, 128);
  tm.wq = map3d(wq, D_, HD_, 64, 3);
  tm.k = map3d(kc, (uint64_t)H_ * S_, DH_, 64, 3);
  tm.v = map3d(vc, (uint64_t)H_ * S_, DH_, 64, 3);
  tm.o = map2d(p_o, S_, HD_, 128);
  tm.wo3 = map3d(wo, HD_, D_, 64, 3);
  tm.wo2 = map3d(wo, HD_, D_, 64, 2);
  tm.xa = map2d(p_xa, S_, D_, 64);
  tm.w1t = map3d(p_w1t, D_, D_, 80, 2);
  tm.us = map2d((const bf16*)p_us + 2 * D_, S_, D_, 64);
  tm.w2t = map3d(p_w2t, D_, D_, 80, 2);
  tm.x1 = map2d(p_x1, S_, D_, 64);
  tm.w3 = map3d(w3, D_, F_, 64, 3);
  tm.g = map2d(p_g, S_, F_, 64);
  tm.w4t = map3d(p_w4t, D_, F_, 80, 2);
  tm.ex = map_e(x, 128); tm.exa = map_e(p_xa, 128); tm.ex1 = map_e(p_x1, 128);
  tm.sxa = map_e(p_xa, 64); tm.sus = map_e(p_us, 64, S_ + 4); tm.sx1 = map_e(p_x1, 64); tm.sout = map_e(out, 64);
  PfList pf;
  pf.p[0] = (const uint8_t*)wo; pf.p[1] = (const uint8_t*)w3; pf.p[2] = (const uint8_t*)p_w4t;
  pf.p[3] = (const uint8_t*)x; pf.p[4] = (const uint8_t*)p_w1t; pf.p[5] = (const uint8_t*)p_w2t;

  launch(fused_kernel, dim3(128), dim3(384), T_SMEM, false, tm, pf, PrepW{w1, w2, w3, w4, c, wmod}, x, out);
}
```

```cpp
#include <cuda_runtime.h>
#include <cuda.h>
#include <cuda_bf16.h>
#include <stdint.h>

typedef __nv_bfloat16 bf16;

constexpr int S_  = 2048;
constexpr int D_  = 640;
constexpr int H_  = 32;
constexpr int DH_ = 192;
constexpr int HD_ = H_ * DH_;
constexpr int F_  = 1536;
constexpr float LN_EPS = 1e-5f;

__device__ __forceinline__ uint32_t smem_u32(const void* p) { return (uint32_t)__cvta_generic_to_shared(p); }
__device__ __forceinline__ void mbar_init(uint32_t a, uint32_t c) { asm volatile("mbarrier.init.shared::cta.b64 [%0], %1;" :: "r"(a), "r"(c) : "memory"); }
__device__ __forceinline__ void mbar_expect(uint32_t a, uint32_t b) { asm volatile("mbarrier.arrive.expect_tx.shared::cta.b64 _, [%0], %1;" :: "r"(a), "r"(b) : "memory"); }
__device__ __forceinline__ void mbar_arrive(uint32_t a) { asm volatile("mbarrier.arrive.shared::cta.b64 _, [%0];" :: "r"(a) : "memory"); }
__device__ __forceinline__ void mbar_arrive_remote(uint32_t ra) { asm volatile("mbarrier.arrive.shared::cluster.b64 _, [%0];" :: "r"(ra) : "memory"); }
__device__ __forceinline__ uint32_t mapa(uint32_t a, uint32_t cta) { uint32_t r; asm volatile("mapa.shared::cluster.u32 %0, %1, %2;" : "=r"(r) : "r"(a), "r"(cta)); return r; }
__device__ __forceinline__ uint32_t mbar_try(uint32_t a, uint32_t ph) {
  uint32_t ok;
  asm volatile("{\n.reg .pred p;\nmbarrier.test_wait.parity.shared::cta.b64 p, [%1], %2;\nselp.u32 %0, 1, 0, p;\n}\n" : "=r"(ok) : "r"(a), "r"(ph) : "memory");
  return ok;
}
__device__ __forceinline__ void mbar_wait(uint32_t a, uint32_t ph) {
  asm volatile(
      "{\n.reg .pred p;\n.reg .u32 n;\n"
      "mov.u32 n, 0;\n"
      "SPIN:\n"
      "mbarrier.try_wait.parity.shared::cta.b64 p, [%0], %1;\n"
      "@p bra DONE;\n"
      "add.u32 n, n, 1;\n"
      "setp.le.u32 p, n, 16777216;\n"
      "@p bra SPIN;\n"
      "trap;\n"
      "DONE:\n}\n" :: "r"(a), "r"(ph) : "memory");
}
#define ELECT_ "{\n.reg .pred p;\nelect.sync _|p, 0xffffffff;\n@p "
__device__ __forceinline__ void mbar_expect_e(uint32_t a, uint32_t b) { asm volatile(ELECT_ "mbarrier.arrive.expect_tx.shared::cta.b64 _, [%0], %1;\n}\n" :: "r"(a), "r"(b) : "memory"); }
__device__ __forceinline__ void tma2d(uint32_t dst, const CUtensorMap* m, uint32_t bar, int c0, int c1) {
  asm volatile(ELECT_ "cp.async.bulk.tensor.2d.shared::cluster.global.mbarrier::complete_tx::bytes [%0], [%1, {%3, %4}], [%2];\n}\n"
               :: "r"(dst), "l"(m), "r"(bar), "r"(c0), "r"(c1) : "memory");
}
__device__ __forceinline__ void tma2d_mc(uint32_t dst, const CUtensorMap* m, uint32_t bar, int c0, int c1, uint16_t mask) {
  asm volatile(ELECT_ "cp.async.bulk.tensor.2d.shared::cluster.global.mbarrier::complete_tx::bytes.multicast::cluster [%0], [%1, {%3, %4}], [%2], %5;\n}\n"
               :: "r"(dst), "l"(m), "r"(bar), "r"(c0), "r"(c1), "h"(mask) : "memory");
}
__device__ __forceinline__ void tma3d(uint32_t dst, const CUtensorMap* m, uint32_t bar, int c0, int c1, int c2) {
  asm volatile(ELECT_ "cp.async.bulk.tensor.3d.shared::cluster.global.mbarrier::complete_tx::bytes [%0], [%1, {%3, %4, %5}], [%2];\n}\n"
               :: "r"(dst), "l"(m), "r"(bar), "r"(c0), "r"(c1), "r"(c2) : "memory");
}
__device__ __forceinline__ void tma3d_mc(uint32_t dst, const CUtensorMap* m, uint32_t bar, int c0, int c1, int c2, uint16_t mask) {
  asm volatile(ELECT_ "cp.async.bulk.tensor.3d.shared::cluster.global.mbarrier::complete_tx::bytes.multicast::cluster [%0], [%1, {%3, %4, %5}], [%2], %6;\n}\n"
               :: "r"(dst), "l"(m), "r"(bar), "r"(c0), "r"(c1), "r"(c2), "h"(mask) : "memory");
}
__device__ __forceinline__ void tma3d_mc_hint(uint32_t dst, const CUtensorMap* m, uint32_t bar, int c0, int c1, int c2, uint16_t mask, uint64_t pol) {
  asm volatile(ELECT_ "cp.async.bulk.tensor.3d.shared::cluster.global.mbarrier::complete_tx::bytes.multicast::cluster.L2::cache_hint [%0], [%1, {%3, %4, %5}], [%2], %6, %7;\n}\n"
               :: "r"(dst), "l"(m), "r"(bar), "r"(c0), "r"(c1), "r"(c2), "h"(mask), "l"(pol) : "memory");
}
__device__ __forceinline__ void bulk_load(uint32_t dst, const void* src, uint32_t bytes, uint32_t bar) {
  asm volatile(ELECT_ "cp.async.bulk.shared::cluster.global.mbarrier::complete_tx::bytes [%0], [%1], %2, [%3];\n}\n"
               :: "r"(dst), "l"(src), "r"(bytes), "r"(bar) : "memory");
}
__device__ __forceinline__ void l2_prefetch16k(const void* p) { asm volatile(ELECT_ "cp.async.bulk.prefetch.L2.global [%0], 16384;\n}\n" :: "l"(p) : "memory"); }
__device__ __forceinline__ void l2_prefetch_t2d(const CUtensorMap* m, int c0, int c1) {
  asm volatile(ELECT_ "cp.async.bulk.prefetch.tensor.2d.L2.global [%0, {%1, %2}];\n}\n" :: "l"(m), "r"(c0), "r"(c1) : "memory");
}
__device__ __forceinline__ void l2_prefetch_t3d(const CUtensorMap* m, int c0, int c1, int c2) {
  asm volatile(ELECT_ "cp.async.bulk.prefetch.tensor.3d.L2.global [%0, {%1, %2, %3}];\n}\n" :: "l"(m), "r"(c0), "r"(c1), "r"(c2) : "memory");
}
__device__ __forceinline__ void stg128(void* p, uint4 v) {
  asm volatile("st.global.v4.u32 [%0], {%1, %2, %3, %4};" :: "l"(p), "r"(v.x), "r"(v.y), "r"(v.z), "r"(v.w) : "memory");
}
__device__ __forceinline__ void prefetch_tmap(const CUtensorMap* m) { asm volatile("prefetch.tensormap [%0];" :: "l"(m) : "memory"); }
__device__ __forceinline__ void wg_fence() { asm volatile("wgmma.fence.sync.aligned;" ::: "memory"); }
__device__ __forceinline__ void wg_commit() { asm volatile("wgmma.commit_group.sync.aligned;" ::: "memory"); }
template <int N> __device__ __forceinline__ void wg_wait() { asm volatile("wgmma.wait_group.sync.aligned %0;" :: "n"(N) : "memory"); }
template <int N> __device__ __forceinline__ void fence_regs(float (&r)[N]) {
#pragma unroll
  for (int i = 0; i < N; i++) asm volatile("" : "+f"(r[i]) :: "memory");
}
template <int N> __device__ __forceinline__ void fence_regs(uint32_t (&r)[N]) {
#pragma unroll
  for (int i = 0; i < N; i++) asm volatile("" : "+r"(r[i]) :: "memory");
}
__device__ __forceinline__ uint64_t mkdesc(uint32_t addr, uint32_t lbo, uint32_t sbo) {
  return (uint64_t)((addr & 0x3FFFF) >> 4) | ((uint64_t)(lbo >> 4) << 16) | ((uint64_t)(sbo >> 4) << 32) | (1ull << 62);
}
__device__ __forceinline__ void bar_sync(int id, int n) { asm volatile("bar.sync %0, %1;" :: "r"(id), "r"(n) : "memory"); }
__device__ __forceinline__ void bar_arrive(int id, int n) { asm volatile("bar.arrive %0, %1;" :: "r"(id), "r"(n) : "memory"); }
__device__ __forceinline__ void cluster_sync() { asm volatile("barrier.cluster.arrive.aligned;\nbarrier.cluster.wait.aligned;" ::: "memory"); }
__device__ __forceinline__ void pdl_wait() { asm volatile("griddepcontrol.wait;" ::: "memory"); }
__device__ __forceinline__ void pdl_launch() { asm volatile("griddepcontrol.launch_dependents;" ::: "memory"); }
__device__ __forceinline__ float ex2(float x) { float y; asm("ex2.approx.ftz.f32 %0, %1;" : "=f"(y) : "f"(x)); return y; }
__device__ __forceinline__ uint32_t pack_bf16(float lo, float hi) { uint32_t r; asm("cvt.rn.bf16x2.f32 %0, %1, %2;" : "=r"(r) : "f"(hi), "f"(lo)); return r; }
__device__ __forceinline__ float bf_lo(uint32_t u) { return __uint_as_float(u << 16); }
__device__ __forceinline__ float bf_hi(uint32_t u) { return __uint_as_float(u & 0xffff0000u); }
__device__ __forceinline__ float bf_round(float x) { return __bfloat162float(__float2bfloat16_rn(x)); }
__device__ __forceinline__ float tanh_fast(float x) { float y; asm("tanh.approx.f32 %0, %1;" : "=f"(y) : "f"(x)); return y; }
__device__ __forceinline__ float gelu_tanh(float x) {
  float u = x * (0.7978845608028654f + 0.035677408136300125f * x * x);
  float hx = 0.5f * x;
  return fmaf(hx, tanh_fast(u), hx);
}
__device__ __forceinline__ float warp_sum(float v) {
#pragma unroll
  for (int o = 16; o > 0; o >>= 1) v += __shfl_xor_sync(0xffffffffu, v, o);
  return v;
}
__device__ __forceinline__ void quad_transpose(uint32_t& v0, uint32_t& v1, uint32_t& v2, uint32_t& v3, int lane) {
  const bool b0 = lane & 1, b1 = lane & 2;
  uint32_t s0 = b0 ? v0 : v1, s1 = b0 ? v2 : v3;
  s0 = __shfl_xor_sync(0xffffffffu, s0, 1); s1 = __shfl_xor_sync(0xffffffffu, s1, 1);
  if (b0) { v0 = s0; v2 = s1; } else { v1 = s0; v3 = s1; }
  uint32_t t0 = b1 ? v0 : v2, t1 = b1 ? v1 : v3;
  t0 = __shfl_xor_sync(0xffffffffu, t0, 2); t1 = __shfl_xor_sync(0xffffffffu, t1, 2);
  if (b1) { v0 = t0; v1 = t1; } else { v2 = t0; v3 = t1; }
}

#define TG(i)
#define TX(i)
#define TXC(i)
#define TSA(item, i)
#define TL_ENTRY(k)
#define TL_WAITED(k)
#define TL_END(k)
#define TS(item, i)
template<int TB> __device__ __forceinline__ void wgmma_rs_n64(float (&d)[32], uint32_t a0, uint32_t a1, uint32_t a2, uint32_t a3, uint64_t db, int scale_d) {
  asm volatile("{\n.reg .pred p;\nsetp.ne.b32 p, %37, 0;\n"
    "wgmma.mma_async.sync.aligned.m64n64k16.f32.bf16.bf16 {%0, %1, %2, %3, %4, %5, %6, %7, %8, %9, %10, %11, %12, %13, %14, %15, %16, %17, %18, %19, %20, %21, %22, %23, %24, %25, %26, %27, %28, %29, %30, %31}, {%32, %33, %34, %35}, %36, p, 1, 1, %38;\n}\n"
    : "+f"(d[0]), "+f"(d[1]), "+f"(d[2]), "+f"(d[3]), "+f"(d[4]), "+f"(d[5]), "+f"(d[6]), "+f"(d[7]), "+f"(d[8]), "+f"(d[9]), "+f"(d[10]), "+f"(d[11]), "+f"(d[12]), "+f"(d[13]), "+f"(d[14]), "+f"(d[15]), "+f"(d[16]), "+f"(d[17]), "+f"(d[18]), "+f"(d[19]), "+f"(d[20]), "+f"(d[21]), "+f"(d[22]), "+f"(d[23]), "+f"(d[24]), "+f"(d[25]), "+f"(d[26]), "+f"(d[27]), "+f"(d[28]), "+f"(d[29]), "+f"(d[30]), "+f"(d[31])
    : "r"(a0), "r"(a1), "r"(a2), "r"(a3), "l"(db), "r"(scale_d), "n"(TB));
}
template<int TB> __device__ __forceinline__ void wgmma_rs_n192(float (&d)[96], uint32_t a0, uint32_t a1, uint32_t a2, uint32_t a3, uint64_t db, int scale_d) {
  asm volatile("{\n.reg .pred p;\nsetp.ne.b32 p, %101, 0;\n"
    "wgmma.mma_async.sync.aligned.m64n192k16.f32.bf16.bf16 {%0, %1, %2, %3, %4, %5, %6, %7, %8, %9, %10, %11, %12, %13, %14, %15, %16, %17, %18, %19, %20, %21, %22, %23, %24, %25, %26, %27, %28, %29, %30, %31, %32, %33, %34, %35, %36, %37, %38, %39, %40, %41, %42, %43, %44, %45, %46, %47, %48, %49, %50, %51, %52, %53, %54, %55, %56, %57, %58, %59, %60, %61, %62, %63, %64, %65, %66, %67, %68, %69, %70, %71, %72, %73, %74, %75, %76, %77, %78, %79, %80, %81, %82, %83, %84, %85, %86, %87, %88, %89, %90, %91, %92, %93, %94, %95}, {%96, %97, %98, %99}, %100, p, 1, 1, %102;\n}\n"
    : "+f"(d[0]), "+f"(d[1]), "+f"(d[2]), "+f"(d[3]), "+f"(d[4]), "+f"(d[5]), "+f"(d[6]), "+f"(d[7]), "+f"(d[8]), "+f"(d[9]), "+f"(d[10]), "+f"(d[11]), "+f"(d[12]), "+f"(d[13]), "+f"(d[14]), "+f"(d[15]), "+f"(d[16]), "+f"(d[17]), "+f"(d[18]), "+f"(d[19]), "+f"(d[20]), "+f"(d[21]), "+f"(d[22]), "+f"(d[23]), "+f"(d[24]), "+f"(d[25]), "+f"(d[26]), "+f"(d[27]), "+f"(d[28]), "+f"(d[29]), "+f"(d[30]), "+f"(d[31]), "+f"(d[32]), "+f"(d[33]), "+f"(d[34]), "+f"(d[35]), "+f"(d[36]), "+f"(d[37]), "+f"(d[38]), "+f"(d[39]), "+f"(d[40]), "+f"(d[41]), "+f"(d[42]), "+f"(d[43]), "+f"(d[44]), "+f"(d[45]), "+f"(d[46]), "+f"(d[47]), "+f"(d[48]), "+f"(d[49]), "+f"(d[50]), "+f"(d[51]), "+f"(d[52]), "+f"(d[53]), "+f"(d[54]), "+f"(d[55]), "+f"(d[56]), "+f"(d[57]), "+f"(d[58]), "+f"(d[59]), "+f"(d[60]), "+f"(d[61]), "+f"(d[62]), "+f"(d[63]), "+f"(d[64]), "+f"(d[65]), "+f"(d[66]), "+f"(d[67]), "+f"(d[68]), "+f"(d[69]), "+f"(d[70]), "+f"(d[71]), "+f"(d[72]), "+f"(d[73]), "+f"(d[74]), "+f"(d[75]), "+f"(d[76]), "+f"(d[77]), "+f"(d[78]), "+f"(d[79]), "+f"(d[80]), "+f"(d[81]), "+f"(d[82]), "+f"(d[83]), "+f"(d[84]), "+f"(d[85]), "+f"(d[86]), "+f"(d[87]), "+f"(d[88]), "+f"(d[89]), "+f"(d[90]), "+f"(d[91]), "+f"(d[92]), "+f"(d[93]), "+f"(d[94]), "+f"(d[95])
    : "r"(a0), "r"(a1), "r"(a2), "r"(a3), "l"(db), "r"(scale_d), "n"(TB));
}
template<int TB> __device__ __forceinline__ void wgmma_ss_n128(float (&d)[64], uint64_t da, uint64_t db, int scale_d) {
  asm volatile("{\n.reg .pred p;\nsetp.ne.b32 p, %66, 0;\n"
    "wgmma.mma_async.sync.aligned.m64n128k16.f32.bf16.bf16 {%0, %1, %2, %3, %4, %5, %6, %7, %8, %9, %10, %11, %12, %13, %14, %15, %16, %17, %18, %19, %20, %21, %22, %23, %24, %25, %26, %27, %28, %29, %30, %31, %32, %33, %34, %35, %36, %37, %38, %39, %40, %41, %42, %43, %44, %45, %46, %47, %48, %49, %50, %51, %52, %53, %54, %55, %56, %57, %58, %59, %60, %61, %62, %63}, %64, %65, p, 1, 1, 0, %67;\n}\n"
    : "+f"(d[0]), "+f"(d[1]), "+f"(d[2]), "+f"(d[3]), "+f"(d[4]), "+f"(d[5]), "+f"(d[6]), "+f"(d[7]), "+f"(d[8]), "+f"(d[9]), "+f"(d[10]), "+f"(d[11]), "+f"(d[12]), "+f"(d[13]), "+f"(d[14]), "+f"(d[15]), "+f"(d[16]), "+f"(d[17]), "+f"(d[18]), "+f"(d[19]), "+f"(d[20]), "+f"(d[21]), "+f"(d[22]), "+f"(d[23]), "+f"(d[24]), "+f"(d[25]), "+f"(d[26]), "+f"(d[27]), "+f"(d[28]), "+f"(d[29]), "+f"(d[30]), "+f"(d[31]), "+f"(d[32]), "+f"(d[33]), "+f"(d[34]), "+f"(d[35]), "+f"(d[36]), "+f"(d[37]), "+f"(d[38]), "+f"(d[39]), "+f"(d[40]), "+f"(d[41]), "+f"(d[42]), "+f"(d[43]), "+f"(d[44]), "+f"(d[45]), "+f"(d[46]), "+f"(d[47]), "+f"(d[48]), "+f"(d[49]), "+f"(d[50]), "+f"(d[51]), "+f"(d[52]), "+f"(d[53]), "+f"(d[54]), "+f"(d[55]), "+f"(d[56]), "+f"(d[57]), "+f"(d[58]), "+f"(d[59]), "+f"(d[60]), "+f"(d[61]), "+f"(d[62]), "+f"(d[63])
    : "l"(da), "l"(db), "r"(scale_d), "n"(TB));
}
template<int TB> __device__ __forceinline__ void wgmma_ss_n192(float (&d)[96], uint64_t da, uint64_t db, int scale_d) {
  asm volatile("{\n.reg .pred p;\nsetp.ne.b32 p, %98, 0;\n"
    "wgmma.mma_async.sync.aligned.m64n192k16.f32.bf16.bf16 {%0, %1, %2, %3, %4, %5, %6, %7, %8, %9, %10, %11, %12, %13, %14, %15, %16, %17, %18, %19, %20, %21, %22, %23, %24, %25, %26, %27, %28, %29, %30, %31, %32, %33, %34, %35, %36, %37, %38, %39, %40, %41, %42, %43, %44, %45, %46, %47, %48, %49, %50, %51, %52, %53, %54, %55, %56, %57, %58, %59, %60, %61, %62, %63, %64, %65, %66, %67, %68, %69, %70, %71, %72, %73, %74, %75, %76, %77, %78, %79, %80, %81, %82, %83, %84, %85, %86, %87, %88, %89, %90, %91, %92, %93, %94, %95}, %96, %97, p, 1, 1, 0, %99;\n}\n"
    : "+f"(d[0]), "+f"(d[1]), "+f"(d[2]), "+f"(d[3]), "+f"(d[4]), "+f"(d[5]), "+f"(d[6]), "+f"(d[7]), "+f"(d[8]), "+f"(d[9]), "+f"(d[10]), "+f"(d[11]), "+f"(d[12]), "+f"(d[13]), "+f"(d[14]), "+f"(d[15]), "+f"(d[16]), "+f"(d[17]), "+f"(d[18]), "+f"(d[19]), "+f"(d[20]), "+f"(d[21]), "+f"(d[22]), "+f"(d[23]), "+f"(d[24]), "+f"(d[25]), "+f"(d[26]), "+f"(d[27]), "+f"(d[28]), "+f"(d[29]), "+f"(d[30]), "+f"(d[31]), "+f"(d[32]), "+f"(d[33]), "+f"(d[34]), "+f"(d[35]), "+f"(d[36]), "+f"(d[37]), "+f"(d[38]), "+f"(d[39]), "+f"(d[40]), "+f"(d[41]), "+f"(d[42]), "+f"(d[43]), "+f"(d[44]), "+f"(d[45]), "+f"(d[46]), "+f"(d[47]), "+f"(d[48]), "+f"(d[49]), "+f"(d[50]), "+f"(d[51]), "+f"(d[52]), "+f"(d[53]), "+f"(d[54]), "+f"(d[55]), "+f"(d[56]), "+f"(d[57]), "+f"(d[58]), "+f"(d[59]), "+f"(d[60]), "+f"(d[61]), "+f"(d[62]), "+f"(d[63]), "+f"(d[64]), "+f"(d[65]), "+f"(d[66]), "+f"(d[67]), "+f"(d[68]), "+f"(d[69]), "+f"(d[70]), "+f"(d[71]), "+f"(d[72]), "+f"(d[73]), "+f"(d[74]), "+f"(d[75]), "+f"(d[76]), "+f"(d[77]), "+f"(d[78]), "+f"(d[79]), "+f"(d[80]), "+f"(d[81]), "+f"(d[82]), "+f"(d[83]), "+f"(d[84]), "+f"(d[85]), "+f"(d[86]), "+f"(d[87]), "+f"(d[88]), "+f"(d[89]), "+f"(d[90]), "+f"(d[91]), "+f"(d[92]), "+f"(d[93]), "+f"(d[94]), "+f"(d[95])
    : "l"(da), "l"(db), "r"(scale_d), "n"(TB));
}
template<int TB> __device__ __forceinline__ void wgmma_ss_n80(float (&d)[40], uint64_t da, uint64_t db, int scale_d) {
  asm volatile("{\n.reg .pred p;\nsetp.ne.b32 p, %42, 0;\n"
    "wgmma.mma_async.sync.aligned.m64n80k16.f32.bf16.bf16 {%0, %1, %2, %3, %4, %5, %6, %7, %8, %9, %10, %11, %12, %13, %14, %15, %16, %17, %18, %19, %20, %21, %22, %23, %24, %25, %26, %27, %28, %29, %30, %31, %32, %33, %34, %35, %36, %37, %38, %39}, %40, %41, p, 1, 1, 0, %43;\n}\n"
    : "+f"(d[0]), "+f"(d[1]), "+f"(d[2]), "+f"(d[3]), "+f"(d[4]), "+f"(d[5]), "+f"(d[6]), "+f"(d[7]), "+f"(d[8]), "+f"(d[9]), "+f"(d[10]), "+f"(d[11]), "+f"(d[12]), "+f"(d[13]), "+f"(d[14]), "+f"(d[15]), "+f"(d[16]), "+f"(d[17]), "+f"(d[18]), "+f"(d[19]), "+f"(d[20]), "+f"(d[21]), "+f"(d[22]), "+f"(d[23]), "+f"(d[24]), "+f"(d[25]), "+f"(d[26]), "+f"(d[27]), "+f"(d[28]), "+f"(d[29]), "+f"(d[30]), "+f"(d[31]), "+f"(d[32]), "+f"(d[33]), "+f"(d[34]), "+f"(d[35]), "+f"(d[36]), "+f"(d[37]), "+f"(d[38]), "+f"(d[39])
    : "l"(da), "l"(db), "r"(scale_d), "n"(TB));
}

__device__ __align__(128) float g_mod[6 * D_];
__device__ __forceinline__ float modv(float v) { return bf_round(v); }
__device__ __forceinline__ float modv1(float v) { return bf_round(1.f + bf_round(v)); }
__device__ __align__(1024) bf16 g_h[S_ * D_];
__device__ __align__(1024) bf16 g_o[S_ * HD_];
__device__ __align__(1024) bf16 g_xch[16 * 2 * 4 * 4 * 128 * 80];
__device__ __align__(1024) bf16 g_w1t[D_ * D_];
__device__ __align__(1024) bf16 g_w2t[D_ * D_];
__device__ __align__(1024) bf16 g_w4t[D_ * F_];
__device__ __align__(32) float g_st1[S_ * 8];
__device__ __align__(32) float g_st2[S_ * 2];
__device__ __align__(32) float g_vec[3 * D_ + F_ + 8];
__device__ unsigned g_flag[1024];
enum { F_XCH = 0, F_XA = 256, F_US = 272, F_X1 = 288, F_G = 304, F_PREP = 320, F_DONE = 323, F_H = 336, F_MOD = 384, F_MOD2 = 416, F_O = 512 };
__device__ __align__(1024) bf16 g_xa[S_ * D_];
__device__ __align__(1024) bf16 g_us[(S_ + 4) * D_];
__device__ __align__(1024) bf16 g_x1[S_ * D_];
__device__ __align__(1024) bf16 g_g[S_ * F_];

__device__ __forceinline__ void row_stats(const float (&v)[20], float& mean, float& rstd) {
  float s = 0.f;
#pragma unroll
  for (int i = 0; i < 20; i++) s += v[i];
  mean = warp_sum(s) * (1.f / D_);
  float q = 0.f;
#pragma unroll
  for (int i = 0; i < 20; i++) { float d = v[i] - mean; q = fmaf(d, d, q); }
  rstd = rsqrtf(warp_sum(q) * (1.f / D_) + LN_EPS);
}
__device__ __forceinline__ void load_row_bf16(const bf16* p, int lane, float (&v)[20]) {
#pragma unroll
  for (int i = 0; i < 5; i++) {
    uint2 u = *reinterpret_cast<const uint2*>(p + (lane + 32 * i) * 4);
    v[4 * i] = bf_lo(u.x); v[4 * i + 1] = bf_hi(u.x); v[4 * i + 2] = bf_lo(u.y); v[4 * i + 3] = bf_hi(u.y);
  }
}
__device__ __forceinline__ void store_row_bf16(bf16* p, int lane, const float (&v)[20]) {
#pragma unroll
  for (int i = 0; i < 5; i++) {
    uint2 u; u.x = pack_bf16(v[4 * i], v[4 * i + 1]); u.y = pack_bf16(v[4 * i + 2], v[4 * i + 3]);
    *reinterpret_cast<uint2*>(p + (lane + 32 * i) * 4) = u;
  }
}
__device__ __forceinline__ void load_row_f32(const float* p, int lane, float (&v)[20]) {
#pragma unroll
  for (int i = 0; i < 5; i++) {
    float4 u = *reinterpret_cast<const float4*>(p + (lane + 32 * i) * 4);
    v[4 * i] = u.x; v[4 * i + 1] = u.y; v[4 * i + 2] = u.z; v[4 * i + 3] = u.w;
  }
}

constexpr int PREP_JOBS = 200 + 200 + 480 + 480;
struct PrepW { const bf16 *w1, *w2, *w3, *w4, *c, *wmod; };
__device__ __forceinline__ void prep_warp(const PrepW& pw, bf16 (*tile)[72], int lane) {
#pragma unroll 1
  for (int job = blockIdx.x; job < PREP_JOBS; job += gridDim.x) {
    const bf16* src; bf16* dst; int ld = D_, ldd = D_, kt, nt, kind = 1;
    if (job < 200) { src = pw.w1; dst = g_w1t; kt = job / 10; nt = job % 10; kind = 0; }
    else if (job < 400) { src = pw.w2; dst = g_w2t; kt = (job - 200) / 10; nt = (job - 200) % 10; }
    else if (job < 880) { src = pw.w4; dst = g_w4t; ldd = F_; kt = (job - 400) / 10; nt = (job - 400) % 10; }
    else { src = pw.w3; dst = nullptr; ld = F_; kt = (job - 880) / 24; nt = (job - 880) % 24; kind = 2; }
    src += (size_t)(kt * 32 + (lane >> 3)) * ld + nt * 64 + (lane & 7) * 8;
    __syncwarp();
#pragma unroll
    for (int h = 0; h < 2; h++) {
      uint4 v[4];
#pragma unroll
      for (int i = 0; i < 4; i++) v[i] = __ldg(reinterpret_cast<const uint4*>(src + (size_t)(h * 16 + i * 4) * ld));
#pragma unroll
      for (int i = 0; i < 4; i++) *reinterpret_cast<uint4*>(&tile[h * 16 + i * 4 + (lane >> 3)][(lane & 7) * 8]) = v[i];
    }
    __syncwarp();
    const float* pa = g_mod + 4 * D_ + kt * 32;
    const float* pb = g_mod + 3 * D_ + kt * 32;
#pragma unroll 1
    for (int h = 0; h < 2; h++) {
      const int n = lane + 32 * h;
      float sa = 0.f, sb = 0.f, sc = 0.f;
#pragma unroll 1
      for (int c = 0; c < 4; c++) {
        uint32_t u[4];
#pragma unroll
        for (int e = 0; e < 4; e++) {
          const int k = c * 8 + 2 * e;
          float lo = __bfloat162float(tile[k][n]), hi = __bfloat162float(tile[k + 1][n]);
          sc += lo + hi;
          if (kind == 0) {
            const float2 a = __ldcg(reinterpret_cast<const float2*>(pa + k)), b = __ldcg(reinterpret_cast<const float2*>(pb + k));
            sb = fmaf(modv(b.x), lo, fmaf(modv(b.y), hi, sb));
            lo *= modv1(a.x); hi *= modv1(a.y);
          }
          u[e] = pack_bf16(lo, hi);
          sa += bf_lo(u[e]) + bf_hi(u[e]);
        }
        if (kind != 2) *reinterpret_cast<uint4*>(dst + (size_t)(nt * 64 + n) * ldd + kt * 32 + c * 8) = make_uint4(u[0], u[1], u[2], u[3]);
      }
      if (kind == 0) { atomicAdd(&g_vec[nt * 64 + n], sa); atomicAdd(&g_vec[D_ + nt * 64 + n], sb); atomicAdd(&g_vec[2 * D_ + nt * 64 + n], sc); }
      else if (kind == 2) atomicAdd(&g_vec[3 * D_ + nt * 64 + n], sc);
    }
  }
  __syncwarp();
  if (lane == 0) {
    asm volatile("fence.acq_rel.gpu;" ::: "memory");
    asm volatile("red.relaxed.gpu.global.add.u32 [%0], 1;" :: "l"(g_flag + F_PREP) : "memory");
  }
}

constexpr int A_NSLOT = 9;
constexpr int A_SLOT = 24576;
constexpr int A_NKV = S_ / 64;
constexpr int PREP_CTAS = 128;

struct Ring {
  uint32_t slot, phase;
  __device__ __forceinline__ void adv(int n) { if (++slot == (uint32_t)n) { slot = 0; phase ^= 1; } }
};
constexpr int T_PAR = A_NSLOT * A_SLOT + 384;
constexpr int T_PREP = T_PAR + 3712;
constexpr int T_SMEM = T_PREP + 32 * 72 * 2 + 1024;
enum { P_OGA = 0, P_OA = 80, P_OB = 160, P_VA = 240, P_VB = 320, P_VC = 400, P_A2 = 480, P_B2 = 560, P_GB = 640, P_CS3 = 720, P_SC = 912 };

__device__ __forceinline__ void flag_wait(const unsigned* p, unsigned target) {
  asm volatile(
      "{\n.reg .pred p;\n.reg .u32 n, v;\n"
      "mov.u32 n, 0;\n"
      "SPIN:\n"
      "ld.relaxed.gpu.global.u32 v, [%0];\n"
      "setp.ge.u32 p, v, %1;\n"
      "@p bra DONE;\n"
      "add.u32 n, n, 1;\n"
      "setp.gt.u32 p, n, 4194304;\n"
      "@p trap;\n"
      "bra SPIN;\n"
      "DONE:\n}\n" :: "l"(p), "r"(target) : "memory");
}
__device__ __forceinline__ void fence_async_global() { asm volatile("fence.proxy.async.global;" ::: "memory"); }
__device__ __forceinline__ float lds_f(uint32_t a) { float v; asm volatile("ld.shared.f32 %0, [%1];" : "=f"(v) : "r"(a)); return v; }
__device__ __forceinline__ float2 lds_f2(uint32_t a) { float2 v; asm volatile("ld.shared.v2.f32 {%0, %1}, [%2];" : "=f"(v.x), "=f"(v.y) : "r"(a)); return v; }
__device__ __forceinline__ uint4 ldcg4(const void* p) { return __ldcg(reinterpret_cast<const uint4*>(p)); }

__device__ __forceinline__ void sts_f2(uint32_t a, float x, float y) { asm volatile("st.shared.v2.f32 [%0], {%1, %2};" :: "r"(a), "f"(x), "f"(y) : "memory"); }
__device__ __forceinline__ void sts_u4(uint32_t a, uint4 v) { asm volatile("st.shared.v4.u32 [%0], {%1, %2, %3, %4};" :: "r"(a), "r"(v.x), "r"(v.y), "r"(v.z), "r"(v.w) : "memory"); }
__device__ __forceinline__ void sts_u1(uint32_t a, uint32_t v) { asm volatile("st.shared.u32 [%0], %1;" :: "r"(a), "r"(v) : "memory"); }
__device__ __forceinline__ void fence_async_smem() { asm volatile("fence.proxy.async.shared::cta;" ::: "memory"); }
__device__ __forceinline__ void bulk_store(void* dst, uint32_t src, uint32_t bytes) {
  asm volatile("cp.async.bulk.global.shared::cta.bulk_group [%0], [%1], %2;" :: "l"(dst), "r"(src), "r"(bytes) : "memory");
}
__device__ __forceinline__ void bulk_red_f32(void* dst, uint32_t src, uint32_t bytes) {
  asm volatile("cp.reduce.async.bulk.global.shared::cta.bulk_group.add.f32 [%0], [%1], %2;" :: "l"(dst), "r"(src), "r"(bytes) : "memory");
}
__device__ __forceinline__ void tma_store2d(const CUtensorMap* m, uint32_t src, int c0, int c1) {
  asm volatile("cp.async.bulk.tensor.2d.global.shared::cta.bulk_group [%0, {%2, %3}], [%1];" :: "l"(m), "r"(src), "r"(c0), "r"(c1) : "memory");
}
__device__ __forceinline__ void bulk_done() { asm volatile("cp.async.bulk.commit_group;\ncp.async.bulk.wait_group 0;" ::: "memory"); }
__device__ __forceinline__ void flag_add(unsigned* f) { asm volatile("red.relaxed.gpu.global.add.u32 [%0], 1;" :: "l"(f) : "memory"); }
__device__ __forceinline__ float4 lds_f4(uint32_t a) { return *reinterpret_cast<const float4*>(__cvta_shared_to_generic(a)); }
__device__ __forceinline__ uint4 lds_u4(uint32_t a) { return *reinterpret_cast<const uint4*>(__cvta_shared_to_generic(a)); }
__device__ __forceinline__ void lds8(uint32_t a, float (&v)[8]) {
  const float4 p = lds_f4(a), q = lds_f4(a + 16);
  v[0] = p.x; v[1] = p.y; v[2] = p.z; v[3] = p.w; v[4] = q.x; v[5] = q.y; v[6] = q.z; v[7] = q.w;
}
__device__ __forceinline__ void lds8_bf(uint32_t a, float (&v)[8]) {
  const uint4 u = lds_u4(a);
  v[0] = bf_lo(u.x); v[1] = bf_hi(u.x); v[2] = bf_lo(u.y); v[3] = bf_hi(u.y); v[4] = bf_lo(u.z); v[5] = bf_hi(u.z); v[6] = bf_lo(u.w); v[7] = bf_hi(u.w);
}
__device__ __forceinline__ uint4 pack8(const float (&v)[8]) {
  return make_uint4(pack_bf16(v[0], v[1]), pack_bf16(v[2], v[3]), pack_bf16(v[4], v[5]), pack_bf16(v[6], v[7]));
}
__device__ __forceinline__ void mbar_wait_c(uint32_t a, uint32_t ph) {
  asm volatile("{\n.reg .pred p;\nSPIN:\nmbarrier.try_wait.parity.shared::cta.b64 p, [%0], %1;\n@!p bra SPIN;\n}\n" :: "r"(a), "r"(ph) : "memory");
}
constexpr int ST_P = 80;
constexpr int E_TILE = 128 * 80 * 2;

struct Maps { CUtensorMap h, wq, k, v, o, wo3, wo2, xa, w1t, us, w2t, x1, w3, g, w4t, ex, exa, ex1, sxa, sus, sx1, sout; };
struct PfList { const uint8_t* p[6]; };

constexpr int M_AOFF = 102400, M_NA = 7;

__global__ void __cluster_dims__(2, 1, 1) __launch_bounds__(384, 1)
fused_kernel(const __grid_constant__ Maps tm, const __grid_constant__ PfList pf, const __grid_constant__ PrepW pw, const bf16* __restrict__ x, bf16* __restrict__ out) {
  extern __shared__ uint8_t smem_raw[];
  const uint32_t sb = (smem_u32(smem_raw) + 1023) & ~1023u;
  TL_ENTRY(2);
  const uint32_t bar_full = sb + A_NSLOT * A_SLOT;
  const uint32_t bar_empty = bar_full + 8 * A_NSLOT;
  const uint32_t bar_sig = bar_empty + 8 * A_NSLOT;
  const uint32_t mb_full = bar_sig + 16;
  const uint32_t mb_empty = mb_full + 96;
  const uint32_t par = sb + T_PAR;
  float* parf = reinterpret_cast<float*>(smem_raw + (par - smem_u32(smem_raw)));
  uint32_t rank;
  asm volatile("mov.u32 %0, %%cluster_ctarank;" : "=r"(rank));
  const int cid = blockIdx.x >> 1;
  const int wid = __shfl_sync(0xffffffffu, threadIdx.x >> 5, 0);
  const int wg = wid >> 2;
  const int qtile = (cid & 7) * 2 + rank, hbase = cid >> 3;
  const int o_qt = qtile, o_nh = (cid >> 3) & 1, o_ks = cid >> 4;
  const int o_col = o_nh * 320 + o_ks * 80;
  const int qt = cid >> 2, js = (cid & 3) * 2 + rank;
  if (threadIdx.x == 0) {
    for (int i = 0; i < A_NSLOT; i++) { mbar_init(bar_full + 8 * i, 1); mbar_init(bar_empty + 8 * i, 16); }
    mbar_init(bar_sig, 4); mbar_init(bar_sig + 8, 4);
    for (int i = 0; i < 12; i++) { mbar_init(mb_full + 8 * i, 1); mbar_init(mb_empty + 8 * i, i < 5 ? 8 : 16); }
    asm volatile("fence.mbarrier_init.release.cluster;" ::: "memory");
    prefetch_tmap(&tm.h); prefetch_tmap(&tm.wq); prefetch_tmap(&tm.k); prefetch_tmap(&tm.v);
  }
  __syncthreads();
  cluster_sync();

  if (wg == 0) {
    asm volatile("setmaxnreg.dec.sync.aligned.u32 40;");
    if (wid == 0) {
      Ring r{0, 1};
#define P_ACQ(bytes_) do { mbar_wait(bar_empty + 8 * r.slot, r.phase); mbar_expect_e(bar_full + 8 * r.slot, bytes_); } while (0)
#define P_DST (sb + r.slot * A_SLOT)
#define P_BAR (bar_full + 8 * r.slot)
      uint64_t pol_ef;
      asm volatile("createpolicy.fractional.L2::evict_first.b64 %0, 1.0;" : "=l"(pol_ef));
      if (qtile < 10) l2_prefetch_t3d(&tm.wq, 0, qtile * 64, hbase * 3);
      else l2_prefetch_t3d((qtile & 1) ? &tm.v : &tm.k, 0, hbase * S_ + ((qtile - 10) >> 1) * 64, 0);
      flag_wait(g_flag + F_H + (blockIdx.x >> 3), 8);
      flag_wait(g_flag + F_H + qtile, 8);
      fence_async_global();
      TL_WAITED(2);
#pragma unroll 1
      for (int item = 0; item < 4; item++) {
        const int head = hbase + 8 * item;
#pragma unroll 1
        for (int kb = 0; kb < 10; kb++) {
          P_ACQ(16384);
          tma2d(P_DST, &tm.h, P_BAR, kb * 64, qtile * 128);
          r.adv(A_NSLOT);
          P_ACQ(A_SLOT);
          if ((uint32_t)(kb & 1) == rank) tma3d_mc_hint(P_DST, &tm.wq, P_BAR, 0, kb * 64, head * 3, 3, pol_ef);
          r.adv(A_NSLOT);
        }
#pragma unroll 1
        for (int j = 0; j <= A_NKV; j++) {
          if (j < A_NKV) {
            P_ACQ(A_SLOT);
            if (rank == 0) tma3d_mc_hint(P_DST, &tm.k, P_BAR, 0, head * S_ + j * 64, 0, 3, pol_ef);
            r.adv(A_NSLOT);
          }
          if (j > 0) {
            P_ACQ(A_SLOT);
            if (rank == 1) tma3d_mc_hint(P_DST, &tm.v, P_BAR, 0, head * S_ + (j - 1) * 64, 0, 3, pol_ef);
            r.adv(A_NSLOT);
          }
          if (item < 3 && j == 16 && qtile < 10) l2_prefetch_t3d(&tm.wq, 0, qtile * 64, (head + 8) * 3);
          if (item == 3 && (j & 3) == 0) {
            const int c = (j >> 2) * 128 + blockIdx.x;
            if (c < 980) {
              const int li = c < 480 ? 0 : c < 600 ? 1 : c < 720 ? 2 : c < 880 ? 3 : c < 930 ? 4 : 5;
              const int c0 = c < 480 ? 0 : c < 600 ? 480 : c < 720 ? 600 : c < 880 ? 720 : c < 930 ? 880 : 930;
              l2_prefetch16k(pf.p[li] + (size_t)(c - c0) * 16384);
            }
          }
          if (item == 3) {
            if (j >= 6 && j < 24) {
              const int kb = j - 6;
              l2_prefetch_t2d(&tm.o, ((kb / 6) * 8 + 2 * o_ks + (kb % 6) / 3) * DH_ + (kb % 3) * 64, o_qt * 128);
            }
            if (j >= 24 && j < 30) flag_wait(g_flag + F_O + o_qt * 32 + ((j - 24) >> 1) * 8 + 2 * o_ks + (j & 1), 2);
            if (j == 0 && threadIdx.x == 0) {
              prefetch_tmap(&tm.o); prefetch_tmap(&tm.wo3); prefetch_tmap(&tm.wo2); prefetch_tmap(&tm.xa); prefetch_tmap(&tm.w1t); prefetch_tmap(&tm.us);
              prefetch_tmap(&tm.w2t); prefetch_tmap(&tm.x1); prefetch_tmap(&tm.w3); prefetch_tmap(&tm.g); prefetch_tmap(&tm.w4t);
              prefetch_tmap(&tm.ex); prefetch_tmap(&tm.exa); prefetch_tmap(&tm.ex1);
              prefetch_tmap(&tm.sxa); prefetch_tmap(&tm.sus); prefetch_tmap(&tm.sx1); prefetch_tmap(&tm.sout);
            }
          }
        }
      }
#pragma unroll 1
      for (int kb = 0; kb < 24; kb++) {
        const int head = (kb / 6) * 8 + 2 * o_ks + (kb % 6) / 3;
        const int kcol = head * DH_ + (kb % 3) * 64;
        P_ACQ(24576);
        if (rank == 0) tma3d_mc(P_DST, &tm.wo3, P_BAR, 0, kcol, o_nh * 5, 3);
        r.adv(A_NSLOT);
        P_ACQ(16384);
        if (rank == 1) tma3d_mc(P_DST, &tm.wo2, P_BAR, 0, kcol, o_nh * 5 + 3, 3);
        r.adv(A_NSLOT);
        if (kb == 18 || kb == 21) flag_wait(g_flag + F_O + o_qt * 32 + head, 2);
        if (kb % 3 == 0) fence_async_global();
        P_ACQ(16384);
        tma2d(P_DST, &tm.o, P_BAR, kcol, o_qt * 128);
        r.adv(A_NSLOT);
      }
      P_ACQ(E_TILE);
      tma2d(P_DST, &tm.ex, P_BAR, o_col, o_qt * 128);
      r.adv(A_NSLOT);
      flag_wait(g_flag + F_XCH + (o_qt * 2 + o_nh) * 4 + o_ks, 6);
      fence_async_global();
#pragma unroll 1
      for (int i = 0; i < 3; i++) {
        P_ACQ(E_TILE);
        bulk_load(P_DST, g_xch + (size_t)((((o_qt * 2 + o_nh) * 4 + o_ks) * 4) + ((o_ks + 1 + i) & 3)) * (E_TILE / 2), E_TILE, P_BAR);
        r.adv(A_NSLOT);
      }
      flag_wait(g_flag + F_PREP, PREP_CTAS);
      fence_async_global();
#pragma unroll 1
      for (int i = 0; i < A_NSLOT; i++) { mbar_wait(bar_empty + 8 * r.slot, r.phase); r.adv(A_NSLOT); }
      Ring ra{0, 1};
      uint32_t bpar = 0x1f;
#pragma unroll 1
      for (int ph = 0; ph < 4; ph++) {
        const CUtensorMap* ma = ph == 0 ? &tm.xa : ph == 1 ? &tm.us : ph == 2 ? &tm.x1 : &tm.g;
        const CUtensorMap* mb = ph == 0 ? &tm.w1t : ph == 1 ? &tm.w2t : ph == 2 ? &tm.w3 : &tm.w4t;
        const int nkb = ph == 3 ? 24 : 10;
        const int nbl = ph == 2 ? 10 : nkb / 2;
        const int nel = ph == 1 ? 1 : ph == 3 ? 2 : 0;
        const uint32_t nbs = ph == 2 ? 4 : 5, bsz = ph == 2 ? 24576 : 20480;
        int bl = 0; uint32_t bs = 0;
#pragma unroll 1
        for (int i = 0; i < 5; i++) mbar_wait(mb_empty + 8 * i, (bpar >> i) & 1);
#define T_LOADB() do { mbar_wait(mb_empty + 8 * bs, (bpar >> bs) & 1); bpar ^= 1u << bs; mbar_expect_e(mb_full + 8 * bs, bsz);    \
                       if (bl < nbl) tma3d(sb + bs * bsz, mb, mb_full + 8 * bs, 0, ph == 2 ? bl * 64 : js * 80, ph == 2 ? js * 3 : bl * 2); \
                       else tma2d(sb + bs * bsz, bl == nbl ? &tm.exa : &tm.ex1, mb_full + 8 * bs, js * 80, qt * 128); \
                       bl++; if (++bs == nbs) bs = 0; } while (0)
#pragma unroll 1
        for (uint32_t i = 0; i < nbs; i++) T_LOADB();
        TX(8 + ph * 4);
        const unsigned* fl = g_flag + F_XA + 16 * ph;
        flag_wait(fl + qt, 16);
        if (ph == 1) { if (qt > 0) flag_wait(fl + qt - 1, 16); if (qt < 15) flag_wait(fl + qt + 1, 16); }
        TX(9 + ph * 4);
        fence_async_global();
#pragma unroll 1
        for (int kb = 0; kb < nkb; kb++) {
          mbar_wait(mb_empty + 40 + 8 * ra.slot, ra.phase);
          mbar_expect_e(mb_full + 40 + 8 * ra.slot, 16384);
          tma2d_mc(sb + M_AOFF + ra.slot * 16384 + rank * 8192, ma, mb_full + 40 + 8 * ra.slot, kb * 64, qt * 128 + (int)rank * 64, 3);
          ra.adv(M_NA);
          while (bl < nbl + nel && (kb == nkb - 1 || kb >= (ph == 2 ? bl + 2 : 2 * bl - 3))) T_LOADB();
        }
      }
    } else if (wid < 3) {
      const int w = wid - 1, lane = threadIdx.x & 31;
#pragma unroll 1
      for (int sig = 0; sig < 4; sig++) {
        mbar_wait(bar_sig + 8 * w, sig & 1);
        if (lane == 0) {
          asm volatile("fence.acq_rel.gpu;" ::: "memory");
          flag_add(g_flag + F_O + qtile * 32 + hbase + 8 * sig);
        }
        __syncwarp();
      }
    } else {
      const int lane = threadIdx.x & 31;
      flag_wait(g_flag + F_MOD2, 128);
      prep_warp(pw, reinterpret_cast<bf16(*)[72]>(smem_raw + (sb + T_PREP - smem_u32(smem_raw))), lane);
      flag_wait(g_flag + F_PREP, PREP_CTAS);
#pragma unroll 1
      for (int i = lane; i < P_SC; i += 32) {
        const int v = i < P_CS3 ? i / 80 : 9, j = i - (i < P_CS3 ? v * 80 : P_CS3);
        const float* src = v == 0 ? g_mod + 2 * D_ + o_col : v == 1 ? g_mod + 4 * D_ + o_col : v == 2 ? g_mod + 3 * D_ + o_col
                         : v < 6 ? g_vec + (v - 3) * D_ + js * 80 : v == 6 ? g_mod + 4 * D_ + js * 80 : v == 7 ? g_mod + 3 * D_ + js * 80
                         : v == 8 ? g_mod + 5 * D_ + js * 80 : g_vec + 3 * D_ + js * 192;
        const float pv = __ldcg(src + j);
        parf[i] = (v == 1 || v == 6) ? modv1(pv) : (v < 3 || (v > 6 && v < 9)) ? modv(pv) : pv;
      }
      float sv[5] = {0.f, 0.f, 0.f, 0.f, 0.f};
#pragma unroll 1
      for (int i = lane; i < D_; i += 32) {
        const float a = modv1(__ldcg(g_mod + 4 * D_ + i)), b = modv(__ldcg(g_mod + 3 * D_ + i));
        sv[0] += a; sv[1] = fmaf(a, a, sv[1]); sv[2] = fmaf(a, b, sv[2]); sv[3] += b; sv[4] = fmaf(b, b, sv[4]);
      }
#pragma unroll 1
      for (int o_ = 16; o_ > 0; o_ >>= 1) {
#pragma unroll
        for (int i = 0; i < 5; i++) sv[i] += __shfl_xor_sync(0xffffffffu, sv[i], o_);
      }
      if (lane == 0) {
#pragma unroll
        for (int i = 0; i < 5; i++) parf[P_SC + i] = sv[i];
      }
      bar_arrive(6, 288);
    }
    __syncwarp();
    cluster_sync();
  } else {
    asm volatile("setmaxnreg.inc.sync.aligned.u32 232;");
    const int w = wg - 1;
    const int lane = threadIdx.x & 31;
    const int warp = wid & 3;
    const int tid = threadIdx.x - 128;
    const uint32_t rel_base = mapa(bar_empty, (lane == 0) ? rank : (rank ^ 1));
    Ring r{0, 0};
#define A_RELEASE(slot_) do { if (lane < 2) mbar_arrive_remote(rel_base + 8 * (slot_)); } while (0)
#define SIGNAL() do { __syncwarp(); if (lane == 0) mbar_arrive(bar_sig + 8 * w); } while (0)
    {
      TG(100);
      const int row = blockIdx.x * 16 + (tid >> 5) * 2;
      const bf16* wp = pw.wmod + (size_t)blockIdx.x * 5 * (6 * D_) + tid * 8;
      uint4 wa[5], wb[5];
      float sv[5];
#pragma unroll
      for (int i = 0; i < 5; i++) {
        wa[i] = __ldg(reinterpret_cast<const uint4*>(wp + i * (6 * D_)));
        wb[i] = __ldg(reinterpret_cast<const uint4*>(wp + i * (6 * D_) + (tid < 224 ? 2048 : 0)));
        sv[i] = __bfloat162float(pw.c[blockIdx.x * 5 + i]);
      }
      float v0[20], v1[20];
      load_row_bf16(x + (size_t)row * D_, lane, v0);
      load_row_bf16(x + (size_t)(row + 1) * D_, lane, v1);
#pragma unroll
      for (int i = 0; i < 5; i++) sv[i] = bf_round(__fdividef(sv[i], 1.f + __expf(-sv[i])));
#pragma unroll 1
      for (int hf = 0; hf < 2; hf++) {
        float acc[8];
#pragma unroll
        for (int j = 0; j < 8; j++) acc[j] = 0.f;
#pragma unroll
        for (int i = 0; i < 5; i++) {
          const uint4 wv = hf ? wb[i] : wa[i];
          acc[0] = fmaf(sv[i], bf_lo(wv.x), acc[0]); acc[1] = fmaf(sv[i], bf_hi(wv.x), acc[1]);
          acc[2] = fmaf(sv[i], bf_lo(wv.y), acc[2]); acc[3] = fmaf(sv[i], bf_hi(wv.y), acc[3]);
          acc[4] = fmaf(sv[i], bf_lo(wv.z), acc[4]); acc[5] = fmaf(sv[i], bf_hi(wv.z), acc[5]);
          acc[6] = fmaf(sv[i], bf_lo(wv.w), acc[6]); acc[7] = fmaf(sv[i], bf_hi(wv.w), acc[7]);
        }
        if (!hf || tid < 224) {
          float* dp = g_mod + hf * 2048 + tid * 8;
          asm volatile("red.global.add.v4.f32 [%0], {%1, %2, %3, %4};" :: "l"(dp), "f"(acc[0]), "f"(acc[1]), "f"(acc[2]), "f"(acc[3]) : "memory");
          asm volatile("red.global.add.v4.f32 [%0], {%1, %2, %3, %4};" :: "l"(dp + 4), "f"(acc[4]), "f"(acc[5]), "f"(acc[6]), "f"(acc[7]) : "memory");
        }
        if (hf) {
          if (tid < 128) g_st1[blockIdx.x * 128 + tid] = 0.f;
          else if (tid < 160) g_st2[blockIdx.x * 32 + tid - 128] = 0.f;
          else if (tid < 187) g_vec[blockIdx.x * 27 + tid - 160] = 0.f;
        }
        bar_sync(5, 256);
        if (tid == hf * 32) {
          asm volatile("fence.acq_rel.gpu;" ::: "memory");
          flag_add(g_flag + (hf ? F_MOD2 : F_MOD));
        }
        __syncwarp();
        TG(101 + hf);
      }
      float m0, r0_, m1, r1_;
      row_stats(v0, m0, r0_);
      row_stats(v1, m1, r1_);
      TG(103);
      if (wid == 11) flag_wait(g_flag + F_MOD, 128);
      bar_sync(5, 256);
      TG(104);
      float4 sa[5], ca[5];
#pragma unroll
      for (int i = 0; i < 5; i++) {
        sa[i] = __ldcg(reinterpret_cast<const float4*>(g_mod + (lane + 32 * i) * 4));
        ca[i] = __ldcg(reinterpret_cast<const float4*>(g_mod + D_ + (lane + 32 * i) * 4));
      }
      bf16* hs = reinterpret_cast<bf16*>(smem_raw + (sb + 8 * A_SLOT - smem_u32(smem_raw))) + (tid >> 5) * 2 * D_;
#pragma unroll
      for (int i = 0; i < 5; i++) {
        const float a0 = modv1(ca[i].x), a1 = modv1(ca[i].y), a2 = modv1(ca[i].z), a3 = modv1(ca[i].w);
        const float b0 = modv(sa[i].x), b1 = modv(sa[i].y), b2 = modv(sa[i].z), b3 = modv(sa[i].w);
        v0[4 * i] = fmaf((v0[4 * i] - m0) * r0_, a0, b0); v0[4 * i + 1] = fmaf((v0[4 * i + 1] - m0) * r0_, a1, b1);
        v0[4 * i + 2] = fmaf((v0[4 * i + 2] - m0) * r0_, a2, b2); v0[4 * i + 3] = fmaf((v0[4 * i + 3] - m0) * r0_, a3, b3);
        v1[4 * i] = fmaf((v1[4 * i] - m1) * r1_, a0, b0); v1[4 * i + 1] = fmaf((v1[4 * i + 1] - m1) * r1_, a1, b1);
        v1[4 * i + 2] = fmaf((v1[4 * i + 2] - m1) * r1_, a2, b2); v1[4 * i + 3] = fmaf((v1[4 * i + 3] - m1) * r1_, a3, b3);
      }
      store_row_bf16(hs, lane, v0);
      store_row_bf16(hs + D_, lane, v1);
      fence_async_smem();
      TG(105);
      bar_sync(5, 256);
      if (tid == 0) {
        bulk_store(g_h + (size_t)blockIdx.x * 16 * D_, sb + 8 * A_SLOT, 16 * D_ * 2);
        bulk_done();
        flag_add(g_flag + F_H + (blockIdx.x >> 3));
      }
      __syncwarp();
      TG(106);
    }
    {
    const float SC = 0.07216878364870322f * 1.4426950408889634f;
    float o[96];
    uint32_t q[48];
    float s[32];
    uint32_t p[16], p2[16];
    if (w == 1) bar_arrive(1, 256);
    bf16* orow = g_o + (size_t)(qtile * 128 + w * 64 + warp * 16 + (lane >> 2)) * HD_ + (hbase - 8) * DH_ + (lane & 3) * 8;
#define O_STORE(g)                                                                                                     \
      {                                                                                                                \
        quad_transpose(q[8 * g], q[8 * g + 2], q[8 * g + 4], q[8 * g + 6], lane);                                      \
        stg128(orow + g * 32, make_uint4(q[8 * g], q[8 * g + 2], q[8 * g + 4], q[8 * g + 6]));                         \
        quad_transpose(q[8 * g + 1], q[8 * g + 3], q[8 * g + 5], q[8 * g + 7], lane);                                  \
        stg128(orow + (size_t)8 * HD_ + g * 32, make_uint4(q[8 * g + 1], q[8 * g + 3], q[8 * g + 5], q[8 * g + 7]));   \
      }
#pragma unroll 1
    for (int item = 0; item < 4; item++) {
      TSA(item, 0);
      {
        uint32_t prevA = 0, prevB = 0;
#pragma unroll
        for (int kb = 0; kb < 10; kb++) {
          const uint32_t sA = r.slot; mbar_wait_c(bar_full + 8 * sA, r.phase); r.adv(A_NSLOT);
          const uint32_t sB = r.slot; mbar_wait_c(bar_full + 8 * sB, r.phase); r.adv(A_NSLOT);
          const uint64_t da = mkdesc(sb + sA * A_SLOT + w * 8192, 16, 1024);
          const uint64_t db = mkdesc(sb + sB * A_SLOT, 8192, 1024);
          wg_fence();
#pragma unroll
          for (int kk = 0; kk < 4; kk++) wgmma_ss_n192<1>(o, da + kk * 2, db + kk * 128, (kb | kk) != 0);
          wg_commit();
          if (kb < 6 && item > 0) { O_STORE((kb < 6 ? kb : 0)) }
          if (kb == 6 && item > 0) SIGNAL();
          if (kb > 0) { wg_wait<1>(); A_RELEASE(prevA); A_RELEASE(prevB); }
          prevA = sA; prevB = sB;
        }
        wg_wait<0>();
        fence_regs(o);
        A_RELEASE(prevA); A_RELEASE(prevB);
#pragma unroll
        for (int i = 0; i < 48; i++) q[i] = pack_bf16(o[2 * i], o[2 * i + 1]);
      }
      orow += 8 * DH_;

      TSA(item, 1);
      float c0, c1, l0, l1;
      {
        const uint32_t sK = r.slot; mbar_wait_c(bar_full + 8 * sK, r.phase); r.adv(A_NSLOT);
        const uint64_t dk = mkdesc(sb + sK * A_SLOT, 16, 1024);
        bar_sync(1 + w, 256);
        wg_fence();
#pragma unroll
        for (int kk = 0; kk < 12; kk++)
          wgmma_rs_n64<0>(s, q[4 * kk], q[4 * kk + 1], q[4 * kk + 2], q[4 * kk + 3], dk + (kk >> 2) * 512 + (kk & 3) * 2, kk != 0);
        wg_commit();
        bar_arrive(1 + (w ^ 1), 256);
        wg_wait<0>();
        fence_regs(s);
        A_RELEASE(sK);
        float mx0 = fmaxf(s[0], s[1]), mx1 = fmaxf(s[2], s[3]);
#pragma unroll
        for (int i = 1; i < 8; i++) { mx0 = fmaxf(mx0, fmaxf(s[4 * i], s[4 * i + 1])); mx1 = fmaxf(mx1, fmaxf(s[4 * i + 2], s[4 * i + 3])); }
        mx0 = fmaxf(mx0, __shfl_xor_sync(0xffffffffu, mx0, 1)); mx1 = fmaxf(mx1, __shfl_xor_sync(0xffffffffu, mx1, 1));
        mx0 = fmaxf(mx0, __shfl_xor_sync(0xffffffffu, mx0, 2)); mx1 = fmaxf(mx1, __shfl_xor_sync(0xffffffffu, mx1, 2));
        c0 = mx0 * SC; c1 = mx1 * SC;
        l0 = 0.f; l1 = 0.f;
#pragma unroll
        for (int i = 0; i < 8; i++) {
          s[4 * i] = ex2(fmaf(s[4 * i], SC, -c0)); s[4 * i + 1] = ex2(fmaf(s[4 * i + 1], SC, -c0));
          s[4 * i + 2] = ex2(fmaf(s[4 * i + 2], SC, -c1)); s[4 * i + 3] = ex2(fmaf(s[4 * i + 3], SC, -c1));
          l0 += s[4 * i] + s[4 * i + 1]; l1 += s[4 * i + 2] + s[4 * i + 3];
        }
#pragma unroll
        for (int i = 0; i < 16; i++) p[i] = pack_bf16(s[2 * i], s[2 * i + 1]);
      }
      TSA(item, 2);
      uint32_t okn;
      {
        Ring r2 = r; r2.adv(A_NSLOT);
        okn = mbar_try(bar_full + 8 * r.slot, r.phase) & mbar_try(bar_full + 8 * r2.slot, r2.phase);
      }
#define A_STEP(PC, PN, FIRST)                                                                                          \
      {                                                                                                                \
        const uint32_t sK = r.slot, phK = r.phase; r.adv(A_NSLOT);                                                     \
        const uint32_t sV = r.slot, phV = r.phase; r.adv(A_NSLOT);                                                     \
        const uint64_t dk = mkdesc(sb + sK * A_SLOT, 16, 1024);                                                        \
        const uint64_t dv = mkdesc(sb + sV * A_SLOT, 8192, 1024);                                                      \
        if (!okn) { mbar_wait_c(bar_full + 8 * sK, phK); mbar_wait_c(bar_full + 8 * sV, phV); }                            \
        bar_sync(1 + w, 256);                                                                                          \
        wg_fence();                                                                                                    \
        _Pragma("unroll") for (int kk = 0; kk < 12; kk++)                                                              \
          wgmma_rs_n64<0>(s, q[4 * kk], q[4 * kk + 1], q[4 * kk + 2], q[4 * kk + 3], dk + (kk >> 2) * 512 + (kk & 3) * 2, kk != 0); \
        wg_commit();                                                                                                   \
        _Pragma("unroll") for (int kk = 0; kk < 4; kk++)                                                               \
          wgmma_rs_n192<1>(o, PC[4 * kk], PC[4 * kk + 1], PC[4 * kk + 2], PC[4 * kk + 3], dv + kk * 128, !(FIRST) || (kk != 0)); \
        wg_commit();                                                                                                   \
        bar_arrive(1 + (w ^ 1), 256);                                                                                  \
        {                                                                                                              \
          Ring r2 = r; r2.adv(A_NSLOT);                                                                                \
          okn = mbar_try(bar_full + 8 * r.slot, r.phase) & mbar_try(bar_full + 8 * r2.slot, r2.phase);                 \
        }                                                                                                              \
        wg_wait<1>();                                                                                                  \
        fence_regs(s);                                                                                                 \
        A_RELEASE(sK);                                                                                                 \
        float b0 = 0.f, b1 = 0.f;                                                                                      \
        _Pragma("unroll") for (int i = 0; i < 8; i++) {                                                                \
          const float e0 = ex2(fmaf(s[4 * i], SC, -c0)), e1 = ex2(fmaf(s[4 * i + 1], SC, -c0));                        \
          const float e2 = ex2(fmaf(s[4 * i + 2], SC, -c1)), e3 = ex2(fmaf(s[4 * i + 3], SC, -c1));                    \
          b0 += e0 + e1; b1 += e2 + e3;                                                                                \
          PN[2 * i] = pack_bf16(e0, e1); PN[2 * i + 1] = pack_bf16(e2, e3);                                            \
        }                                                                                                              \
        wg_wait<0>();                                                                                                  \
        fence_regs(o);                                                                                                 \
        fence_regs(PC);                                                                                                \
        A_RELEASE(sV);                                                                                                 \
        if (__any_sync(0xffffffffu, !(b0 <= 65536.f) || !(b1 <= 65536.f))) {                                           \
          float mx0 = fmaxf(s[0], s[1]), mx1 = fmaxf(s[2], s[3]);                                                      \
          _Pragma("unroll") for (int i = 1; i < 8; i++) {                                                              \
            mx0 = fmaxf(mx0, fmaxf(s[4 * i], s[4 * i + 1])); mx1 = fmaxf(mx1, fmaxf(s[4 * i + 2], s[4 * i + 3]));     \
          }                                                                                                            \
          mx0 = fmaxf(mx0, __shfl_xor_sync(0xffffffffu, mx0, 1)); mx1 = fmaxf(mx1, __shfl_xor_sync(0xffffffffu, mx1, 1)); \
          mx0 = fmaxf(mx0, __shfl_xor_sync(0xffffffffu, mx0, 2)); mx1 = fmaxf(mx1, __shfl_xor_sync(0xffffffffu, mx1, 2)); \
          const float n0 = fmaxf(c0, mx0 * SC), n1 = fmaxf(c1, mx1 * SC);                                              \
          const float a0 = ex2(c0 - n0), a1 = ex2(c1 - n1);                                                            \
          c0 = n0; c1 = n1;                                                                                            \
          l0 *= a0; l1 *= a1;                                                                                          \
          _Pragma("unroll") for (int i = 0; i < 24; i++) { o[4 * i] *= a0; o[4 * i + 1] *= a0; o[4 * i + 2] *= a1; o[4 * i + 3] *= a1; } \
          b0 = 0.f; b1 = 0.f;                                                                                          \
          _Pragma("unroll") for (int i = 0; i < 8; i++) {                                                              \
            const float e0 = ex2(fmaf(s[4 * i], SC, -c0)), e1 = ex2(fmaf(s[4 * i + 1], SC, -c0));                      \
            const float e2 = ex2(fmaf(s[4 * i + 2], SC, -c1)), e3 = ex2(fmaf(s[4 * i + 3], SC, -c1));                  \
            b0 += e0 + e1; b1 += e2 + e3;                                                                              \
            PN[2 * i] = pack_bf16(e0, e1); PN[2 * i + 1] = pack_bf16(e2, e3);                                          \
          }                                                                                                            \
        }                                                                                                              \
        l0 += b0; l1 += b1;                                                                                            \
      }
      for (int jj = 0; jj < 15; jj++) {
        A_STEP(p, p2, jj == 0)
        A_STEP(p2, p, false)
      }
      A_STEP(p, p2, false)
      TSA(item, 3);
      {
        const uint32_t sV = r.slot; mbar_wait_c(bar_full + 8 * sV, r.phase); r.adv(A_NSLOT);
        const uint64_t dv = mkdesc(sb + sV * A_SLOT, 8192, 1024);
        bar_sync(1 + w, 256);
        wg_fence();
#pragma unroll
        for (int kk = 0; kk < 4; kk++)
          wgmma_rs_n192<1>(o, p2[4 * kk], p2[4 * kk + 1], p2[4 * kk + 2], p2[4 * kk + 3], dv + kk * 128, 1);
        wg_commit();
        bar_arrive(1 + (w ^ 1), 256);
        wg_wait<0>();
        fence_regs(o);
        A_RELEASE(sV);
      }
      TSA(item, 4);
      l0 += __shfl_xor_sync(0xffffffffu, l0, 1); l1 += __shfl_xor_sync(0xffffffffu, l1, 1);
      l0 += __shfl_xor_sync(0xffffffffu, l0, 2); l1 += __shfl_xor_sync(0xffffffffu, l1, 2);
      const float i0 = __fdividef(1.f, l0), i1 = __fdividef(1.f, l1);
#pragma unroll
      for (int i = 0; i < 24; i++) { q[2 * i] = pack_bf16(o[4 * i] * i0, o[4 * i + 1] * i0); q[2 * i + 1] = pack_bf16(o[4 * i + 2] * i1, o[4 * i + 3] * i1); }
      TSA(item, 5);
    }
#pragma unroll
    for (int g = 0; g < 6; g++) { O_STORE(g) }
    SIGNAL();
    }
    TS(3, 2);
    const uint32_t st_w = (uint32_t)((warp * 16 + (lane >> 2)) * ST_P + (lane & 3) * 2) * 4;
    const uint32_t st_x = (lane & 8) << 2;
    const int er = (tid & 127) >> 1, eh = tid & 1;
    const uint32_t st_r = (uint32_t)(er * ST_P + (eh ^ ((er >> 1) & 1)) * 8) * 4;
    const uint32_t e_r = (uint32_t)((w * 64 + er) * 160 + eh * 16);
    const uint32_t p_r = par + eh * 32;
    const uint32_t stat = sb + T_PREP + w * 2048;
    const bool leader = (tid & 127) == 0;
#define STAGE10(ACC, BASE)                                                                                             \
    _Pragma("unroll") for (int nb = 0; nb < 10; nb++) {                                                                \
      sts_f2(stg + st_w + ((nb * 32) ^ st_x), ACC(BASE + 4 * nb), ACC(BASE + 4 * nb + 1));                                       \
      sts_f2(stg + st_w + ((nb * 32) ^ st_x) + 8 * ST_P * 4, ACC(BASE + 4 * nb + 2), ACC(BASE + 4 * nb + 3));                    \
    }

    {
      float acc1[96], acc2[64];
      uint32_t p0 = 0, p1 = 0, p2 = 0;
#pragma unroll 1
      for (int kb = 0; kb < 24; kb++) {
        const uint32_t s1 = r.slot; mbar_wait_c(bar_full + 8 * s1, r.phase); r.adv(A_NSLOT);
        const uint32_t s2 = r.slot; mbar_wait_c(bar_full + 8 * s2, r.phase); r.adv(A_NSLOT);
        const uint32_t sa = r.slot; mbar_wait_c(bar_full + 8 * sa, r.phase); r.adv(A_NSLOT);
        const uint64_t da = mkdesc(sb + sa * A_SLOT + w * 8192, 16, 1024);
        const uint64_t d1 = mkdesc(sb + s1 * A_SLOT, 8192, 1024), d2 = mkdesc(sb + s2 * A_SLOT, 8192, 1024);
        wg_fence();
#pragma unroll
        for (int kk = 0; kk < 4; kk++) {
          wgmma_ss_n192<1>(acc1, da + kk * 2, d1 + kk * 128, (kb | kk) != 0);
          wgmma_ss_n128<1>(acc2, da + kk * 2, d2 + kk * 128, (kb | kk) != 0);
        }
        wg_commit();
        if (kb > 0) { wg_wait<1>(); A_RELEASE(p0); A_RELEASE(p1); A_RELEASE(p2); }
        p0 = s1; p1 = s2; p2 = sa;
      }
      wg_wait<0>();
      fence_regs(acc1); fence_regs(acc2);
      A_RELEASE(p2);
      bar_sync(6, 288);
      TS(0, 0);
      const uint32_t stg = sb + (w ? p1 : p0) * A_SLOT;
#define OACC(e) (((e) < 96) ? acc1[(e) < 96 ? (e) : 0] : acc2[(e) >= 96 ? (e) - 96 : 0])
#define PACK10(BASE)                                                                                                   \
      _Pragma("unroll") for (int nb = 0; nb < 10; nb++) {                                                              \
        sts_u1(xo + nb * 16, pack_bf16(OACC(BASE + 4 * nb), OACC(BASE + 4 * nb + 1)));                                 \
        sts_u1(xo + nb * 16 + 8 * 160, pack_bf16(OACC(BASE + 4 * nb + 2), OACC(BASE + 4 * nb + 3)));                   \
      }
      const uint32_t f1 = r.slot + 4 >= A_NSLOT ? r.slot + 4 - A_NSLOT : r.slot + 4, f2 = f1 + 1 >= A_NSLOT ? 0 : f1 + 1;
#pragma unroll
      for (int d = 0; d < 4; d++) {
        if (d != o_ks) {
          const int i = (d - o_ks - 1) & 3;
          const uint32_t xo = sb + (i == 0 ? p2 : i == 1 ? f1 : f2) * A_SLOT + (w * 64 + warp * 16 + (lane >> 2)) * 160 + (lane & 3) * 4;
          PACK10(d * 40)
        }
      }
      fence_async_smem();
      bar_sync(3 + w, 128);
      if (leader) {
#pragma unroll 1
        for (int i = 0; i < 3; i++)
          bulk_store(g_xch + (size_t)((((o_qt * 2 + o_nh) * 4 + ((o_ks + 1 + i) & 3)) * 4) + o_ks) * (E_TILE / 2) + w * (E_TILE / 4),
                     sb + (i == 0 ? p2 : i == 1 ? f1 : f2) * A_SLOT + w * (E_TILE / 2), E_TILE / 2);
        bulk_done();
#pragma unroll 1
        for (int i = 0; i < 3; i++) flag_add(g_flag + F_XCH + (o_qt * 2 + o_nh) * 4 + ((o_ks + 1 + i) & 3));
        TX(40 + w);
      }
      if (o_ks == 0) { STAGE10(OACC, 0) } else if (o_ks == 1) { STAGE10(OACC, 40) } else if (o_ks == 2) { STAGE10(OACC, 80) } else { STAGE10(OACC, 120) }
      bar_sync(3 + w, 128);
      const uint32_t sx = r.slot; mbar_wait_c(bar_full + 8 * sx, r.phase); r.adv(A_NSLOT);
      const uint32_t q0 = r.slot; mbar_wait_c(bar_full + 8 * q0, r.phase); r.adv(A_NSLOT);
      const uint32_t q1 = r.slot; mbar_wait_c(bar_full + 8 * q1, r.phase); r.adv(A_NSLOT);
      const uint32_t q2 = r.slot; mbar_wait_c(bar_full + 8 * q2, r.phase); r.adv(A_NSLOT);
      TS(0, 1);
      float st[6] = {0.f, 0.f, 0.f, 0.f, 0.f, 0.f};
      const uint32_t ot = sb + p2 * A_SLOT;
#pragma unroll 1
      for (int c = 0; c < 5; c++) {
        float v[8], t0[8], t1[8], t2[8], xv[8], pg[8], pa_[8], pb_[8];
        lds8(stg + st_r + c * 64, v);
        lds8_bf(sb + q0 * A_SLOT + e_r + c * 32, t0); lds8_bf(sb + q1 * A_SLOT + e_r + c * 32, t1); lds8_bf(sb + q2 * A_SLOT + e_r + c * 32, t2);
        lds8_bf(sb + sx * A_SLOT + e_r + c * 32, xv);
        lds8(p_r + P_OGA * 4 + c * 64, pg); lds8(p_r + P_OA * 4 + c * 64, pa_); lds8(p_r + P_OB * 4 + c * 64, pb_);
#pragma unroll
        for (int e = 0; e < 8; e++) v[e] = fmaf(pg[e], v[e] + ((t0[e] + t1[e]) + t2[e]), xv[e]);
        const uint4 pk = pack8(v);
        sts_u4(ot + e_r + c * 32, pk);
        v[0] = bf_lo(pk.x); v[1] = bf_hi(pk.x); v[2] = bf_lo(pk.y); v[3] = bf_hi(pk.y); v[4] = bf_lo(pk.z); v[5] = bf_hi(pk.z); v[6] = bf_lo(pk.w); v[7] = bf_hi(pk.w);
#pragma unroll
        for (int e = 0; e < 8; e++) {
          const float y = pa_[e] * v[e];
          st[0] += v[e]; st[1] = fmaf(v[e], v[e], st[1]); st[2] += y; st[3] = fmaf(pa_[e], y, st[3]); st[4] = fmaf(y, y, st[4]); st[5] = fmaf(pb_[e], y, st[5]);
        }
      }
#pragma unroll
      for (int i = 0; i < 6; i++) st[i] += __shfl_xor_sync(0xffffffffu, st[i], 1);
      sts_u4(stat + er * 32 + eh * 16, eh ? make_uint4(__float_as_uint(st[4]), __float_as_uint(st[5]), 0u, 0u)
                                          : make_uint4(__float_as_uint(st[0]), __float_as_uint(st[1]), __float_as_uint(st[2]), __float_as_uint(st[3])));
      fence_async_smem();
      bar_sync(3 + w, 128);
      if (leader) {
        tma_store2d(&tm.sxa, ot + w * (E_TILE / 2), o_col, o_qt * 128 + w * 64);
        bulk_red_f32(g_st1 + (size_t)(o_qt * 128 + w * 64) * 8, stat, 2048);
        bulk_done();
        flag_add(g_flag + F_XA + o_qt);
      }
      bar_sync(5, 256);
      A_RELEASE(p0); A_RELEASE(p1); A_RELEASE(sx); A_RELEASE(q0); A_RELEASE(q1); A_RELEASE(q2);
      TS(0, 2);
    }

    Ring ra{0, 0};
    uint32_t bpar = 0;
    const uint32_t rel_a = mapa(mb_empty + 40, (lane == 0) ? rank : (rank ^ 1));
#define B_NEXT(s_) do { s_ = bs; mbar_wait_c(mb_full + 8 * bs, (bpar >> bs) & 1); bpar ^= 1u << bs; if (++bs == nbs) bs = 0; } while (0)
#define A_NEXT(s_) do { s_ = ra.slot; mbar_wait_c(mb_full + 40 + 8 * s_, ra.phase); ra.adv(M_NA); } while (0)
#define B_RELEASE(s_) do { if (lane == 0) mbar_arrive(mb_empty + 8 * (s_)); } while (0)
#define MA_RELEASE(s_) do { if (lane < 2) mbar_arrive_remote(rel_a + 8 * (s_)); } while (0)
    const int grow = qt * 128 + w * 64 + er;
    float mu = 0.f, rs = 0.f;
#pragma unroll 1
    for (int ph = 0; ph < 4; ph++) {
      float acc[96];
      float (&acc80)[40] = *reinterpret_cast<float(*)[40]>(&acc[0]);
      uint32_t pa = 0, pa2 = 0, pb = 0;
      float4 s03 = make_float4(0.f, 0.f, 0.f, 0.f);
      float2 s45 = make_float2(0.f, 0.f);
      const int nit = ph == 3 ? 12 : ph == 2 ? 10 : 5;
      const uint32_t nbs = ph == 2 ? 4 : 5, bsz = ph == 2 ? 24576 : 20480;
      uint32_t bs = 0;
#pragma unroll 1
      for (int it = 0; it < nit; it++) {
        uint32_t sbq, sa, sa2;
        B_NEXT(sbq);
        A_NEXT(sa);
        if (it == 0) TXC(ph);
        const uint64_t da = mkdesc(sb + M_AOFF + sa * 16384 + w * 8192, 16, 1024);
        if (ph == 2) {
          sa2 = sa;
          const uint64_t db = mkdesc(sb + sbq * 24576, 8192, 1024);
          wg_fence();
#pragma unroll
          for (int kk = 0; kk < 4; kk++) wgmma_ss_n192<1>(acc, da + kk * 2, db + kk * 128, (it | kk) != 0);
          wg_commit();
        } else {
          A_NEXT(sa2);
          const uint64_t da2 = mkdesc(sb + M_AOFF + sa2 * 16384 + w * 8192, 16, 1024);
          const uint64_t db = mkdesc(sb + sbq * 20480, 16, 1024);
          wg_fence();
#pragma unroll
          for (int kk = 0; kk < 4; kk++) wgmma_ss_n80<0>(acc80, da + kk * 2, db + kk * 2, (it | kk) != 0);
#pragma unroll
          for (int kk = 0; kk < 4; kk++) wgmma_ss_n80<0>(acc80, da2 + kk * 2, db + 640 + kk * 2, 1);
          wg_commit();
        }
        if (it > 0) { wg_wait<1>(); MA_RELEASE(pa); if (ph != 2) MA_RELEASE(pa2); B_RELEASE(pb); }
        else {
          if (ph == 0) { s03 = __ldcg(reinterpret_cast<const float4*>(g_st1 + (size_t)grow * 8)); s45 = __ldcg(reinterpret_cast<const float2*>(g_st1 + (size_t)grow * 8 + 4)); }
          if (ph == 2) s45 = __ldcg(reinterpret_cast<const float2*>(g_st2 + (size_t)grow * 2));
        }
        pa = sa; pa2 = sa2; pb = sbq;
      }
      wg_wait<0>();
      fence_regs(acc);
      MA_RELEASE(pa); if (ph != 2) MA_RELEASE(pa2);
      bar_sync(5, 256);
      TS(1 + (ph == 3 ? 0 : ph), ph == 3 ? 2 : 0);
      const uint32_t pb1 = pb == 0 ? nbs - 1 : pb - 1, pb2 = pb1 == 0 ? nbs - 1 : pb1 - 1, pb3 = pb2 == 0 ? nbs - 1 : pb2 - 1;
      const uint32_t stg = sb + (w ? pb : pb1) * bsz;
      uint32_t e1 = 0;
#define MACC(e) acc[e]
      if (!(ph & 1)) {
        float c0, c1, c2 = 0.f, c3 = 0.f;
        if (ph == 0) {
          const float4 sc = lds_f4(par + P_SC * 4);
          const float sbb = lds_f(par + (P_SC + 4) * 4);
          mu = s03.x * (1.f / D_);
          rs = rsqrtf(fmaxf(s03.y * (1.f / D_) - mu * mu, 0.f) + LN_EPS);
          const float m2 = (rs * (s03.z - mu * sc.x) + sc.w) * (1.f / D_);
          const float e2 = (rs * rs * (s45.x - 2.f * mu * s03.w + mu * mu * sc.y) + 2.f * rs * (s45.y - mu * sc.z) + sbb) * (1.f / D_);
          c2 = rsqrtf(fmaxf(e2 - m2 * m2, 0.f) + LN_EPS);
          c0 = c2 * rs; c1 = -c0 * mu; c3 = -c2 * m2;
          if (tid < 20) sts_u4(stat + 2048 * 2 + tid * 16, make_uint4(0, 0, 0, 0));
        } else {
          const float m = s45.x * (1.f / D_);
          c0 = rsqrtf(fmaxf(s45.y * (1.f / D_) - m * m, 0.f) + LN_EPS);
          c1 = -c0 * m;
        }
        const int npass = ph == 0 ? 1 : 3, nch = ph == 0 ? 5 : 4;
        const uint32_t ot = ph == 0 ? sb + pb2 * bsz + w * (E_TILE / 2) : sb + (w ? pb2 : pb3) * bsz;
#pragma unroll 1
        for (int ps = 0; ps < npass; ps++) {
          if (ps == 0) { STAGE10(MACC, 0) } else if (ps == 1) { STAGE10(MACC, 32) } else { STAGE10(MACC, 56) }
          bar_sync(3 + w, 128);
          const uint32_t cofs = ps == 2 ? 64 : 0;
          const uint32_t pp = p_r + (ph == 0 ? P_VA : P_CS3 + ps * 64) * 4, pq = p_r + P_VB * 4;
#pragma unroll 1
          for (int c = 0; c < nch; c++) {
            float v[8], t[8], t2[8], t3[8];
            lds8(stg + st_r + cofs + c * 64, v);
            lds8(pp + c * 64, t);
            if (ph == 0) {
              lds8(pq + c * 64, t2); lds8(pq + 320 + c * 64, t3);
#pragma unroll
              for (int e = 0; e < 8; e++) t[e] = fmaf(c1, t[e], fmaf(c2, t2[e], c3 * t3[e]));
            } else {
#pragma unroll
              for (int e = 0; e < 8; e++) t[e] *= c1;
            }
#pragma unroll
            for (int e = 0; e < 8; e++) v[e] = gelu_tanh(fmaf(c0, v[e], t[e]));
            sts_u4(ot + (ph == 0 ? er * 160 + eh * 16 + c * 32 : ps * 8192 + er * 128 + (((2 * c + eh) ^ (er & 7)) << 4)), pack8(v));
          }
          fence_async_smem();
          bar_sync(3 + w, 128);
          if (leader) {
            if (ph == 0) {
              const int grp = js >> 1;
              const int sh = (grp & 2 ? 2 : 1) * (grp & 1 ? -1 : 1);
              tma_store2d(&tm.sus, ot, js * 80, qt * 128 + w * 64 + sh + 2);
              if (w == 0 && qt == (sh > 0 ? 0 : 15)) {
                const int r0 = sh > 0 ? 0 : S_ + sh, n = sh > 0 ? sh : -sh;
                for (int i = 0; i < n; i++) bulk_store(g_us + (size_t)(r0 + i + 2) * D_ + js * 80, stat + 2048 * 2, 160);
              }
            } else {
              tma_store2d(&tm.g, ot + ps * 8192, js * 192 + ps * 64, qt * 128 + w * 64);
            }
          }
        }
      } else {
        STAGE10(MACC, 0)
        uint32_t e2;
        B_NEXT(e1);
        e2 = e1;
        if (ph == 3) B_NEXT(e2);
        bar_sync(3 + w, 128);
        float s1 = 0.f, s2 = 0.f;
        const uint32_t ot = sb + pb2 * bsz;
#pragma unroll 1
        for (int c = 0; c < 5; c++) {
          float v[8], xa[8], x1[8], ta[8], tb[8];
          lds8(stg + st_r + c * 64, v);
          lds8_bf(sb + e1 * 20480 + e_r + c * 32, xa); lds8_bf(sb + e2 * 20480 + e_r + c * 32, x1);
          lds8(p_r + (ph == 1 ? P_A2 : P_GB) * 4 + c * 64, ta); lds8(p_r + P_B2 * 4 + c * 64, tb);
          if (ph == 1) {
#pragma unroll
            for (int e = 0; e < 8; e++) v[e] += fmaf(ta[e] * rs, xa[e] - mu, tb[e]);
          } else {
#pragma unroll
            for (int e = 0; e < 8; e++) v[e] = fmaf(ta[e], v[e] + x1[e], xa[e]);
          }
          const uint4 pk = pack8(v);
          sts_u4(ot + e_r + c * 32, pk);
          v[0] = bf_lo(pk.x); v[1] = bf_hi(pk.x); v[2] = bf_lo(pk.y); v[3] = bf_hi(pk.y); v[4] = bf_lo(pk.z); v[5] = bf_hi(pk.z); v[6] = bf_lo(pk.w); v[7] = bf_hi(pk.w);
#pragma unroll
          for (int e = 0; e < 8; e++) { s1 += v[e]; s2 = fmaf(v[e], v[e], s2); }
        }
        s1 += __shfl_xor_sync(0xffffffffu, s1, 1); s2 += __shfl_xor_sync(0xffffffffu, s2, 1);
        if (eh == 0) sts_f2(stat + er * 8, s1, s2);
        fence_async_smem();
        bar_sync(3 + w, 128);
        if (leader) {
          tma_store2d(ph == 1 ? &tm.sx1 : &tm.sout, ot + w * (E_TILE / 2), js * 80, qt * 128 + w * 64);
          if (ph == 1) bulk_red_f32(g_st2 + (size_t)(qt * 128 + w * 64) * 2, stat, 512);
        }
      }
      if (leader) {
        bulk_done();
        if (ph < 3) flag_add(g_flag + F_US + 16 * ph + qt);
      }
      if (ph < 3) {
        bar_sync(5, 256);
        B_RELEASE(pb);
        if (ph == 1) B_RELEASE(e1);
      }
      TS(1 + (ph == 3 ? 0 : ph), ph == 3 ? 3 : 1);
    }
    if ((threadIdx.x & 127) == 0) TL_END(2);
    cluster_sync();
    if (wid == 4) {
      unsigned n = 0;
      if (lane == 0) n = atomicAdd(g_flag + F_DONE, 1u);
      n = __shfl_sync(0xffffffffu, n, 0);
      if (n == 127) {
#pragma unroll 1
        for (int i = lane; i < 1024; i += 32) g_flag[i] = 0u;
#pragma unroll 1
        for (int i = lane; i < 6 * D_; i += 32) g_mod[i] = 0.f;
      }
    }
  }
}

typedef CUresult (*EncFn)(CUtensorMap*, CUtensorMapDataType, cuuint32_t, void*, const cuuint64_t*, const cuuint64_t*,
                          const cuuint32_t*, const cuuint32_t*, CUtensorMapInterleave, CUtensorMapSwizzle,
                          CUtensorMapL2promotion, CUtensorMapFloatOOBfill);
static EncFn g_enc = nullptr;

static CUtensorMap map2d(const void* p, uint64_t rows, uint64_t cols, uint32_t box_rows) {
  CUtensorMap m;
  cuuint64_t gd[2] = {cols, rows}; cuuint64_t gs[1] = {cols * 2};
  cuuint32_t bx[2] = {64, box_rows}; cuuint32_t es[2] = {1, 1};
  g_enc(&m, CU_TENSOR_MAP_DATA_TYPE_BFLOAT16, 2, const_cast<void*>(p), gd, gs, bx, es, CU_TENSOR_MAP_INTERLEAVE_NONE,
        CU_TENSOR_MAP_SWIZZLE_128B, CU_TENSOR_MAP_L2_PROMOTION_L2_256B, CU_TENSOR_MAP_FLOAT_OOB_FILL_NONE);
  return m;
}
static CUtensorMap map3d(const void* p, uint64_t rows, uint64_t cols, uint32_t box_rows, uint32_t nblk) {
  CUtensorMap m;
  cuuint64_t gd[3] = {64, rows, cols / 64}; cuuint64_t gs[2] = {cols * 2, 128};
  cuuint32_t bx[3] = {64, box_rows, nblk}; cuuint32_t es[3] = {1, 1, 1};
  g_enc(&m, CU_TENSOR_MAP_DATA_TYPE_BFLOAT16, 3, const_cast<void*>(p), gd, gs, bx, es, CU_TENSOR_MAP_INTERLEAVE_NONE,
        CU_TENSOR_MAP_SWIZZLE_128B, CU_TENSOR_MAP_L2_PROMOTION_L2_256B, CU_TENSOR_MAP_FLOAT_OOB_FILL_NONE);
  return m;
}

static CUtensorMap map_e(const void* p, uint32_t rows, uint64_t total_rows = S_) {
  CUtensorMap m;
  cuuint64_t gd[2] = {D_, total_rows}; cuuint64_t gs[1] = {D_ * 2};
  cuuint32_t bx[2] = {80, rows}; cuuint32_t es[2] = {1, 1};
  g_enc(&m, CU_TENSOR_MAP_DATA_TYPE_BFLOAT16, 2, const_cast<void*>(p), gd, gs, bx, es, CU_TENSOR_MAP_INTERLEAVE_NONE,
        CU_TENSOR_MAP_SWIZZLE_NONE, CU_TENSOR_MAP_L2_PROMOTION_L2_256B, CU_TENSOR_MAP_FLOAT_OOB_FILL_NONE);
  return m;
}

template <typename... KArgs, typename... Args>
static void launch(void (*kern)(KArgs...), dim3 grid, dim3 block, int smem, bool pdl, Args... args) {
  cudaLaunchConfig_t cfg = {};
  cfg.gridDim = grid; cfg.blockDim = block; cfg.dynamicSmemBytes = smem; cfg.stream = cudaStreamPerThread;
  cudaLaunchAttribute at[1];
  at[0].id = cudaLaunchAttributeProgrammaticStreamSerialization;
  at[0].val.programmaticStreamSerializationAllowed = 1;
  cfg.attrs = at; cfg.numAttrs = pdl ? 1 : 0;
  cudaLaunchKernelEx(&cfg, kern, KArgs(args)...);
}

extern "C" void kernel_launch(void* const* d_in, const int* in_sizes, int n_in, void* d_out, int out_size) {
  const bf16* x = (const bf16*)d_in[0];
  const bf16* kc = (const bf16*)d_in[1];
  const bf16* vc = (const bf16*)d_in[2];
  const bf16* wq = (const bf16*)d_in[3];
  const bf16* wo = (const bf16*)d_in[4];
  const bf16* w1 = (const bf16*)d_in[6];
  const bf16* w2 = (const bf16*)d_in[7];
  const bf16* w3 = (const bf16*)d_in[8];
  const bf16* w4 = (const bf16*)d_in[9];
  const bf16* c = (const bf16*)d_in[10];
  const bf16* wmod = (const bf16*)d_in[11];
  bf16* out = (bf16*)d_out;

  static void *p_h, *p_o, *p_xa, *p_us, *p_x1, *p_g, *p_w1t, *p_w2t, *p_w4t;
  if (!g_enc) {
    void* fn = nullptr; cudaDriverEntryPointQueryResult qr;
    cudaGetDriverEntryPoint("cuTensorMapEncodeTiled", &fn, cudaEnableDefault, &qr);
    g_enc = (EncFn)fn;
    cudaGetSymbolAddress(&p_h, g_h); cudaGetSymbolAddress(&p_o, g_o); cudaGetSymbolAddress(&p_xa, g_xa);
    cudaGetSymbolAddress(&p_us, g_us); cudaGetSymbolAddress(&p_x1, g_x1); cudaGetSymbolAddress(&p_g, g_g);
    cudaGetSymbolAddress(&p_w1t, g_w1t); cudaGetSymbolAddress(&p_w2t, g_w2t); cudaGetSymbolAddress(&p_w4t, g_w4t);
    cudaFuncSetAttribute(fused_kernel, cudaFuncAttributeMaxDynamicSharedMemorySize, T_SMEM);
  }
  Maps tm;
  tm.h = map2d(p_h, S_, D_, 128);
  tm.wq = map3d(wq, D_, HD_, 64, 3);
  tm.k = map3d(kc, (uint64_t)H_ * S_, DH_, 64, 3);
  tm.v = map3d(vc, (uint64_t)H_ * S_, DH_, 64, 3);
  tm.o = map2d(p_o, S_, HD_, 128);
  tm.wo3 = map3d(wo, HD_, D_, 64, 3);
  tm.wo2 = map3d(wo, HD_, D_, 64, 2);
  tm.xa = map2d(p_xa, S_, D_, 64);
  tm.w1t = map3d(p_w1t, D_, D_, 80, 2);
  tm.us = map2d((const bf16*)p_us + 2 * D_, S_, D_, 64);
  tm.w2t = map3d(p_w2t, D_, D_, 80, 2);
  tm.x1 = map2d(p_x1, S_, D_, 64);
  tm.w3 = map3d(w3, D_, F_, 64, 3);
  tm.g = map2d(p_g, S_, F_, 64);
  tm.w4t = map3d(p_w4t, D_, F_, 80, 2);
  tm.ex = map_e(x, 128); tm.exa = map_e(p_xa, 128); tm.ex1 = map_e(p_x1, 128);
  tm.sxa = map_e(p_xa, 64); tm.sus = map_e(p_us, 64, S_ + 4); tm.sx1 = map_e(p_x1, 64); tm.sout = map_e(out, 64);
  PfList pf;
  pf.p[0] = (const uint8_t*)wo; pf.p[1] = (const uint8_t*)w3; pf.p[2] = (const uint8_t*)p_w4t;
  pf.p[3] = (const uint8_t*)x; pf.p[4] = (const uint8_t*)p_w1t; pf.p[5] = (const uint8_t*)p_w2t;

  launch(fused_kernel, dim3(128), dim3(384), T_SMEM, false, tm, pf, PrepW{w1, w2, w3, w4, c, wmod}, x, out);
}
```

```cpp
#include <cuda_runtime.h>
#include <cuda.h>
#include <cuda_bf16.h>
#include <stdint.h>

typedef __nv_bfloat16 bf16;

constexpr int S_  = 2048;
constexpr int D_  = 640;
constexpr int H_  = 32;
constexpr int DH_ = 192;
constexpr int HD_ = H_ * DH_;
constexpr int F_  = 1536;
constexpr float LN_EPS = 1e-5f;

__device__ __forceinline__ uint32_t smem_u32(const void* p) { return (uint32_t)__cvta_generic_to_shared(p); }
__device__ __forceinline__ void mbar_init(uint32_t a, uint32_t c) { asm volatile("mbarrier.init.shared::cta.b64 [%0], %1;" :: "r"(a), "r"(c) : "memory"); }
__device__ __forceinline__ void mbar_expect(uint32_t a, uint32_t b) { asm volatile("mbarrier.arrive.expect_tx.shared::cta.b64 _, [%0], %1;" :: "r"(a), "r"(b) : "memory"); }
__device__ __forceinline__ void mbar_arrive(uint32_t a) { asm volatile("mbarrier.arrive.shared::cta.b64 _, [%0];" :: "r"(a) : "memory"); }
__device__ __forceinline__ void mbar_arrive_remote(uint32_t ra) { asm volatile("mbarrier.arrive.shared::cluster.b64 _, [%0];" :: "r"(ra) : "memory"); }
__device__ __forceinline__ uint32_t mapa(uint32_t a, uint32_t cta) { uint32_t r; asm volatile("mapa.shared::cluster.u32 %0, %1, %2;" : "=r"(r) : "r"(a), "r"(cta)); return r; }
__device__ __forceinline__ uint32_t mbar_try(uint32_t a, uint32_t ph) {
  uint32_t ok;
  asm volatile("{\n.reg .pred p;\nmbarrier.test_wait.parity.shared::cta.b64 p, [%1], %2;\nselp.u32 %0, 1, 0, p;\n}\n" : "=r"(ok) : "r"(a), "r"(ph) : "memory");
  return ok;
}
__device__ __forceinline__ void mbar_wait(uint32_t a, uint32_t ph) {
  asm volatile(
      "{\n.reg .pred p;\n.reg .u32 n;\n"
      "mov.u32 n, 0;\n"
      "SPIN:\n"
      "mbarrier.try_wait.parity.shared::cta.b64 p, [%0], %1;\n"
      "@p bra DONE;\n"
      "add.u32 n, n, 1;\n"
      "setp.le.u32 p, n, 16777216;\n"
      "@p bra SPIN;\n"
      "trap;\n"
      "DONE:\n}\n" :: "r"(a), "r"(ph) : "memory");
}
#define ELECT_ "{\n.reg .pred p;\nelect.sync _|p, 0xffffffff;\n@p "
__device__ __forceinline__ void mbar_expect_e(uint32_t a, uint32_t b) { asm volatile(ELECT_ "mbarrier.arrive.expect_tx.shared::cta.b64 _, [%0], %1;\n}\n" :: "r"(a), "r"(b) : "memory"); }
__device__ __forceinline__ void tma2d(uint32_t dst, const CUtensorMap* m, uint32_t bar, int c0, int c1) {
  asm volatile(ELECT_ "cp.async.bulk.tensor.2d.shared::cluster.global.mbarrier::complete_tx::bytes [%0], [%1, {%3, %4}], [%2];\n}\n"
               :: "r"(dst), "l"(m), "r"(bar), "r"(c0), "r"(c1) : "memory");
}
__device__ __forceinline__ void tma2d_mc(uint32_t dst, const CUtensorMap* m, uint32_t bar, int c0, int c1, uint16_t mask) {
  asm volatile(ELECT_ "cp.async.bulk.tensor.2d.shared::cluster.global.mbarrier::complete_tx::bytes.multicast::cluster [%0], [%1, {%3, %4}], [%2], %5;\n}\n"
               :: "r"(dst), "l"(m), "r"(bar), "r"(c0), "r"(c1), "h"(mask) : "memory");
}
__device__ __forceinline__ void tma3d(uint32_t dst, const CUtensorMap* m, uint32_t bar, int c0, int c1, int c2) {
  asm volatile(ELECT_ "cp.async.bulk.tensor.3d.shared::cluster.global.mbarrier::complete_tx::bytes [%0], [%1, {%3, %4, %5}], [%2];\n}\n"
               :: "r"(dst), "l"(m), "r"(bar), "r"(c0), "r"(c1), "r"(c2) : "memory");
}
__device__ __forceinline__ void tma3d_mc(uint32_t dst, const CUtensorMap* m, uint32_t bar, int c0, int c1, int c2, uint16_t mask) {
  asm volatile(ELECT_ "cp.async.bulk.tensor.3d.shared::cluster.global.mbarrier::complete_tx::bytes.multicast::cluster [%0], [%1, {%3, %4, %5}], [%2], %6;\n}\n"
               :: "r"(dst), "l"(m), "r"(bar), "r"(c0), "r"(c1), "r"(c2), "h"(mask) : "memory");
}
__device__ __forceinline__ void tma3d_mc_hint(uint32_t dst, const CUtensorMap* m, uint32_t bar, int c0, int c1, int c2, uint16_t mask, uint64_t pol) {
  asm volatile(ELECT_ "cp.async.bulk.tensor.3d.shared::cluster.global.mbarrier::complete_tx::bytes.multicast::cluster.L2::cache_hint [%0], [%1, {%3, %4, %5}], [%2], %6, %7;\n}\n"
               :: "r"(dst), "l"(m), "r"(bar), "r"(c0), "r"(c1), "r"(c2), "h"(mask), "l"(pol) : "memory");
}
__device__ __forceinline__ void bulk_load(uint32_t dst, const void* src, uint32_t bytes, uint32_t bar) {
  asm volatile(ELECT_ "cp.async.bulk.shared::cluster.global.mbarrier::complete_tx::bytes [%0], [%1], %2, [%3];\n}\n"
               :: "r"(dst), "l"(src), "r"(bytes), "r"(bar) : "memory");
}
__device__ __forceinline__ void l2_prefetch16k(const void* p) { asm volatile(ELECT_ "cp.async.bulk.prefetch.L2.global [%0], 16384;\n}\n" :: "l"(p) : "memory"); }
__device__ __forceinline__ void l2_prefetch_t2d(const CUtensorMap* m, int c0, int c1) {
  asm volatile(ELECT_ "cp.async.bulk.prefetch.tensor.2d.L2.global [%0, {%1, %2}];\n}\n" :: "l"(m), "r"(c0), "r"(c1) : "memory");
}
__device__ __forceinline__ void l2_prefetch_t3d(const CUtensorMap* m, int c0, int c1, int c2) {
  asm volatile(ELECT_ "cp.async.bulk.prefetch.tensor.3d.L2.global [%0, {%1, %2, %3}];\n}\n" :: "l"(m), "r"(c0), "r"(c1), "r"(c2) : "memory");
}
__device__ __forceinline__ void stg128(void* p, uint4 v) {
  asm volatile("st.global.v4.u32 [%0], {%1, %2, %3, %4};" :: "l"(p), "r"(v.x), "r"(v.y), "r"(v.z), "r"(v.w) : "memory");
}
__device__ __forceinline__ void prefetch_tmap(const CUtensorMap* m) { asm volatile("prefetch.tensormap [%0];" :: "l"(m) : "memory"); }
__device__ __forceinline__ void wg_fence() { asm volatile("wgmma.fence.sync.aligned;" ::: "memory"); }
__device__ __forceinline__ void wg_commit() { asm volatile("wgmma.commit_group.sync.aligned;" ::: "memory"); }
template <int N> __device__ __forceinline__ void wg_wait() { asm volatile("wgmma.wait_group.sync.aligned %0;" :: "n"(N) : "memory"); }
template <int N> __device__ __forceinline__ void fence_regs(float (&r)[N]) {
#pragma unroll
  for (int i = 0; i < N; i++) asm volatile("" : "+f"(r[i]) :: "memory");
}
template <int N> __device__ __forceinline__ void fence_regs(uint32_t (&r)[N]) {
#pragma unroll
  for (int i = 0; i < N; i++) asm volatile("" : "+r"(r[i]) :: "memory");
}
__device__ __forceinline__ uint64_t mkdesc(uint32_t addr, uint32_t lbo, uint32_t sbo) {
  return (uint64_t)((addr & 0x3FFFF) >> 4) | ((uint64_t)(lbo >> 4) << 16) | ((uint64_t)(sbo >> 4) << 32) | (1ull << 62);
}
__device__ __forceinline__ void bar_sync(int id, int n) { asm volatile("bar.sync %0, %1;" :: "r"(id), "r"(n) : "memory"); }
__device__ __forceinline__ void bar_arrive(int id, int n) { asm volatile("bar.arrive %0, %1;" :: "r"(id), "r"(n) : "memory"); }
__device__ __forceinline__ void cluster_sync() { asm volatile("barrier.cluster.arrive.aligned;\nbarrier.cluster.wait.aligned;" ::: "memory"); }
__device__ __forceinline__ void pdl_wait() { asm volatile("griddepcontrol.wait;" ::: "memory"); }
__device__ __forceinline__ void pdl_launch() { asm volatile("griddepcontrol.launch_dependents;" ::: "memory"); }
__device__ __forceinline__ float ex2(float x) { float y; asm("ex2.approx.ftz.f32 %0, %1;" : "=f"(y) : "f"(x)); return y; }
__device__ __forceinline__ uint32_t pack_bf16(float lo, float hi) { uint32_t r; asm("cvt.rn.bf16x2.f32 %0, %1, %2;" : "=r"(r) : "f"(hi), "f"(lo)); return r; }
__device__ __forceinline__ float bf_lo(uint32_t u) { return __uint_as_float(u << 16); }
__device__ __forceinline__ float bf_hi(uint32_t u) { return __uint_as_float(u & 0xffff0000u); }
__device__ __forceinline__ float bf_round(float x) { return __bfloat162float(__float2bfloat16_rn(x)); }
__device__ __forceinline__ float tanh_fast(float x) { float y; asm("tanh.approx.f32 %0, %1;" : "=f"(y) : "f"(x)); return y; }
__device__ __forceinline__ float gelu_tanh(float x) {
  float u = x * (0.7978845608028654f + 0.035677408136300125f * x * x);
  float hx = 0.5f * x;
  return fmaf(hx, tanh_fast(u), hx);
}
__device__ __forceinline__ float warp_sum(float v) {
#pragma unroll
  for (int o = 16; o > 0; o >>= 1) v += __shfl_xor_sync(0xffffffffu, v, o);
  return v;
}
__device__ __forceinline__ void quad_transpose(uint32_t& v0, uint32_t& v1, uint32_t& v2, uint32_t& v3, int lane) {
  const bool b0 = lane & 1, b1 = lane & 2;
  uint32_t s0 = b0 ? v0 : v1, s1 = b0 ? v2 : v3;
  s0 = __shfl_xor_sync(0xffffffffu, s0, 1); s1 = __shfl_xor_sync(0xffffffffu, s1, 1);
  if (b0) { v0 = s0; v2 = s1; } else { v1 = s0; v3 = s1; }
  uint32_t t0 = b1 ? v0 : v2, t1 = b1 ? v1 : v3;
  t0 = __shfl_xor_sync(0xffffffffu, t0, 2); t1 = __shfl_xor_sync(0xffffffffu, t1, 2);
  if (b1) { v0 = t0; v1 = t1; } else { v2 = t0; v3 = t1; }
}

#define TG(i)
#define TX(i)
#define TXC(i)
#define TSA(item, i)
#define TL_ENTRY(k)
#define TL_WAITED(k)
#define TL_END(k)
#define TS(item, i)
template<int TB> __device__ __forceinline__ void wgmma_rs_n64(float (&d)[32], uint32_t a0, uint32_t a1, uint32_t a2, uint32_t a3, uint64_t db, int scale_d) {
  asm volatile("{\n.reg .pred p;\nsetp.ne.b32 p, %37, 0;\n"
    "wgmma.mma_async.sync.aligned.m64n64k16.f32.bf16.bf16 {%0, %1, %2, %3, %4, %5, %6, %7, %8, %9, %10, %11, %12, %13, %14, %15, %16, %17, %18, %19, %20, %21, %22, %23, %24, %25, %26, %27, %28, %29, %30, %31}, {%32, %33, %34, %35}, %36, p, 1, 1, %38;\n}\n"
    : "+f"(d[0]), "+f"(d[1]), "+f"(d[2]), "+f"(d[3]), "+f"(d[4]), "+f"(d[5]), "+f"(d[6]), "+f"(d[7]), "+f"(d[8]), "+f"(d[9]), "+f"(d[10]), "+f"(d[11]), "+f"(d[12]), "+f"(d[13]), "+f"(d[14]), "+f"(d[15]), "+f"(d[16]), "+f"(d[17]), "+f"(d[18]), "+f"(d[19]), "+f"(d[20]), "+f"(d[21]), "+f"(d[22]), "+f"(d[23]), "+f"(d[24]), "+f"(d[25]), "+f"(d[26]), "+f"(d[27]), "+f"(d[28]), "+f"(d[29]), "+f"(d[30]), "+f"(d[31])
    : "r"(a0), "r"(a1), "r"(a2), "r"(a3), "l"(db), "r"(scale_d), "n"(TB));
}
template<int TB> __device__ __forceinline__ void wgmma_rs_n192(float (&d)[96], uint32_t a0, uint32_t a1, uint32_t a2, uint32_t a3, uint64_t db, int scale_d) {
  asm volatile("{\n.reg .pred p;\nsetp.ne.b32 p, %101, 0;\n"
    "wgmma.mma_async.sync.aligned.m64n192k16.f32.bf16.bf16 {%0, %1, %2, %3, %4, %5, %6, %7, %8, %9, %10, %11, %12, %13, %14, %15, %16, %17, %18, %19, %20, %21, %22, %23, %24, %25, %26, %27, %28, %29, %30, %31, %32, %33, %34, %35, %36, %37, %38, %39, %40, %41, %42, %43, %44, %45, %46, %47, %48, %49, %50, %51, %52, %53, %54, %55, %56, %57, %58, %59, %60, %61, %62, %63, %64, %65, %66, %67, %68, %69, %70, %71, %72, %73, %74, %75, %76, %77, %78, %79, %80, %81, %82, %83, %84, %85, %86, %87, %88, %89, %90, %91, %92, %93, %94, %95}, {%96, %97, %98, %99}, %100, p, 1, 1, %102;\n}\n"
    : "+f"(d[0]), "+f"(d[1]), "+f"(d[2]), "+f"(d[3]), "+f"(d[4]), "+f"(d[5]), "+f"(d[6]), "+f"(d[7]), "+f"(d[8]), "+f"(d[9]), "+f"(d[10]), "+f"(d[11]), "+f"(d[12]), "+f"(d[13]), "+f"(d[14]), "+f"(d[15]), "+f"(d[16]), "+f"(d[17]), "+f"(d[18]), "+f"(d[19]), "+f"(d[20]), "+f"(d[21]), "+f"(d[22]), "+f"(d[23]), "+f"(d[24]), "+f"(d[25]), "+f"(d[26]), "+f"(d[27]), "+f"(d[28]), "+f"(d[29]), "+f"(d[30]), "+f"(d[31]), "+f"(d[32]), "+f"(d[33]), "+f"(d[34]), "+f"(d[35]), "+f"(d[36]), "+f"(d[37]), "+f"(d[38]), "+f"(d[39]), "+f"(d[40]), "+f"(d[41]), "+f"(d[42]), "+f"(d[43]), "+f"(d[44]), "+f"(d[45]), "+f"(d[46]), "+f"(d[47]), "+f"(d[48]), "+f"(d[49]), "+f"(d[50]), "+f"(d[51]), "+f"(d[52]), "+f"(d[53]), "+f"(d[54]), "+f"(d[55]), "+f"(d[56]), "+f"(d[57]), "+f"(d[58]), "+f"(d[59]), "+f"(d[60]), "+f"(d[61]), "+f"(d[62]), "+f"(d[63]), "+f"(d[64]), "+f"(d[65]), "+f"(d[66]), "+f"(d[67]), "+f"(d[68]), "+f"(d[69]), "+f"(d[70]), "+f"(d[71]), "+f"(d[72]), "+f"(d[73]), "+f"(d[74]), "+f"(d[75]), "+f"(d[76]), "+f"(d[77]), "+f"(d[78]), "+f"(d[79]), "+f"(d[80]), "+f"(d[81]), "+f"(d[82]), "+f"(d[83]), "+f"(d[84]), "+f"(d[85]), "+f"(d[86]), "+f"(d[87]), "+f"(d[88]), "+f"(d[89]), "+f"(d[90]), "+f"(d[91]), "+f"(d[92]), "+f"(d[93]), "+f"(d[94]), "+f"(d[95])
    : "r"(a0), "r"(a1), "r"(a2), "r"(a3), "l"(db), "r"(scale_d), "n"(TB));
}
template<int TB> __device__ __forceinline__ void wgmma_ss_n128(float (&d)[64], uint64_t da, uint64_t db, int scale_d) {
  asm volatile("{\n.reg .pred p;\nsetp.ne.b32 p, %66, 0;\n"
    "wgmma.mma_async.sync.aligned.m64n128k16.f32.bf16.bf16 {%0, %1, %2, %3, %4, %5, %6, %7, %8, %9, %10, %11, %12, %13, %14, %15, %16, %17, %18, %19, %20, %21, %22, %23, %24, %25, %26, %27, %28, %29, %30, %31, %32, %33, %34, %35, %36, %37, %38, %39, %40, %41, %42, %43, %44, %45, %46, %47, %48, %49, %50, %51, %52, %53, %54, %55, %56, %57, %58, %59, %60, %61, %62, %63}, %64, %65, p, 1, 1, 0, %67;\n}\n"
    : "+f"(d[0]), "+f"(d[1]), "+f"(d[2]), "+f"(d[3]), "+f"(d[4]), "+f"(d[5]), "+f"(d[6]), "+f"(d[7]), "+f"(d[8]), "+f"(d[9]), "+f"(d[10]), "+f"(d[11]), "+f"(d[12]), "+f"(d[13]), "+f"(d[14]), "+f"(d[15]), "+f"(d[16]), "+f"(d[17]), "+f"(d[18]), "+f"(d[19]), "+f"(d[20]), "+f"(d[21]), "+f"(d[22]), "+f"(d[23]), "+f"(d[24]), "+f"(d[25]), "+f"(d[26]), "+f"(d[27]), "+f"(d[28]), "+f"(d[29]), "+f"(d[30]), "+f"(d[31]), "+f"(d[32]), "+f"(d[33]), "+f"(d[34]), "+f"(d[35]), "+f"(d[36]), "+f"(d[37]), "+f"(d[38]), "+f"(d[39]), "+f"(d[40]), "+f"(d[41]), "+f"(d[42]), "+f"(d[43]), "+f"(d[44]), "+f"(d[45]), "+f"(d[46]), "+f"(d[47]), "+f"(d[48]), "+f"(d[49]), "+f"(d[50]), "+f"(d[51]), "+f"(d[52]), "+f"(d[53]), "+f"(d[54]), "+f"(d[55]), "+f"(d[56]), "+f"(d[57]), "+f"(d[58]), "+f"(d[59]), "+f"(d[60]), "+f"(d[61]), "+f"(d[62]), "+f"(d[63])
    : "l"(da), "l"(db), "r"(scale_d), "n"(TB));
}
template<int TB> __device__ __forceinline__ void wgmma_ss_n192(float (&d)[96], uint64_t da, uint64_t db, int scale_d) {
  asm volatile("{\n.reg .pred p;\nsetp.ne.b32 p, %98, 0;\n"
    "wgmma.mma_async.sync.aligned.m64n192k16.f32.bf16.bf16 {%0, %1, %2, %3, %4, %5, %6, %7, %8, %9, %10, %11, %12, %13, %14, %15, %16, %17, %18, %19, %20, %21, %22, %23, %24, %25, %26, %27, %28, %29, %30, %31, %32, %33, %34, %35, %36, %37, %38, %39, %40, %41, %42, %43, %44, %45, %46, %47, %48, %49, %50, %51, %52, %53, %54, %55, %56, %57, %58, %59, %60, %61, %62, %63, %64, %65, %66, %67, %68, %69, %70, %71, %72, %73, %74, %75, %76, %77, %78, %79, %80, %81, %82, %83, %84, %85, %86, %87, %88, %89, %90, %91, %92, %93, %94, %95}, %96, %97, p, 1, 1, 0, %99;\n}\n"
    : "+f"(d[0]), "+f"(d[1]), "+f"(d[2]), "+f"(d[3]), "+f"(d[4]), "+f"(d[5]), "+f"(d[6]), "+f"(d[7]), "+f"(d[8]), "+f"(d[9]), "+f"(d[10]), "+f"(d[11]), "+f"(d[12]), "+f"(d[13]), "+f"(d[14]), "+f"(d[15]), "+f"(d[16]), "+f"(d[17]), "+f"(d[18]), "+f"(d[19]), "+f"(d[20]), "+f"(d[21]), "+f"(d[22]), "+f"(d[23]), "+f"(d[24]), "+f"(d[25]), "+f"(d[26]), "+f"(d[27]), "+f"(d[28]), "+f"(d[29]), "+f"(d[30]), "+f"(d[31]), "+f"(d[32]), "+f"(d[33]), "+f"(d[34]), "+f"(d[35]), "+f"(d[36]), "+f"(d[37]), "+f"(d[38]), "+f"(d[39]), "+f"(d[40]), "+f"(d[41]), "+f"(d[42]), "+f"(d[43]), "+f"(d[44]), "+f"(d[45]), "+f"(d[46]), "+f"(d[47]), "+f"(d[48]), "+f"(d[49]), "+f"(d[50]), "+f"(d[51]), "+f"(d[52]), "+f"(d[53]), "+f"(d[54]), "+f"(d[55]), "+f"(d[56]), "+f"(d[57]), "+f"(d[58]), "+f"(d[59]), "+f"(d[60]), "+f"(d[61]), "+f"(d[62]), "+f"(d[63]), "+f"(d[64]), "+f"(d[65]), "+f"(d[66]), "+f"(d[67]), "+f"(d[68]), "+f"(d[69]), "+f"(d[70]), "+f"(d[71]), "+f"(d[72]), "+f"(d[73]), "+f"(d[74]), "+f"(d[75]), "+f"(d[76]), "+f"(d[77]), "+f"(d[78]), "+f"(d[79]), "+f"(d[80]), "+f"(d[81]), "+f"(d[82]), "+f"(d[83]), "+f"(d[84]), "+f"(d[85]), "+f"(d[86]), "+f"(d[87]), "+f"(d[88]), "+f"(d[89]), "+f"(d[90]), "+f"(d[91]), "+f"(d[92]), "+f"(d[93]), "+f"(d[94]), "+f"(d[95])
    : "l"(da), "l"(db), "r"(scale_d), "n"(TB));
}
template<int TB> __device__ __forceinline__ void wgmma_ss_n80(float (&d)[40], uint64_t da, uint64_t db, int scale_d) {
  asm volatile("{\n.reg .pred p;\nsetp.ne.b32 p, %42, 0;\n"
    "wgmma.mma_async.sync.aligned.m64n80k16.f32.bf16.bf16 {%0, %1, %2, %3, %4, %5, %6, %7, %8, %9, %10, %11, %12, %13, %14, %15, %16, %17, %18, %19, %20, %21, %22, %23, %24, %25, %26, %27, %28, %29, %30, %31, %32, %33, %34, %35, %36, %37, %38, %39}, %40, %41, p, 1, 1, 0, %43;\n}\n"
    : "+f"(d[0]), "+f"(d[1]), "+f"(d[2]), "+f"(d[3]), "+f"(d[4]), "+f"(d[5]), "+f"(d[6]), "+f"(d[7]), "+f"(d[8]), "+f"(d[9]), "+f"(d[10]), "+f"(d[11]), "+f"(d[12]), "+f"(d[13]), "+f"(d[14]), "+f"(d[15]), "+f"(d[16]), "+f"(d[17]), "+f"(d[18]), "+f"(d[19]), "+f"(d[20]), "+f"(d[21]), "+f"(d[22]), "+f"(d[23]), "+f"(d[24]), "+f"(d[25]), "+f"(d[26]), "+f"(d[27]), "+f"(d[28]), "+f"(d[29]), "+f"(d[30]), "+f"(d[31]), "+f"(d[32]), "+f"(d[33]), "+f"(d[34]), "+f"(d[35]), "+f"(d[36]), "+f"(d[37]), "+f"(d[38]), "+f"(d[39])
    : "l"(da), "l"(db), "r"(scale_d), "n"(TB));
}

__device__ __align__(128) float g_mod[6 * D_];
__device__ __align__(128) float g_modp[2][2 * D_];
__device__ __align__(1024) bf16 g_h[S_ * D_];
__device__ __align__(1024) bf16 g_o[S_ * HD_];
__device__ __align__(1024) bf16 g_xch[16 * 2 * 4 * 4 * 128 * 80];
__device__ __align__(1024) bf16 g_w1t[D_ * D_];
__device__ __align__(1024) bf16 g_w2t[D_ * D_];
__device__ __align__(1024) bf16 g_w4t[D_ * F_];
__device__ __align__(32) float g_st1[S_ * 8];
__device__ __align__(32) float g_st2[S_ * 2];
__device__ __align__(32) float g_vec[3 * D_ + F_ + 8];
__device__ unsigned g_flag[1024];
enum { F_XCH = 0, F_XA = 256, F_US = 272, F_X1 = 288, F_G = 304, F_PREP = 320, F_MOD2 = 352, F_O = 512 };
__device__ __align__(1024) bf16 g_xa[S_ * D_];
__device__ __align__(1024) bf16 g_us[(S_ + 4) * D_];
__device__ __align__(1024) bf16 g_x1[S_ * D_];
__device__ __align__(1024) bf16 g_g[S_ * F_];

__device__ __forceinline__ void row_stats(const float (&v)[20], float& mean, float& rstd) {
  float s = 0.f;
#pragma unroll
  for (int i = 0; i < 20; i++) s += v[i];
  mean = warp_sum(s) * (1.f / D_);
  float q = 0.f;
#pragma unroll
  for (int i = 0; i < 20; i++) { float d = v[i] - mean; q = fmaf(d, d, q); }
  rstd = rsqrtf(warp_sum(q) * (1.f / D_) + LN_EPS);
}
__device__ __forceinline__ void load_row_bf16(const bf16* p, int lane, float (&v)[20]) {
#pragma unroll
  for (int i = 0; i < 5; i++) {
    uint2 u = *reinterpret_cast<const uint2*>(p + (lane + 32 * i) * 4);
    v[4 * i] = bf_lo(u.x); v[4 * i + 1] = bf_hi(u.x); v[4 * i + 2] = bf_lo(u.y); v[4 * i + 3] = bf_hi(u.y);
  }
}
__device__ __forceinline__ void store_row_bf16(bf16* p, int lane, const float (&v)[20]) {
#pragma unroll
  for (int i = 0; i < 5; i++) {
    uint2 u; u.x = pack_bf16(v[4 * i], v[4 * i + 1]); u.y = pack_bf16(v[4 * i + 2], v[4 * i + 3]);
    *reinterpret_cast<uint2*>(p + (lane + 32 * i) * 4) = u;
  }
}
__device__ __forceinline__ void load_row_f32(const float* p, int lane, float (&v)[20]) {
#pragma unroll
  for (int i = 0; i < 5; i++) {
    float4 u = *reinterpret_cast<const float4*>(p + (lane + 32 * i) * 4);
    v[4 * i] = u.x; v[4 * i + 1] = u.y; v[4 * i + 2] = u.z; v[4 * i + 3] = u.w;
  }
}

__device__ __forceinline__ float silu_bf(float c) { return bf_round(__fdividef(c, 1.f + __expf(-c))); }
__device__ __forceinline__ void fma8(float (&acc)[8], float s, const uint4& w) {
  acc[0] = fmaf(s, bf_lo(w.x), acc[0]); acc[1] = fmaf(s, bf_hi(w.x), acc[1]); acc[2] = fmaf(s, bf_lo(w.y), acc[2]); acc[3] = fmaf(s, bf_hi(w.y), acc[3]);
  acc[4] = fmaf(s, bf_lo(w.z), acc[4]); acc[5] = fmaf(s, bf_hi(w.z), acc[5]); acc[6] = fmaf(s, bf_lo(w.w), acc[6]); acc[7] = fmaf(s, bf_hi(w.w), acc[7]);
}
__global__ void __launch_bounds__(256) mod_kernel(const bf16* __restrict__ c, const bf16* __restrict__ w_mod) {
  TL_ENTRY(0);
  pdl_launch();
  __shared__ float red[8][32];
  const int t = threadIdx.x, cg = t & 3, r0 = (blockIdx.x / 40) * 320 + (t >> 2), strip = blockIdx.x % 40;
  uint4 w[5];
  float cv[5];
#pragma unroll
  for (int i = 0; i < 5; i++) {
    w[i] = __ldg(reinterpret_cast<const uint4*>(w_mod + (size_t)(r0 + 64 * i) * (6 * D_) + strip * 32 + cg * 8));
    cv[i] = __bfloat162float(c[r0 + 64 * i]);
  }
  if (blockIdx.x < 14) { const int i = blockIdx.x * 256 + t; if (i < 3 * D_ + F_) g_vec[i] = 0.f; }
  else if (blockIdx.x < 18) g_flag[(blockIdx.x - 14) * 256 + t] = 0u;
  float acc[8];
#pragma unroll
  for (int j = 0; j < 8; j++) acc[j] = 0.f;
#pragma unroll
  for (int i = 0; i < 5; i++) fma8(acc, silu_bf(cv[i]), w[i]);
#pragma unroll 1
  for (int o = 4; o < 32; o <<= 1) {
#pragma unroll
    for (int j = 0; j < 8; j++) acc[j] += __shfl_xor_sync(0xffffffffu, acc[j], o);
  }
  if ((t & 31) < 4) {
    *reinterpret_cast<float4*>(&red[t >> 5][cg * 8]) = make_float4(acc[0], acc[1], acc[2], acc[3]);
    *reinterpret_cast<float4*>(&red[t >> 5][cg * 8 + 4]) = make_float4(acc[4], acc[5], acc[6], acc[7]);
  }
  __syncthreads();
  if (t < 32) {
    float s = 0.f;
#pragma unroll
    for (int w8 = 0; w8 < 8; w8++) s += red[w8][t];
    g_modp[blockIdx.x / 40][strip * 32 + t] = s;
    if (t == 0) TL_END(0);
  }
}

__global__ void __launch_bounds__(256) ln1_kernel(const bf16* __restrict__ x) {
  TL_ENTRY(1);
  pdl_launch();
  const int lane = threadIdx.x & 31, row = blockIdx.x * 8 + (threadIdx.x >> 5);
  float v[20];
  load_row_bf16(x + (size_t)row * D_, lane, v);
  float mean, rstd;
  row_stats(v, mean, rstd);
  if (lane < 8) g_st1[row * 8 + lane] = 0.f;
  if (lane < 2) g_st2[row * 2 + lane] = 0.f;
  pdl_wait();
  if (threadIdx.x == 0) TL_WAITED(1);
  float s0[20], s1[20], c0[20], c1[20];
  load_row_f32(g_modp[0], lane, s0); load_row_f32(g_modp[1], lane, s1);
  load_row_f32(g_modp[0] + D_, lane, c0); load_row_f32(g_modp[1] + D_, lane, c1);
#pragma unroll
  for (int i = 0; i < 20; i++) v[i] = fmaf((v[i] - mean) * rstd, bf_round(1.f + bf_round(c0[i] + c1[i])), bf_round(s0[i] + s1[i]));
  store_row_bf16(g_h + (size_t)row * D_, lane, v);
  if (threadIdx.x == 0) TL_END(1);
}

constexpr int PREP_JOBS = 200 + 200 + 480 + 480;
struct PrepW { const bf16 *w1, *w2, *w3, *w4, *c, *wmod; };
__device__ __forceinline__ void flag_wait(const unsigned* p, unsigned target);
__device__ __forceinline__ void prep_warp(const PrepW& pw, bf16 (*tile)[72], int lane) {
  if (blockIdx.x < 80) {
    const bf16* wp = pw.wmod + (size_t)(lane >> 2) * (6 * D_) + 2 * D_ + blockIdx.x * 32 + (lane & 3) * 8;
    float acc[8];
#pragma unroll
    for (int j = 0; j < 8; j++) acc[j] = 0.f;
#pragma unroll 1
    for (int i = 0; i < 80; i += 4) {
      uint4 w[4];
      float cv[4];
#pragma unroll
      for (int e = 0; e < 4; e++) { w[e] = __ldg(reinterpret_cast<const uint4*>(wp + (size_t)(i + e) * 8 * (6 * D_))); cv[e] = __bfloat162float(pw.c[(i + e) * 8 + (lane >> 2)]); }
#pragma unroll
      for (int e = 0; e < 4; e++) fma8(acc, silu_bf(cv[e]), w[e]);
    }
    const bool one = blockIdx.x >= 40 && blockIdx.x < 60;
#pragma unroll
    for (int j = 0; j < 8; j++) {
      acc[j] += __shfl_xor_sync(0xffffffffu, acc[j], 4); acc[j] += __shfl_xor_sync(0xffffffffu, acc[j], 8); acc[j] += __shfl_xor_sync(0xffffffffu, acc[j], 16);
      const float v = bf_round(acc[j]);
      if (lane < 4) g_mod[2 * D_ + blockIdx.x * 32 + lane * 8 + j] = one ? bf_round(1.f + v) : v;
    }
    __syncwarp();
    if (lane == 0) {
      asm volatile("fence.acq_rel.gpu;" ::: "memory");
      asm volatile("red.relaxed.gpu.global.add.u32 [%0], 1;" :: "l"(g_flag + F_MOD2) : "memory");
    }
  }
  flag_wait(g_flag + F_MOD2, 80);
#pragma unroll 1
  for (int job = blockIdx.x; job < PREP_JOBS; job += gridDim.x) {
    const bf16* src; bf16* dst; int ld = D_, ldd = D_, kt, nt, kind = 1;
    if (job < 200) { src = pw.w1; dst = g_w1t; kt = job / 10; nt = job % 10; kind = 0; }
    else if (job < 400) { src = pw.w2; dst = g_w2t; kt = (job - 200) / 10; nt = (job - 200) % 10; }
    else if (job < 880) { src = pw.w4; dst = g_w4t; ldd = F_; kt = (job - 400) / 10; nt = (job - 400) % 10; }
    else { src = pw.w3; dst = nullptr; ld = F_; kt = (job - 880) / 24; nt = (job - 880) % 24; kind = 2; }
    src += (size_t)(kt * 32 + (lane >> 3)) * ld + nt * 64 + (lane & 7) * 8;
    __syncwarp();
#pragma unroll
    for (int h = 0; h < 2; h++) {
      uint4 v[4];
#pragma unroll
      for (int i = 0; i < 4; i++) v[i] = __ldg(reinterpret_cast<const uint4*>(src + (size_t)(h * 16 + i * 4) * ld));
#pragma unroll
      for (int i = 0; i < 4; i++) *reinterpret_cast<uint4*>(&tile[h * 16 + i * 4 + (lane >> 3)][(lane & 7) * 8]) = v[i];
    }
    __syncwarp();
    const float* pa = g_mod + 4 * D_ + kt * 32;
    const float* pb = g_mod + 3 * D_ + kt * 32;
#pragma unroll 1
    for (int h = 0; h < 2; h++) {
      const int n = lane + 32 * h;
      float sa = 0.f, sb = 0.f, sc = 0.f;
#pragma unroll 1
      for (int c = 0; c < 4; c++) {
        uint32_t u[4];
#pragma unroll
        for (int e = 0; e < 4; e++) {
          const int k = c * 8 + 2 * e;
          float lo = __bfloat162float(tile[k][n]), hi = __bfloat162float(tile[k + 1][n]);
          sc += lo + hi;
          if (kind == 0) {
            const float2 a = __ldcg(reinterpret_cast<const float2*>(pa + k)), b = __ldcg(reinterpret_cast<const float2*>(pb + k));
            sb = fmaf(b.x, lo, fmaf(b.y, hi, sb));
            lo *= a.x; hi *= a.y;
          }
          u[e] = pack_bf16(lo, hi);
          sa += bf_lo(u[e]) + bf_hi(u[e]);
        }
        if (kind != 2) *reinterpret_cast<uint4*>(dst + (size_t)(nt * 64 + n) * ldd + kt * 32 + c * 8) = make_uint4(u[0], u[1], u[2], u[3]);
      }
      if (kind == 0) { atomicAdd(&g_vec[nt * 64 + n], sa); atomicAdd(&g_vec[D_ + nt * 64 + n], sb); atomicAdd(&g_vec[2 * D_ + nt * 64 + n], sc); }
      else if (kind == 2) atomicAdd(&g_vec[3 * D_ + nt * 64 + n], sc);
    }
  }
  __syncwarp();
  if (lane == 0) {
    asm volatile("fence.acq_rel.gpu;" ::: "memory");
    asm volatile("red.relaxed.gpu.global.add.u32 [%0], 1;" :: "l"(g_flag + F_PREP) : "memory");
  }
}

constexpr int A_NSLOT = 9;
constexpr int A_SLOT = 24576;
constexpr int A_NKV = S_ / 64;
constexpr int PREP_CTAS = 128;

struct Ring {
  uint32_t slot, phase;
  __device__ __forceinline__ void adv(int n) { if (++slot == (uint32_t)n) { slot = 0; phase ^= 1; } }
};
constexpr int T_PAR = A_NSLOT * A_SLOT + 384;
constexpr int T_PREP = T_PAR + 3712;
constexpr int T_SMEM = T_PREP + 32 * 72 * 2 + 1024;
enum { P_OGA = 0, P_OA = 80, P_OB = 160, P_VA = 240, P_VB = 320, P_VC = 400, P_A2 = 480, P_B2 = 560, P_GB = 640, P_CS3 = 720, P_SC = 912 };

__device__ __forceinline__ void flag_wait(const unsigned* p, unsigned target) {
  asm volatile(
      "{\n.reg .pred p;\n.reg .u32 n, v;\n"
      "mov.u32 n, 0;\n"
      "SPIN:\n"
      "ld.relaxed.gpu.global.u32 v, [%0];\n"
      "setp.ge.u32 p, v, %1;\n"
      "@p bra DONE;\n"
      "add.u32 n, n, 1;\n"
      "setp.gt.u32 p, n, 4194304;\n"
      "@p trap;\n"
      "bra SPIN;\n"
      "DONE:\n}\n" :: "l"(p), "r"(target) : "memory");
}
__device__ __forceinline__ void fence_async_global() { asm volatile("fence.proxy.async.global;" ::: "memory"); }
__device__ __forceinline__ float lds_f(uint32_t a) { float v; asm volatile("ld.shared.f32 %0, [%1];" : "=f"(v) : "r"(a)); return v; }
__device__ __forceinline__ float2 lds_f2(uint32_t a) { float2 v; asm volatile("ld.shared.v2.f32 {%0, %1}, [%2];" : "=f"(v.x), "=f"(v.y) : "r"(a)); return v; }
__device__ __forceinline__ uint4 ldcg4(const void* p) { return __ldcg(reinterpret_cast<const uint4*>(p)); }

__device__ __forceinline__ void sts_f2(uint32_t a, float x, float y) { asm volatile("st.shared.v2.f32 [%0], {%1, %2};" :: "r"(a), "f"(x), "f"(y) : "memory"); }
__device__ __forceinline__ void sts_u4(uint32_t a, uint4 v) { asm volatile("st.shared.v4.u32 [%0], {%1, %2, %3, %4};" :: "r"(a), "r"(v.x), "r"(v.y), "r"(v.z), "r"(v.w) : "memory"); }
__device__ __forceinline__ void sts_u1(uint32_t a, uint32_t v) { asm volatile("st.shared.u32 [%0], %1;" :: "r"(a), "r"(v) : "memory"); }
__device__ __forceinline__ void fence_async_smem() { asm volatile("fence.proxy.async.shared::cta;" ::: "memory"); }
__device__ __forceinline__ void bulk_store(void* dst, uint32_t src, uint32_t bytes) {
  asm volatile("cp.async.bulk.global.shared::cta.bulk_group [%0], [%1], %2;" :: "l"(dst), "r"(src), "r"(bytes) : "memory");
}
__device__ __forceinline__ void bulk_red_f32(void* dst, uint32_t src, uint32_t bytes) {
  asm volatile("cp.reduce.async.bulk.global.shared::cta.bulk_group.add.f32 [%0], [%1], %2;" :: "l"(dst), "r"(src), "r"(bytes) : "memory");
}
__device__ __forceinline__ void tma_store2d(const CUtensorMap* m, uint32_t src, int c0, int c1) {
  asm volatile("cp.async.bulk.tensor.2d.global.shared::cta.bulk_group [%0, {%2, %3}], [%1];" :: "l"(m), "r"(src), "r"(c0), "r"(c1) : "memory");
}
__device__ __forceinline__ void bulk_done() { asm volatile("cp.async.bulk.commit_group;\ncp.async.bulk.wait_group 0;" ::: "memory"); }
__device__ __forceinline__ void flag_add(unsigned* f) { asm volatile("red.relaxed.gpu.global.add.u32 [%0], 1;" :: "l"(f) : "memory"); }
__device__ __forceinline__ float4 lds_f4(uint32_t a) { return *reinterpret_cast<const float4*>(__cvta_shared_to_generic(a)); }
__device__ __forceinline__ uint4 lds_u4(uint32_t a) { return *reinterpret_cast<const uint4*>(__cvta_shared_to_generic(a)); }
__device__ __forceinline__ void lds8(uint32_t a, float (&v)[8]) {
  const float4 p = lds_f4(a), q = lds_f4(a + 16);
  v[0] = p.x; v[1] = p.y; v[2] = p.z; v[3] = p.w; v[4] = q.x; v[5] = q.y; v[6] = q.z; v[7] = q.w;
}
__device__ __forceinline__ void lds8_bf(uint32_t a, float (&v)[8]) {
  const uint4 u = lds_u4(a);
  v[0] = bf_lo(u.x); v[1] = bf_hi(u.x); v[2] = bf_lo(u.y); v[3] = bf_hi(u.y); v[4] = bf_lo(u.z); v[5] = bf_hi(u.z); v[6] = bf_lo(u.w); v[7] = bf_hi(u.w);
}
__device__ __forceinline__ uint4 pack8(const float (&v)[8]) {
  return make_uint4(pack_bf16(v[0], v[1]), pack_bf16(v[2], v[3]), pack_bf16(v[4], v[5]), pack_bf16(v[6], v[7]));
}
__device__ __forceinline__ void mbar_wait_c(uint32_t a, uint32_t ph) {
  asm volatile("{\n.reg .pred p;\nSPIN:\nmbarrier.try_wait.parity.shared::cta.b64 p, [%0], %1;\n@!p bra SPIN;\n}\n" :: "r"(a), "r"(ph) : "memory");
}
constexpr int ST_P = 80;
constexpr int E_TILE = 128 * 80 * 2;

struct Maps { CUtensorMap h, wq, k, v, o, wo3, wo2, xa, w1t, us, w2t, x1, w3, g, w4t, ex, exa, ex1, sxa, sus, sx1, sout; };
struct PfList { const uint8_t* p[6]; };

constexpr int M_AOFF = 102400, M_NA = 7;

__global__ void __cluster_dims__(2, 1, 1) __launch_bounds__(384, 1)
fused_kernel(const __grid_constant__ Maps tm, const __grid_constant__ PfList pf, const __grid_constant__ PrepW pw, const bf16* __restrict__ x, bf16* __restrict__ out) {
  extern __shared__ uint8_t smem_raw[];
  const uint32_t sb = (smem_u32(smem_raw) + 1023) & ~1023u;
  TL_ENTRY(2);
  const uint32_t bar_full = sb + A_NSLOT * A_SLOT;
  const uint32_t bar_empty = bar_full + 8 * A_NSLOT;
  const uint32_t bar_sig = bar_empty + 8 * A_NSLOT;
  const uint32_t mb_full = bar_sig + 16;
  const uint32_t mb_empty = mb_full + 96;
  const uint32_t par = sb + T_PAR;
  float* parf = reinterpret_cast<float*>(smem_raw + (par - smem_u32(smem_raw)));
  uint32_t rank;
  asm volatile("mov.u32 %0, %%cluster_ctarank;" : "=r"(rank));
  const int cid = blockIdx.x >> 1;
  const int wid = __shfl_sync(0xffffffffu, threadIdx.x >> 5, 0);
  const int wg = wid >> 2;
  const int qtile = (cid & 7) * 2 + rank, hbase = cid >> 3;
  const int o_qt = qtile, o_nh = (cid >> 3) & 1, o_ks = cid >> 4;
  const int o_col = o_nh * 320 + o_ks * 80;
  const int qt = cid >> 2, js = (cid & 3) * 2 + rank;
  if (threadIdx.x == 0) {
    for (int i = 0; i < A_NSLOT; i++) { mbar_init(bar_full + 8 * i, 1); mbar_init(bar_empty + 8 * i, 16); }
    mbar_init(bar_sig, 4); mbar_init(bar_sig + 8, 4);
    for (int i = 0; i < 12; i++) { mbar_init(mb_full + 8 * i, 1); mbar_init(mb_empty + 8 * i, i < 5 ? 8 : 16); }
    asm volatile("fence.mbarrier_init.release.cluster;" ::: "memory");
    prefetch_tmap(&tm.h); prefetch_tmap(&tm.wq); prefetch_tmap(&tm.k); prefetch_tmap(&tm.v);
  }
  __syncthreads();
  cluster_sync();

  if (wg == 0) {
    asm volatile("setmaxnreg.dec.sync.aligned.u32 40;");
    if (wid == 0) {
      Ring r{0, 1};
#define P_ACQ(bytes_) do { mbar_wait(bar_empty + 8 * r.slot, r.phase); mbar_expect_e(bar_full + 8 * r.slot, bytes_); } while (0)
#define P_DST (sb + r.slot * A_SLOT)
#define P_BAR (bar_full + 8 * r.slot)
      uint64_t pol_ef;
      asm volatile("createpolicy.fractional.L2::evict_first.b64 %0, 1.0;" : "=l"(pol_ef));
      if (qtile < 10) l2_prefetch_t3d(&tm.wq, 0, qtile * 64, hbase * 3);
      else l2_prefetch_t3d((qtile & 1) ? &tm.v : &tm.k, 0, hbase * S_ + ((qtile - 10) >> 1) * 64, 0);
      pdl_wait();
      TL_WAITED(2);
#pragma unroll 1
      for (int item = 0; item < 4; item++) {
        const int head = hbase + 8 * item;
#pragma unroll 1
        for (int kb = 0; kb < 10; kb++) {
          P_ACQ(16384);
          tma2d(P_DST, &tm.h, P_BAR, kb * 64, qtile * 128);
          r.adv(A_NSLOT);
          P_ACQ(A_SLOT);
          if ((uint32_t)(kb & 1) == rank) tma3d_mc_hint(P_DST, &tm.wq, P_BAR, 0, kb * 64, head * 3, 3, pol_ef);
          r.adv(A_NSLOT);
        }
#pragma unroll 1
        for (int j = 0; j <= A_NKV; j++) {
          if (j < A_NKV) {
            P_ACQ(A_SLOT);
            if (rank == 0) tma3d_mc_hint(P_DST, &tm.k, P_BAR, 0, head * S_ + j * 64, 0, 3, pol_ef);
            r.adv(A_NSLOT);
          }
          if (j > 0) {
            P_ACQ(A_SLOT);
            if (rank == 1) tma3d_mc_hint(P_DST, &tm.v, P_BAR, 0, head * S_ + (j - 1) * 64, 0, 3, pol_ef);
            r.adv(A_NSLOT);
          }
          if (item < 3 && j == 16 && qtile < 10) l2_prefetch_t3d(&tm.wq, 0, qtile * 64, (head + 8) * 3);
          if (item == 3 && (j & 3) == 0) {
            const int c = (j >> 2) * 128 + blockIdx.x;
            if (c < 980) {
              const int li = c < 480 ? 0 : c < 600 ? 1 : c < 720 ? 2 : c < 880 ? 3 : c < 930 ? 4 : 5;
              const int c0 = c < 480 ? 0 : c < 600 ? 480 : c < 720 ? 600 : c < 880 ? 720 : c < 930 ? 880 : 930;
              l2_prefetch16k(pf.p[li] + (size_t)(c - c0) * 16384);
            }
          }
          if (item == 3) {
            if (j >= 6 && j < 24) {
              const int kb = j - 6;
              l2_prefetch_t2d(&tm.o, ((kb / 6) * 8 + 2 * o_ks + (kb % 6) / 3) * DH_ + (kb % 3) * 64, o_qt * 128);
            }
            if (j >= 24 && j < 30) flag_wait(g_flag + F_O + o_qt * 32 + ((j - 24) >> 1) * 8 + 2 * o_ks + (j & 1), 2);
            if (j == 0 && threadIdx.x == 0) {
              prefetch_tmap(&tm.o); prefetch_tmap(&tm.wo3); prefetch_tmap(&tm.wo2); prefetch_tmap(&tm.xa); prefetch_tmap(&tm.w1t); prefetch_tmap(&tm.us);
              prefetch_tmap(&tm.w2t); prefetch_tmap(&tm.x1); prefetch_tmap(&tm.w3); prefetch_tmap(&tm.g); prefetch_tmap(&tm.w4t);
              prefetch_tmap(&tm.ex); prefetch_tmap(&tm.exa); prefetch_tmap(&tm.ex1);
              prefetch_tmap(&tm.sxa); prefetch_tmap(&tm.sus); prefetch_tmap(&tm.sx1); prefetch_tmap(&tm.sout);
            }
          }
        }
      }
#pragma unroll 1
      for (int kb = 0; kb < 24; kb++) {
        const int head = (kb / 6) * 8 + 2 * o_ks + (kb % 6) / 3;
        const int kcol = head * DH_ + (kb % 3) * 64;
        P_ACQ(24576);
        if (rank == 0) tma3d_mc(P_DST, &tm.wo3, P_BAR, 0, kcol, o_nh * 5, 3);
        r.adv(A_NSLOT);
        P_ACQ(16384);
        if (rank == 1) tma3d_mc(P_DST, &tm.wo2, P_BAR, 0, kcol, o_nh * 5 + 3, 3);
        r.adv(A_NSLOT);
        if (kb == 18 || kb == 21) flag_wait(g_flag + F_O + o_qt * 32 + head, 2);
        if (kb % 3 == 0) fence_async_global();
        P_ACQ(16384);
        tma2d(P_DST, &tm.o, P_BAR, kcol, o_qt * 128);
        r.adv(A_NSLOT);
      }
      P_ACQ(E_TILE);
      tma2d(P_DST, &tm.ex, P_BAR, o_col, o_qt * 128);
      r.adv(A_NSLOT);
      flag_wait(g_flag + F_XCH + (o_qt * 2 + o_nh) * 4 + o_ks, 6);
      fence_async_global();
#pragma unroll 1
      for (int i = 0; i < 3; i++) {
        P_ACQ(E_TILE);
        bulk_load(P_DST, g_xch + (size_t)((((o_qt * 2 + o_nh) * 4 + o_ks) * 4) + ((o_ks + 1 + i) & 3)) * (E_TILE / 2), E_TILE, P_BAR);
        r.adv(A_NSLOT);
      }
      flag_wait(g_flag + F_PREP, PREP_CTAS);
      fence_async_global();
#pragma unroll 1
      for (int i = 0; i < A_NSLOT; i++) { mbar_wait(bar_empty + 8 * r.slot, r.phase); r.adv(A_NSLOT); }
      Ring ra{0, 1};
      uint32_t bpar = 0x1f;
#pragma unroll 1
      for (int ph = 0; ph < 4; ph++) {
        const CUtensorMap* ma = ph == 0 ? &tm.xa : ph == 1 ? &tm.us : ph == 2 ? &tm.x1 : &tm.g;
        const CUtensorMap* mb = ph == 0 ? &tm.w1t : ph == 1 ? &tm.w2t : ph == 2 ? &tm.w3 : &tm.w4t;
        const int nkb = ph == 3 ? 24 : 10;
        const int nbl = ph == 2 ? 10 : nkb / 2;
        const int nel = ph == 1 ? 1 : ph == 3 ? 2 : 0;
        const uint32_t nbs = ph == 2 ? 4 : 5, bsz = ph == 2 ? 24576 : 20480;
        int bl = 0; uint32_t bs = 0;
#pragma unroll 1
        for (int i = 0; i < 5; i++) mbar_wait(mb_empty + 8 * i, (bpar >> i) & 1);
#define T_LOADB() do { mbar_wait(mb_empty + 8 * bs, (bpar >> bs) & 1); bpar ^= 1u << bs; mbar_expect_e(mb_full + 8 * bs, bsz);    \
                       if (bl < nbl) tma3d(sb + bs * bsz, mb, mb_full + 8 * bs, 0, ph == 2 ? bl * 64 : js * 80, ph == 2 ? js * 3 : bl * 2); \
                       else tma2d(sb + bs * bsz, bl == nbl ? &tm.exa : &tm.ex1, mb_full + 8 * bs, js * 80, qt * 128); \
                       bl++; if (++bs == nbs) bs = 0; } while (0)
#pragma unroll 1
        for (uint32_t i = 0; i < nbs; i++) T_LOADB();
        TX(8 + ph * 4);
        const unsigned* fl = g_flag + F_XA + 16 * ph;
        flag_wait(fl + qt, 16);
        if (ph == 1) { if (qt > 0) flag_wait(fl + qt - 1, 16); if (qt < 15) flag_wait(fl + qt + 1, 16); }
        TX(9 + ph * 4);
        fence_async_global();
#pragma unroll 1
        for (int kb = 0; kb < nkb; kb++) {
          mbar_wait(mb_empty + 40 + 8 * ra.slot, ra.phase);
          mbar_expect_e(mb_full + 40 + 8 * ra.slot, 16384);
          tma2d_mc(sb + M_AOFF + ra.slot * 16384 + rank * 8192, ma, mb_full + 40 + 8 * ra.slot, kb * 64, qt * 128 + (int)rank * 64, 3);
          ra.adv(M_NA);
          while (bl < nbl + nel && (kb == nkb - 1 || kb >= (ph == 2 ? bl + 2 : 2 * bl - 3))) T_LOADB();
        }
      }
    } else if (wid < 3) {
      const int w = wid - 1, lane = threadIdx.x & 31;
#pragma unroll 1
      for (int sig = 0; sig < 4; sig++) {
        mbar_wait(bar_sig + 8 * w, sig & 1);
        if (lane == 0) {
          asm volatile("fence.acq_rel.gpu;" ::: "memory");
          flag_add(g_flag + F_O + qtile * 32 + hbase + 8 * sig);
        }
        __syncwarp();
      }
    } else {
      const int lane = threadIdx.x & 31;
      pdl_wait();
      prep_warp(pw, reinterpret_cast<bf16(*)[72]>(smem_raw + (sb + T_PREP - smem_u32(smem_raw))), lane);
      flag_wait(g_flag + F_PREP, PREP_CTAS);
#pragma unroll 1
      for (int i = lane; i < P_SC; i += 32) {
        const int v = i < P_CS3 ? i / 80 : 9, j = i - (i < P_CS3 ? v * 80 : P_CS3);
        const float* src = v == 0 ? g_mod + 2 * D_ + o_col : v == 1 ? g_mod + 4 * D_ + o_col : v == 2 ? g_mod + 3 * D_ + o_col
                         : v < 6 ? g_vec + (v - 3) * D_ + js * 80 : v == 6 ? g_mod + 4 * D_ + js * 80 : v == 7 ? g_mod + 3 * D_ + js * 80
                         : v == 8 ? g_mod + 5 * D_ + js * 80 : g_vec + 3 * D_ + js * 192;
        parf[i] = __ldcg(src + j);
      }
      float sv[5] = {0.f, 0.f, 0.f, 0.f, 0.f};
#pragma unroll 1
      for (int i = lane; i < D_; i += 32) {
        const float a = __ldcg(g_mod + 4 * D_ + i), b = __ldcg(g_mod + 3 * D_ + i);
        sv[0] += a; sv[1] = fmaf(a, a, sv[1]); sv[2] = fmaf(a, b, sv[2]); sv[3] += b; sv[4] = fmaf(b, b, sv[4]);
      }
#pragma unroll 1
      for (int o_ = 16; o_ > 0; o_ >>= 1) {
#pragma unroll
        for (int i = 0; i < 5; i++) sv[i] += __shfl_xor_sync(0xffffffffu, sv[i], o_);
      }
      if (lane == 0) {
#pragma unroll
        for (int i = 0; i < 5; i++) parf[P_SC + i] = sv[i];
      }
      bar_arrive(6, 288);
    }
    __syncwarp();
    cluster_sync();
  } else {
    asm volatile("setmaxnreg.inc.sync.aligned.u32 232;");
    const int w = wg - 1;
    const int lane = threadIdx.x & 31;
    const int warp = wid & 3;
    const int tid = threadIdx.x - 128;
    const uint32_t rel_base = mapa(bar_empty, (lane == 0) ? rank : (rank ^ 1));
    Ring r{0, 0};
#define A_RELEASE(slot_) do { if (lane < 2) mbar_arrive_remote(rel_base + 8 * (slot_)); } while (0)
#define SIGNAL() do { __syncwarp(); if (lane == 0) mbar_arrive(bar_sig + 8 * w); } while (0)
    {
    const float SC = 0.07216878364870322f * 1.4426950408889634f;
    float o[96];
    uint32_t q[48];
    float s[32];
    uint32_t p[16], p2[16];
    if (w == 1) bar_arrive(1, 256);
    bf16* orow = g_o + (size_t)(qtile * 128 + w * 64 + warp * 16 + (lane >> 2)) * HD_ + (hbase - 8) * DH_ + (lane & 3) * 8;
#define O_STORE(g)                                                                                                     \
      {                                                                                                                \
        quad_transpose(q[8 * g], q[8 * g + 2], q[8 * g + 4], q[8 * g + 6], lane);                                      \
        stg128(orow + g * 32, make_uint4(q[8 * g], q[8 * g + 2], q[8 * g + 4], q[8 * g + 6]));                         \
        quad_transpose(q[8 * g + 1], q[8 * g + 3], q[8 * g + 5], q[8 * g + 7], lane);                                  \
        stg128(orow + (size_t)8 * HD_ + g * 32, make_uint4(q[8 * g + 1], q[8 * g + 3], q[8 * g + 5], q[8 * g + 7]));   \
      }
#pragma unroll 1
    for (int item = 0; item < 4; item++) {
      TSA(item, 0);
      {
        uint32_t prevA = 0, prevB = 0;
#pragma unroll
        for (int kb = 0; kb < 10; kb++) {
          const uint32_t sA = r.slot; mbar_wait_c(bar_full + 8 * sA, r.phase); r.adv(A_NSLOT);
          const uint32_t sB = r.slot; mbar_wait_c(bar_full + 8 * sB, r.phase); r.adv(A_NSLOT);
          const uint64_t da = mkdesc(sb + sA * A_SLOT + w * 8192, 16, 1024);
          const uint64_t db = mkdesc(sb + sB * A_SLOT, 8192, 1024);
          wg_fence();
#pragma unroll
          for (int kk = 0; kk < 4; kk++) wgmma_ss_n192<1>(o, da + kk * 2, db + kk * 128, (kb | kk) != 0);
          wg_commit();
          if (kb < 6 && item > 0) { O_STORE((kb < 6 ? kb : 0)) }
          if (kb == 6 && item > 0) SIGNAL();
          if (kb > 0) { wg_wait<1>(); A_RELEASE(prevA); A_RELEASE(prevB); }
          prevA = sA; prevB = sB;
        }
        wg_wait<0>();
        fence_regs(o);
        A_RELEASE(prevA); A_RELEASE(prevB);
#pragma unroll
        for (int i = 0; i < 48; i++) q[i] = pack_bf16(o[2 * i], o[2 * i + 1]);
      }
      orow += 8 * DH_;

      TSA(item, 1);
      float c0, c1, l0, l1;
      {
        const uint32_t sK = r.slot; mbar_wait_c(bar_full + 8 * sK, r.phase); r.adv(A_NSLOT);
        const uint64_t dk = mkdesc(sb + sK * A_SLOT, 16, 1024);
        bar_sync(1 + w, 256);
        wg_fence();
#pragma unroll
        for (int kk = 0; kk < 12; kk++)
          wgmma_rs_n64<0>(s, q[4 * kk], q[4 * kk + 1], q[4 * kk + 2], q[4 * kk + 3], dk + (kk >> 2) * 512 + (kk & 3) * 2, kk != 0);
        wg_commit();
        bar_arrive(1 + (w ^ 1), 256);
        wg_wait<0>();
        fence_regs(s);
        A_RELEASE(sK);
        float mx0 = fmaxf(s[0], s[1]), mx1 = fmaxf(s[2], s[3]);
#pragma unroll
        for (int i = 1; i < 8; i++) { mx0 = fmaxf(mx0, fmaxf(s[4 * i], s[4 * i + 1])); mx1 = fmaxf(mx1, fmaxf(s[4 * i + 2], s[4 * i + 3])); }
        mx0 = fmaxf(mx0, __shfl_xor_sync(0xffffffffu, mx0, 1)); mx1 = fmaxf(mx1, __shfl_xor_sync(0xffffffffu, mx1, 1));
        mx0 = fmaxf(mx0, __shfl_xor_sync(0xffffffffu, mx0, 2)); mx1 = fmaxf(mx1, __shfl_xor_sync(0xffffffffu, mx1, 2));
        c0 = mx0 * SC; c1 = mx1 * SC;
        l0 = 0.f; l1 = 0.f;
#pragma unroll
        for (int i = 0; i < 8; i++) {
          s[4 * i] = ex2(fmaf(s[4 * i], SC, -c0)); s[4 * i + 1] = ex2(fmaf(s[4 * i + 1], SC, -c0));
          s[4 * i + 2] = ex2(fmaf(s[4 * i + 2], SC, -c1)); s[4 * i + 3] = ex2(fmaf(s[4 * i + 3], SC, -c1));
          l0 += s[4 * i] + s[4 * i + 1]; l1 += s[4 * i + 2] + s[4 * i + 3];
        }
#pragma unroll
        for (int i = 0; i < 16; i++) p[i] = pack_bf16(s[2 * i], s[2 * i + 1]);
      }
      TSA(item, 2);
      uint32_t okn;
      {
        Ring r2 = r; r2.adv(A_NSLOT);
        okn = mbar_try(bar_full + 8 * r.slot, r.phase) & mbar_try(bar_full + 8 * r2.slot, r2.phase);
      }
#define A_STEP(PC, PN, FIRST)                                                                                          \
      {                                                                                                                \
        const uint32_t sK = r.slot, phK = r.phase; r.adv(A_NSLOT);                                                     \
        const uint32_t sV = r.slot, phV = r.phase; r.adv(A_NSLOT);                                                     \
        const uint64_t dk = mkdesc(sb + sK * A_SLOT, 16, 1024);                                                        \
        const uint64_t dv = mkdesc(sb + sV * A_SLOT, 8192, 1024);                                                      \
        if (!okn) { mbar_wait_c(bar_full + 8 * sK, phK); mbar_wait_c(bar_full + 8 * sV, phV); }                            \
        bar_sync(1 + w, 256);                                                                                          \
        wg_fence();                                                                                                    \
        _Pragma("unroll") for (int kk = 0; kk < 12; kk++)                                                              \
          wgmma_rs_n64<0>(s, q[4 * kk], q[4 * kk + 1], q[4 * kk + 2], q[4 * kk + 3], dk + (kk >> 2) * 512 + (kk & 3) * 2, kk != 0); \
        wg_commit();                                                                                                   \
        _Pragma("unroll") for (int kk = 0; kk < 4; kk++)                                                               \
          wgmma_rs_n192<1>(o, PC[4 * kk], PC[4 * kk + 1], PC[4 * kk + 2], PC[4 * kk + 3], dv + kk * 128, !(FIRST) || (kk != 0)); \
        wg_commit();                                                                                                   \
        bar_arrive(1 + (w ^ 1), 256);                                                                                  \
        {                                                                                                              \
          Ring r2 = r; r2.adv(A_NSLOT);                                                                                \
          okn = mbar_try(bar_full + 8 * r.slot, r.phase) & mbar_try(bar_full + 8 * r2.slot, r2.phase);                 \
        }                                                                                                              \
        wg_wait<1>();                                                                                                  \
        fence_regs(s);                                                                                                 \
        A_RELEASE(sK);                                                                                                 \
        float b0 = 0.f, b1 = 0.f;                                                                                      \
        _Pragma("unroll") for (int i = 0; i < 8; i++) {                                                                \
          const float e0 = ex2(fmaf(s[4 * i], SC, -c0)), e1 = ex2(fmaf(s[4 * i + 1], SC, -c0));                        \
          const float e2 = ex2(fmaf(s[4 * i + 2], SC, -c1)), e3 = ex2(fmaf(s[4 * i + 3], SC, -c1));                    \
          b0 += e0 + e1; b1 += e2 + e3;                                                                                \
          PN[2 * i] = pack_bf16(e0, e1); PN[2 * i + 1] = pack_bf16(e2, e3);                                            \
        }                                                                                                              \
        wg_wait<0>();                                                                                                  \
        fence_regs(o);                                                                                                 \
        fence_regs(PC);                                                                                                \
        A_RELEASE(sV);                                                                                                 \
        if (__any_sync(0xffffffffu, !(b0 <= 65536.f) || !(b1 <= 65536.f))) {                                           \
          float mx0 = fmaxf(s[0], s[1]), mx1 = fmaxf(s[2], s[3]);                                                      \
          _Pragma("unroll") for (int i = 1; i < 8; i++) {                                                              \
            mx0 = fmaxf(mx0, fmaxf(s[4 * i], s[4 * i + 1])); mx1 = fmaxf(mx1, fmaxf(s[4 * i + 2], s[4 * i + 3]));     \
          }                                                                                                            \
          mx0 = fmaxf(mx0, __shfl_xor_sync(0xffffffffu, mx0, 1)); mx1 = fmaxf(mx1, __shfl_xor_sync(0xffffffffu, mx1, 1)); \
          mx0 = fmaxf(mx0, __shfl_xor_sync(0xffffffffu, mx0, 2)); mx1 = fmaxf(mx1, __shfl_xor_sync(0xffffffffu, mx1, 2)); \
          const float n0 = fmaxf(c0, mx0 * SC), n1 = fmaxf(c1, mx1 * SC);                                              \
          const float a0 = ex2(c0 - n0), a1 = ex2(c1 - n1);                                                            \
          c0 = n0; c1 = n1;                                                                                            \
          l0 *= a0; l1 *= a1;                                                                                          \
          _Pragma("unroll") for (int i = 0; i < 24; i++) { o[4 * i] *= a0; o[4 * i + 1] *= a0; o[4 * i + 2] *= a1; o[4 * i + 3] *= a1; } \
          b0 = 0.f; b1 = 0.f;                                                                                          \
          _Pragma("unroll") for (int i = 0; i < 8; i++) {                                                              \
            const float e0 = ex2(fmaf(s[4 * i], SC, -c0)), e1 = ex2(fmaf(s[4 * i + 1], SC, -c0));                      \
            const float e2 = ex2(fmaf(s[4 * i + 2], SC, -c1)), e3 = ex2(fmaf(s[4 * i + 3], SC, -c1));                  \
            b0 += e0 + e1; b1 += e2 + e3;                                                                              \
            PN[2 * i] = pack_bf16(e0, e1); PN[2 * i + 1] = pack_bf16(e2, e3);                                          \
          }                                                                                                            \
        }                                                                                                              \
        l0 += b0; l1 += b1;                                                                                            \
      }
      for (int jj = 0; jj < 15; jj++) {
        A_STEP(p, p2, jj == 0)
        A_STEP(p2, p, false)
      }
      A_STEP(p, p2, false)
      TSA(item, 3);
      {
        const uint32_t sV = r.slot; mbar_wait_c(bar_full + 8 * sV, r.phase); r.adv(A_NSLOT);
        const uint64_t dv = mkdesc(sb + sV * A_SLOT, 8192, 1024);
        bar_sync(1 + w, 256);
        wg_fence();
#pragma unroll
        for (int kk = 0; kk < 4; kk++)
          wgmma_rs_n192<1>(o, p2[4 * kk], p2[4 * kk + 1], p2[4 * kk + 2], p2[4 * kk + 3], dv + kk * 128, 1);
        wg_commit();
        bar_arrive(1 + (w ^ 1), 256);
        wg_wait<0>();
        fence_regs(o);
        A_RELEASE(sV);
      }
      TSA(item, 4);
      l0 += __shfl_xor_sync(0xffffffffu, l0, 1); l1 += __shfl_xor_sync(0xffffffffu, l1, 1);
      l0 += __shfl_xor_sync(0xffffffffu, l0, 2); l1 += __shfl_xor_sync(0xffffffffu, l1, 2);
      const float i0 = __fdividef(1.f, l0), i1 = __fdividef(1.f, l1);
#pragma unroll
      for (int i = 0; i < 24; i++) { q[2 * i] = pack_bf16(o[4 * i] * i0, o[4 * i + 1] * i0); q[2 * i + 1] = pack_bf16(o[4 * i + 2] * i1, o[4 * i + 3] * i1); }
      TSA(item, 5);
    }
#pragma unroll
    for (int g = 0; g < 6; g++) { O_STORE(g) }
    SIGNAL();
    }
    TS(3, 2);
    const uint32_t st_w = (uint32_t)((warp * 16 + (lane >> 2)) * ST_P + (lane & 3) * 2) * 4;
    const uint32_t st_x = (lane & 8) << 2;
    const int er = (tid & 127) >> 1, eh = tid & 1;
    const uint32_t st_r = (uint32_t)(er * ST_P + (eh ^ ((er >> 1) & 1)) * 8) * 4;
    const uint32_t e_r = (uint32_t)((w * 64 + er) * 160 + eh * 16);
    const uint32_t p_r = par + eh * 32;
    const uint32_t stat = sb + T_PREP + w * 2048;
    const bool leader = (tid & 127) == 0;
#define STAGE10(ACC, BASE)                                                                                             \
    _Pragma("unroll") for (int nb = 0; nb < 10; nb++) {                                                                \
      sts_f2(stg + st_w + ((nb * 32) ^ st_x), ACC(BASE + 4 * nb), ACC(BASE + 4 * nb + 1));                                       \
      sts_f2(stg + st_w + ((nb * 32) ^ st_x) + 8 * ST_P * 4, ACC(BASE + 4 * nb + 2), ACC(BASE + 4 * nb + 3));                    \
    }

    {
      float acc1[96], acc2[64];
      uint32_t p0 = 0, p1 = 0, p2 = 0;
#pragma unroll 1
      for (int kb = 0; kb < 24; kb++) {
        const uint32_t s1 = r.slot; mbar_wait_c(bar_full + 8 * s1, r.phase); r.adv(A_NSLOT);
        const uint32_t s2 = r.slot; mbar_wait_c(bar_full + 8 * s2, r.phase); r.adv(A_NSLOT);
        const uint32_t sa = r.slot; mbar_wait_c(bar_full + 8 * sa, r.phase); r.adv(A_NSLOT);
        const uint64_t da = mkdesc(sb + sa * A_SLOT + w * 8192, 16, 1024);
        const uint64_t d1 = mkdesc(sb + s1 * A_SLOT, 8192, 1024), d2 = mkdesc(sb + s2 * A_SLOT, 8192, 1024);
        wg_fence();
#pragma unroll
        for (int kk = 0; kk < 4; kk++) {
          wgmma_ss_n192<1>(acc1, da + kk * 2, d1 + kk * 128, (kb | kk) != 0);
          wgmma_ss_n128<1>(acc2, da + kk * 2, d2 + kk * 128, (kb | kk) != 0);
        }
        wg_commit();
        if (kb > 0) { wg_wait<1>(); A_RELEASE(p0); A_RELEASE(p1); A_RELEASE(p2); }
        p0 = s1; p1 = s2; p2 = sa;
      }
      wg_wait<0>();
      fence_regs(acc1); fence_regs(acc2);
      A_RELEASE(p2);
      bar_sync(6, 288);
      TS(0, 0);
      const uint32_t stg = sb + (w ? p1 : p0) * A_SLOT;
#define OACC(e) (((e) < 96) ? acc1[(e) < 96 ? (e) : 0] : acc2[(e) >= 96 ? (e) - 96 : 0])
#define PACK10(BASE)                                                                                                   \
      _Pragma("unroll") for (int nb = 0; nb < 10; nb++) {                                                              \
        sts_u1(xo + nb * 16, pack_bf16(OACC(BASE + 4 * nb), OACC(BASE + 4 * nb + 1)));                                 \
        sts_u1(xo + nb * 16 + 8 * 160, pack_bf16(OACC(BASE + 4 * nb + 2), OACC(BASE + 4 * nb + 3)));                   \
      }
      const uint32_t f1 = r.slot + 4 >= A_NSLOT ? r.slot + 4 - A_NSLOT : r.slot + 4, f2 = f1 + 1 >= A_NSLOT ? 0 : f1 + 1;
#pragma unroll
      for (int d = 0; d < 4; d++) {
        if (d != o_ks) {
          const int i = (d - o_ks - 1) & 3;
          const uint32_t xo = sb + (i == 0 ? p2 : i == 1 ? f1 : f2) * A_SLOT + (w * 64 + warp * 16 + (lane >> 2)) * 160 + (lane & 3) * 4;
          PACK10(d * 40)
        }
      }
      fence_async_smem();
      bar_sync(3 + w, 128);
      if (leader) {
#pragma unroll 1
        for (int i = 0; i < 3; i++)
          bulk_store(g_xch + (size_t)((((o_qt * 2 + o_nh) * 4 + ((o_ks + 1 + i) & 3)) * 4) + o_ks) * (E_TILE / 2) + w * (E_TILE / 4),
                     sb + (i == 0 ? p2 : i == 1 ? f1 : f2) * A_SLOT + w * (E_TILE / 2), E_TILE / 2);
        bulk_done();
#pragma unroll 1
        for (int i = 0; i < 3; i++) flag_add(g_flag + F_XCH + (o_qt * 2 + o_nh) * 4 + ((o_ks + 1 + i) & 3));
        TX(40 + w);
      }
      if (o_ks == 0) { STAGE10(OACC, 0) } else if (o_ks == 1) { STAGE10(OACC, 40) } else if (o_ks == 2) { STAGE10(OACC, 80) } else { STAGE10(OACC, 120) }
      bar_sync(3 + w, 128);
      const uint32_t sx = r.slot; mbar_wait_c(bar_full + 8 * sx, r.phase); r.adv(A_NSLOT);
      const uint32_t q0 = r.slot; mbar_wait_c(bar_full + 8 * q0, r.phase); r.adv(A_NSLOT);
      const uint32_t q1 = r.slot; mbar_wait_c(bar_full + 8 * q1, r.phase); r.adv(A_NSLOT);
      const uint32_t q2 = r.slot; mbar_wait_c(bar_full + 8 * q2, r.phase); r.adv(A_NSLOT);
      TS(0, 1);
      float st[6] = {0.f, 0.f, 0.f, 0.f, 0.f, 0.f};
      const uint32_t ot = sb + p2 * A_SLOT;
#pragma unroll 1
      for (int c = 0; c < 5; c++) {
        float v[8], t0[8], t1[8], t2[8], xv[8], pg[8], pa_[8], pb_[8];
        lds8(stg + st_r + c * 64, v);
        lds8_bf(sb + q0 * A_SLOT + e_r + c * 32, t0); lds8_bf(sb + q1 * A_SLOT + e_r + c * 32, t1); lds8_bf(sb + q2 * A_SLOT + e_r + c * 32, t2);
        lds8_bf(sb + sx * A_SLOT + e_r + c * 32, xv);
        lds8(p_r + P_OGA * 4 + c * 64, pg); lds8(p_r + P_OA * 4 + c * 64, pa_); lds8(p_r + P_OB * 4 + c * 64, pb_);
#pragma unroll
        for (int e = 0; e < 8; e++) v[e] = fmaf(pg[e], v[e] + ((t0[e] + t1[e]) + t2[e]), xv[e]);
        const uint4 pk = pack8(v);
        sts_u4(ot + e_r + c * 32, pk);
        v[0] = bf_lo(pk.x); v[1] = bf_hi(pk.x); v[2] = bf_lo(pk.y); v[3] = bf_hi(pk.y); v[4] = bf_lo(pk.z); v[5] = bf_hi(pk.z); v[6] = bf_lo(pk.w); v[7] = bf_hi(pk.w);
#pragma unroll
        for (int e = 0; e < 8; e++) {
          const float y = pa_[e] * v[e];
          st[0] += v[e]; st[1] = fmaf(v[e], v[e], st[1]); st[2] += y; st[3] = fmaf(pa_[e], y, st[3]); st[4] = fmaf(y, y, st[4]); st[5] = fmaf(pb_[e], y, st[5]);
        }
      }
#pragma unroll
      for (int i = 0; i < 6; i++) st[i] += __shfl_xor_sync(0xffffffffu, st[i], 1);
      sts_u4(stat + er * 32 + eh * 16, eh ? make_uint4(__float_as_uint(st[4]), __float_as_uint(st[5]), 0u, 0u)
                                          : make_uint4(__float_as_uint(st[0]), __float_as_uint(st[1]), __float_as_uint(st[2]), __float_as_uint(st[3])));
      fence_async_smem();
      bar_sync(3 + w, 128);
      if (leader) {
        tma_store2d(&tm.sxa, ot + w * (E_TILE / 2), o_col, o_qt * 128 + w * 64);
        bulk_red_f32(g_st1 + (size_t)(o_qt * 128 + w * 64) * 8, stat, 2048);
        bulk_done();
        flag_add(g_flag + F_XA + o_qt);
      }
      bar_sync(5, 256);
      A_RELEASE(p0); A_RELEASE(p1); A_RELEASE(sx); A_RELEASE(q0); A_RELEASE(q1); A_RELEASE(q2);
      TS(0, 2);
    }

    Ring ra{0, 0};
    uint32_t bpar = 0;
    const uint32_t rel_a = mapa(mb_empty + 40, (lane == 0) ? rank : (rank ^ 1));
#define B_NEXT(s_) do { s_ = bs; mbar_wait_c(mb_full + 8 * bs, (bpar >> bs) & 1); bpar ^= 1u << bs; if (++bs == nbs) bs = 0; } while (0)
#define A_NEXT(s_) do { s_ = ra.slot; mbar_wait_c(mb_full + 40 + 8 * s_, ra.phase); ra.adv(M_NA); } while (0)
#define B_RELEASE(s_) do { if (lane == 0) mbar_arrive(mb_empty + 8 * (s_)); } while (0)
#define MA_RELEASE(s_) do { if (lane < 2) mbar_arrive_remote(rel_a + 8 * (s_)); } while (0)
    const int grow = qt * 128 + w * 64 + er;
    float mu = 0.f, rs = 0.f;
#pragma unroll 1
    for (int ph = 0; ph < 4; ph++) {
      float acc[96];
      float (&acc80)[40] = *reinterpret_cast<float(*)[40]>(&acc[0]);
      uint32_t pa = 0, pa2 = 0, pb = 0;
      float4 s03 = make_float4(0.f, 0.f, 0.f, 0.f);
      float2 s45 = make_float2(0.f, 0.f);
      const int nit = ph == 3 ? 12 : ph == 2 ? 10 : 5;
      const uint32_t nbs = ph == 2 ? 4 : 5, bsz = ph == 2 ? 24576 : 20480;
      uint32_t bs = 0;
#pragma unroll 1
      for (int it = 0; it < nit; it++) {
        uint32_t sbq, sa, sa2;
        B_NEXT(sbq);
        A_NEXT(sa);
        if (it == 0) TXC(ph);
        const uint64_t da = mkdesc(sb + M_AOFF + sa * 16384 + w * 8192, 16, 1024);
        if (ph == 2) {
          sa2 = sa;
          const uint64_t db = mkdesc(sb + sbq * 24576, 8192, 1024);
          wg_fence();
#pragma unroll
          for (int kk = 0; kk < 4; kk++) wgmma_ss_n192<1>(acc, da + kk * 2, db + kk * 128, (it | kk) != 0);
          wg_commit();
        } else {
          A_NEXT(sa2);
          const uint64_t da2 = mkdesc(sb + M_AOFF + sa2 * 16384 + w * 8192, 16, 1024);
          const uint64_t db = mkdesc(sb + sbq * 20480, 16, 1024);
          wg_fence();
#pragma unroll
          for (int kk = 0; kk < 4; kk++) wgmma_ss_n80<0>(acc80, da + kk * 2, db + kk * 2, (it | kk) != 0);
#pragma unroll
          for (int kk = 0; kk < 4; kk++) wgmma_ss_n80<0>(acc80, da2 + kk * 2, db + 640 + kk * 2, 1);
          wg_commit();
        }
        if (it > 0) { wg_wait<1>(); MA_RELEASE(pa); if (ph != 2) MA_RELEASE(pa2); B_RELEASE(pb); }
        else {
          if (ph == 0) { s03 = __ldcg(reinterpret_cast<const float4*>(g_st1 + (size_t)grow * 8)); s45 = __ldcg(reinterpret_cast<const float2*>(g_st1 + (size_t)grow * 8 + 4)); }
          if (ph == 2) s45 = __ldcg(reinterpret_cast<const float2*>(g_st2 + (size_t)grow * 2));
        }
        pa = sa; pa2 = sa2; pb = sbq;
      }
      wg_wait<0>();
      fence_regs(acc);
      MA_RELEASE(pa); if (ph != 2) MA_RELEASE(pa2);
      bar_sync(5, 256);
      TS(1 + (ph == 3 ? 0 : ph), ph == 3 ? 2 : 0);
      const uint32_t pb1 = pb == 0 ? nbs - 1 : pb - 1, pb2 = pb1 == 0 ? nbs - 1 : pb1 - 1, pb3 = pb2 == 0 ? nbs - 1 : pb2 - 1;
      const uint32_t stg = sb + (w ? pb : pb1) * bsz;
      uint32_t e1 = 0;
#define MACC(e) acc[e]
      if (!(ph & 1)) {
        float c0, c1, c2 = 0.f, c3 = 0.f;
        if (ph == 0) {
          const float4 sc = lds_f4(par + P_SC * 4);
          const float sbb = lds_f(par + (P_SC + 4) * 4);
          mu = s03.x * (1.f / D_);
          rs = rsqrtf(fmaxf(s03.y * (1.f / D_) - mu * mu, 0.f) + LN_EPS);
          const float m2 = (rs * (s03.z - mu * sc.x) + sc.w) * (1.f / D_);
          const float e2 = (rs * rs * (s45.x - 2.f * mu * s03.w + mu * mu * sc.y) + 2.f * rs * (s45.y - mu * sc.z) + sbb) * (1.f / D_);
          c2 = rsqrtf(fmaxf(e2 - m2 * m2, 0.f) + LN_EPS);
          c0 = c2 * rs; c1 = -c0 * mu; c3 = -c2 * m2;
          if (tid < 20) sts_u4(stat + 2048 * 2 + tid * 16, make_uint4(0, 0, 0, 0));
        } else {
          const float m = s45.x * (1.f / D_);
          c0 = rsqrtf(fmaxf(s45.y * (1.f / D_) - m * m, 0.f) + LN_EPS);
          c1 = -c0 * m;
        }
        const int npass = ph == 0 ? 1 : 3, nch = ph == 0 ? 5 : 4;
        const uint32_t ot = ph == 0 ? sb + pb2 * bsz + w * (E_TILE / 2) : sb + (w ? pb2 : pb3) * bsz;
#pragma unroll 1
        for (int ps = 0; ps < npass; ps++) {
          if (ps == 0) { STAGE10(MACC, 0) } else if (ps == 1) { STAGE10(MACC, 32) } else { STAGE10(MACC, 56) }
          bar_sync(3 + w, 128);
          const uint32_t cofs = ps == 2 ? 64 : 0;
          const uint32_t pp = p_r + (ph == 0 ? P_VA : P_CS3 + ps * 64) * 4, pq = p_r + P_VB * 4;
#pragma unroll 1
          for (int c = 0; c < nch; c++) {
            float v[8], t[8], t2[8], t3[8];
            lds8(stg + st_r + cofs + c * 64, v);
            lds8(pp + c * 64, t);
            if (ph == 0) {
              lds8(pq + c * 64, t2); lds8(pq + 320 + c * 64, t3);
#pragma unroll
              for (int e = 0; e < 8; e++) t[e] = fmaf(c1, t[e], fmaf(c2, t2[e], c3 * t3[e]));
            } else {
#pragma unroll
              for (int e = 0; e < 8; e++) t[e] *= c1;
            }
#pragma unroll
            for (int e = 0; e < 8; e++) v[e] = gelu_tanh(fmaf(c0, v[e], t[e]));
            sts_u4(ot + (ph == 0 ? er * 160 + eh * 16 + c * 32 : ps * 8192 + er * 128 + (((2 * c + eh) ^ (er & 7)) << 4)), pack8(v));
          }
          fence_async_smem();
          bar_sync(3 + w, 128);
          if (leader) {
            if (ph == 0) {
              const int grp = js >> 1;
              const int sh = (grp & 2 ? 2 : 1) * (grp & 1 ? -1 : 1);
              tma_store2d(&tm.sus, ot, js * 80, qt * 128 + w * 64 + sh + 2);
              if (w == 0 && qt == (sh > 0 ? 0 : 15)) {
                const int r0 = sh > 0 ? 0 : S_ + sh, n = sh > 0 ? sh : -sh;
                for (int i = 0; i < n; i++) bulk_store(g_us + (size_t)(r0 + i + 2) * D_ + js * 80, stat + 2048 * 2, 160);
              }
            } else {
              tma_store2d(&tm.g, ot + ps * 8192, js * 192 + ps * 64, qt * 128 + w * 64);
            }
          }
        }
      } else {
        STAGE10(MACC, 0)
        uint32_t e2;
        B_NEXT(e1);
        e2 = e1;
        if (ph == 3) B_NEXT(e2);
        bar_sync(3 + w, 128);
        float s1 = 0.f, s2 = 0.f;
        const uint32_t ot = sb + pb2 * bsz;
#pragma unroll 1
        for (int c = 0; c < 5; c++) {
          float v[8], xa[8], x1[8], ta[8], tb[8];
          lds8(stg + st_r + c * 64, v);
          lds8_bf(sb + e1 * 20480 + e_r + c * 32, xa); lds8_bf(sb + e2 * 20480 + e_r + c * 32, x1);
          lds8(p_r + (ph == 1 ? P_A2 : P_GB) * 4 + c * 64, ta); lds8(p_r + P_B2 * 4 + c * 64, tb);
          if (ph == 1) {
#pragma unroll
            for (int e = 0; e < 8; e++) v[e] += fmaf(ta[e] * rs, xa[e] - mu, tb[e]);
          } else {
#pragma unroll
            for (int e = 0; e < 8; e++) v[e] = fmaf(ta[e], v[e] + x1[e], xa[e]);
          }
          const uint4 pk = pack8(v);
          sts_u4(ot + e_r + c * 32, pk);
          v[0] = bf_lo(pk.x); v[1] = bf_hi(pk.x); v[2] = bf_lo(pk.y); v[3] = bf_hi(pk.y); v[4] = bf_lo(pk.z); v[5] = bf_hi(pk.z); v[6] = bf_lo(pk.w); v[7] = bf_hi(pk.w);
#pragma unroll
          for (int e = 0; e < 8; e++) { s1 += v[e]; s2 = fmaf(v[e], v[e], s2); }
        }
        s1 += __shfl_xor_sync(0xffffffffu, s1, 1); s2 += __shfl_xor_sync(0xffffffffu, s2, 1);
        if (eh == 0) sts_f2(stat + er * 8, s1, s2);
        fence_async_smem();
        bar_sync(3 + w, 128);
        if (leader) {
          tma_store2d(ph == 1 ? &tm.sx1 : &tm.sout, ot + w * (E_TILE / 2), js * 80, qt * 128 + w * 64);
          if (ph == 1) bulk_red_f32(g_st2 + (size_t)(qt * 128 + w * 64) * 2, stat, 512);
        }
      }
      if (leader) {
        bulk_done();
        if (ph < 3) flag_add(g_flag + F_US + 16 * ph + qt);
      }
      if (ph < 3) {
        bar_sync(5, 256);
        B_RELEASE(pb);
        if (ph == 1) B_RELEASE(e1);
      }
      TS(1 + (ph == 3 ? 0 : ph), ph == 3 ? 3 : 1);
    }
    if ((threadIdx.x & 127) == 0) TL_END(2);
    cluster_sync();
  }
}

typedef CUresult (*EncFn)(CUtensorMap*, CUtensorMapDataType, cuuint32_t, void*, const cuuint64_t*, const cuuint64_t*,
                          const cuuint32_t*, const cuuint32_t*, CUtensorMapInterleave, CUtensorMapSwizzle,
                          CUtensorMapL2promotion, CUtensorMapFloatOOBfill);
static EncFn g_enc = nullptr;

static CUtensorMap map2d(const void* p, uint64_t rows, uint64_t cols, uint32_t box_rows) {
  CUtensorMap m;
  cuuint64_t gd[2] = {cols, rows}; cuuint64_t gs[1] = {cols * 2};
  cuuint32_t bx[2] = {64, box_rows}; cuuint32_t es[2] = {1, 1};
  g_enc(&m, CU_TENSOR_MAP_DATA_TYPE_BFLOAT16, 2, const_cast<void*>(p), gd, gs, bx, es, CU_TENSOR_MAP_INTERLEAVE_NONE,
        CU_TENSOR_MAP_SWIZZLE_128B, CU_TENSOR_MAP_L2_PROMOTION_L2_256B, CU_TENSOR_MAP_FLOAT_OOB_FILL_NONE);
  return m;
}
static CUtensorMap map3d(const void* p, uint64_t rows, uint64_t cols, uint32_t box_rows, uint32_t nblk) {
  CUtensorMap m;
  cuuint64_t gd[3] = {64, rows, cols / 64}; cuuint64_t gs[2] = {cols * 2, 128};
  cuuint32_t bx[3] = {64, box_rows, nblk}; cuuint32_t es[3] = {1, 1, 1};
  g_enc(&m, CU_TENSOR_MAP_DATA_TYPE_BFLOAT16, 3, const_cast<void*>(p), gd, gs, bx, es, CU_TENSOR_MAP_INTERLEAVE_NONE,
        CU_TENSOR_MAP_SWIZZLE_128B, CU_TENSOR_MAP_L2_PROMOTION_L2_256B, CU_TENSOR_MAP_FLOAT_OOB_FILL_NONE);
  return m;
}

static CUtensorMap map_e(const void* p, uint32_t rows, uint64_t total_rows = S_) {
  CUtensorMap m;
  cuuint64_t gd[2] = {D_, total_rows}; cuuint64_t gs[1] = {D_ * 2};
  cuuint32_t bx[2] = {80, rows}; cuuint32_t es[2] = {1, 1};
  g_enc(&m, CU_TENSOR_MAP_DATA_TYPE_BFLOAT16, 2, const_cast<void*>(p), gd, gs, bx, es, CU_TENSOR_MAP_INTERLEAVE_NONE,
        CU_TENSOR_MAP_SWIZZLE_NONE, CU_TENSOR_MAP_L2_PROMOTION_L2_256B, CU_TENSOR_MAP_FLOAT_OOB_FILL_NONE);
  return m;
}

template <typename... KArgs, typename... Args>
static void launch(void (*kern)(KArgs...), dim3 grid, dim3 block, int smem, bool pdl, Args... args) {
  cudaLaunchConfig_t cfg = {};
  cfg.gridDim = grid; cfg.blockDim = block; cfg.dynamicSmemBytes = smem; cfg.stream = cudaStreamPerThread;
  cudaLaunchAttribute at[1];
  at[0].id = cudaLaunchAttributeProgrammaticStreamSerialization;
  at[0].val.programmaticStreamSerializationAllowed = 1;
  cfg.attrs = at; cfg.numAttrs = pdl ? 1 : 0;
  cudaLaunchKernelEx(&cfg, kern, KArgs(args)...);
}

extern "C" void kernel_launch(void* const* d_in, const int* in_sizes, int n_in, void* d_out, int out_size) {
  const bf16* x = (const bf16*)d_in[0];
  const bf16* kc = (const bf16*)d_in[1];
  const bf16* vc = (const bf16*)d_in[2];
  const bf16* wq = (const bf16*)d_in[3];
  const bf16* wo = (const bf16*)d_in[4];
  const bf16* w1 = (const bf16*)d_in[6];
  const bf16* w2 = (const bf16*)d_in[7];
  const bf16* w3 = (const bf16*)d_in[8];
  const bf16* w4 = (const bf16*)d_in[9];
  const bf16* c = (const bf16*)d_in[10];
  const bf16* wmod = (const bf16*)d_in[11];
  bf16* out = (bf16*)d_out;

  static void *p_h, *p_o, *p_xa, *p_us, *p_x1, *p_g, *p_w1t, *p_w2t, *p_w4t;
  if (!g_enc) {
    void* fn = nullptr; cudaDriverEntryPointQueryResult qr;
    cudaGetDriverEntryPoint("cuTensorMapEncodeTiled", &fn, cudaEnableDefault, &qr);
    g_enc = (EncFn)fn;
    cudaGetSymbolAddress(&p_h, g_h); cudaGetSymbolAddress(&p_o, g_o); cudaGetSymbolAddress(&p_xa, g_xa);
    cudaGetSymbolAddress(&p_us, g_us); cudaGetSymbolAddress(&p_x1, g_x1); cudaGetSymbolAddress(&p_g, g_g);
    cudaGetSymbolAddress(&p_w1t, g_w1t); cudaGetSymbolAddress(&p_w2t, g_w2t); cudaGetSymbolAddress(&p_w4t, g_w4t);
    cudaFuncSetAttribute(fused_kernel, cudaFuncAttributeMaxDynamicSharedMemorySize, T_SMEM);
  }
  Maps tm;
  tm.h = map2d(p_h, S_, D_, 128);
  tm.wq = map3d(wq, D_, HD_, 64, 3);
  tm.k = map3d(kc, (uint64_t)H_ * S_, DH_, 64, 3);
  tm.v = map3d(vc, (uint64_t)H_ * S_, DH_, 64, 3);
  tm.o = map2d(p_o, S_, HD_, 128);
  tm.wo3 = map3d(wo, HD_, D_, 64, 3);
  tm.wo2 = map3d(wo, HD_, D_, 64, 2);
  tm.xa = map2d(p_xa, S_, D_, 64);
  tm.w1t = map3d(p_w1t, D_, D_, 80, 2);
  tm.us = map2d((const bf16*)p_us + 2 * D_, S_, D_, 64);
  tm.w2t = map3d(p_w2t, D_, D_, 80, 2);
  tm.x1 = map2d(p_x1, S_, D_, 64);
  tm.w3 = map3d(w3, D_, F_, 64, 3);
  tm.g = map2d(p_g, S_, F_, 64);
  tm.w4t = map3d(p_w4t, D_, F_, 80, 2);
  tm.ex = map_e(x, 128); tm.exa = map_e(p_xa, 128); tm.ex1 = map_e(p_x1, 128);
  tm.sxa = map_e(p_xa, 64); tm.sus = map_e(p_us, 64, S_ + 4); tm.sx1 = map_e(p_x1, 64); tm.sout = map_e(out, 64);
  PfList pf;
  pf.p[0] = (const uint8_t*)wo; pf.p[1] = (const uint8_t*)w3; pf.p[2] = (const uint8_t*)p_w4t;
  pf.p[3] = (const uint8_t*)x; pf.p[4] = (const uint8_t*)p_w1t; pf.p[5] = (const uint8_t*)p_w2t;

  launch(mod_kernel, dim3(80), dim3(256), 0, false, c, wmod);
  launch(ln1_kernel, dim3(256), dim3(256), 0, true, x);
  launch(fused_kernel, dim3(128), dim3(384), T_SMEM, true, tm, pf, PrepW{w1, w2, w3, w4, c, wmod}, x, out);
}
```

```cpp
#include <cuda_runtime.h>
#include <cuda.h>
#include <cuda_bf16.h>
#include <stdint.h>

typedef __nv_bfloat16 bf16;

constexpr int S_  = 2048;
constexpr int D_  = 640;
constexpr int H_  = 32;
constexpr int DH_ = 192;
constexpr int HD_ = H_ * DH_;
constexpr int F_  = 1536;
constexpr float LN_EPS = 1e-5f;

__device__ __forceinline__ uint32_t smem_u32(const void* p) { return (uint32_t)__cvta_generic_to_shared(p); }
__device__ __forceinline__ void mbar_init(uint32_t a, uint32_t c) { asm volatile("mbarrier.init.shared::cta.b64 [%0], %1;" :: "r"(a), "r"(c) : "memory"); }
__device__ __forceinline__ void mbar_expect(uint32_t a, uint32_t b) { asm volatile("mbarrier.arrive.expect_tx.shared::cta.b64 _, [%0], %1;" :: "r"(a), "r"(b) : "memory"); }
__device__ __forceinline__ void mbar_arrive(uint32_t a) { asm volatile("mbarrier.arrive.shared::cta.b64 _, [%0];" :: "r"(a) : "memory"); }
__device__ __forceinline__ void mbar_arrive_remote(uint32_t ra) { asm volatile("mbarrier.arrive.shared::cluster.b64 _, [%0];" :: "r"(ra) : "memory"); }
__device__ __forceinline__ uint32_t mapa(uint32_t a, uint32_t cta) { uint32_t r; asm volatile("mapa.shared::cluster.u32 %0, %1, %2;" : "=r"(r) : "r"(a), "r"(cta)); return r; }
__device__ __forceinline__ uint32_t mbar_try(uint32_t a, uint32_t ph) {
  uint32_t ok;
  asm volatile("{\n.reg .pred p;\nmbarrier.test_wait.parity.shared::cta.b64 p, [%1], %2;\nselp.u32 %0, 1, 0, p;\n}\n" : "=r"(ok) : "r"(a), "r"(ph) : "memory");
  return ok;
}
__device__ __forceinline__ void mbar_wait(uint32_t a, uint32_t ph) {
  asm volatile(
      "{\n.reg .pred p;\n.reg .u32 n;\n"
      "mov.u32 n, 0;\n"
      "SPIN:\n"
      "mbarrier.try_wait.parity.shared::cta.b64 p, [%0], %1;\n"
      "@p bra DONE;\n"
      "add.u32 n, n, 1;\n"
      "setp.le.u32 p, n, 16777216;\n"
      "@p bra SPIN;\n"
      "trap;\n"
      "DONE:\n}\n" :: "r"(a), "r"(ph) : "memory");
}
#define ELECT_ "{\n.reg .pred p;\nelect.sync _|p, 0xffffffff;\n@p "
__device__ __forceinline__ void mbar_expect_e(uint32_t a, uint32_t b) { asm volatile(ELECT_ "mbarrier.arrive.expect_tx.shared::cta.b64 _, [%0], %1;\n}\n" :: "r"(a), "r"(b) : "memory"); }
__device__ __forceinline__ void tma2d(uint32_t dst, const CUtensorMap* m, uint32_t bar, int c0, int c1) {
  asm volatile(ELECT_ "cp.async.bulk.tensor.2d.shared::cluster.global.mbarrier::complete_tx::bytes [%0], [%1, {%3, %4}], [%2];\n}\n"
               :: "r"(dst), "l"(m), "r"(bar), "r"(c0), "r"(c1) : "memory");
}
__device__ __forceinline__ void tma2d_mc(uint32_t dst, const CUtensorMap* m, uint32_t bar, int c0, int c1, uint16_t mask) {
  asm volatile(ELECT_ "cp.async.bulk.tensor.2d.shared::cluster.global.mbarrier::complete_tx::bytes.multicast::cluster [%0], [%1, {%3, %4}], [%2], %5;\n}\n"
               :: "r"(dst), "l"(m), "r"(bar), "r"(c0), "r"(c1), "h"(mask) : "memory");
}
__device__ __forceinline__ void tma3d(uint32_t dst, const CUtensorMap* m, uint32_t bar, int c0, int c1, int c2) {
  asm volatile(ELECT_ "cp.async.bulk.tensor.3d.shared::cluster.global.mbarrier::complete_tx::bytes [%0], [%1, {%3, %4, %5}], [%2];\n}\n"
               :: "r"(dst), "l"(m), "r"(bar), "r"(c0), "r"(c1), "r"(c2) : "memory");
}
__device__ __forceinline__ void tma3d_mc(uint32_t dst, const CUtensorMap* m, uint32_t bar, int c0, int c1, int c2, uint16_t mask) {
  asm volatile(ELECT_ "cp.async.bulk.tensor.3d.shared::cluster.global.mbarrier::complete_tx::bytes.multicast::cluster [%0], [%1, {%3, %4, %5}], [%2], %6;\n}\n"
               :: "r"(dst), "l"(m), "r"(bar), "r"(c0), "r"(c1), "r"(c2), "h"(mask) : "memory");
}
__device__ __forceinline__ void tma3d_mc_hint(uint32_t dst, const CUtensorMap* m, uint32_t bar, int c0, int c1, int c2, uint16_t mask, uint64_t pol) {
  asm volatile(ELECT_ "cp.async.bulk.tensor.3d.shared::cluster.global.mbarrier::complete_tx::bytes.multicast::cluster.L2::cache_hint [%0], [%1, {%3, %4, %5}], [%2], %6, %7;\n}\n"
               :: "r"(dst), "l"(m), "r"(bar), "r"(c0), "r"(c1), "r"(c2), "h"(mask), "l"(pol) : "memory");
}
__device__ __forceinline__ void bulk_load(uint32_t dst, const void* src, uint32_t bytes, uint32_t bar) {
  asm volatile(ELECT_ "cp.async.bulk.shared::cluster.global.mbarrier::complete_tx::bytes [%0], [%1], %2, [%3];\n}\n"
               :: "r"(dst), "l"(src), "r"(bytes), "r"(bar) : "memory");
}
__device__ __forceinline__ void l2_prefetch16k(const void* p) { asm volatile(ELECT_ "cp.async.bulk.prefetch.L2.global [%0], 16384;\n}\n" :: "l"(p) : "memory"); }
__device__ __forceinline__ void l2_prefetch_t2d(const CUtensorMap* m, int c0, int c1) {
  asm volatile(ELECT_ "cp.async.bulk.prefetch.tensor.2d.L2.global [%0, {%1, %2}];\n}\n" :: "l"(m), "r"(c0), "r"(c1) : "memory");
}
__device__ __forceinline__ void l2_prefetch_t3d(const CUtensorMap* m, int c0, int c1, int c2) {
  asm volatile(ELECT_ "cp.async.bulk.prefetch.tensor.3d.L2.global [%0, {%1, %2, %3}];\n}\n" :: "l"(m), "r"(c0), "r"(c1), "r"(c2) : "memory");
}
__device__ __forceinline__ void stg128(void* p, uint4 v) {
  asm volatile("st.global.v4.u32 [%0], {%1, %2, %3, %4};" :: "l"(p), "r"(v.x), "r"(v.y), "r"(v.z), "r"(v.w) : "memory");
}
__device__ __forceinline__ void prefetch_tmap(const CUtensorMap* m) { asm volatile("prefetch.tensormap [%0];" :: "l"(m) : "memory"); }
__device__ __forceinline__ void wg_fence() { asm volatile("wgmma.fence.sync.aligned;" ::: "memory"); }
__device__ __forceinline__ void wg_commit() { asm volatile("wgmma.commit_group.sync.aligned;" ::: "memory"); }
template <int N> __device__ __forceinline__ void wg_wait() { asm volatile("wgmma.wait_group.sync.aligned %0;" :: "n"(N) : "memory"); }
template <int N> __device__ __forceinline__ void fence_regs(float (&r)[N]) {
#pragma unroll
  for (int i = 0; i < N; i++) asm volatile("" : "+f"(r[i]) :: "memory");
}
template <int N> __device__ __forceinline__ void fence_regs(uint32_t (&r)[N]) {
#pragma unroll
  for (int i = 0; i < N; i++) asm volatile("" : "+r"(r[i]) :: "memory");
}
__device__ __forceinline__ uint64_t mkdesc(uint32_t addr, uint32_t lbo, uint32_t sbo) {
  return (uint64_t)((addr & 0x3FFFF) >> 4) | ((uint64_t)(lbo >> 4) << 16) | ((uint64_t)(sbo >> 4) << 32) | (1ull << 62);
}
__device__ __forceinline__ void bar_sync(int id, int n) { asm volatile("bar.sync %0, %1;" :: "r"(id), "r"(n) : "memory"); }
__device__ __forceinline__ void bar_arrive(int id, int n) { asm volatile("bar.arrive %0, %1;" :: "r"(id), "r"(n) : "memory"); }
__device__ __forceinline__ void cluster_sync() { asm volatile("barrier.cluster.arrive.aligned;\nbarrier.cluster.wait.aligned;" ::: "memory"); }
__device__ __forceinline__ void pdl_wait() { asm volatile("griddepcontrol.wait;" ::: "memory"); }
__device__ __forceinline__ void pdl_launch() { asm volatile("griddepcontrol.launch_dependents;" ::: "memory"); }
__device__ __forceinline__ float ex2(float x) { float y; asm("ex2.approx.ftz.f32 %0, %1;" : "=f"(y) : "f"(x)); return y; }
__device__ __forceinline__ uint32_t pack_bf16(float lo, float hi) { uint32_t r; asm("cvt.rn.bf16x2.f32 %0, %1, %2;" : "=r"(r) : "f"(hi), "f"(lo)); return r; }
__device__ __forceinline__ float bf_lo(uint32_t u) { return __uint_as_float(u << 16); }
__device__ __forceinline__ float bf_hi(uint32_t u) { return __uint_as_float(u & 0xffff0000u); }
__device__ __forceinline__ float bf_round(float x) { return __bfloat162float(__float2bfloat16_rn(x)); }
__device__ __forceinline__ float tanh_fast(float x) { float y; asm("tanh.approx.f32 %0, %1;" : "=f"(y) : "f"(x)); return y; }
__device__ __forceinline__ float gelu_tanh(float x) {
  float u = x * (0.7978845608028654f + 0.035677408136300125f * x * x);
  float hx = 0.5f * x;
  return fmaf(hx, tanh_fast(u), hx);
}
__device__ __forceinline__ float warp_sum(float v) {
#pragma unroll
  for (int o = 16; o > 0; o >>= 1) v += __shfl_xor_sync(0xffffffffu, v, o);
  return v;
}
__device__ __forceinline__ void quad_transpose(uint32_t& v0, uint32_t& v1, uint32_t& v2, uint32_t& v3, int lane) {
  const bool b0 = lane & 1, b1 = lane & 2;
  uint32_t s0 = b0 ? v0 : v1, s1 = b0 ? v2 : v3;
  s0 = __shfl_xor_sync(0xffffffffu, s0, 1); s1 = __shfl_xor_sync(0xffffffffu, s1, 1);
  if (b0) { v0 = s0; v2 = s1; } else { v1 = s0; v3 = s1; }
  uint32_t t0 = b1 ? v0 : v2, t1 = b1 ? v1 : v3;
  t0 = __shfl_xor_sync(0xffffffffu, t0, 2); t1 = __shfl_xor_sync(0xffffffffu, t1, 2);
  if (b1) { v0 = t0; v1 = t1; } else { v2 = t0; v3 = t1; }
}

#define TG(i)
#define TX(i)
#define TXC(i)
#define TSA(item, i)
#define TL_ENTRY(k)
#define TL_WAITED(k)
#define TL_END(k)
#define TS(item, i)
template<int TB> __device__ __forceinline__ void wgmma_rs_n64(float (&d)[32], uint32_t a0, uint32_t a1, uint32_t a2, uint32_t a3, uint64_t db, int scale_d) {
  asm volatile("{\n.reg .pred p;\nsetp.ne.b32 p, %37, 0;\n"
    "wgmma.mma_async.sync.aligned.m64n64k16.f32.bf16.bf16 {%0, %1, %2, %3, %4, %5, %6, %7, %8, %9, %10, %11, %12, %13, %14, %15, %16, %17, %18, %19, %20, %21, %22, %23, %24, %25, %26, %27, %28, %29, %30, %31}, {%32, %33, %34, %35}, %36, p, 1, 1, %38;\n}\n"
    : "+f"(d[0]), "+f"(d[1]), "+f"(d[2]), "+f"(d[3]), "+f"(d[4]), "+f"(d[5]), "+f"(d[6]), "+f"(d[7]), "+f"(d[8]), "+f"(d[9]), "+f"(d[10]), "+f"(d[11]), "+f"(d[12]), "+f"(d[13]), "+f"(d[14]), "+f"(d[15]), "+f"(d[16]), "+f"(d[17]), "+f"(d[18]), "+f"(d[19]), "+f"(d[20]), "+f"(d[21]), "+f"(d[22]), "+f"(d[23]), "+f"(d[24]), "+f"(d[25]), "+f"(d[26]), "+f"(d[27]), "+f"(d[28]), "+f"(d[29]), "+f"(d[30]), "+f"(d[31])
    : "r"(a0), "r"(a1), "r"(a2), "r"(a3), "l"(db), "r"(scale_d), "n"(TB));
}
template<int TB> __device__ __forceinline__ void wgmma_rs_n192(float (&d)[96], uint32_t a0, uint32_t a1, uint32_t a2, uint32_t a3, uint64_t db, int scale_d) {
  asm volatile("{\n.reg .pred p;\nsetp.ne.b32 p, %101, 0;\n"
    "wgmma.mma_async.sync.aligned.m64n192k16.f32.bf16.bf16 {%0, %1, %2, %3, %4, %5, %6, %7, %8, %9, %10, %11, %12, %13, %14, %15, %16, %17, %18, %19, %20, %21, %22, %23, %24, %25, %26, %27, %28, %29, %30, %31, %32, %33, %34, %35, %36, %37, %38, %39, %40, %41, %42, %43, %44, %45, %46, %47, %48, %49, %50, %51, %52, %53, %54, %55, %56, %57, %58, %59, %60, %61, %62, %63, %64, %65, %66, %67, %68, %69, %70, %71, %72, %73, %74, %75, %76, %77, %78, %79, %80, %81, %82, %83, %84, %85, %86, %87, %88, %89, %90, %91, %92, %93, %94, %95}, {%96, %97, %98, %99}, %100, p, 1, 1, %102;\n}\n"
    : "+f"(d[0]), "+f"(d[1]), "+f"(d[2]), "+f"(d[3]), "+f"(d[4]), "+f"(d[5]), "+f"(d[6]), "+f"(d[7]), "+f"(d[8]), "+f"(d[9]), "+f"(d[10]), "+f"(d[11]), "+f"(d[12]), "+f"(d[13]), "+f"(d[14]), "+f"(d[15]), "+f"(d[16]), "+f"(d[17]), "+f"(d[18]), "+f"(d[19]), "+f"(d[20]), "+f"(d[21]), "+f"(d[22]), "+f"(d[23]), "+f"(d[24]), "+f"(d[25]), "+f"(d[26]), "+f"(d[27]), "+f"(d[28]), "+f"(d[29]), "+f"(d[30]), "+f"(d[31]), "+f"(d[32]), "+f"(d[33]), "+f"(d[34]), "+f"(d[35]), "+f"(d[36]), "+f"(d[37]), "+f"(d[38]), "+f"(d[39]), "+f"(d[40]), "+f"(d[41]), "+f"(d[42]), "+f"(d[43]), "+f"(d[44]), "+f"(d[45]), "+f"(d[46]), "+f"(d[47]), "+f"(d[48]), "+f"(d[49]), "+f"(d[50]), "+f"(d[51]), "+f"(d[52]), "+f"(d[53]), "+f"(d[54]), "+f"(d[55]), "+f"(d[56]), "+f"(d[57]), "+f"(d[58]), "+f"(d[59]), "+f"(d[60]), "+f"(d[61]), "+f"(d[62]), "+f"(d[63]), "+f"(d[64]), "+f"(d[65]), "+f"(d[66]), "+f"(d[67]), "+f"(d[68]), "+f"(d[69]), "+f"(d[70]), "+f"(d[71]), "+f"(d[72]), "+f"(d[73]), "+f"(d[74]), "+f"(d[75]), "+f"(d[76]), "+f"(d[77]), "+f"(d[78]), "+f"(d[79]), "+f"(d[80]), "+f"(d[81]), "+f"(d[82]), "+f"(d[83]), "+f"(d[84]), "+f"(d[85]), "+f"(d[86]), "+f"(d[87]), "+f"(d[88]), "+f"(d[89]), "+f"(d[90]), "+f"(d[91]), "+f"(d[92]), "+f"(d[93]), "+f"(d[94]), "+f"(d[95])
    : "r"(a0), "r"(a1), "r"(a2), "r"(a3), "l"(db), "r"(scale_d), "n"(TB));
}
template<int TB> __device__ __forceinline__ void wgmma_ss_n128(float (&d)[64], uint64_t da, uint64_t db, int scale_d) {
  asm volatile("{\n.reg .pred p;\nsetp.ne.b32 p, %66, 0;\n"
    "wgmma.mma_async.sync.aligned.m64n128k16.f32.bf16.bf16 {%0, %1, %2, %3, %4, %5, %6, %7, %8, %9, %10, %11, %12, %13, %14, %15, %16, %17, %18, %19, %20, %21, %22, %23, %24, %25, %26, %27, %28, %29, %30, %31, %32, %33, %34, %35, %36, %37, %38, %39, %40, %41, %42, %43, %44, %45, %46, %47, %48, %49, %50, %51, %52, %53, %54, %55, %56, %57, %58, %59, %60, %61, %62, %63}, %64, %65, p, 1, 1, 0, %67;\n}\n"
    : "+f"(d[0]), "+f"(d[1]), "+f"(d[2]), "+f"(d[3]), "+f"(d[4]), "+f"(d[5]), "+f"(d[6]), "+f"(d[7]), "+f"(d[8]), "+f"(d[9]), "+f"(d[10]), "+f"(d[11]), "+f"(d[12]), "+f"(d[13]), "+f"(d[14]), "+f"(d[15]), "+f"(d[16]), "+f"(d[17]), "+f"(d[18]), "+f"(d[19]), "+f"(d[20]), "+f"(d[21]), "+f"(d[22]), "+f"(d[23]), "+f"(d[24]), "+f"(d[25]), "+f"(d[26]), "+f"(d[27]), "+f"(d[28]), "+f"(d[29]), "+f"(d[30]), "+f"(d[31]), "+f"(d[32]), "+f"(d[33]), "+f"(d[34]), "+f"(d[35]), "+f"(d[36]), "+f"(d[37]), "+f"(d[38]), "+f"(d[39]), "+f"(d[40]), "+f"(d[41]), "+f"(d[42]), "+f"(d[43]), "+f"(d[44]), "+f"(d[45]), "+f"(d[46]), "+f"(d[47]), "+f"(d[48]), "+f"(d[49]), "+f"(d[50]), "+f"(d[51]), "+f"(d[52]), "+f"(d[53]), "+f"(d[54]), "+f"(d[55]), "+f"(d[56]), "+f"(d[57]), "+f"(d[58]), "+f"(d[59]), "+f"(d[60]), "+f"(d[61]), "+f"(d[62]), "+f"(d[63])
    : "l"(da), "l"(db), "r"(scale_d), "n"(TB));
}
template<int TB> __device__ __forceinline__ void wgmma_ss_n192(float (&d)[96], uint64_t da, uint64_t db, int scale_d) {
  asm volatile("{\n.reg .pred p;\nsetp.ne.b32 p, %98, 0;\n"
    "wgmma.mma_async.sync.aligned.m64n192k16.f32.bf16.bf16 {%0, %1, %2, %3, %4, %5, %6, %7, %8, %9, %10, %11, %12, %13, %14, %15, %16, %17, %18, %19, %20, %21, %22, %23, %24, %25, %26, %27, %28, %29, %30, %31, %32, %33, %34, %35, %36, %37, %38, %39, %40, %41, %42, %43, %44, %45, %46, %47, %48, %49, %50, %51, %52, %53, %54, %55, %56, %57, %58, %59, %60, %61, %62, %63, %64, %65, %66, %67, %68, %69, %70, %71, %72, %73, %74, %75, %76, %77, %78, %79, %80, %81, %82, %83, %84, %85, %86, %87, %88, %89, %90, %91, %92, %93, %94, %95}, %96, %97, p, 1, 1, 0, %99;\n}\n"
    : "+f"(d[0]), "+f"(d[1]), "+f"(d[2]), "+f"(d[3]), "+f"(d[4]), "+f"(d[5]), "+f"(d[6]), "+f"(d[7]), "+f"(d[8]), "+f"(d[9]), "+f"(d[10]), "+f"(d[11]), "+f"(d[12]), "+f"(d[13]), "+f"(d[14]), "+f"(d[15]), "+f"(d[16]), "+f"(d[17]), "+f"(d[18]), "+f"(d[19]), "+f"(d[20]), "+f"(d[21]), "+f"(d[22]), "+f"(d[23]), "+f"(d[24]), "+f"(d[25]), "+f"(d[26]), "+f"(d[27]), "+f"(d[28]), "+f"(d[29]), "+f"(d[30]), "+f"(d[31]), "+f"(d[32]), "+f"(d[33]), "+f"(d[34]), "+f"(d[35]), "+f"(d[36]), "+f"(d[37]), "+f"(d[38]), "+f"(d[39]), "+f"(d[40]), "+f"(d[41]), "+f"(d[42]), "+f"(d[43]), "+f"(d[44]), "+f"(d[45]), "+f"(d[46]), "+f"(d[47]), "+f"(d[48]), "+f"(d[49]), "+f"(d[50]), "+f"(d[51]), "+f"(d[52]), "+f"(d[53]), "+f"(d[54]), "+f"(d[55]), "+f"(d[56]), "+f"(d[57]), "+f"(d[58]), "+f"(d[59]), "+f"(d[60]), "+f"(d[61]), "+f"(d[62]), "+f"(d[63]), "+f"(d[64]), "+f"(d[65]), "+f"(d[66]), "+f"(d[67]), "+f"(d[68]), "+f"(d[69]), "+f"(d[70]), "+f"(d[71]), "+f"(d[72]), "+f"(d[73]), "+f"(d[74]), "+f"(d[75]), "+f"(d[76]), "+f"(d[77]), "+f"(d[78]), "+f"(d[79]), "+f"(d[80]), "+f"(d[81]), "+f"(d[82]), "+f"(d[83]), "+f"(d[84]), "+f"(d[85]), "+f"(d[86]), "+f"(d[87]), "+f"(d[88]), "+f"(d[89]), "+f"(d[90]), "+f"(d[91]), "+f"(d[92]), "+f"(d[93]), "+f"(d[94]), "+f"(d[95])
    : "l"(da), "l"(db), "r"(scale_d), "n"(TB));
}
template<int TB> __device__ __forceinline__ void wgmma_ss_n80(float (&d)[40], uint64_t da, uint64_t db, int scale_d) {
  asm volatile("{\n.reg .pred p;\nsetp.ne.b32 p, %42, 0;\n"
    "wgmma.mma_async.sync.aligned.m64n80k16.f32.bf16.bf16 {%0, %1, %2, %3, %4, %5, %6, %7, %8, %9, %10, %11, %12, %13, %14, %15, %16, %17, %18, %19, %20, %21, %22, %23, %24, %25, %26, %27, %28, %29, %30, %31, %32, %33, %34, %35, %36, %37, %38, %39}, %40, %41, p, 1, 1, 0, %43;\n}\n"
    : "+f"(d[0]), "+f"(d[1]), "+f"(d[2]), "+f"(d[3]), "+f"(d[4]), "+f"(d[5]), "+f"(d[6]), "+f"(d[7]), "+f"(d[8]), "+f"(d[9]), "+f"(d[10]), "+f"(d[11]), "+f"(d[12]), "+f"(d[13]), "+f"(d[14]), "+f"(d[15]), "+f"(d[16]), "+f"(d[17]), "+f"(d[18]), "+f"(d[19]), "+f"(d[20]), "+f"(d[21]), "+f"(d[22]), "+f"(d[23]), "+f"(d[24]), "+f"(d[25]), "+f"(d[26]), "+f"(d[27]), "+f"(d[28]), "+f"(d[29]), "+f"(d[30]), "+f"(d[31]), "+f"(d[32]), "+f"(d[33]), "+f"(d[34]), "+f"(d[35]), "+f"(d[36]), "+f"(d[37]), "+f"(d[38]), "+f"(d[39])
    : "l"(da), "l"(db), "r"(scale_d), "n"(TB));
}

__device__ __align__(128) float g_mod[6 * D_];
__device__ __align__(128) float g_modp[2][2 * D_];
__device__ __align__(1024) bf16 g_h[S_ * D_];
__device__ __align__(1024) bf16 g_o[S_ * HD_];
__device__ __align__(1024) bf16 g_xch[16 * 2 * 4 * 4 * 128 * 80];
__device__ __align__(1024) bf16 g_w1t[D_ * D_];
__device__ __align__(1024) bf16 g_w2t[D_ * D_];
__device__ __align__(1024) bf16 g_w4t[D_ * F_];
__device__ __align__(32) float g_st1[S_ * 8];
__device__ __align__(32) float g_st2[S_ * 2];
__device__ __align__(32) float g_vec[3 * D_ + F_ + 8];
__device__ unsigned g_flag[1024];
enum { F_XCH = 0, F_XA = 256, F_US = 288, F_X1 = 320, F_G = 352, F_PREP = 384, F_MOD2 = 416, F_O = 512 };
__device__ __align__(1024) bf16 g_xa[S_ * D_];
__device__ __align__(1024) bf16 g_us[(S_ + 4) * D_];
__device__ __align__(1024) bf16 g_x1[S_ * D_];
__device__ __align__(1024) bf16 g_g[S_ * F_];

__device__ __forceinline__ void row_stats(const float (&v)[20], float& mean, float& rstd) {
  float s = 0.f;
#pragma unroll
  for (int i = 0; i < 20; i++) s += v[i];
  mean = warp_sum(s) * (1.f / D_);
  float q = 0.f;
#pragma unroll
  for (int i = 0; i < 20; i++) { float d = v[i] - mean; q = fmaf(d, d, q); }
  rstd = rsqrtf(warp_sum(q) * (1.f / D_) + LN_EPS);
}
__device__ __forceinline__ void load_row_bf16(const bf16* p, int lane, float (&v)[20]) {
#pragma unroll
  for (int i = 0; i < 5; i++) {
    uint2 u = *reinterpret_cast<const uint2*>(p + (lane + 32 * i) * 4);
    v[4 * i] = bf_lo(u.x); v[4 * i + 1] = bf_hi(u.x); v[4 * i + 2] = bf_lo(u.y); v[4 * i + 3] = bf_hi(u.y);
  }
}
__device__ __forceinline__ void store_row_bf16(bf16* p, int lane, const float (&v)[20]) {
#pragma unroll
  for (int i = 0; i < 5; i++) {
    uint2 u; u.x = pack_bf16(v[4 * i], v[4 * i + 1]); u.y = pack_bf16(v[4 * i + 2], v[4 * i + 3]);
    *reinterpret_cast<uint2*>(p + (lane + 32 * i) * 4) = u;
  }
}
__device__ __forceinline__ void load_row_f32(const float* p, int lane, float (&v)[20]) {
#pragma unroll
  for (int i = 0; i < 5; i++) {
    float4 u = *reinterpret_cast<const float4*>(p + (lane + 32 * i) * 4);
    v[4 * i] = u.x; v[4 * i + 1] = u.y; v[4 * i + 2] = u.z; v[4 * i + 3] = u.w;
  }
}

__device__ __forceinline__ float silu_bf(float c) { return bf_round(__fdividef(c, 1.f + __expf(-c))); }
__device__ __forceinline__ void fma8(float (&acc)[8], float s, const uint4& w) {
  acc[0] = fmaf(s, bf_lo(w.x), acc[0]); acc[1] = fmaf(s, bf_hi(w.x), acc[1]); acc[2] = fmaf(s, bf_lo(w.y), acc[2]); acc[3] = fmaf(s, bf_hi(w.y), acc[3]);
  acc[4] = fmaf(s, bf_lo(w.z), acc[4]); acc[5] = fmaf(s, bf_hi(w.z), acc[5]); acc[6] = fmaf(s, bf_lo(w.w), acc[6]); acc[7] = fmaf(s, bf_hi(w.w), acc[7]);
}
__global__ void __launch_bounds__(256) mod_kernel(const bf16* __restrict__ c, const bf16* __restrict__ w_mod) {
  TL_ENTRY(0);
  pdl_launch();
  __shared__ float red[8][32];
  const int t = threadIdx.x, cg = t & 3, r0 = (blockIdx.x / 40) * 320 + (t >> 2), strip = blockIdx.x % 40;
  uint4 w[5];
  float cv[5];
#pragma unroll
  for (int i = 0; i < 5; i++) {
    w[i] = __ldg(reinterpret_cast<const uint4*>(w_mod + (size_t)(r0 + 64 * i) * (6 * D_) + strip * 32 + cg * 8));
    cv[i] = __bfloat162float(c[r0 + 64 * i]);
  }
  if (blockIdx.x < 14) { const int i = blockIdx.x * 256 + t; if (i < 3 * D_ + F_) g_vec[i] = 0.f; }
  else if (blockIdx.x < 18) g_flag[(blockIdx.x - 14) * 256 + t] = 0u;
  float acc[8];
#pragma unroll
  for (int j = 0; j < 8; j++) acc[j] = 0.f;
#pragma unroll
  for (int i = 0; i < 5; i++) fma8(acc, silu_bf(cv[i]), w[i]);
#pragma unroll 1
  for (int o = 4; o < 32; o <<= 1) {
#pragma unroll
    for (int j = 0; j < 8; j++) acc[j] += __shfl_xor_sync(0xffffffffu, acc[j], o);
  }
  if ((t & 31) < 4) {
    *reinterpret_cast<float4*>(&red[t >> 5][cg * 8]) = make_float4(acc[0], acc[1], acc[2], acc[3]);
    *reinterpret_cast<float4*>(&red[t >> 5][cg * 8 + 4]) = make_float4(acc[4], acc[5], acc[6], acc[7]);
  }
  __syncthreads();
  if (t < 32) {
    float s = 0.f;
#pragma unroll
    for (int w8 = 0; w8 < 8; w8++) s += red[w8][t];
    g_modp[blockIdx.x / 40][strip * 32 + t] = s;
    if (t == 0) TL_END(0);
  }
}

__global__ void __launch_bounds__(256) ln1_kernel(const bf16* __restrict__ x) {
  TL_ENTRY(1);
  pdl_launch();
  const int lane = threadIdx.x & 31, row = blockIdx.x * 8 + (threadIdx.x >> 5);
  float v[20];
  load_row_bf16(x + (size_t)row * D_, lane, v);
  float mean, rstd;
  row_stats(v, mean, rstd);
  if (lane < 8) g_st1[row * 8 + lane] = 0.f;
  if (lane < 2) g_st2[row * 2 + lane] = 0.f;
  pdl_wait();
  if (threadIdx.x == 0) TL_WAITED(1);
  float s0[20], s1[20], c0[20], c1[20];
  load_row_f32(g_modp[0], lane, s0); load_row_f32(g_modp[1], lane, s1);
  load_row_f32(g_modp[0] + D_, lane, c0); load_row_f32(g_modp[1] + D_, lane, c1);
#pragma unroll
  for (int i = 0; i < 20; i++) v[i] = fmaf((v[i] - mean) * rstd, bf_round(1.f + bf_round(c0[i] + c1[i])), bf_round(s0[i] + s1[i]));
  store_row_bf16(g_h + (size_t)row * D_, lane, v);
  if (threadIdx.x == 0) TL_END(1);
}

constexpr int PREP_JOBS = 200 + 200 + 480 + 480;
struct PrepW { const bf16 *w1, *w2, *w3, *w4, *c, *wmod; };
__device__ __forceinline__ void flag_wait(const unsigned* p, unsigned target);
__device__ __forceinline__ void prep_warp(const PrepW& pw, bf16 (*tile)[72], int lane) {
  if (blockIdx.x < 80) {
    const bf16* wp = pw.wmod + (size_t)(lane >> 2) * (6 * D_) + 2 * D_ + blockIdx.x * 32 + (lane & 3) * 8;
    float acc[8];
#pragma unroll
    for (int j = 0; j < 8; j++) acc[j] = 0.f;
#pragma unroll 1
    for (int i = 0; i < 80; i += 4) {
      uint4 w[4];
      float cv[4];
#pragma unroll
      for (int e = 0; e < 4; e++) { w[e] = __ldg(reinterpret_cast<const uint4*>(wp + (size_t)(i + e) * 8 * (6 * D_))); cv[e] = __bfloat162float(pw.c[(i + e) * 8 + (lane >> 2)]); }
#pragma unroll
      for (int e = 0; e < 4; e++) fma8(acc, silu_bf(cv[e]), w[e]);
    }
    const bool one = blockIdx.x >= 40 && blockIdx.x < 60;
#pragma unroll
    for (int j = 0; j < 8; j++) {
      acc[j] += __shfl_xor_sync(0xffffffffu, acc[j], 4); acc[j] += __shfl_xor_sync(0xffffffffu, acc[j], 8); acc[j] += __shfl_xor_sync(0xffffffffu, acc[j], 16);
      const float v = bf_round(acc[j]);
      if (lane < 4) g_mod[2 * D_ + blockIdx.x * 32 + lane * 8 + j] = one ? bf_round(1.f + v) : v;
    }
    __syncwarp();
    if (lane == 0) {
      asm volatile("fence.acq_rel.gpu;" ::: "memory");
      asm volatile("red.relaxed.gpu.global.add.u32 [%0], 1;" :: "l"(g_flag + F_MOD2) : "memory");
    }
  }
  flag_wait(g_flag + F_MOD2, 80);
#pragma unroll 1
  for (int job = blockIdx.x; job < PREP_JOBS; job += gridDim.x) {
    const bf16* src; bf16* dst; int ld = D_, ldd = D_, kt, nt, kind = 1;
    if (job < 200) { src = pw.w1; dst = g_w1t; kt = job / 10; nt = job % 10; kind = 0; }
    else if (job < 400) { src = pw.w2; dst = g_w2t; kt = (job - 200) / 10; nt = (job - 200) % 10; }
    else if (job < 880) { src = pw.w4; dst = g_w4t; ldd = F_; kt = (job - 400) / 10; nt = (job - 400) % 10; }
    else { src = pw.w3; dst = nullptr; ld = F_; kt = (job - 880) / 24; nt = (job - 880) % 24; kind = 2; }
    src += (size_t)(kt * 32 + (lane >> 3)) * ld + nt * 64 + (lane & 7) * 8;
    __syncwarp();
#pragma unroll
    for (int h = 0; h < 2; h++) {
      uint4 v[4];
#pragma unroll
      for (int i = 0; i < 4; i++) v[i] = __ldg(reinterpret_cast<const uint4*>(src + (size_t)(h * 16 + i * 4) * ld));
#pragma unroll
      for (int i = 0; i < 4; i++) *reinterpret_cast<uint4*>(&tile[h * 16 + i * 4 + (lane >> 3)][(lane & 7) * 8]) = v[i];
    }
    __syncwarp();
    const float* pa = g_mod + 4 * D_ + kt * 32;
    const float* pb = g_mod + 3 * D_ + kt * 32;
#pragma unroll 1
    for (int h = 0; h < 2; h++) {
      const int n = lane + 32 * h;
      float sa = 0.f, sb = 0.f, sc = 0.f;
#pragma unroll 1
      for (int c = 0; c < 4; c++) {
        uint32_t u[4];
#pragma unroll
        for (int e = 0; e < 4; e++) {
          const int k = c * 8 + 2 * e;
          float lo = __bfloat162float(tile[k][n]), hi = __bfloat162float(tile[k + 1][n]);
          sc += lo + hi;
          if (kind == 0) {
            const float2 a = __ldcg(reinterpret_cast<const float2*>(pa + k)), b = __ldcg(reinterpret_cast<const float2*>(pb + k));
            sb = fmaf(b.x, lo, fmaf(b.y, hi, sb));
            lo *= a.x; hi *= a.y;
          }
          u[e] = pack_bf16(lo, hi);
          sa += bf_lo(u[e]) + bf_hi(u[e]);
        }
        if (kind != 2) *reinterpret_cast<uint4*>(dst + (size_t)(nt * 64 + n) * ldd + kt * 32 + c * 8) = make_uint4(u[0], u[1], u[2], u[3]);
      }
      if (kind == 0) { atomicAdd(&g_vec[nt * 64 + n], sa); atomicAdd(&g_vec[D_ + nt * 64 + n], sb); atomicAdd(&g_vec[2 * D_ + nt * 64 + n], sc); }
      else if (kind == 2) atomicAdd(&g_vec[3 * D_ + nt * 64 + n], sc);
    }
  }
  __syncwarp();
  if (lane == 0) {
    asm volatile("fence.acq_rel.gpu;" ::: "memory");
    asm volatile("red.relaxed.gpu.global.add.u32 [%0], 1;" :: "l"(g_flag + F_PREP) : "memory");
  }
}

constexpr int A_NSLOT = 9;
constexpr int A_SLOT = 24576;
constexpr int A_NKV = S_ / 64;
constexpr int PREP_CTAS = 128;

struct Ring {
  uint32_t slot, phase;
  __device__ __forceinline__ void adv(int n) { if (++slot == (uint32_t)n) { slot = 0; phase ^= 1; } }
};
constexpr int T_PAR = A_NSLOT * A_SLOT + 448;
constexpr int T_PREP = T_PAR + 3712;
constexpr int T_SMEM = T_PREP + 32 * 72 * 2 + 1024;
enum { P_OGA = 0, P_OA = 80, P_OB = 160, P_VA = 240, P_VB = 320, P_VC = 400, P_A2 = 480, P_B2 = 560, P_GB = 640, P_CS3 = 720, P_SC = 912 };

__device__ __forceinline__ void flag_wait(const unsigned* p, unsigned target) {
  asm volatile(
      "{\n.reg .pred p;\n.reg .u32 n, v;\n"
      "mov.u32 n, 0;\n"
      "SPIN:\n"
      "ld.relaxed.gpu.global.u32 v, [%0];\n"
      "setp.ge.u32 p, v, %1;\n"
      "@p bra DONE;\n"
      "add.u32 n, n, 1;\n"
      "setp.gt.u32 p, n, 4194304;\n"
      "@p trap;\n"
      "bra SPIN;\n"
      "DONE:\n}\n" :: "l"(p), "r"(target) : "memory");
}
__device__ __forceinline__ void fence_async_global() { asm volatile("fence.proxy.async.global;" ::: "memory"); }
__device__ __forceinline__ float lds_f(uint32_t a) { float v; asm volatile("ld.shared.f32 %0, [%1];" : "=f"(v) : "r"(a)); return v; }
__device__ __forceinline__ float2 lds_f2(uint32_t a) { float2 v; asm volatile("ld.shared.v2.f32 {%0, %1}, [%2];" : "=f"(v.x), "=f"(v.y) : "r"(a)); return v; }
__device__ __forceinline__ uint4 ldcg4(const void* p) { return __ldcg(reinterpret_cast<const uint4*>(p)); }

__device__ __forceinline__ void sts_f2(uint32_t a, float x, float y) { asm volatile("st.shared.v2.f32 [%0], {%1, %2};" :: "r"(a), "f"(x), "f"(y) : "memory"); }
__device__ __forceinline__ void sts_u4(uint32_t a, uint4 v) { asm volatile("st.shared.v4.u32 [%0], {%1, %2, %3, %4};" :: "r"(a), "r"(v.x), "r"(v.y), "r"(v.z), "r"(v.w) : "memory"); }
__device__ __forceinline__ void sts_u1(uint32_t a, uint32_t v) { asm volatile("st.shared.u32 [%0], %1;" :: "r"(a), "r"(v) : "memory"); }
__device__ __forceinline__ void fence_async_smem() { asm volatile("fence.proxy.async.shared::cta;" ::: "memory"); }
__device__ __forceinline__ void bulk_store(void* dst, uint32_t src, uint32_t bytes) {
  asm volatile("cp.async.bulk.global.shared::cta.bulk_group [%0], [%1], %2;" :: "l"(dst), "r"(src), "r"(bytes) : "memory");
}
__device__ __forceinline__ void bulk_red_f32(void* dst, uint32_t src, uint32_t bytes) {
  asm volatile("cp.reduce.async.bulk.global.shared::cta.bulk_group.add.f32 [%0], [%1], %2;" :: "l"(dst), "r"(src), "r"(bytes) : "memory");
}
__device__ __forceinline__ void tma_store2d(const CUtensorMap* m, uint32_t src, int c0, int c1) {
  asm volatile("cp.async.bulk.tensor.2d.global.shared::cta.bulk_group [%0, {%2, %3}], [%1];" :: "l"(m), "r"(src), "r"(c0), "r"(c1) : "memory");
}
__device__ __forceinline__ void bulk_done() { asm volatile("cp.async.bulk.commit_group;\ncp.async.bulk.wait_group 0;" ::: "memory"); }
__device__ __forceinline__ void flag_add(unsigned* f) { asm volatile("red.relaxed.gpu.global.add.u32 [%0], 1;" :: "l"(f) : "memory"); }
__device__ __forceinline__ float4 lds_f4(uint32_t a) { return *reinterpret_cast<const float4*>(__cvta_shared_to_generic(a)); }
__device__ __forceinline__ uint4 lds_u4(uint32_t a) { return *reinterpret_cast<const uint4*>(__cvta_shared_to_generic(a)); }
__device__ __forceinline__ void lds8(uint32_t a, float (&v)[8]) {
  const float4 p = lds_f4(a), q = lds_f4(a + 16);
  v[0] = p.x; v[1] = p.y; v[2] = p.z; v[3] = p.w; v[4] = q.x; v[5] = q.y; v[6] = q.z; v[7] = q.w;
}
__device__ __forceinline__ void lds8_bf(uint32_t a, float (&v)[8]) {
  const uint4 u = lds_u4(a);
  v[0] = bf_lo(u.x); v[1] = bf_hi(u.x); v[2] = bf_lo(u.y); v[3] = bf_hi(u.y); v[4] = bf_lo(u.z); v[5] = bf_hi(u.z); v[6] = bf_lo(u.w); v[7] = bf_hi(u.w);
}
__device__ __forceinline__ uint4 pack8(const float (&v)[8]) {
  return make_uint4(pack_bf16(v[0], v[1]), pack_bf16(v[2], v[3]), pack_bf16(v[4], v[5]), pack_bf16(v[6], v[7]));
}
__device__ __forceinline__ void mbar_wait_c(uint32_t a, uint32_t ph) {
  asm volatile("{\n.reg .pred p;\nSPIN:\nmbarrier.try_wait.parity.shared::cta.b64 p, [%0], %1;\n@!p bra SPIN;\n}\n" :: "r"(a), "r"(ph) : "memory");
}
constexpr int ST_P = 80;
constexpr int E_TILE = 128 * 80 * 2;

struct Maps { CUtensorMap h, wq, k, v, o, wo3, wo2, xa, w1t, us, w2t, x1, w3, g, w4t, ex, exa, ex1, sxa, sus, sx1, sout; };
struct PfList { const uint8_t* p[6]; };

constexpr int M_AOFF = 5 * A_SLOT, M_NA = 6, M_ARING = M_NA * 8192;

__global__ void __cluster_dims__(2, 1, 1) __launch_bounds__(384, 1)
fused_kernel(const __grid_constant__ Maps tm, const __grid_constant__ PfList pf, const __grid_constant__ PrepW pw, const bf16* __restrict__ x, bf16* __restrict__ out) {
  extern __shared__ uint8_t smem_raw[];
  const uint32_t sb = (smem_u32(smem_raw) + 1023) & ~1023u;
  TL_ENTRY(2);
  const uint32_t bar_full = sb + A_NSLOT * A_SLOT;
  const uint32_t bar_empty = bar_full + 8 * A_NSLOT;
  const uint32_t bar_sig = bar_empty + 8 * A_NSLOT;
  const uint32_t mb_full = bar_sig + 16;
  const uint32_t mb_empty = mb_full + 136;
  const uint32_t par = sb + T_PAR;
  float* parf = reinterpret_cast<float*>(smem_raw + (par - smem_u32(smem_raw)));
  uint32_t rank;
  asm volatile("mov.u32 %0, %%cluster_ctarank;" : "=r"(rank));
  const int cid = blockIdx.x >> 1;
  const int wid = __shfl_sync(0xffffffffu, threadIdx.x >> 5, 0);
  const int wg = wid >> 2;
  const int qtile = (cid & 7) * 2 + rank, hbase = cid >> 3;
  const int o_qt = qtile, o_nh = (cid >> 3) & 1, o_ks = cid >> 4;
  const int o_col = o_nh * 320 + o_ks * 80;
  const int qt = cid >> 2, js = (cid & 3) * 2 + rank;
  if (threadIdx.x == 0) {
    for (int i = 0; i < A_NSLOT; i++) { mbar_init(bar_full + 8 * i, 1); mbar_init(bar_empty + 8 * i, 16); }
    mbar_init(bar_sig, 4); mbar_init(bar_sig + 8, 4);
    for (int i = 0; i < 17; i++) mbar_init(mb_full + 8 * i, 1);
    for (int i = 0; i < 11; i++) mbar_init(mb_empty + 8 * i, 8);
    asm volatile("fence.mbarrier_init.release.cluster;" ::: "memory");
    prefetch_tmap(&tm.h); prefetch_tmap(&tm.wq); prefetch_tmap(&tm.k); prefetch_tmap(&tm.v);
  }
  __syncthreads();
  cluster_sync();

  if (wg == 0) {
    asm volatile("setmaxnreg.dec.sync.aligned.u32 40;");
    if (wid == 0) {
      Ring r{0, 1};
#define P_ACQ(bytes_) do { mbar_wait(bar_empty + 8 * r.slot, r.phase); mbar_expect_e(bar_full + 8 * r.slot, bytes_); } while (0)
#define P_DST (sb + r.slot * A_SLOT)
#define P_BAR (bar_full + 8 * r.slot)
      uint64_t pol_ef;
      asm volatile("createpolicy.fractional.L2::evict_first.b64 %0, 1.0;" : "=l"(pol_ef));
      if (qtile < 10) l2_prefetch_t3d(&tm.wq, 0, qtile * 64, hbase * 3);
      else l2_prefetch_t3d((qtile & 1) ? &tm.v : &tm.k, 0, hbase * S_ + ((qtile - 10) >> 1) * 64, 0);
      pdl_wait();
      TL_WAITED(2);
#pragma unroll 1
      for (int item = 0; item < 4; item++) {
        const int head = hbase + 8 * item;
#pragma unroll 1
        for (int kb = 0; kb < 10; kb++) {
          P_ACQ(16384);
          tma2d(P_DST, &tm.h, P_BAR, kb * 64, qtile * 128);
          r.adv(A_NSLOT);
          P_ACQ(A_SLOT);
          if ((uint32_t)(kb & 1) == rank) tma3d_mc_hint(P_DST, &tm.wq, P_BAR, 0, kb * 64, head * 3, 3, pol_ef);
          r.adv(A_NSLOT);
        }
#pragma unroll 1
        for (int j = 0; j <= A_NKV; j++) {
          if (j < A_NKV) {
            P_ACQ(A_SLOT);
            if (rank == 0) tma3d_mc_hint(P_DST, &tm.k, P_BAR, 0, head * S_ + j * 64, 0, 3, pol_ef);
            r.adv(A_NSLOT);
          }
          if (j > 0) {
            P_ACQ(A_SLOT);
            if (rank == 1) tma3d_mc_hint(P_DST, &tm.v, P_BAR, 0, head * S_ + (j - 1) * 64, 0, 3, pol_ef);
            r.adv(A_NSLOT);
          }
          if (item < 3 && j == 16 && qtile < 10) l2_prefetch_t3d(&tm.wq, 0, qtile * 64, (head + 8) * 3);
          if (item == 3 && (j & 3) == 0) {
            const int c = (j >> 2) * 128 + blockIdx.x;
            if (c < 980) {
              const int li = c < 480 ? 0 : c < 600 ? 1 : c < 720 ? 2 : c < 880 ? 3 : c < 930 ? 4 : 5;
              const int c0 = c < 480 ? 0 : c < 600 ? 480 : c < 720 ? 600 : c < 880 ? 720 : c < 930 ? 880 : 930;
              l2_prefetch16k(pf.p[li] + (size_t)(c - c0) * 16384);
            }
          }
          if (item == 3) {
            if (j >= 6 && j < 24) {
              const int kb = j - 6;
              l2_prefetch_t2d(&tm.o, ((kb / 6) * 8 + 2 * o_ks + (kb % 6) / 3) * DH_ + (kb % 3) * 64, o_qt * 128);
            }
            if (j >= 24 && j < 30) flag_wait(g_flag + F_O + o_qt * 32 + ((j - 24) >> 1) * 8 + 2 * o_ks + (j & 1), 2);
            if (j == 0 && threadIdx.x == 0) {
              prefetch_tmap(&tm.o); prefetch_tmap(&tm.wo3); prefetch_tmap(&tm.wo2); prefetch_tmap(&tm.xa); prefetch_tmap(&tm.w1t); prefetch_tmap(&tm.us);
              prefetch_tmap(&tm.w2t); prefetch_tmap(&tm.x1); prefetch_tmap(&tm.w3); prefetch_tmap(&tm.g); prefetch_tmap(&tm.w4t);
              prefetch_tmap(&tm.ex); prefetch_tmap(&tm.exa); prefetch_tmap(&tm.ex1);
              prefetch_tmap(&tm.sxa); prefetch_tmap(&tm.sus); prefetch_tmap(&tm.sx1); prefetch_tmap(&tm.sout);
            }
          }
        }
      }
#pragma unroll 1
      for (int kb = 0; kb < 24; kb++) {
        const int head = (kb / 6) * 8 + 2 * o_ks + (kb % 6) / 3;
        const int kcol = head * DH_ + (kb % 3) * 64;
        P_ACQ(24576);
        if (rank == 0) tma3d_mc(P_DST, &tm.wo3, P_BAR, 0, kcol, o_nh * 5, 3);
        r.adv(A_NSLOT);
        P_ACQ(16384);
        if (rank == 1) tma3d_mc(P_DST, &tm.wo2, P_BAR, 0, kcol, o_nh * 5 + 3, 3);
        r.adv(A_NSLOT);
        if (kb == 18 || kb == 21) flag_wait(g_flag + F_O + o_qt * 32 + head, 2);
        if (kb % 3 == 0) fence_async_global();
        P_ACQ(16384);
        tma2d(P_DST, &tm.o, P_BAR, kcol, o_qt * 128);
        r.adv(A_NSLOT);
      }
      P_ACQ(E_TILE);
      tma2d(P_DST, &tm.ex, P_BAR, o_col, o_qt * 128);
      r.adv(A_NSLOT);
      flag_wait(g_flag + F_XCH + (o_qt * 2 + o_nh) * 4 + o_ks, 6);
      fence_async_global();
#pragma unroll 1
      for (int i = 0; i < 3; i++) {
        P_ACQ(E_TILE);
        bulk_load(P_DST, g_xch + (size_t)((((o_qt * 2 + o_nh) * 4 + o_ks) * 4) + ((o_ks + 1 + i) & 3)) * (E_TILE / 2), E_TILE, P_BAR);
        r.adv(A_NSLOT);
      }
#pragma unroll 1
      for (int i = 0; i < A_NSLOT; i++) { mbar_wait(bar_empty + 8 * r.slot, r.phase); r.adv(A_NSLOT); }
      bar_arrive(7, 64);
      Ring ra{0, 1};
      const uint32_t fa = mb_full + 40 + rank * 48, fa_peer = mapa(fa, rank ^ 1);
      const int blk = qt * 2 + rank;
#pragma unroll 1
      for (int ph = 0; ph < 4; ph++) {
        const CUtensorMap* ma = ph == 0 ? &tm.xa : ph == 1 ? &tm.us : ph == 2 ? &tm.x1 : &tm.g;
        const int nkb = ph == 3 ? 24 : 10;
        const unsigned* fl = g_flag + F_XA + 32 * ph;
        TX(8 + ph * 4);
        flag_wait(fl + blk, 8);
        if (ph == 1) { if (blk > 0) flag_wait(fl + blk - 1, 8); if (blk < 31) flag_wait(fl + blk + 1, 8); }
        TX(9 + ph * 4);
        fence_async_global();
#pragma unroll 1
        for (int kb = 0; kb < nkb; kb++) {
          mbar_wait(mb_empty + 40 + 8 * ra.slot, ra.phase);
          mbar_expect_e(fa + 8 * ra.slot, 8192);
          asm volatile(ELECT_ "mbarrier.arrive.expect_tx.shared::cluster.b64 _, [%0], 8192;\n}\n" :: "r"(fa_peer + 8 * ra.slot) : "memory");
          tma2d_mc(sb + M_AOFF + rank * M_ARING + ra.slot * 8192, ma, fa + 8 * ra.slot, kb * 64, blk * 64, 3);
          ra.adv(M_NA);
        }
      }
    } else if (wid < 3) {
      const int w = wid - 1, lane = threadIdx.x & 31;
#pragma unroll 1
      for (int sig = 0; sig < 4; sig++) {
        mbar_wait(bar_sig + 8 * w, sig & 1);
        if (lane == 0) {
          asm volatile("fence.acq_rel.gpu;" ::: "memory");
          flag_add(g_flag + F_O + qtile * 32 + hbase + 8 * sig);
        }
        __syncwarp();
      }
    } else {
      const int lane = threadIdx.x & 31;
      pdl_wait();
      prep_warp(pw, reinterpret_cast<bf16(*)[72]>(smem_raw + (sb + T_PREP - smem_u32(smem_raw))), lane);
      flag_wait(g_flag + F_PREP, PREP_CTAS);
#pragma unroll 1
      for (int i = lane; i < P_SC; i += 32) {
        const int v = i < P_CS3 ? i / 80 : 9, j = i - (i < P_CS3 ? v * 80 : P_CS3);
        const float* src = v == 0 ? g_mod + 2 * D_ + o_col : v == 1 ? g_mod + 4 * D_ + o_col : v == 2 ? g_mod + 3 * D_ + o_col
                         : v < 6 ? g_vec + (v - 3) * D_ + js * 80 : v == 6 ? g_mod + 4 * D_ + js * 80 : v == 7 ? g_mod + 3 * D_ + js * 80
                         : v == 8 ? g_mod + 5 * D_ + js * 80 : g_vec + 3 * D_ + js * 192;
        parf[i] = __ldcg(src + j);
      }
      float sv[5] = {0.f, 0.f, 0.f, 0.f, 0.f};
#pragma unroll 1
      for (int i = lane; i < D_; i += 32) {
        const float a = __ldcg(g_mod + 4 * D_ + i), b = __ldcg(g_mod + 3 * D_ + i);
        sv[0] += a; sv[1] = fmaf(a, a, sv[1]); sv[2] = fmaf(a, b, sv[2]); sv[3] += b; sv[4] = fmaf(b, b, sv[4]);
      }
#pragma unroll 1
      for (int o_ = 16; o_ > 0; o_ >>= 1) {
#pragma unroll
        for (int i = 0; i < 5; i++) sv[i] += __shfl_xor_sync(0xffffffffu, sv[i], o_);
      }
      if (lane == 0) {
#pragma unroll
        for (int i = 0; i < 5; i++) parf[P_SC + i] = sv[i];
      }
      bar_arrive(6, 288);
      fence_async_global();
      bar_sync(7, 64);
      Ring rb{0, 1};
#pragma unroll 1
      for (int ph = 0; ph < 4; ph++) {
        const CUtensorMap* mb = ph == 0 ? &tm.w1t : ph == 1 ? &tm.w2t : ph == 2 ? &tm.w3 : &tm.w4t;
        const int nbl = ph == 2 ? 10 : ph == 3 ? 12 : 5;
        const int nel = ph == 1 ? 1 : ph == 3 ? 2 : 0;
#pragma unroll 1
        for (int bl = 0; bl < nbl + nel; bl++) {
          if (bl >= nbl) {
            const unsigned* fl = g_flag + (bl == nbl ? F_XA : F_X1) + qt * 2;
            flag_wait(fl, 8); flag_wait(fl + 1, 8);
            fence_async_global();
          }
          mbar_wait(mb_empty + 8 * rb.slot, rb.phase);
          mbar_expect_e(mb_full + 8 * rb.slot, ph == 2 ? 24576 : 20480);
          if (bl < nbl) tma3d(sb + rb.slot * A_SLOT, mb, mb_full + 8 * rb.slot, 0, ph == 2 ? bl * 64 : js * 80, ph == 2 ? js * 3 : bl * 2);
          else tma2d(sb + rb.slot * A_SLOT, bl == nbl ? &tm.exa : &tm.ex1, mb_full + 8 * rb.slot, js * 80, qt * 128);
          rb.adv(5);
        }
      }
    }
    __syncwarp();
    cluster_sync();
  } else {
    asm volatile("setmaxnreg.inc.sync.aligned.u32 232;");
    const int w = wg - 1;
    const int lane = threadIdx.x & 31;
    const int warp = wid & 3;
    const int tid = threadIdx.x - 128;
    const uint32_t rel_base = mapa(bar_empty, (lane == 0) ? rank : (rank ^ 1));
    Ring r{0, 0};
#define A_RELEASE(slot_) do { if (lane < 2) mbar_arrive_remote(rel_base + 8 * (slot_)); } while (0)
#define SIGNAL() do { __syncwarp(); if (lane == 0) mbar_arrive(bar_sig + 8 * w); } while (0)
    {
    const float SC = 0.07216878364870322f * 1.4426950408889634f;
    float o[96];
    uint32_t q[48];
    float s[32];
    uint32_t p[16], p2[16];
    if (w == 1) bar_arrive(1, 256);
    bf16* orow = g_o + (size_t)(qtile * 128 + w * 64 + warp * 16 + (lane >> 2)) * HD_ + (hbase - 8) * DH_ + (lane & 3) * 8;
#define O_STORE(g)                                                                                                     \
      {                                                                                                                \
        quad_transpose(q[8 * g], q[8 * g + 2], q[8 * g + 4], q[8 * g + 6], lane);                                      \
        stg128(orow + g * 32, make_uint4(q[8 * g], q[8 * g + 2], q[8 * g + 4], q[8 * g + 6]));                         \
        quad_transpose(q[8 * g + 1], q[8 * g + 3], q[8 * g + 5], q[8 * g + 7], lane);                                  \
        stg128(orow + (size_t)8 * HD_ + g * 32, make_uint4(q[8 * g + 1], q[8 * g + 3], q[8 * g + 5], q[8 * g + 7]));   \
      }
#pragma unroll 1
    for (int item = 0; item < 4; item++) {
      TSA(item, 0);
      {
        uint32_t prevA = 0, prevB = 0;
#pragma unroll
        for (int kb = 0; kb < 10; kb++) {
          const uint32_t sA = r.slot; mbar_wait_c(bar_full + 8 * sA, r.phase); r.adv(A_NSLOT);
          const uint32_t sB = r.slot; mbar_wait_c(bar_full + 8 * sB, r.phase); r.adv(A_NSLOT);
          const uint64_t da = mkdesc(sb + sA * A_SLOT + w * 8192, 16, 1024);
          const uint64_t db = mkdesc(sb + sB * A_SLOT, 8192, 1024);
          wg_fence();
#pragma unroll
          for (int kk = 0; kk < 4; kk++) wgmma_ss_n192<1>(o, da + kk * 2, db + kk * 128, (kb | kk) != 0);
          wg_commit();
          if (kb < 6 && item > 0) { O_STORE((kb < 6 ? kb : 0)) }
          if (kb == 6 && item > 0) SIGNAL();
          if (kb > 0) { wg_wait<1>(); A_RELEASE(prevA); A_RELEASE(prevB); }
          prevA = sA; prevB = sB;
        }
        wg_wait<0>();
        fence_regs(o);
        A_RELEASE(prevA); A_RELEASE(prevB);
#pragma unroll
        for (int i = 0; i < 48; i++) q[i] = pack_bf16(o[2 * i], o[2 * i + 1]);
      }
      orow += 8 * DH_;

      TSA(item, 1);
      float c0, c1, l0, l1;
      {
        const uint32_t sK = r.slot; mbar_wait_c(bar_full + 8 * sK, r.phase); r.adv(A_NSLOT);
        const uint64_t dk = mkdesc(sb + sK * A_SLOT, 16, 1024);
        bar_sync(1 + w, 256);
        wg_fence();
#pragma unroll
        for (int kk = 0; kk < 12; kk++)
          wgmma_rs_n64<0>(s, q[4 * kk], q[4 * kk + 1], q[4 * kk + 2], q[4 * kk + 3], dk + (kk >> 2) * 512 + (kk & 3) * 2, kk != 0);
        wg_commit();
        bar_arrive(1 + (w ^ 1), 256);
        wg_wait<0>();
        fence_regs(s);
        A_RELEASE(sK);
        float mx0 = fmaxf(s[0], s[1]), mx1 = fmaxf(s[2], s[3]);
#pragma unroll
        for (int i = 1; i < 8; i++) { mx0 = fmaxf(mx0, fmaxf(s[4 * i], s[4 * i + 1])); mx1 = fmaxf(mx1, fmaxf(s[4 * i + 2], s[4 * i + 3])); }
        mx0 = fmaxf(mx0, __shfl_xor_sync(0xffffffffu, mx0, 1)); mx1 = fmaxf(mx1, __shfl_xor_sync(0xffffffffu, mx1, 1));
        mx0 = fmaxf(mx0, __shfl_xor_sync(0xffffffffu, mx0, 2)); mx1 = fmaxf(mx1, __shfl_xor_sync(0xffffffffu, mx1, 2));
        c0 = mx0 * SC; c1 = mx1 * SC;
        l0 = 0.f; l1 = 0.f;
#pragma unroll
        for (int i = 0; i < 8; i++) {
          s[4 * i] = ex2(fmaf(s[4 * i], SC, -c0)); s[4 * i + 1] = ex2(fmaf(s[4 * i + 1], SC, -c0));
          s[4 * i + 2] = ex2(fmaf(s[4 * i + 2], SC, -c1)); s[4 * i + 3] = ex2(fmaf(s[4 * i + 3], SC, -c1));
          l0 += s[4 * i] + s[4 * i + 1]; l1 += s[4 * i + 2] + s[4 * i + 3];
        }
#pragma unroll
        for (int i = 0; i < 16; i++) p[i] = pack_bf16(s[2 * i], s[2 * i + 1]);
      }
      TSA(item, 2);
      uint32_t okn;
      {
        Ring r2 = r; r2.adv(A_NSLOT);
        okn = mbar_try(bar_full + 8 * r.slot, r.phase) & mbar_try(bar_full + 8 * r2.slot, r2.phase);
      }
#define A_STEP(PC, PN, FIRST)                                                                                          \
      {                                                                                                                \
        const uint32_t sK = r.slot, phK = r.phase; r.adv(A_NSLOT);                                                     \
        const uint32_t sV = r.slot, phV = r.phase; r.adv(A_NSLOT);                                                     \
        const uint64_t dk = mkdesc(sb + sK * A_SLOT, 16, 1024);                                                        \
        const uint64_t dv = mkdesc(sb + sV * A_SLOT, 8192, 1024);                                                      \
        if (!okn) { mbar_wait_c(bar_full + 8 * sK, phK); mbar_wait_c(bar_full + 8 * sV, phV); }                            \
        bar_sync(1 + w, 256);                                                                                          \
        wg_fence();                                                                                                    \
        _Pragma("unroll") for (int kk = 0; kk < 12; kk++)                                                              \
          wgmma_rs_n64<0>(s, q[4 * kk], q[4 * kk + 1], q[4 * kk + 2], q[4 * kk + 3], dk + (kk >> 2) * 512 + (kk & 3) * 2, kk != 0); \
        wg_commit();                                                                                                   \
        _Pragma("unroll") for (int kk = 0; kk < 4; kk++)                                                               \
          wgmma_rs_n192<1>(o, PC[4 * kk], PC[4 * kk + 1], PC[4 * kk + 2], PC[4 * kk + 3], dv + kk * 128, !(FIRST) || (kk != 0)); \
        wg_commit();                                                                                                   \
        bar_arrive(1 + (w ^ 1), 256);                                                                                  \
        {                                                                                                              \
          Ring r2 = r; r2.adv(A_NSLOT);                                                                                \
          okn = mbar_try(bar_full + 8 * r.slot, r.phase) & mbar_try(bar_full + 8 * r2.slot, r2.phase);                 \
        }                                                                                                              \
        wg_wait<1>();                                                                                                  \
        fence_regs(s);                                                                                                 \
        A_RELEASE(sK);                                                                                                 \
        float b0 = 0.f, b1 = 0.f;                                                                                      \
        _Pragma("unroll") for (int i = 0; i < 8; i++) {                                                                \
          const float e0 = ex2(fmaf(s[4 * i], SC, -c0)), e1 = ex2(fmaf(s[4 * i + 1], SC, -c0));                        \
          const float e2 = ex2(fmaf(s[4 * i + 2], SC, -c1)), e3 = ex2(fmaf(s[4 * i + 3], SC, -c1));                    \
          b0 += e0 + e1; b1 += e2 + e3;                                                                                \
          PN[2 * i] = pack_bf16(e0, e1); PN[2 * i + 1] = pack_bf16(e2, e3);                                            \
        }                                                                                                              \
        wg_wait<0>();                                                                                                  \
        fence_regs(o);                                                                                                 \
        fence_regs(PC);                                                                                                \
        A_RELEASE(sV);                                                                                                 \
        if (__any_sync(0xffffffffu, !(b0 <= 65536.f) || !(b1 <= 65536.f))) {                                           \
          float mx0 = fmaxf(s[0], s[1]), mx1 = fmaxf(s[2], s[3]);                                                      \
          _Pragma("unroll") for (int i = 1; i < 8; i++) {                                                              \
            mx0 = fmaxf(mx0, fmaxf(s[4 * i], s[4 * i + 1])); mx1 = fmaxf(mx1, fmaxf(s[4 * i + 2], s[4 * i + 3]));     \
          }                                                                                                            \
          mx0 = fmaxf(mx0, __shfl_xor_sync(0xffffffffu, mx0, 1)); mx1 = fmaxf(mx1, __shfl_xor_sync(0xffffffffu, mx1, 1)); \
          mx0 = fmaxf(mx0, __shfl_xor_sync(0xffffffffu, mx0, 2)); mx1 = fmaxf(mx1, __shfl_xor_sync(0xffffffffu, mx1, 2)); \
          const float n0 = fmaxf(c0, mx0 * SC), n1 = fmaxf(c1, mx1 * SC);                                              \
          const float a0 = ex2(c0 - n0), a1 = ex2(c1 - n1);                                                            \
          c0 = n0; c1 = n1;                                                                                            \
          l0 *= a0; l1 *= a1;                                                                                          \
          _Pragma("unroll") for (int i = 0; i < 24; i++) { o[4 * i] *= a0; o[4 * i + 1] *= a0; o[4 * i + 2] *= a1; o[4 * i + 3] *= a1; } \
          b0 = 0.f; b1 = 0.f;                                                                                          \
          _Pragma("unroll") for (int i = 0; i < 8; i++) {                                                              \
            const float e0 = ex2(fmaf(s[4 * i], SC, -c0)), e1 = ex2(fmaf(s[4 * i + 1], SC, -c0));                      \
            const float e2 = ex2(fmaf(s[4 * i + 2], SC, -c1)), e3 = ex2(fmaf(s[4 * i + 3], SC, -c1));                  \
            b0 += e0 + e1; b1 += e2 + e3;                                                                              \
            PN[2 * i] = pack_bf16(e0, e1); PN[2 * i + 1] = pack_bf16(e2, e3);                                          \
          }                                                                                                            \
        }                                                                                                              \
        l0 += b0; l1 += b1;                                                                                            \
      }
      for (int jj = 0; jj < 15; jj++) {
        A_STEP(p, p2, jj == 0)
        A_STEP(p2, p, false)
      }
      A_STEP(p, p2, false)
      TSA(item, 3);
      {
        const uint32_t sV = r.slot; mbar_wait_c(bar_full + 8 * sV, r.phase); r.adv(A_NSLOT);
        const uint64_t dv = mkdesc(sb + sV * A_SLOT, 8192, 1024);
        bar_sync(1 + w, 256);
        wg_fence();
#pragma unroll
        for (int kk = 0; kk < 4; kk++)
          wgmma_rs_n192<1>(o, p2[4 * kk], p2[4 * kk + 1], p2[4 * kk + 2], p2[4 * kk + 3], dv + kk * 128, 1);
        wg_commit();
        bar_arrive(1 + (w ^ 1), 256);
        wg_wait<0>();
        fence_regs(o);
        A_RELEASE(sV);
      }
      TSA(item, 4);
      l0 += __shfl_xor_sync(0xffffffffu, l0, 1); l1 += __shfl_xor_sync(0xffffffffu, l1, 1);
      l0 += __shfl_xor_sync(0xffffffffu, l0, 2); l1 += __shfl_xor_sync(0xffffffffu, l1, 2);
      const float i0 = __fdividef(1.f, l0), i1 = __fdividef(1.f, l1);
#pragma unroll
      for (int i = 0; i < 24; i++) { q[2 * i] = pack_bf16(o[4 * i] * i0, o[4 * i + 1] * i0); q[2 * i + 1] = pack_bf16(o[4 * i + 2] * i1, o[4 * i + 3] * i1); }
      TSA(item, 5);
    }
#pragma unroll
    for (int g = 0; g < 6; g++) { O_STORE(g) }
    SIGNAL();
    }
    TS(3, 2);
    const uint32_t st_w = (uint32_t)((warp * 16 + (lane >> 2)) * ST_P + (lane & 3) * 2) * 4;
    const uint32_t st_x = (lane & 8) << 2;
    const int er = (tid & 127) >> 1, eh = tid & 1;
    const uint32_t st_r = (uint32_t)(er * ST_P + (eh ^ ((er >> 1) & 1)) * 8) * 4;
    const uint32_t e_r = (uint32_t)((w * 64 + er) * 160 + eh * 16);
    const uint32_t p_r = par + eh * 32;
    const uint32_t stat = sb + T_PREP + w * 2048;
    const bool leader = (tid & 127) == 0;
#define STAGE10(ACC, BASE)                                                                                             \
    _Pragma("unroll") for (int nb = 0; nb < 10; nb++) {                                                                \
      sts_f2(stg + st_w + ((nb * 32) ^ st_x), ACC(BASE + 4 * nb), ACC(BASE + 4 * nb + 1));                                       \
      sts_f2(stg + st_w + ((nb * 32) ^ st_x) + 8 * ST_P * 4, ACC(BASE + 4 * nb + 2), ACC(BASE + 4 * nb + 3));                    \
    }

    {
      float acc1[96], acc2[64];
      uint32_t p0 = 0, p1 = 0, p2 = 0;
#pragma unroll 1
      for (int kb = 0; kb < 24; kb++) {
        const uint32_t s1 = r.slot; mbar_wait_c(bar_full + 8 * s1, r.phase); r.adv(A_NSLOT);
        const uint32_t s2 = r.slot; mbar_wait_c(bar_full + 8 * s2, r.phase); r.adv(A_NSLOT);
        const uint32_t sa = r.slot; mbar_wait_c(bar_full + 8 * sa, r.phase); r.adv(A_NSLOT);
        const uint64_t da = mkdesc(sb + sa * A_SLOT + w * 8192, 16, 1024);
        const uint64_t d1 = mkdesc(sb + s1 * A_SLOT, 8192, 1024), d2 = mkdesc(sb + s2 * A_SLOT, 8192, 1024);
        wg_fence();
#pragma unroll
        for (int kk = 0; kk < 4; kk++) {
          wgmma_ss_n192<1>(acc1, da + kk * 2, d1 + kk * 128, (kb | kk) != 0);
          wgmma_ss_n128<1>(acc2, da + kk * 2, d2 + kk * 128, (kb | kk) != 0);
        }
        wg_commit();
        if (kb > 0) { wg_wait<1>(); A_RELEASE(p0); A_RELEASE(p1); A_RELEASE(p2); }
        p0 = s1; p1 = s2; p2 = sa;
      }
      wg_wait<0>();
      fence_regs(acc1); fence_regs(acc2);
      A_RELEASE(p2);
      bar_sync(6, 288);
      TS(0, 0);
      const uint32_t stg = sb + (w ? p1 : p0) * A_SLOT;
#define OACC(e) (((e) < 96) ? acc1[(e) < 96 ? (e) : 0] : acc2[(e) >= 96 ? (e) - 96 : 0])
#define PACK10(BASE)                                                                                                   \
      _Pragma("unroll") for (int nb = 0; nb < 10; nb++) {                                                              \
        sts_u1(xo + nb * 16, pack_bf16(OACC(BASE + 4 * nb), OACC(BASE + 4 * nb + 1)));                                 \
        sts_u1(xo + nb * 16 + 8 * 160, pack_bf16(OACC(BASE + 4 * nb + 2), OACC(BASE + 4 * nb + 3)));                   \
      }
      const uint32_t f1 = r.slot + 4 >= A_NSLOT ? r.slot + 4 - A_NSLOT : r.slot + 4, f2 = f1 + 1 >= A_NSLOT ? 0 : f1 + 1;
#pragma unroll
      for (int d = 0; d < 4; d++) {
        if (d != o_ks) {
          const int i = (d - o_ks - 1) & 3;
          const uint32_t xo = sb + (i == 0 ? p2 : i == 1 ? f1 : f2) * A_SLOT + (w * 64 + warp * 16 + (lane >> 2)) * 160 + (lane & 3) * 4;
          PACK10(d * 40)
        }
      }
      fence_async_smem();
      bar_sync(3 + w, 128);
      if (leader) {
#pragma unroll 1
        for (int i = 0; i < 3; i++)
          bulk_store(g_xch + (size_t)((((o_qt * 2 + o_nh) * 4 + ((o_ks + 1 + i) & 3)) * 4) + o_ks) * (E_TILE / 2) + w * (E_TILE / 4),
                     sb + (i == 0 ? p2 : i == 1 ? f1 : f2) * A_SLOT + w * (E_TILE / 2), E_TILE / 2);
        bulk_done();
#pragma unroll 1
        for (int i = 0; i < 3; i++) flag_add(g_flag + F_XCH + (o_qt * 2 + o_nh) * 4 + ((o_ks + 1 + i) & 3));
        TX(40 + w);
      }
      if (o_ks == 0) { STAGE10(OACC, 0) } else if (o_ks == 1) { STAGE10(OACC, 40) } else if (o_ks == 2) { STAGE10(OACC, 80) } else { STAGE10(OACC, 120) }
      bar_sync(3 + w, 128);
      const uint32_t sx = r.slot; mbar_wait_c(bar_full + 8 * sx, r.phase); r.adv(A_NSLOT);
      const uint32_t q0 = r.slot; mbar_wait_c(bar_full + 8 * q0, r.phase); r.adv(A_NSLOT);
      const uint32_t q1 = r.slot; mbar_wait_c(bar_full + 8 * q1, r.phase); r.adv(A_NSLOT);
      const uint32_t q2 = r.slot; mbar_wait_c(bar_full + 8 * q2, r.phase); r.adv(A_NSLOT);
      TS(0, 1);
      float st[6] = {0.f, 0.f, 0.f, 0.f, 0.f, 0.f};
      const uint32_t ot = sb + p2 * A_SLOT;
#pragma unroll 1
      for (int c = 0; c < 5; c++) {
        float v[8], t0[8], t1[8], t2[8], xv[8], pg[8], pa_[8], pb_[8];
        lds8(stg + st_r + c * 64, v);
        lds8_bf(sb + q0 * A_SLOT + e_r + c * 32, t0); lds8_bf(sb + q1 * A_SLOT + e_r + c * 32, t1); lds8_bf(sb + q2 * A_SLOT + e_r + c * 32, t2);
        lds8_bf(sb + sx * A_SLOT + e_r + c * 32, xv);
        lds8(p_r + P_OGA * 4 + c * 64, pg); lds8(p_r + P_OA * 4 + c * 64, pa_); lds8(p_r + P_OB * 4 + c * 64, pb_);
#pragma unroll
        for (int e = 0; e < 8; e++) v[e] = fmaf(pg[e], v[e] + ((t0[e] + t1[e]) + t2[e]), xv[e]);
        const uint4 pk = pack8(v);
        sts_u4(ot + e_r + c * 32, pk);
        v[0] = bf_lo(pk.x); v[1] = bf_hi(pk.x); v[2] = bf_lo(pk.y); v[3] = bf_hi(pk.y); v[4] = bf_lo(pk.z); v[5] = bf_hi(pk.z); v[6] = bf_lo(pk.w); v[7] = bf_hi(pk.w);
#pragma unroll
        for (int e = 0; e < 8; e++) {
          const float y = pa_[e] * v[e];
          st[0] += v[e]; st[1] = fmaf(v[e], v[e], st[1]); st[2] += y; st[3] = fmaf(pa_[e], y, st[3]); st[4] = fmaf(y, y, st[4]); st[5] = fmaf(pb_[e], y, st[5]);
        }
      }
#pragma unroll
      for (int i = 0; i < 6; i++) st[i] += __shfl_xor_sync(0xffffffffu, st[i], 1);
      sts_u4(stat + er * 32 + eh * 16, eh ? make_uint4(__float_as_uint(st[4]), __float_as_uint(st[5]), 0u, 0u)
                                          : make_uint4(__float_as_uint(st[0]), __float_as_uint(st[1]), __float_as_uint(st[2]), __float_as_uint(st[3])));
      fence_async_smem();
      bar_sync(3 + w, 128);
      if (leader) {
        tma_store2d(&tm.sxa, ot + w * (E_TILE / 2), o_col, o_qt * 128 + w * 64);
        bulk_red_f32(g_st1 + (size_t)(o_qt * 128 + w * 64) * 8, stat, 2048);
        bulk_done();
        flag_add(g_flag + F_XA + o_qt * 2 + w);
      }
      bar_sync(5, 256);
      A_RELEASE(p0); A_RELEASE(p1); A_RELEASE(sx); A_RELEASE(q0); A_RELEASE(q1); A_RELEASE(q2);
      TS(0, 2);
    }

    Ring ra{0, 0}, rb{0, 0};
    const uint32_t rel_a = mapa(mb_empty + 40, w);
    const uint32_t aring = sb + M_AOFF + w * M_ARING;
#define B_NEXT(s_) do { s_ = rb.slot; mbar_wait_c(mb_full + 8 * s_, rb.phase); rb.adv(5); } while (0)
#define A_NEXT(s_) do { s_ = ra.slot; mbar_wait_c(mb_full + 40 + w * 48 + 8 * s_, ra.phase); ra.adv(M_NA); } while (0)
#define B_RELEASE(s_) do { if (lane == 0) mbar_arrive(mb_empty + 8 * (s_)); } while (0)
#define MA_RELEASE(s_) do { if (lane == 0) mbar_arrive_remote(rel_a + 8 * (s_)); } while (0)
    const int grow = qt * 128 + w * 64 + er;
    float mu = 0.f, rs = 0.f;
#pragma unroll 1
    for (int ph = 0; ph < 4; ph++) {
      float acc[96];
      float (&acc80)[40] = *reinterpret_cast<float(*)[40]>(&acc[0]);
      uint32_t pa = 0, pa2 = 0, pb = 0;
      float4 s03 = make_float4(0.f, 0.f, 0.f, 0.f);
      float2 s45 = make_float2(0.f, 0.f);
      const int nit = ph == 3 ? 12 : ph == 2 ? 10 : 5;
      if (w == 1 && ph < 2) bar_sync(5, 256);
#pragma unroll 1
      for (int it = 0; it < nit; it++) {
        uint32_t sbq, sa, sa2;
        B_NEXT(sbq);
        A_NEXT(sa);
        if (it == 0) TXC(ph);
        const uint64_t da = mkdesc(aring + sa * 8192, 16, 1024);
        if (ph == 2) {
          sa2 = sa;
          const uint64_t db = mkdesc(sb + sbq * A_SLOT, 8192, 1024);
          wg_fence();
#pragma unroll
          for (int kk = 0; kk < 4; kk++) wgmma_ss_n192<1>(acc, da + kk * 2, db + kk * 128, (it | kk) != 0);
          wg_commit();
        } else {
          A_NEXT(sa2);
          const uint64_t da2 = mkdesc(aring + sa2 * 8192, 16, 1024);
          const uint64_t db = mkdesc(sb + sbq * A_SLOT, 16, 1024);
          wg_fence();
#pragma unroll
          for (int kk = 0; kk < 4; kk++) wgmma_ss_n80<0>(acc80, da + kk * 2, db + kk * 2, (it | kk) != 0);
#pragma unroll
          for (int kk = 0; kk < 4; kk++) wgmma_ss_n80<0>(acc80, da2 + kk * 2, db + 640 + kk * 2, 1);
          wg_commit();
        }
        if (it > 0) { wg_wait<1>(); MA_RELEASE(pa); if (ph != 2) MA_RELEASE(pa2); B_RELEASE(pb); }
        else {
          if (ph == 0) { s03 = __ldcg(reinterpret_cast<const float4*>(g_st1 + (size_t)grow * 8)); s45 = __ldcg(reinterpret_cast<const float2*>(g_st1 + (size_t)grow * 8 + 4)); }
          if (ph == 2) s45 = __ldcg(reinterpret_cast<const float2*>(g_st2 + (size_t)grow * 2));
        }
        pa = sa; pa2 = sa2; pb = sbq;
      }
      if (w == 0 && ph < 2) bar_arrive(5, 256);
      wg_wait<0>();
      fence_regs(acc);
      MA_RELEASE(pa); if (ph != 2) MA_RELEASE(pa2);
      B_RELEASE(pb);
      bar_sync(3 + w, 128);
      TS(1 + (ph == 3 ? 0 : ph), ph == 3 ? 2 : 0);
      const uint32_t stg = aring, ot = aring + 20480;
      uint32_t e1 = 0;
#define MACC(e) acc[e]
      if (!(ph & 1)) {
        float c0, c1, c2 = 0.f, c3 = 0.f;
        if (ph == 0) {
          const float4 sc = lds_f4(par + P_SC * 4);
          const float sbb = lds_f(par + (P_SC + 4) * 4);
          mu = s03.x * (1.f / D_);
          rs = rsqrtf(fmaxf(s03.y * (1.f / D_) - mu * mu, 0.f) + LN_EPS);
          const float m2 = (rs * (s03.z - mu * sc.x) + sc.w) * (1.f / D_);
          const float e2 = (rs * rs * (s45.x - 2.f * mu * s03.w + mu * mu * sc.y) + 2.f * rs * (s45.y - mu * sc.z) + sbb) * (1.f / D_);
          c2 = rsqrtf(fmaxf(e2 - m2 * m2, 0.f) + LN_EPS);
          c0 = c2 * rs; c1 = -c0 * mu; c3 = -c2 * m2;
          if ((tid & 127) < 10) sts_u4(stat + (tid & 127) * 16, make_uint4(0, 0, 0, 0));
        } else {
          const float m = s45.x * (1.f / D_);
          c0 = rsqrtf(fmaxf(s45.y * (1.f / D_) - m * m, 0.f) + LN_EPS);
          c1 = -c0 * m;
        }
        const int npass = ph == 0 ? 1 : 3, nch = ph == 0 ? 5 : 4;
#pragma unroll 1
        for (int ps = 0; ps < npass; ps++) {
          if (ps == 0) { STAGE10(MACC, 0) } else if (ps == 1) { STAGE10(MACC, 32) } else { STAGE10(MACC, 56) }
          bar_sync(3 + w, 128);
          const uint32_t cofs = ps == 2 ? 64 : 0;
          const uint32_t pp = p_r + (ph == 0 ? P_VA : P_CS3 + ps * 64) * 4, pq = p_r + P_VB * 4;
#pragma unroll 1
          for (int c = 0; c < nch; c++) {
            float v[8], t[8], t2[8], t3[8];
            lds8(stg + st_r + cofs + c * 64, v);
            lds8(pp + c * 64, t);
            if (ph == 0) {
              lds8(pq + c * 64, t2); lds8(pq + 320 + c * 64, t3);
#pragma unroll
              for (int e = 0; e < 8; e++) t[e] = fmaf(c1, t[e], fmaf(c2, t2[e], c3 * t3[e]));
            } else {
#pragma unroll
              for (int e = 0; e < 8; e++) t[e] *= c1;
            }
#pragma unroll
            for (int e = 0; e < 8; e++) v[e] = gelu_tanh(fmaf(c0, v[e], t[e]));
            sts_u4(ot + (ph == 0 ? er * 160 + eh * 16 + c * 32 : ps * 8192 + er * 128 + (((2 * c + eh) ^ (er & 7)) << 4)), pack8(v));
          }
          fence_async_smem();
          bar_sync(3 + w, 128);
          if (leader) {
            if (ph == 0) {
              const int grp = js >> 1;
              const int sh = (grp & 2 ? 2 : 1) * (grp & 1 ? -1 : 1);
              tma_store2d(&tm.sus, ot, js * 80, qt * 128 + w * 64 + sh + 2);
              if (qt * 2 + w == (sh > 0 ? 0 : 31)) {
                const int r0 = sh > 0 ? 0 : S_ + sh, n = sh > 0 ? sh : -sh;
                for (int i = 0; i < n; i++) bulk_store(g_us + (size_t)(r0 + i + 2) * D_ + js * 80, stat, 160);
              }
            } else {
              tma_store2d(&tm.g, ot + ps * 8192, js * 192 + ps * 64, qt * 128 + w * 64);
            }
          }
        }
      } else {
        STAGE10(MACC, 0)
        uint32_t e2;
        B_NEXT(e1);
        e2 = e1;
        if (ph == 3) B_NEXT(e2);
        bar_sync(3 + w, 128);
        float s1 = 0.f, s2 = 0.f;
#pragma unroll 1
        for (int c = 0; c < 5; c++) {
          float v[8], xa[8], x1[8], ta[8], tb[8];
          lds8(stg + st_r + c * 64, v);
          lds8_bf(sb + e1 * A_SLOT + e_r + c * 32, xa); lds8_bf(sb + e2 * A_SLOT + e_r + c * 32, x1);
          lds8(p_r + (ph == 1 ? P_A2 : P_GB) * 4 + c * 64, ta); lds8(p_r + P_B2 * 4 + c * 64, tb);
          if (ph == 1) {
#pragma unroll
            for (int e = 0; e < 8; e++) v[e] += fmaf(ta[e] * rs, xa[e] - mu, tb[e]);
          } else {
#pragma unroll
            for (int e = 0; e < 8; e++) v[e] = fmaf(ta[e], v[e] + x1[e], xa[e]);
          }
          const uint4 pk = pack8(v);
          sts_u4(ot + er * 160 + eh * 16 + c * 32, pk);
          v[0] = bf_lo(pk.x); v[1] = bf_hi(pk.x); v[2] = bf_lo(pk.y); v[3] = bf_hi(pk.y); v[4] = bf_lo(pk.z); v[5] = bf_hi(pk.z); v[6] = bf_lo(pk.w); v[7] = bf_hi(pk.w);
#pragma unroll
          for (int e = 0; e < 8; e++) { s1 += v[e]; s2 = fmaf(v[e], v[e], s2); }
        }
        s1 += __shfl_xor_sync(0xffffffffu, s1, 1); s2 += __shfl_xor_sync(0xffffffffu, s2, 1);
        if (eh == 0) sts_f2(stat + er * 8, s1, s2);
        fence_async_smem();
        bar_sync(3 + w, 128);
        if (leader) {
          tma_store2d(ph == 1 ? &tm.sx1 : &tm.sout, ot, js * 80, qt * 128 + w * 64);
          if (ph == 1) bulk_red_f32(g_st2 + (size_t)(qt * 128 + w * 64) * 2, stat, 512);
        }
      }
      if (ph == 1) B_RELEASE(e1);
      if (leader) {
        bulk_done();
        if (ph < 3) flag_add(g_flag + F_US + 32 * ph + qt * 2 + w);
      }
      __syncwarp();
      TS(1 + (ph == 3 ? 0 : ph), ph == 3 ? 3 : 1);
    }
    if ((threadIdx.x & 127) == 0) TL_END(2);
    cluster_sync();
  }
}

typedef CUresult (*EncFn)(CUtensorMap*, CUtensorMapDataType, cuuint32_t, void*, const cuuint64_t*, const cuuint64_t*,
                          const cuuint32_t*, const cuuint32_t*, CUtensorMapInterleave, CUtensorMapSwizzle,
                          CUtensorMapL2promotion, CUtensorMapFloatOOBfill);
static EncFn g_enc = nullptr;

static CUtensorMap map2d(const void* p, uint64_t rows, uint64_t cols, uint32_t box_rows) {
  CUtensorMap m;
  cuuint64_t gd[2] = {cols, rows}; cuuint64_t gs[1] = {cols * 2};
  cuuint32_t bx[2] = {64, box_rows}; cuuint32_t es[2] = {1, 1};
  g_enc(&m, CU_TENSOR_MAP_DATA_TYPE_BFLOAT16, 2, const_cast<void*>(p), gd, gs, bx, es, CU_TENSOR_MAP_INTERLEAVE_NONE,
        CU_TENSOR_MAP_SWIZZLE_128B, CU_TENSOR_MAP_L2_PROMOTION_L2_256B, CU_TENSOR_MAP_FLOAT_OOB_FILL_NONE);
  return m;
}
static CUtensorMap map3d(const void* p, uint64_t rows, uint64_t cols, uint32_t box_rows, uint32_t nblk) {
  CUtensorMap m;
  cuuint64_t gd[3] = {64, rows, cols / 64}; cuuint64_t gs[2] = {cols * 2, 128};
  cuuint32_t bx[3] = {64, box_rows, nblk}; cuuint32_t es[3] = {1, 1, 1};
  g_enc(&m, CU_TENSOR_MAP_DATA_TYPE_BFLOAT16, 3, const_cast<void*>(p), gd, gs, bx, es, CU_TENSOR_MAP_INTERLEAVE_NONE,
        CU_TENSOR_MAP_SWIZZLE_128B, CU_TENSOR_MAP_L2_PROMOTION_L2_256B, CU_TENSOR_MAP_FLOAT_OOB_FILL_NONE);
  return m;
}

static CUtensorMap map_e(const void* p, uint32_t rows, uint64_t total_rows = S_) {
  CUtensorMap m;
  cuuint64_t gd[2] = {D_, total_rows}; cuuint64_t gs[1] = {D_ * 2};
  cuuint32_t bx[2] = {80, rows}; cuuint32_t es[2] = {1, 1};
  g_enc(&m, CU_TENSOR_MAP_DATA_TYPE_BFLOAT16, 2, const_cast<void*>(p), gd, gs, bx, es, CU_TENSOR_MAP_INTERLEAVE_NONE,
        CU_TENSOR_MAP_SWIZZLE_NONE, CU_TENSOR_MAP_L2_PROMOTION_L2_256B, CU_TENSOR_MAP_FLOAT_OOB_FILL_NONE);
  return m;
}

template <typename... KArgs, typename... Args>
static void launch(void (*kern)(KArgs...), dim3 grid, dim3 block, int smem, bool pdl, Args... args) {
  cudaLaunchConfig_t cfg = {};
  cfg.gridDim = grid; cfg.blockDim = block; cfg.dynamicSmemBytes = smem; cfg.stream = cudaStreamPerThread;
  cudaLaunchAttribute at[1];
  at[0].id = cudaLaunchAttributeProgrammaticStreamSerialization;
  at[0].val.programmaticStreamSerializationAllowed = 1;
  cfg.attrs = at; cfg.numAttrs = pdl ? 1 : 0;
  cudaLaunchKernelEx(&cfg, kern, KArgs(args)...);
}

extern "C" void kernel_launch(void* const* d_in, const int* in_sizes, int n_in, void* d_out, int out_size) {
  const bf16* x = (const bf16*)d_in[0];
  const bf16* kc = (const bf16*)d_in[1];
  const bf16* vc = (const bf16*)d_in[2];
  const bf16* wq = (const bf16*)d_in[3];
  const bf16* wo = (const bf16*)d_in[4];
  const bf16* w1 = (const bf16*)d_in[6];
  const bf16* w2 = (const bf16*)d_in[7];
  const bf16* w3 = (const bf16*)d_in[8];
  const bf16* w4 = (const bf16*)d_in[9];
  const bf16* c = (const bf16*)d_in[10];
  const bf16* wmod = (const bf16*)d_in[11];
  bf16* out = (bf16*)d_out;

  static void *p_h, *p_o, *p_xa, *p_us, *p_x1, *p_g, *p_w1t, *p_w2t, *p_w4t;
  if (!g_enc) {
    void* fn = nullptr; cudaDriverEntryPointQueryResult qr;
    cudaGetDriverEntryPoint("cuTensorMapEncodeTiled", &fn, cudaEnableDefault, &qr);
    g_enc = (EncFn)fn;
    cudaGetSymbolAddress(&p_h, g_h); cudaGetSymbolAddress(&p_o, g_o); cudaGetSymbolAddress(&p_xa, g_xa);
    cudaGetSymbolAddress(&p_us, g_us); cudaGetSymbolAddress(&p_x1, g_x1); cudaGetSymbolAddress(&p_g, g_g);
    cudaGetSymbolAddress(&p_w1t, g_w1t); cudaGetSymbolAddress(&p_w2t, g_w2t); cudaGetSymbolAddress(&p_w4t, g_w4t);
    cudaFuncSetAttribute(fused_kernel, cudaFuncAttributeMaxDynamicSharedMemorySize, T_SMEM);
  }
  Maps tm;
  tm.h = map2d(p_h, S_, D_, 128);
  tm.wq = map3d(wq, D_, HD_, 64, 3);
  tm.k = map3d(kc, (uint64_t)H_ * S_, DH_, 64, 3);
  tm.v = map3d(vc, (uint64_t)H_ * S_, DH_, 64, 3);
  tm.o = map2d(p_o, S_, HD_, 128);
  tm.wo3 = map3d(wo, HD_, D_, 64, 3);
  tm.wo2 = map3d(wo, HD_, D_, 64, 2);
  tm.xa = map2d(p_xa, S_, D_, 64);
  tm.w1t = map3d(p_w1t, D_, D_, 80, 2);
  tm.us = map2d((const bf16*)p_us + 2 * D_, S_, D_, 64);
  tm.w2t = map3d(p_w2t, D_, D_, 80, 2);
  tm.x1 = map2d(p_x1, S_, D_, 64);
  tm.w3 = map3d(w3, D_, F_, 64, 3);
  tm.g = map2d(p_g, S_, F_, 64);
  tm.w4t = map3d(p_w4t, D_, F_, 80, 2);
  tm.ex = map_e(x, 128); tm.exa = map_e(p_xa, 128); tm.ex1 = map_e(p_x1, 128);
  tm.sxa = map_e(p_xa, 64); tm.sus = map_e(p_us, 64, S_ + 4); tm.sx1 = map_e(p_x1, 64); tm.sout = map_e(out, 64);
  PfList pf;
  pf.p[0] = (const uint8_t*)wo; pf.p[1] = (const uint8_t*)w3; pf.p[2] = (const uint8_t*)p_w4t;
  pf.p[3] = (const uint8_t*)x; pf.p[4] = (const uint8_t*)p_w1t; pf.p[5] = (const uint8_t*)p_w2t;

  launch(mod_kernel, dim3(80), dim3(256), 0, false, c, wmod);
  launch(ln1_kernel, dim3(256), dim3(256), 0, true, x);
  launch(fused_kernel, dim3(128), dim3(384), T_SMEM, true, tm, pf, PrepW{w1, w2, w3, w4, c, wmod}, x, out);
}
```

```cpp
#include <cuda_runtime.h>
#include <cuda.h>
#include <cuda_bf16.h>
#include <stdint.h>

typedef __nv_bfloat16 bf16;

constexpr int S_  = 2048;
constexpr int D_  = 640;
constexpr int H_  = 32;
constexpr int DH_ = 192;
constexpr int HD_ = H_ * DH_;
constexpr int F_  = 1536;
constexpr float LN_EPS = 1e-5f;

__device__ __forceinline__ uint32_t smem_u32(const void* p) { return (uint32_t)__cvta_generic_to_shared(p); }
__device__ __forceinline__ void mbar_init(uint32_t a, uint32_t c) { asm volatile("mbarrier.init.shared::cta.b64 [%0], %1;" :: "r"(a), "r"(c) : "memory"); }
__device__ __forceinline__ void mbar_expect(uint32_t a, uint32_t b) { asm volatile("mbarrier.arrive.expect_tx.shared::cta.b64 _, [%0], %1;" :: "r"(a), "r"(b) : "memory"); }
__device__ __forceinline__ void mbar_arrive(uint32_t a) { asm volatile("mbarrier.arrive.shared::cta.b64 _, [%0];" :: "r"(a) : "memory"); }
__device__ __forceinline__ void mbar_arrive_remote(uint32_t ra) { asm volatile("mbarrier.arrive.shared::cluster.b64 _, [%0];" :: "r"(ra) : "memory"); }
__device__ __forceinline__ uint32_t mapa(uint32_t a, uint32_t cta) { uint32_t r; asm volatile("mapa.shared::cluster.u32 %0, %1, %2;" : "=r"(r) : "r"(a), "r"(cta)); return r; }
__device__ __forceinline__ uint32_t mbar_try(uint32_t a, uint32_t ph) {
  uint32_t ok;
  asm volatile("{\n.reg .pred p;\nmbarrier.test_wait.parity.shared::cta.b64 p, [%1], %2;\nselp.u32 %0, 1, 0, p;\n}\n" : "=r"(ok) : "r"(a), "r"(ph) : "memory");
  return ok;
}
__device__ __forceinline__ void mbar_wait(uint32_t a, uint32_t ph) {
  asm volatile(
      "{\n.reg .pred p;\n.reg .u32 n;\n"
      "mov.u32 n, 0;\n"
      "SPIN:\n"
      "mbarrier.try_wait.parity.shared::cta.b64 p, [%0], %1;\n"
      "@p bra DONE;\n"
      "add.u32 n, n, 1;\n"
      "setp.le.u32 p, n, 16777216;\n"
      "@p bra SPIN;\n"
      "trap;\n"
      "DONE:\n}\n" :: "r"(a), "r"(ph) : "memory");
}
#define ELECT_ "{\n.reg .pred p;\nelect.sync _|p, 0xffffffff;\n@p "
__device__ __forceinline__ void mbar_expect_e(uint32_t a, uint32_t b) { asm volatile(ELECT_ "mbarrier.arrive.expect_tx.shared::cta.b64 _, [%0], %1;\n}\n" :: "r"(a), "r"(b) : "memory"); }
__device__ __forceinline__ void tma2d(uint32_t dst, const CUtensorMap* m, uint32_t bar, int c0, int c1) {
  asm volatile(ELECT_ "cp.async.bulk.tensor.2d.shared::cluster.global.mbarrier::complete_tx::bytes [%0], [%1, {%3, %4}], [%2];\n}\n"
               :: "r"(dst), "l"(m), "r"(bar), "r"(c0), "r"(c1) : "memory");
}
__device__ __forceinline__ void tma2d_mc(uint32_t dst, const CUtensorMap* m, uint32_t bar, int c0, int c1, uint16_t mask) {
  asm volatile(ELECT_ "cp.async.bulk.tensor.2d.shared::cluster.global.mbarrier::complete_tx::bytes.multicast::cluster [%0], [%1, {%3, %4}], [%2], %5;\n}\n"
               :: "r"(dst), "l"(m), "r"(bar), "r"(c0), "r"(c1), "h"(mask) : "memory");
}
__device__ __forceinline__ void tma3d(uint32_t dst, const CUtensorMap* m, uint32_t bar, int c0, int c1, int c2) {
  asm volatile(ELECT_ "cp.async.bulk.tensor.3d.shared::cluster.global.mbarrier::complete_tx::bytes [%0], [%1, {%3, %4, %5}], [%2];\n}\n"
               :: "r"(dst), "l"(m), "r"(bar), "r"(c0), "r"(c1), "r"(c2) : "memory");
}
__device__ __forceinline__ void tma3d_mc(uint32_t dst, const CUtensorMap* m, uint32_t bar, int c0, int c1, int c2, uint16_t mask) {
  asm volatile(ELECT_ "cp.async.bulk.tensor.3d.shared::cluster.global.mbarrier::complete_tx::bytes.multicast::cluster [%0], [%1, {%3, %4, %5}], [%2], %6;\n}\n"
               :: "r"(dst), "l"(m), "r"(bar), "r"(c0), "r"(c1), "r"(c2), "h"(mask) : "memory");
}
__device__ __forceinline__ void tma3d_mc_hint(uint32_t dst, const CUtensorMap* m, uint32_t bar, int c0, int c1, int c2, uint16_t mask, uint64_t pol) {
  asm volatile(ELECT_ "cp.async.bulk.tensor.3d.shared::cluster.global.mbarrier::complete_tx::bytes.multicast::cluster.L2::cache_hint [%0], [%1, {%3, %4, %5}], [%2], %6, %7;\n}\n"
               :: "r"(dst), "l"(m), "r"(bar), "r"(c0), "r"(c1), "r"(c2), "h"(mask), "l"(pol) : "memory");
}
__device__ __forceinline__ void bulk_load(uint32_t dst, const void* src, uint32_t bytes, uint32_t bar) {
  asm volatile(ELECT_ "cp.async.bulk.shared::cluster.global.mbarrier::complete_tx::bytes [%0], [%1], %2, [%3];\n}\n"
               :: "r"(dst), "l"(src), "r"(bytes), "r"(bar) : "memory");
}
__device__ __forceinline__ void l2_prefetch16k(const void* p) { asm volatile(ELECT_ "cp.async.bulk.prefetch.L2.global [%0], 16384;\n}\n" :: "l"(p) : "memory"); }
__device__ __forceinline__ void l2_prefetch_t2d(const CUtensorMap* m, int c0, int c1) {
  asm volatile(ELECT_ "cp.async.bulk.prefetch.tensor.2d.L2.global [%0, {%1, %2}];\n}\n" :: "l"(m), "r"(c0), "r"(c1) : "memory");
}
__device__ __forceinline__ void l2_prefetch_t3d(const CUtensorMap* m, int c0, int c1, int c2) {
  asm volatile(ELECT_ "cp.async.bulk.prefetch.tensor.3d.L2.global [%0, {%1, %2, %3}];\n}\n" :: "l"(m), "r"(c0), "r"(c1), "r"(c2) : "memory");
}
__device__ __forceinline__ void stg128(void* p, uint4 v) {
  asm volatile("st.global.v4.u32 [%0], {%1, %2, %3, %4};" :: "l"(p), "r"(v.x), "r"(v.y), "r"(v.z), "r"(v.w) : "memory");
}
__device__ __forceinline__ void prefetch_tmap(const CUtensorMap* m) { asm volatile("prefetch.tensormap [%0];" :: "l"(m) : "memory"); }
__device__ __forceinline__ void wg_fence() { asm volatile("wgmma.fence.sync.aligned;" ::: "memory"); }
__device__ __forceinline__ void wg_commit() { asm volatile("wgmma.commit_group.sync.aligned;" ::: "memory"); }
template <int N> __device__ __forceinline__ void wg_wait() { asm volatile("wgmma.wait_group.sync.aligned %0;" :: "n"(N) : "memory"); }
template <int N> __device__ __forceinline__ void fence_regs(float (&r)[N]) {
#pragma unroll
  for (int i = 0; i < N; i++) asm volatile("" : "+f"(r[i]) :: "memory");
}
template <int N> __device__ __forceinline__ void fence_regs(uint32_t (&r)[N]) {
#pragma unroll
  for (int i = 0; i < N; i++) asm volatile("" : "+r"(r[i]) :: "memory");
}
__device__ __forceinline__ uint64_t mkdesc(uint32_t addr, uint32_t lbo, uint32_t sbo) {
  return (uint64_t)((addr & 0x3FFFF) >> 4) | ((uint64_t)(lbo >> 4) << 16) | ((uint64_t)(sbo >> 4) << 32) | (1ull << 62);
}
__device__ __forceinline__ void bar_sync(int id, int n) { asm volatile("bar.sync %0, %1;" :: "r"(id), "r"(n) : "memory"); }
__device__ __forceinline__ void bar_arrive(int id, int n) { asm volatile("bar.arrive %0, %1;" :: "r"(id), "r"(n) : "memory"); }
__device__ __forceinline__ void cluster_sync() { asm volatile("barrier.cluster.arrive.aligned;\nbarrier.cluster.wait.aligned;" ::: "memory"); }
__device__ __forceinline__ void pdl_wait() { asm volatile("griddepcontrol.wait;" ::: "memory"); }
__device__ __forceinline__ void pdl_launch() { asm volatile("griddepcontrol.launch_dependents;" ::: "memory"); }
__device__ __forceinline__ float ex2(float x) { float y; asm("ex2.approx.ftz.f32 %0, %1;" : "=f"(y) : "f"(x)); return y; }
__device__ __forceinline__ uint32_t pack_bf16(float lo, float hi) { uint32_t r; asm("cvt.rn.bf16x2.f32 %0, %1, %2;" : "=r"(r) : "f"(hi), "f"(lo)); return r; }
__device__ __forceinline__ float bf_lo(uint32_t u) { return __uint_as_float(u << 16); }
__device__ __forceinline__ float bf_hi(uint32_t u) { return __uint_as_float(u & 0xffff0000u); }
__device__ __forceinline__ float bf_round(float x) { return __bfloat162float(__float2bfloat16_rn(x)); }
__device__ __forceinline__ float tanh_fast(float x) { float y; asm("tanh.approx.f32 %0, %1;" : "=f"(y) : "f"(x)); return y; }
__device__ __forceinline__ float gelu_tanh(float x) {
  float u = x * (0.7978845608028654f + 0.035677408136300125f * x * x);
  float hx = 0.5f * x;
  return fmaf(hx, tanh_fast(u), hx);
}
__device__ __forceinline__ float warp_sum(float v) {
#pragma unroll
  for (int o = 16; o > 0; o >>= 1) v += __shfl_xor_sync(0xffffffffu, v, o);
  return v;
}
__device__ __forceinline__ void quad_transpose(uint32_t& v0, uint32_t& v1, uint32_t& v2, uint32_t& v3, int lane) {
  const bool b0 = lane & 1, b1 = lane & 2;
  uint32_t s0 = b0 ? v0 : v1, s1 = b0 ? v2 : v3;
  s0 = __shfl_xor_sync(0xffffffffu, s0, 1); s1 = __shfl_xor_sync(0xffffffffu, s1, 1);
  if (b0) { v0 = s0; v2 = s1; } else { v1 = s0; v3 = s1; }
  uint32_t t0 = b1 ? v0 : v2, t1 = b1 ? v1 : v3;
  t0 = __shfl_xor_sync(0xffffffffu, t0, 2); t1 = __shfl_xor_sync(0xffffffffu, t1, 2);
  if (b1) { v0 = t0; v1 = t1; } else { v2 = t0; v3 = t1; }
}

#define TG(i)
#define TX(i)
#define TXC(i)
#define TSA(item, i)
#define TL_ENTRY(k)
#define TL_WAITED(k)
#define TL_END(k)
#define TS(item, i)
template<int TB> __device__ __forceinline__ void wgmma_rs_n64(float (&d)[32], uint32_t a0, uint32_t a1, uint32_t a2, uint32_t a3, uint64_t db, int scale_d) {
  asm volatile("{\n.reg .pred p;\nsetp.ne.b32 p, %37, 0;\n"
    "wgmma.mma_async.sync.aligned.m64n64k16.f32.bf16.bf16 {%0, %1, %2, %3, %4, %5, %6, %7, %8, %9, %10, %11, %12, %13, %14, %15, %16, %17, %18, %19, %20, %21, %22, %23, %24, %25, %26, %27, %28, %29, %30, %31}, {%32, %33, %34, %35}, %36, p, 1, 1, %38;\n}\n"
    : "+f"(d[0]), "+f"(d[1]), "+f"(d[2]), "+f"(d[3]), "+f"(d[4]), "+f"(d[5]), "+f"(d[6]), "+f"(d[7]), "+f"(d[8]), "+f"(d[9]), "+f"(d[10]), "+f"(d[11]), "+f"(d[12]), "+f"(d[13]), "+f"(d[14]), "+f"(d[15]), "+f"(d[16]), "+f"(d[17]), "+f"(d[18]), "+f"(d[19]), "+f"(d[20]), "+f"(d[21]), "+f"(d[22]), "+f"(d[23]), "+f"(d[24]), "+f"(d[25]), "+f"(d[26]), "+f"(d[27]), "+f"(d[28]), "+f"(d[29]), "+f"(d[30]), "+f"(d[31])
    : "r"(a0), "r"(a1), "r"(a2), "r"(a3), "l"(db), "r"(scale_d), "n"(TB));
}
template<int TB> __device__ __forceinline__ void wgmma_rs_n192(float (&d)[96], uint32_t a0, uint32_t a1, uint32_t a2, uint32_t a3, uint64_t db, int scale_d) {
  asm volatile("{\n.reg .pred p;\nsetp.ne.b32 p, %101, 0;\n"
    "wgmma.mma_async.sync.aligned.m64n192k16.f32.bf16.bf16 {%0, %1, %2, %3, %4, %5, %6, %7, %8, %9, %10, %11, %12, %13, %14, %15, %16, %17, %18, %19, %20, %21, %22, %23, %24, %25, %26, %27, %28, %29, %30, %31, %32, %33, %34, %35, %36, %37, %38, %39, %40, %41, %42, %43, %44, %45, %46, %47, %48, %49, %50, %51, %52, %53, %54, %55, %56, %57, %58, %59, %60, %61, %62, %63, %64, %65, %66, %67, %68, %69, %70, %71, %72, %73, %74, %75, %76, %77, %78, %79, %80, %81, %82, %83, %84, %85, %86, %87, %88, %89, %90, %91, %92, %93, %94, %95}, {%96, %97, %98, %99}, %100, p, 1, 1, %102;\n}\n"
    : "+f"(d[0]), "+f"(d[1]), "+f"(d[2]), "+f"(d[3]), "+f"(d[4]), "+f"(d[5]), "+f"(d[6]), "+f"(d[7]), "+f"(d[8]), "+f"(d[9]), "+f"(d[10]), "+f"(d[11]), "+f"(d[12]), "+f"(d[13]), "+f"(d[14]), "+f"(d[15]), "+f"(d[16]), "+f"(d[17]), "+f"(d[18]), "+f"(d[19]), "+f"(d[20]), "+f"(d[21]), "+f"(d[22]), "+f"(d[23]), "+f"(d[24]), "+f"(d[25]), "+f"(d[26]), "+f"(d[27]), "+f"(d[28]), "+f"(d[29]), "+f"(d[30]), "+f"(d[31]), "+f"(d[32]), "+f"(d[33]), "+f"(d[34]), "+f"(d[35]), "+f"(d[36]), "+f"(d[37]), "+f"(d[38]), "+f"(d[39]), "+f"(d[40]), "+f"(d[41]), "+f"(d[42]), "+f"(d[43]), "+f"(d[44]), "+f"(d[45]), "+f"(d[46]), "+f"(d[47]), "+f"(d[48]), "+f"(d[49]), "+f"(d[50]), "+f"(d[51]), "+f"(d[52]), "+f"(d[53]), "+f"(d[54]), "+f"(d[55]), "+f"(d[56]), "+f"(d[57]), "+f"(d[58]), "+f"(d[59]), "+f"(d[60]), "+f"(d[61]), "+f"(d[62]), "+f"(d[63]), "+f"(d[64]), "+f"(d[65]), "+f"(d[66]), "+f"(d[67]), "+f"(d[68]), "+f"(d[69]), "+f"(d[70]), "+f"(d[71]), "+f"(d[72]), "+f"(d[73]), "+f"(d[74]), "+f"(d[75]), "+f"(d[76]), "+f"(d[77]), "+f"(d[78]), "+f"(d[79]), "+f"(d[80]), "+f"(d[81]), "+f"(d[82]), "+f"(d[83]), "+f"(d[84]), "+f"(d[85]), "+f"(d[86]), "+f"(d[87]), "+f"(d[88]), "+f"(d[89]), "+f"(d[90]), "+f"(d[91]), "+f"(d[92]), "+f"(d[93]), "+f"(d[94]), "+f"(d[95])
    : "r"(a0), "r"(a1), "r"(a2), "r"(a3), "l"(db), "r"(scale_d), "n"(TB));
}
template<int TB> __device__ __forceinline__ void wgmma_ss_n128(float (&d)[64], uint64_t da, uint64_t db, int scale_d) {
  asm volatile("{\n.reg .pred p;\nsetp.ne.b32 p, %66, 0;\n"
    "wgmma.mma_async.sync.aligned.m64n128k16.f32.bf16.bf16 {%0, %1, %2, %3, %4, %5, %6, %7, %8, %9, %10, %11, %12, %13, %14, %15, %16, %17, %18, %19, %20, %21, %22, %23, %24, %25, %26, %27, %28, %29, %30, %31, %32, %33, %34, %35, %36, %37, %38, %39, %40, %41, %42, %43, %44, %45, %46, %47, %48, %49, %50, %51, %52, %53, %54, %55, %56, %57, %58, %59, %60, %61, %62, %63}, %64, %65, p, 1, 1, 0, %67;\n}\n"
    : "+f"(d[0]), "+f"(d[1]), "+f"(d[2]), "+f"(d[3]), "+f"(d[4]), "+f"(d[5]), "+f"(d[6]), "+f"(d[7]), "+f"(d[8]), "+f"(d[9]), "+f"(d[10]), "+f"(d[11]), "+f"(d[12]), "+f"(d[13]), "+f"(d[14]), "+f"(d[15]), "+f"(d[16]), "+f"(d[17]), "+f"(d[18]), "+f"(d[19]), "+f"(d[20]), "+f"(d[21]), "+f"(d[22]), "+f"(d[23]), "+f"(d[24]), "+f"(d[25]), "+f"(d[26]), "+f"(d[27]), "+f"(d[28]), "+f"(d[29]), "+f"(d[30]), "+f"(d[31]), "+f"(d[32]), "+f"(d[33]), "+f"(d[34]), "+f"(d[35]), "+f"(d[36]), "+f"(d[37]), "+f"(d[38]), "+f"(d[39]), "+f"(d[40]), "+f"(d[41]), "+f"(d[42]), "+f"(d[43]), "+f"(d[44]), "+f"(d[45]), "+f"(d[46]), "+f"(d[47]), "+f"(d[48]), "+f"(d[49]), "+f"(d[50]), "+f"(d[51]), "+f"(d[52]), "+f"(d[53]), "+f"(d[54]), "+f"(d[55]), "+f"(d[56]), "+f"(d[57]), "+f"(d[58]), "+f"(d[59]), "+f"(d[60]), "+f"(d[61]), "+f"(d[62]), "+f"(d[63])
    : "l"(da), "l"(db), "r"(scale_d), "n"(TB));
}
template<int TB> __device__ __forceinline__ void wgmma_ss_n192(float (&d)[96], uint64_t da, uint64_t db, int scale_d) {
  asm volatile("{\n.reg .pred p;\nsetp.ne.b32 p, %98, 0;\n"
    "wgmma.mma_async.sync.aligned.m64n192k16.f32.bf16.bf16 {%0, %1, %2, %3, %4, %5, %6, %7, %8, %9, %10, %11, %12, %13, %14, %15, %16, %17, %18, %19, %20, %21, %22, %23, %24, %25, %26, %27, %28, %29, %30, %31, %32, %33, %34, %35, %36, %37, %38, %39, %40, %41, %42, %43, %44, %45, %46, %47, %48, %49, %50, %51, %52, %53, %54, %55, %56, %57, %58, %59, %60, %61, %62, %63, %64, %65, %66, %67, %68, %69, %70, %71, %72, %73, %74, %75, %76, %77, %78, %79, %80, %81, %82, %83, %84, %85, %86, %87, %88, %89, %90, %91, %92, %93, %94, %95}, %96, %97, p, 1, 1, 0, %99;\n}\n"
    : "+f"(d[0]), "+f"(d[1]), "+f"(d[2]), "+f"(d[3]), "+f"(d[4]), "+f"(d[5]), "+f"(d[6]), "+f"(d[7]), "+f"(d[8]), "+f"(d[9]), "+f"(d[10]), "+f"(d[11]), "+f"(d[12]), "+f"(d[13]), "+f"(d[14]), "+f"(d[15]), "+f"(d[16]), "+f"(d[17]), "+f"(d[18]), "+f"(d[19]), "+f"(d[20]), "+f"(d[21]), "+f"(d[22]), "+f"(d[23]), "+f"(d[24]), "+f"(d[25]), "+f"(d[26]), "+f"(d[27]), "+f"(d[28]), "+f"(d[29]), "+f"(d[30]), "+f"(d[31]), "+f"(d[32]), "+f"(d[33]), "+f"(d[34]), "+f"(d[35]), "+f"(d[36]), "+f"(d[37]), "+f"(d[38]), "+f"(d[39]), "+f"(d[40]), "+f"(d[41]), "+f"(d[42]), "+f"(d[43]), "+f"(d[44]), "+f"(d[45]), "+f"(d[46]), "+f"(d[47]), "+f"(d[48]), "+f"(d[49]), "+f"(d[50]), "+f"(d[51]), "+f"(d[52]), "+f"(d[53]), "+f"(d[54]), "+f"(d[55]), "+f"(d[56]), "+f"(d[57]), "+f"(d[58]), "+f"(d[59]), "+f"(d[60]), "+f"(d[61]), "+f"(d[62]), "+f"(d[63]), "+f"(d[64]), "+f"(d[65]), "+f"(d[66]), "+f"(d[67]), "+f"(d[68]), "+f"(d[69]), "+f"(d[70]), "+f"(d[71]), "+f"(d[72]), "+f"(d[73]), "+f"(d[74]), "+f"(d[75]), "+f"(d[76]), "+f"(d[77]), "+f"(d[78]), "+f"(d[79]), "+f"(d[80]), "+f"(d[81]), "+f"(d[82]), "+f"(d[83]), "+f"(d[84]), "+f"(d[85]), "+f"(d[86]), "+f"(d[87]), "+f"(d[88]), "+f"(d[89]), "+f"(d[90]), "+f"(d[91]), "+f"(d[92]), "+f"(d[93]), "+f"(d[94]), "+f"(d[95])
    : "l"(da), "l"(db), "r"(scale_d), "n"(TB));
}
template<int TB> __device__ __forceinline__ void wgmma_ss_n80(float (&d)[40], uint64_t da, uint64_t db, int scale_d) {
  asm volatile("{\n.reg .pred p;\nsetp.ne.b32 p, %42, 0;\n"
    "wgmma.mma_async.sync.aligned.m64n80k16.f32.bf16.bf16 {%0, %1, %2, %3, %4, %5, %6, %7, %8, %9, %10, %11, %12, %13, %14, %15, %16, %17, %18, %19, %20, %21, %22, %23, %24, %25, %26, %27, %28, %29, %30, %31, %32, %33, %34, %35, %36, %37, %38, %39}, %40, %41, p, 1, 1, 0, %43;\n}\n"
    : "+f"(d[0]), "+f"(d[1]), "+f"(d[2]), "+f"(d[3]), "+f"(d[4]), "+f"(d[5]), "+f"(d[6]), "+f"(d[7]), "+f"(d[8]), "+f"(d[9]), "+f"(d[10]), "+f"(d[11]), "+f"(d[12]), "+f"(d[13]), "+f"(d[14]), "+f"(d[15]), "+f"(d[16]), "+f"(d[17]), "+f"(d[18]), "+f"(d[19]), "+f"(d[20]), "+f"(d[21]), "+f"(d[22]), "+f"(d[23]), "+f"(d[24]), "+f"(d[25]), "+f"(d[26]), "+f"(d[27]), "+f"(d[28]), "+f"(d[29]), "+f"(d[30]), "+f"(d[31]), "+f"(d[32]), "+f"(d[33]), "+f"(d[34]), "+f"(d[35]), "+f"(d[36]), "+f"(d[37]), "+f"(d[38]), "+f"(d[39])
    : "l"(da), "l"(db), "r"(scale_d), "n"(TB));
}

__device__ __align__(128) float g_mod[6 * D_];
__device__ __align__(128) float g_modp[2][2 * D_];
__device__ __align__(1024) bf16 g_h[S_ * D_];
__device__ __align__(1024) bf16 g_o[S_ * HD_];
__device__ __align__(1024) bf16 g_xch[16 * 2 * 4 * 4 * 128 * 80];
__device__ __align__(1024) bf16 g_w1t[D_ * D_];
__device__ __align__(1024) bf16 g_w2t[D_ * D_];
__device__ __align__(1024) bf16 g_w4t[D_ * F_];
__device__ __align__(32) float g_st1[S_ * 8];
__device__ __align__(32) float g_st2[S_ * 2];
__device__ __align__(32) float g_vec[3 * D_ + F_ + 8];
__device__ unsigned g_flag[1024];
enum { F_XCH = 0, F_XA = 256, F_US = 288, F_X1 = 320, F_G = 352, F_PREP = 384, F_MOD2 = 416, F_O = 512 };
__device__ __align__(1024) bf16 g_xa[S_ * D_];
__device__ __align__(1024) bf16 g_us[(S_ + 4) * D_];
__device__ __align__(1024) bf16 g_x1[S_ * D_];
__device__ __align__(1024) bf16 g_g[S_ * F_];

__device__ __forceinline__ void row_stats(const float (&v)[20], float& mean, float& rstd) {
  float s = 0.f;
#pragma unroll
  for (int i = 0; i < 20; i++) s += v[i];
  mean = warp_sum(s) * (1.f / D_);
  float q = 0.f;
#pragma unroll
  for (int i = 0; i < 20; i++) { float d = v[i] - mean; q = fmaf(d, d, q); }
  rstd = rsqrtf(warp_sum(q) * (1.f / D_) + LN_EPS);
}
__device__ __forceinline__ void load_row_bf16(const bf16* p, int lane, float (&v)[20]) {
#pragma unroll
  for (int i = 0; i < 5; i++) {
    uint2 u = *reinterpret_cast<const uint2*>(p + (lane + 32 * i) * 4);
    v[4 * i] = bf_lo(u.x); v[4 * i + 1] = bf_hi(u.x); v[4 * i + 2] = bf_lo(u.y); v[4 * i + 3] = bf_hi(u.y);
  }
}
__device__ __forceinline__ void store_row_bf16(bf16* p, int lane, const float (&v)[20]) {
#pragma unroll
  for (int i = 0; i < 5; i++) {
    uint2 u; u.x = pack_bf16(v[4 * i], v[4 * i + 1]); u.y = pack_bf16(v[4 * i + 2], v[4 * i + 3]);
    *reinterpret_cast<uint2*>(p + (lane + 32 * i) * 4) = u;
  }
}
__device__ __forceinline__ void load_row_f32(const float* p, int lane, float (&v)[20]) {
#pragma unroll
  for (int i = 0; i < 5; i++) {
    float4 u = *reinterpret_cast<const float4*>(p + (lane + 32 * i) * 4);
    v[4 * i] = u.x; v[4 * i + 1] = u.y; v[4 * i + 2] = u.z; v[4 * i + 3] = u.w;
  }
}

__device__ __forceinline__ float silu_bf(float c) { return bf_round(__fdividef(c, 1.f + __expf(-c))); }
__device__ __forceinline__ void fma8(float (&acc)[8], float s, const uint4& w) {
  acc[0] = fmaf(s, bf_lo(w.x), acc[0]); acc[1] = fmaf(s, bf_hi(w.x), acc[1]); acc[2] = fmaf(s, bf_lo(w.y), acc[2]); acc[3] = fmaf(s, bf_hi(w.y), acc[3]);
  acc[4] = fmaf(s, bf_lo(w.z), acc[4]); acc[5] = fmaf(s, bf_hi(w.z), acc[5]); acc[6] = fmaf(s, bf_lo(w.w), acc[6]); acc[7] = fmaf(s, bf_hi(w.w), acc[7]);
}
__global__ void __launch_bounds__(256) mod_kernel(const bf16* __restrict__ c, const bf16* __restrict__ w_mod) {
  TL_ENTRY(0);
  pdl_launch();
  __shared__ float red[8][32];
  const int t = threadIdx.x, cg = t & 3, r0 = (blockIdx.x / 40) * 320 + (t >> 2), strip = blockIdx.x % 40;
  uint4 w[5];
  float cv[5];
#pragma unroll
  for (int i = 0; i < 5; i++) {
    w[i] = __ldg(reinterpret_cast<const uint4*>(w_mod + (size_t)(r0 + 64 * i) * (6 * D_) + strip * 32 + cg * 8));
    cv[i] = __bfloat162float(c[r0 + 64 * i]);
  }
  if (blockIdx.x < 14) { const int i = blockIdx.x * 256 + t; if (i < 3 * D_ + F_) g_vec[i] = 0.f; }
  else if (blockIdx.x < 18) g_flag[(blockIdx.x - 14) * 256 + t] = 0u;
  float acc[8];
#pragma unroll
  for (int j = 0; j < 8; j++) acc[j] = 0.f;
#pragma unroll
  for (int i = 0; i < 5; i++) fma8(acc, silu_bf(cv[i]), w[i]);
#pragma unroll 1
  for (int o = 4; o < 32; o <<= 1) {
#pragma unroll
    for (int j = 0; j < 8; j++) acc[j] += __shfl_xor_sync(0xffffffffu, acc[j], o);
  }
  if ((t & 31) < 4) {
    *reinterpret_cast<float4*>(&red[t >> 5][cg * 8]) = make_float4(acc[0], acc[1], acc[2], acc[3]);
    *reinterpret_cast<float4*>(&red[t >> 5][cg * 8 + 4]) = make_float4(acc[4], acc[5], acc[6], acc[7]);
  }
  __syncthreads();
  if (t < 32) {
    float s = 0.f;
#pragma unroll
    for (int w8 = 0; w8 < 8; w8++) s += red[w8][t];
    g_modp[blockIdx.x / 40][strip * 32 + t] = s;
    if (t == 0) TL_END(0);
  }
}

__global__ void __launch_bounds__(256) ln1_kernel(const bf16* __restrict__ x) {
  TL_ENTRY(1);
  pdl_launch();
  const int lane = threadIdx.x & 31, row = blockIdx.x * 8 + (threadIdx.x >> 5);
  float v[20];
  load_row_bf16(x + (size_t)row * D_, lane, v);
  float mean, rstd;
  row_stats(v, mean, rstd);
  if (lane < 8) g_st1[row * 8 + lane] = 0.f;
  if (lane < 2) g_st2[row * 2 + lane] = 0.f;
  pdl_wait();
  if (threadIdx.x == 0) TL_WAITED(1);
  float s0[20], s1[20], c0[20], c1[20];
  load_row_f32(g_modp[0], lane, s0); load_row_f32(g_modp[1], lane, s1);
  load_row_f32(g_modp[0] + D_, lane, c0); load_row_f32(g_modp[1] + D_, lane, c1);
#pragma unroll
  for (int i = 0; i < 20; i++) v[i] = fmaf((v[i] - mean) * rstd, bf_round(1.f + bf_round(c0[i] + c1[i])), bf_round(s0[i] + s1[i]));
  store_row_bf16(g_h + (size_t)row * D_, lane, v);
  if (threadIdx.x == 0) TL_END(1);
}

constexpr int PREP_JOBS = 200 + 200 + 480 + 480;
struct PrepW { const bf16 *w1, *w2, *w3, *w4, *c, *wmod; };
__device__ __forceinline__ void flag_wait(const unsigned* p, unsigned target);
__device__ __forceinline__ void prep_warp(const PrepW& pw, bf16 (*tile)[72], int lane) {
  if (blockIdx.x < 80) {
    const bf16* wp = pw.wmod + (size_t)(lane >> 2) * (6 * D_) + 2 * D_ + blockIdx.x * 32 + (lane & 3) * 8;
    float acc[8];
#pragma unroll
    for (int j = 0; j < 8; j++) acc[j] = 0.f;
#pragma unroll 1
    for (int i = 0; i < 80; i += 4) {
      uint4 w[4];
      float cv[4];
#pragma unroll
      for (int e = 0; e < 4; e++) { w[e] = __ldg(reinterpret_cast<const uint4*>(wp + (size_t)(i + e) * 8 * (6 * D_))); cv[e] = __bfloat162float(pw.c[(i + e) * 8 + (lane >> 2)]); }
#pragma unroll
      for (int e = 0; e < 4; e++) fma8(acc, silu_bf(cv[e]), w[e]);
    }
    const bool one = blockIdx.x >= 40 && blockIdx.x < 60;
#pragma unroll
    for (int j = 0; j < 8; j++) {
      acc[j] += __shfl_xor_sync(0xffffffffu, acc[j], 4); acc[j] += __shfl_xor_sync(0xffffffffu, acc[j], 8); acc[j] += __shfl_xor_sync(0xffffffffu, acc[j], 16);
      const float v = bf_round(acc[j]);
      if (lane < 4) g_mod[2 * D_ + blockIdx.x * 32 + lane * 8 + j] = one ? bf_round(1.f + v) : v;
    }
    __syncwarp();
    if (lane == 0) {
      asm volatile("fence.acq_rel.gpu;" ::: "memory");
      asm volatile("red.relaxed.gpu.global.add.u32 [%0], 1;" :: "l"(g_flag + F_MOD2) : "memory");
    }
  }
  flag_wait(g_flag + F_MOD2, 80);
#pragma unroll 1
  for (int job = blockIdx.x; job < PREP_JOBS; job += gridDim.x) {
    const bf16* src; bf16* dst; int ld = D_, ldd = D_, kt, nt, kind = 1;
    if (job < 200) { src = pw.w1; dst = g_w1t; kt = job / 10; nt = job % 10; kind = 0; }
    else if (job < 400) { src = pw.w2; dst = g_w2t; kt = (job - 200) / 10; nt = (job - 200) % 10; }
    else if (job < 880) { src = pw.w4; dst = g_w4t; ldd = F_; kt = (job - 400) / 10; nt = (job - 400) % 10; }
    else { src = pw.w3; dst = nullptr; ld = F_; kt = (job - 880) / 24; nt = (job - 880) % 24; kind = 2; }
    src += (size_t)(kt * 32 + (lane >> 3)) * ld + nt * 64 + (lane & 7) * 8;
    __syncwarp();
#pragma unroll
    for (int h = 0; h < 2; h++) {
      uint4 v[4];
#pragma unroll
      for (int i = 0; i < 4; i++) v[i] = __ldg(reinterpret_cast<const uint4*>(src + (size_t)(h * 16 + i * 4) * ld));
#pragma unroll
      for (int i = 0; i < 4; i++) *reinterpret_cast<uint4*>(&tile[h * 16 + i * 4 + (lane >> 3)][(lane & 7) * 8]) = v[i];
    }
    __syncwarp();
    const float* pa = g_mod + 4 * D_ + kt * 32;
    const float* pb = g_mod + 3 * D_ + kt * 32;
#pragma unroll 1
    for (int h = 0; h < 2; h++) {
      const int n = lane + 32 * h;
      float sa = 0.f, sb = 0.f, sc = 0.f;
#pragma unroll 1
      for (int c = 0; c < 4; c++) {
        uint32_t u[4];
#pragma unroll
        for (int e = 0; e < 4; e++) {
          const int k = c * 8 + 2 * e;
          float lo = __bfloat162float(tile[k][n]), hi = __bfloat162float(tile[k + 1][n]);
          sc += lo + hi;
          if (kind == 0) {
            const float2 a = __ldcg(reinterpret_cast<const float2*>(pa + k)), b = __ldcg(reinterpret_cast<const float2*>(pb + k));
            sb = fmaf(b.x, lo, fmaf(b.y, hi, sb));
            lo *= a.x; hi *= a.y;
          }
          u[e] = pack_bf16(lo, hi);
          sa += bf_lo(u[e]) + bf_hi(u[e]);
        }
        if (kind != 2) *reinterpret_cast<uint4*>(dst + (size_t)(nt * 64 + n) * ldd + kt * 32 + c * 8) = make_uint4(u[0], u[1], u[2], u[3]);
      }
      if (kind == 0) { atomicAdd(&g_vec[nt * 64 + n], sa); atomicAdd(&g_vec[D_ + nt * 64 + n], sb); atomicAdd(&g_vec[2 * D_ + nt * 64 + n], sc); }
      else if (kind == 2) atomicAdd(&g_vec[3 * D_ + nt * 64 + n], sc);
    }
  }
  __syncwarp();
  if (lane == 0) {
    asm volatile("fence.acq_rel.gpu;" ::: "memory");
    asm volatile("red.relaxed.gpu.global.add.u32 [%0], 1;" :: "l"(g_flag + F_PREP) : "memory");
  }
}

constexpr int A_NSLOT = 9;
constexpr int A_SLOT = 24576;
constexpr int A_NKV = S_ / 64;
constexpr int PREP_CTAS = 128;

struct Ring {
  uint32_t slot, phase;
  __device__ __forceinline__ void adv(int n) { if (++slot == (uint32_t)n) { slot = 0; phase ^= 1; } }
};
constexpr int T_PAR = A_NSLOT * A_SLOT + 448;
constexpr int T_PREP = T_PAR + 3712;
constexpr int T_SMEM = T_PREP + 32 * 72 * 2 + 1024;
enum { P_OGA = 0, P_OA = 80, P_OB = 160, P_VA = 240, P_VB = 320, P_VC = 400, P_A2 = 480, P_B2 = 560, P_GB = 640, P_CS3 = 720, P_SC = 912 };

__device__ __forceinline__ void flag_wait(const unsigned* p, unsigned target) {
  asm volatile(
      "{\n.reg .pred p;\n.reg .u32 n, v;\n"
      "mov.u32 n, 0;\n"
      "SPIN:\n"
      "ld.relaxed.gpu.global.u32 v, [%0];\n"
      "setp.ge.u32 p, v, %1;\n"
      "@p bra DONE;\n"
      "add.u32 n, n, 1;\n"
      "setp.gt.u32 p, n, 4194304;\n"
      "@p trap;\n"
      "bra SPIN;\n"
      "DONE:\n}\n" :: "l"(p), "r"(target) : "memory");
}
__device__ __forceinline__ void fence_async_global() { asm volatile("fence.proxy.async.global;" ::: "memory"); }
__device__ __forceinline__ float lds_f(uint32_t a) { float v; asm volatile("ld.shared.f32 %0, [%1];" : "=f"(v) : "r"(a)); return v; }
__device__ __forceinline__ float2 lds_f2(uint32_t a) { float2 v; asm volatile("ld.shared.v2.f32 {%0, %1}, [%2];" : "=f"(v.x), "=f"(v.y) : "r"(a)); return v; }
__device__ __forceinline__ uint4 ldcg4(const void* p) { return __ldcg(reinterpret_cast<const uint4*>(p)); }

__device__ __forceinline__ void sts_f2(uint32_t a, float x, float y) { asm volatile("st.shared.v2.f32 [%0], {%1, %2};" :: "r"(a), "f"(x), "f"(y) : "memory"); }
__device__ __forceinline__ void sts_u4(uint32_t a, uint4 v) { asm volatile("st.shared.v4.u32 [%0], {%1, %2, %3, %4};" :: "r"(a), "r"(v.x), "r"(v.y), "r"(v.z), "r"(v.w) : "memory"); }
__device__ __forceinline__ void sts_u1(uint32_t a, uint32_t v) { asm volatile("st.shared.u32 [%0], %1;" :: "r"(a), "r"(v) : "memory"); }
__device__ __forceinline__ void fence_async_smem() { asm volatile("fence.proxy.async.shared::cta;" ::: "memory"); }
__device__ __forceinline__ void bulk_store(void* dst, uint32_t src, uint32_t bytes) {
  asm volatile("cp.async.bulk.global.shared::cta.bulk_group [%0], [%1], %2;" :: "l"(dst), "r"(src), "r"(bytes) : "memory");
}
__device__ __forceinline__ void bulk_red_f32(void* dst, uint32_t src, uint32_t bytes) {
  asm volatile("cp.reduce.async.bulk.global.shared::cta.bulk_group.add.f32 [%0], [%1], %2;" :: "l"(dst), "r"(src), "r"(bytes) : "memory");
}
__device__ __forceinline__ void tma_store2d(const CUtensorMap* m, uint32_t src, int c0, int c1) {
  asm volatile("cp.async.bulk.tensor.2d.global.shared::cta.bulk_group [%0, {%2, %3}], [%1];" :: "l"(m), "r"(src), "r"(c0), "r"(c1) : "memory");
}
__device__ __forceinline__ void bulk_done() { asm volatile("cp.async.bulk.commit_group;\ncp.async.bulk.wait_group 0;" ::: "memory"); }
__device__ __forceinline__ void flag_add(unsigned* f) { asm volatile("red.relaxed.gpu.global.add.u32 [%0], 1;" :: "l"(f) : "memory"); }
__device__ __forceinline__ float4 lds_f4(uint32_t a) { return *reinterpret_cast<const float4*>(__cvta_shared_to_generic(a)); }
__device__ __forceinline__ uint4 lds_u4(uint32_t a) { return *reinterpret_cast<const uint4*>(__cvta_shared_to_generic(a)); }
__device__ __forceinline__ void lds8(uint32_t a, float (&v)[8]) {
  const float4 p = lds_f4(a), q = lds_f4(a + 16);
  v[0] = p.x; v[1] = p.y; v[2] = p.z; v[3] = p.w; v[4] = q.x; v[5] = q.y; v[6] = q.z; v[7] = q.w;
}
__device__ __forceinline__ void lds8_bf(uint32_t a, float (&v)[8]) {
  const uint4 u = lds_u4(a);
  v[0] = bf_lo(u.x); v[1] = bf_hi(u.x); v[2] = bf_lo(u.y); v[3] = bf_hi(u.y); v[4] = bf_lo(u.z); v[5] = bf_hi(u.z); v[6] = bf_lo(u.w); v[7] = bf_hi(u.w);
}
__device__ __forceinline__ uint4 pack8(const float (&v)[8]) {
  return make_uint4(pack_bf16(v[0], v[1]), pack_bf16(v[2], v[3]), pack_bf16(v[4], v[5]), pack_bf16(v[6], v[7]));
}
__device__ __forceinline__ void mbar_wait_c(uint32_t a, uint32_t ph) {
  asm volatile("{\n.reg .pred p;\nSPIN:\nmbarrier.try_wait.parity.shared::cta.b64 p, [%0], %1;\n@!p bra SPIN;\n}\n" :: "r"(a), "r"(ph) : "memory");
}
constexpr int ST_P = 80;
constexpr int E_TILE = 128 * 80 * 2;

struct Maps { CUtensorMap h, wq, k, v, o, wo3, wo2, xa, w1t, us, w2t, x1, w3, g, w4t, ex, sxa, sus, sx1, sout; };
struct PfList { const uint8_t* p[6]; };

constexpr int M_AOFF = 5 * A_SLOT, M_NA = 6, M_ARING = M_NA * 8192;

__global__ void __cluster_dims__(2, 1, 1) __launch_bounds__(384, 1)
fused_kernel(const __grid_constant__ Maps tm, const __grid_constant__ PfList pf, const __grid_constant__ PrepW pw, const bf16* __restrict__ x, bf16* __restrict__ out) {
  extern __shared__ uint8_t smem_raw[];
  const uint32_t sb = (smem_u32(smem_raw) + 1023) & ~1023u;
  TL_ENTRY(2);
  const uint32_t bar_full = sb + A_NSLOT * A_SLOT;
  const uint32_t bar_empty = bar_full + 8 * A_NSLOT;
  const uint32_t bar_sig = bar_empty + 8 * A_NSLOT;
  const uint32_t mb_full = bar_sig + 16;
  const uint32_t mb_e = mb_full + 136 + 88;
  const uint32_t mb_empty = mb_full + 136;
  const uint32_t par = sb + T_PAR;
  float* parf = reinterpret_cast<float*>(smem_raw + (par - smem_u32(smem_raw)));
  uint32_t rank;
  asm volatile("mov.u32 %0, %%cluster_ctarank;" : "=r"(rank));
  const int cid = blockIdx.x >> 1;
  const int wid = __shfl_sync(0xffffffffu, threadIdx.x >> 5, 0);
  const int wg = wid >> 2;
  const int qtile = (cid & 7) * 2 + rank, hbase = cid >> 3;
  const int o_qt = qtile, o_nh = (cid >> 3) & 1, o_ks = cid >> 4;
  const int o_col = o_nh * 320 + o_ks * 80;
  const int qt = cid >> 2, js = (cid & 3) * 2 + rank;
  if (threadIdx.x == 0) {
    for (int i = 0; i < A_NSLOT; i++) { mbar_init(bar_full + 8 * i, 1); mbar_init(bar_empty + 8 * i, 16); }
    mbar_init(bar_sig, 4); mbar_init(bar_sig + 8, 4);
    for (int i = 0; i < 17; i++) mbar_init(mb_full + 8 * i, 1);
    for (int i = 0; i < 11; i++) mbar_init(mb_empty + 8 * i, 8);
    mbar_init(mb_e, 1); mbar_init(mb_e + 8, 1);
    asm volatile("fence.mbarrier_init.release.cluster;" ::: "memory");
    prefetch_tmap(&tm.h); prefetch_tmap(&tm.wq); prefetch_tmap(&tm.k); prefetch_tmap(&tm.v);
  }
  __syncthreads();
  cluster_sync();

  if (wg == 0) {
    asm volatile("setmaxnreg.dec.sync.aligned.u32 40;");
    if (wid == 0) {
      Ring r{0, 1};
#define P_ACQ(bytes_) do { mbar_wait(bar_empty + 8 * r.slot, r.phase); mbar_expect_e(bar_full + 8 * r.slot, bytes_); } while (0)
#define P_DST (sb + r.slot * A_SLOT)
#define P_BAR (bar_full + 8 * r.slot)
      uint64_t pol_ef;
      asm volatile("createpolicy.fractional.L2::evict_first.b64 %0, 1.0;" : "=l"(pol_ef));
      if (qtile < 10) l2_prefetch_t3d(&tm.wq, 0, qtile * 64, hbase * 3);
      else l2_prefetch_t3d((qtile & 1) ? &tm.v : &tm.k, 0, hbase * S_ + ((qtile - 10) >> 1) * 64, 0);
      pdl_wait();
      TL_WAITED(2);
#pragma unroll 1
      for (int item = 0; item < 4; item++) {
        const int head = hbase + 8 * item;
#pragma unroll 1
        for (int kb = 0; kb < 10; kb++) {
          P_ACQ(16384);
          tma2d(P_DST, &tm.h, P_BAR, kb * 64, qtile * 128);
          r.adv(A_NSLOT);
          P_ACQ(A_SLOT);
          if ((uint32_t)(kb & 1) == rank) tma3d_mc_hint(P_DST, &tm.wq, P_BAR, 0, kb * 64, head * 3, 3, pol_ef);
          r.adv(A_NSLOT);
        }
#pragma unroll 1
        for (int j = 0; j <= A_NKV; j++) {
          if (j < A_NKV) {
            P_ACQ(A_SLOT);
            if (rank == 0) tma3d_mc_hint(P_DST, &tm.k, P_BAR, 0, head * S_ + j * 64, 0, 3, pol_ef);
            r.adv(A_NSLOT);
          }
          if (j > 0) {
            P_ACQ(A_SLOT);
            if (rank == 1) tma3d_mc_hint(P_DST, &tm.v, P_BAR, 0, head * S_ + (j - 1) * 64, 0, 3, pol_ef);
            r.adv(A_NSLOT);
          }
          if (item < 3 && j == 16 && qtile < 10) l2_prefetch_t3d(&tm.wq, 0, qtile * 64, (head + 8) * 3);
          if (item == 3 && (j & 3) == 0) {
            const int c = (j >> 2) * 128 + blockIdx.x;
            if (c < 980) {
              const int li = c < 480 ? 0 : c < 600 ? 1 : c < 720 ? 2 : c < 880 ? 3 : c < 930 ? 4 : 5;
              const int c0 = c < 480 ? 0 : c < 600 ? 480 : c < 720 ? 600 : c < 880 ? 720 : c < 930 ? 880 : 930;
              l2_prefetch16k(pf.p[li] + (size_t)(c - c0) * 16384);
            }
          }
          if (item == 3) {
            if (j >= 6 && j < 24) {
              const int kb = j - 6;
              l2_prefetch_t2d(&tm.o, ((kb / 6) * 8 + 2 * o_ks + (kb % 6) / 3) * DH_ + (kb % 3) * 64, o_qt * 128);
            }
            if (j >= 24 && j < 30) flag_wait(g_flag + F_O + o_qt * 32 + ((j - 24) >> 1) * 8 + 2 * o_ks + (j & 1), 2);
            if (j == 0 && threadIdx.x == 0) {
              prefetch_tmap(&tm.o); prefetch_tmap(&tm.wo3); prefetch_tmap(&tm.wo2); prefetch_tmap(&tm.xa); prefetch_tmap(&tm.w1t); prefetch_tmap(&tm.us);
              prefetch_tmap(&tm.w2t); prefetch_tmap(&tm.x1); prefetch_tmap(&tm.w3); prefetch_tmap(&tm.g); prefetch_tmap(&tm.w4t);
              prefetch_tmap(&tm.ex);
              prefetch_tmap(&tm.sxa); prefetch_tmap(&tm.sus); prefetch_tmap(&tm.sx1); prefetch_tmap(&tm.sout);
            }
          }
        }
      }
#pragma unroll 1
      for (int kb = 0; kb < 24; kb++) {
        const int head = (kb / 6) * 8 + 2 * o_ks + (kb % 6) / 3;
        const int kcol = head * DH_ + (kb % 3) * 64;
        P_ACQ(24576);
        if (rank == 0) tma3d_mc(P_DST, &tm.wo3, P_BAR, 0, kcol, o_nh * 5, 3);
        r.adv(A_NSLOT);
        P_ACQ(16384);
        if (rank == 1) tma3d_mc(P_DST, &tm.wo2, P_BAR, 0, kcol, o_nh * 5 + 3, 3);
        r.adv(A_NSLOT);
        if (kb == 18 || kb == 21) flag_wait(g_flag + F_O + o_qt * 32 + head, 2);
        if (kb % 3 == 0) fence_async_global();
        P_ACQ(16384);
        tma2d(P_DST, &tm.o, P_BAR, kcol, o_qt * 128);
        r.adv(A_NSLOT);
      }
      P_ACQ(E_TILE);
      tma2d(P_DST, &tm.ex, P_BAR, o_col, o_qt * 128);
      r.adv(A_NSLOT);
      flag_wait(g_flag + F_XCH + (o_qt * 2 + o_nh) * 4 + o_ks, 6);
      fence_async_global();
#pragma unroll 1
      for (int i = 0; i < 3; i++) {
        P_ACQ(E_TILE);
        bulk_load(P_DST, g_xch + (size_t)((((o_qt * 2 + o_nh) * 4 + o_ks) * 4) + ((o_ks + 1 + i) & 3)) * (E_TILE / 2), E_TILE, P_BAR);
        r.adv(A_NSLOT);
      }
#pragma unroll 1
      for (int i = 0; i < A_NSLOT; i++) { mbar_wait(bar_empty + 8 * r.slot, r.phase); r.adv(A_NSLOT); }
      bar_arrive(7, 64);
      Ring ra{0, 1};
      const uint32_t fa = mb_full + 40 + rank * 48, fa_peer = mapa(fa, rank ^ 1);
      const int blk = qt * 2 + rank;
#pragma unroll 1
      for (int ph = 0; ph < 4; ph++) {
        const CUtensorMap* ma = ph == 0 ? &tm.xa : ph == 1 ? &tm.us : ph == 2 ? &tm.x1 : &tm.g;
        const int nkb = ph == 3 ? 24 : 10;
        const unsigned* fl = g_flag + F_XA + 32 * ph;
        TX(8 + ph * 4);
        flag_wait(fl + blk, 8);
        if (ph == 1) { if (blk > 0) flag_wait(fl + blk - 1, 8); if (blk < 31) flag_wait(fl + blk + 1, 8); }
        TX(9 + ph * 4);
        fence_async_global();
#pragma unroll 1
        for (int kb = 0; kb < nkb; kb++) {
          mbar_wait(mb_empty + 40 + 8 * ra.slot, ra.phase);
          mbar_expect_e(fa + 8 * ra.slot, 8192);
          asm volatile(ELECT_ "mbarrier.arrive.expect_tx.shared::cluster.b64 _, [%0], 8192;\n}\n" :: "r"(fa_peer + 8 * ra.slot) : "memory");
          tma2d_mc(sb + M_AOFF + rank * M_ARING + ra.slot * 8192, ma, fa + 8 * ra.slot, kb * 64, blk * 64, 3);
          ra.adv(M_NA);
        }
      }
    } else if (wid < 3) {
      const int w = wid - 1, lane = threadIdx.x & 31;
#pragma unroll 1
      for (int sig = 0; sig < 4; sig++) {
        mbar_wait(bar_sig + 8 * w, sig & 1);
        if (lane == 0) {
          asm volatile("fence.acq_rel.gpu;" ::: "memory");
          flag_add(g_flag + F_O + qtile * 32 + hbase + 8 * sig);
        }
        __syncwarp();
      }
    } else {
      const int lane = threadIdx.x & 31;
      pdl_wait();
      prep_warp(pw, reinterpret_cast<bf16(*)[72]>(smem_raw + (sb + T_PREP - smem_u32(smem_raw))), lane);
      flag_wait(g_flag + F_PREP, PREP_CTAS);
#pragma unroll 1
      for (int i = lane; i < P_SC; i += 32) {
        const int v = i < P_CS3 ? i / 80 : 9, j = i - (i < P_CS3 ? v * 80 : P_CS3);
        const float* src = v == 0 ? g_mod + 2 * D_ + o_col : v == 1 ? g_mod + 4 * D_ + o_col : v == 2 ? g_mod + 3 * D_ + o_col
                         : v < 6 ? g_vec + (v - 3) * D_ + js * 80 : v == 6 ? g_mod + 4 * D_ + js * 80 : v == 7 ? g_mod + 3 * D_ + js * 80
                         : v == 8 ? g_mod + 5 * D_ + js * 80 : g_vec + 3 * D_ + js * 192;
        parf[i] = __ldcg(src + j);
      }
      float sv[5] = {0.f, 0.f, 0.f, 0.f, 0.f};
#pragma unroll 1
      for (int i = lane; i < D_; i += 32) {
        const float a = __ldcg(g_mod + 4 * D_ + i), b = __ldcg(g_mod + 3 * D_ + i);
        sv[0] += a; sv[1] = fmaf(a, a, sv[1]); sv[2] = fmaf(a, b, sv[2]); sv[3] += b; sv[4] = fmaf(b, b, sv[4]);
      }
#pragma unroll 1
      for (int o_ = 16; o_ > 0; o_ >>= 1) {
#pragma unroll
        for (int i = 0; i < 5; i++) sv[i] += __shfl_xor_sync(0xffffffffu, sv[i], o_);
      }
      if (lane == 0) {
#pragma unroll
        for (int i = 0; i < 5; i++) parf[P_SC + i] = sv[i];
      }
      bar_arrive(6, 288);
      fence_async_global();
      bar_sync(7, 64);
      Ring rb{0, 1};
#pragma unroll 1
      for (int ph = 0; ph < 4; ph++) {
        const CUtensorMap* mb = ph == 0 ? &tm.w1t : ph == 1 ? &tm.w2t : ph == 2 ? &tm.w3 : &tm.w4t;
        const int nbl = ph == 2 ? 10 : ph == 3 ? 12 : 5;
#pragma unroll 1
        for (int bl = 0; bl < nbl; bl++) {
          mbar_wait(mb_empty + 8 * rb.slot, rb.phase);
          mbar_expect_e(mb_full + 8 * rb.slot, ph == 2 ? 24576 : 20480);
          tma3d(sb + rb.slot * A_SLOT, mb, mb_full + 8 * rb.slot, 0, ph == 2 ? bl * 64 : js * 80, ph == 2 ? js * 3 : bl * 2);
          rb.adv(5);
        }
      }
    }
    __syncwarp();
    cluster_sync();
  } else {
    asm volatile("setmaxnreg.inc.sync.aligned.u32 232;");
    const int w = wg - 1;
    const int lane = threadIdx.x & 31;
    const int warp = wid & 3;
    const int tid = threadIdx.x - 128;
    const uint32_t rel_base = mapa(bar_empty, (lane == 0) ? rank : (rank ^ 1));
    Ring r{0, 0};
#define A_RELEASE(slot_) do { if (lane < 2) mbar_arrive_remote(rel_base + 8 * (slot_)); } while (0)
#define SIGNAL() do { __syncwarp(); if (lane == 0) mbar_arrive(bar_sig + 8 * w); } while (0)
    {
    const float SC = 0.07216878364870322f * 1.4426950408889634f;
    float o[96];
    uint32_t q[48];
    float s[32];
    uint32_t p[16], p2[16];
    if (w == 1) bar_arrive(1, 256);
    bf16* orow = g_o + (size_t)(qtile * 128 + w * 64 + warp * 16 + (lane >> 2)) * HD_ + (hbase - 8) * DH_ + (lane & 3) * 8;
#define O_STORE(g)                                                                                                     \
      {                                                                                                                \
        quad_transpose(q[8 * g], q[8 * g + 2], q[8 * g + 4], q[8 * g + 6], lane);                                      \
        stg128(orow + g * 32, make_uint4(q[8 * g], q[8 * g + 2], q[8 * g + 4], q[8 * g + 6]));                         \
        quad_transpose(q[8 * g + 1], q[8 * g + 3], q[8 * g + 5], q[8 * g + 7], lane);                                  \
        stg128(orow + (size_t)8 * HD_ + g * 32, make_uint4(q[8 * g + 1], q[8 * g + 3], q[8 * g + 5], q[8 * g + 7]));   \
      }
#pragma unroll 1
    for (int item = 0; item < 4; item++) {
      TSA(item, 0);
      {
        uint32_t prevA = 0, prevB = 0;
#pragma unroll
        for (int kb = 0; kb < 10; kb++) {
          const uint32_t sA = r.slot; mbar_wait_c(bar_full + 8 * sA, r.phase); r.adv(A_NSLOT);
          const uint32_t sB = r.slot; mbar_wait_c(bar_full + 8 * sB, r.phase); r.adv(A_NSLOT);
          const uint64_t da = mkdesc(sb + sA * A_SLOT + w * 8192, 16, 1024);
          const uint64_t db = mkdesc(sb + sB * A_SLOT, 8192, 1024);
          wg_fence();
#pragma unroll
          for (int kk = 0; kk < 4; kk++) wgmma_ss_n192<1>(o, da + kk * 2, db + kk * 128, (kb | kk) != 0);
          wg_commit();
          if (kb < 6 && item > 0) { O_STORE((kb < 6 ? kb : 0)) }
          if (kb == 6 && item > 0) SIGNAL();
          if (kb > 0) { wg_wait<1>(); A_RELEASE(prevA); A_RELEASE(prevB); }
          prevA = sA; prevB = sB;
        }
        wg_wait<0>();
        fence_regs(o);
        A_RELEASE(prevA); A_RELEASE(prevB);
#pragma unroll
        for (int i = 0; i < 48; i++) q[i] = pack_bf16(o[2 * i], o[2 * i + 1]);
      }
      orow += 8 * DH_;

      TSA(item, 1);
      float c0, c1, l0, l1;
      {
        const uint32_t sK = r.slot; mbar_wait_c(bar_full + 8 * sK, r.phase); r.adv(A_NSLOT);
        const uint64_t dk = mkdesc(sb + sK * A_SLOT, 16, 1024);
        bar_sync(1 + w, 256);
        wg_fence();
#pragma unroll
        for (int kk = 0; kk < 12; kk++)
          wgmma_rs_n64<0>(s, q[4 * kk], q[4 * kk + 1], q[4 * kk + 2], q[4 * kk + 3], dk + (kk >> 2) * 512 + (kk & 3) * 2, kk != 0);
        wg_commit();
        bar_arrive(1 + (w ^ 1), 256);
        wg_wait<0>();
        fence_regs(s);
        A_RELEASE(sK);
        float mx0 = fmaxf(s[0], s[1]), mx1 = fmaxf(s[2], s[3]);
#pragma unroll
        for (int i = 1; i < 8; i++) { mx0 = fmaxf(mx0, fmaxf(s[4 * i], s[4 * i + 1])); mx1 = fmaxf(mx1, fmaxf(s[4 * i + 2], s[4 * i + 3])); }
        mx0 = fmaxf(mx0, __shfl_xor_sync(0xffffffffu, mx0, 1)); mx1 = fmaxf(mx1, __shfl_xor_sync(0xffffffffu, mx1, 1));
        mx0 = fmaxf(mx0, __shfl_xor_sync(0xffffffffu, mx0, 2)); mx1 = fmaxf(mx1, __shfl_xor_sync(0xffffffffu, mx1, 2));
        c0 = mx0 * SC; c1 = mx1 * SC;
        l0 = 0.f; l1 = 0.f;
#pragma unroll
        for (int i = 0; i < 8; i++) {
          s[4 * i] = ex2(fmaf(s[4 * i], SC, -c0)); s[4 * i + 1] = ex2(fmaf(s[4 * i + 1], SC, -c0));
          s[4 * i + 2] = ex2(fmaf(s[4 * i + 2], SC, -c1)); s[4 * i + 3] = ex2(fmaf(s[4 * i + 3], SC, -c1));
          l0 += s[4 * i] + s[4 * i + 1]; l1 += s[4 * i + 2] + s[4 * i + 3];
        }
#pragma unroll
        for (int i = 0; i < 16; i++) p[i] = pack_bf16(s[2 * i], s[2 * i + 1]);
      }
      TSA(item, 2);
      uint32_t okn;
      {
        Ring r2 = r; r2.adv(A_NSLOT);
        okn = mbar_try(bar_full + 8 * r.slot, r.phase) & mbar_try(bar_full + 8 * r2.slot, r2.phase);
      }
#define A_STEP(PC, PN, FIRST)                                                                                          \
      {                                                                                                                \
        const uint32_t sK = r.slot, phK = r.phase; r.adv(A_NSLOT);                                                     \
        const uint32_t sV = r.slot, phV = r.phase; r.adv(A_NSLOT);                                                     \
        const uint64_t dk = mkdesc(sb + sK * A_SLOT, 16, 1024);                                                        \
        const uint64_t dv = mkdesc(sb + sV * A_SLOT, 8192, 1024);                                                      \
        if (!okn) { mbar_wait_c(bar_full + 8 * sK, phK); mbar_wait_c(bar_full + 8 * sV, phV); }                            \
        bar_sync(1 + w, 256);                                                                                          \
        wg_fence();                                                                                                    \
        _Pragma("unroll") for (int kk = 0; kk < 12; kk++)                                                              \
          wgmma_rs_n64<0>(s, q[4 * kk], q[4 * kk + 1], q[4 * kk + 2], q[4 * kk + 3], dk + (kk >> 2) * 512 + (kk & 3) * 2, kk != 0); \
        wg_commit();                                                                                                   \
        _Pragma("unroll") for (int kk = 0; kk < 4; kk++)                                                               \
          wgmma_rs_n192<1>(o, PC[4 * kk], PC[4 * kk + 1], PC[4 * kk + 2], PC[4 * kk + 3], dv + kk * 128, !(FIRST) || (kk != 0)); \
        wg_commit();                                                                                                   \
        bar_arrive(1 + (w ^ 1), 256);                                                                                  \
        {                                                                                                              \
          Ring r2 = r; r2.adv(A_NSLOT);                                                                                \
          okn = mbar_try(bar_full + 8 * r.slot, r.phase) & mbar_try(bar_full + 8 * r2.slot, r2.phase);                 \
        }                                                                                                              \
        wg_wait<1>();                                                                                                  \
        fence_regs(s);                                                                                                 \
        A_RELEASE(sK);                                                                                                 \
        float b0 = 0.f, b1 = 0.f;                                                                                      \
        _Pragma("unroll") for (int i = 0; i < 8; i++) {                                                                \
          const float e0 = ex2(fmaf(s[4 * i], SC, -c0)), e1 = ex2(fmaf(s[4 * i + 1], SC, -c0));                        \
          const float e2 = ex2(fmaf(s[4 * i + 2], SC, -c1)), e3 = ex2(fmaf(s[4 * i + 3], SC, -c1));                    \
          b0 += e0 + e1; b1 += e2 + e3;                                                                                \
          PN[2 * i] = pack_bf16(e0, e1); PN[2 * i + 1] = pack_bf16(e2, e3);                                            \
        }                                                                                                              \
        wg_wait<0>();                                                                                                  \
        fence_regs(o);                                                                                                 \
        fence_regs(PC);                                                                                                \
        A_RELEASE(sV);                                                                                                 \
        if (__any_sync(0xffffffffu, !(b0 <= 65536.f) || !(b1 <= 65536.f))) {                                           \
          float mx0 = fmaxf(s[0], s[1]), mx1 = fmaxf(s[2], s[3]);                                                      \
          _Pragma("unroll") for (int i = 1; i < 8; i++) {                                                              \
            mx0 = fmaxf(mx0, fmaxf(s[4 * i], s[4 * i + 1])); mx1 = fmaxf(mx1, fmaxf(s[4 * i + 2], s[4 * i + 3]));     \
          }                                                                                                            \
          mx0 = fmaxf(mx0, __shfl_xor_sync(0xffffffffu, mx0, 1)); mx1 = fmaxf(mx1, __shfl_xor_sync(0xffffffffu, mx1, 1)); \
          mx0 = fmaxf(mx0, __shfl_xor_sync(0xffffffffu, mx0, 2)); mx1 = fmaxf(mx1, __shfl_xor_sync(0xffffffffu, mx1, 2)); \
          const float n0 = fmaxf(c0, mx0 * SC), n1 = fmaxf(c1, mx1 * SC);                                              \
          const float a0 = ex2(c0 - n0), a1 = ex2(c1 - n1);                                                            \
          c0 = n0; c1 = n1;                                                                                            \
          l0 *= a0; l1 *= a1;                                                                                          \
          _Pragma("unroll") for (int i = 0; i < 24; i++) { o[4 * i] *= a0; o[4 * i + 1] *= a0; o[4 * i + 2] *= a1; o[4 * i + 3] *= a1; } \
          b0 = 0.f; b1 = 0.f;                                                                                          \
          _Pragma("unroll") for (int i = 0; i < 8; i++) {                                                              \
            const float e0 = ex2(fmaf(s[4 * i], SC, -c0)), e1 = ex2(fmaf(s[4 * i + 1], SC, -c0));                      \
            const float e2 = ex2(fmaf(s[4 * i + 2], SC, -c1)), e3 = ex2(fmaf(s[4 * i + 3], SC, -c1));                  \
            b0 += e0 + e1; b1 += e2 + e3;                                                                              \
            PN[2 * i] = pack_bf16(e0, e1); PN[2 * i + 1] = pack_bf16(e2, e3);                                          \
          }                                                                                                            \
        }                                                                                                              \
        l0 += b0; l1 += b1;                                                                                            \
      }
      for (int jj = 0; jj < 15; jj++) {
        A_STEP(p, p2, jj == 0)
        A_STEP(p2, p, false)
      }
      A_STEP(p, p2, false)
      TSA(item, 3);
      {
        const uint32_t sV = r.slot; mbar_wait_c(bar_full + 8 * sV, r.phase); r.adv(A_NSLOT);
        const uint64_t dv = mkdesc(sb + sV * A_SLOT, 8192, 1024);
        bar_sync(1 + w, 256);
        wg_fence();
#pragma unroll
        for (int kk = 0; kk < 4; kk++)
          wgmma_rs_n192<1>(o, p2[4 * kk], p2[4 * kk + 1], p2[4 * kk + 2], p2[4 * kk + 3], dv + kk * 128, 1);
        wg_commit();
        bar_arrive(1 + (w ^ 1), 256);
        wg_wait<0>();
        fence_regs(o);
        A_RELEASE(sV);
      }
      TSA(item, 4);
      l0 += __shfl_xor_sync(0xffffffffu, l0, 1); l1 += __shfl_xor_sync(0xffffffffu, l1, 1);
      l0 += __shfl_xor_sync(0xffffffffu, l0, 2); l1 += __shfl_xor_sync(0xffffffffu, l1, 2);
      const float i0 = __fdividef(1.f, l0), i1 = __fdividef(1.f, l1);
#pragma unroll
      for (int i = 0; i < 24; i++) { q[2 * i] = pack_bf16(o[4 * i] * i0, o[4 * i + 1] * i0); q[2 * i + 1] = pack_bf16(o[4 * i + 2] * i1, o[4 * i + 3] * i1); }
      TSA(item, 5);
    }
#pragma unroll
    for (int g = 0; g < 6; g++) { O_STORE(g) }
    SIGNAL();
    }
    TS(3, 2);
    const uint32_t st_w = (uint32_t)((warp * 16 + (lane >> 2)) * ST_P + (lane & 3) * 2) * 4;
    const uint32_t st_x = (lane & 8) << 2;
    const int er = (tid & 127) >> 1, eh = tid & 1;
    const uint32_t st_r = (uint32_t)(er * ST_P + (eh ^ ((er >> 1) & 1)) * 8) * 4;
    const uint32_t e_r = (uint32_t)((w * 64 + er) * 160 + eh * 16);
    const uint32_t p_r = par + eh * 32;
    const uint32_t stat = sb + T_PREP + w * 2048;
    const bool leader = (tid & 127) == 0;
#define STAGE10(ACC, BASE)                                                                                             \
    _Pragma("unroll") for (int nb = 0; nb < 10; nb++) {                                                                \
      sts_f2(stg + st_w + ((nb * 32) ^ st_x), ACC(BASE + 4 * nb), ACC(BASE + 4 * nb + 1));                                       \
      sts_f2(stg + st_w + ((nb * 32) ^ st_x) + 8 * ST_P * 4, ACC(BASE + 4 * nb + 2), ACC(BASE + 4 * nb + 3));                    \
    }

    {
      float acc1[96], acc2[64];
      uint32_t p0 = 0, p1 = 0, p2 = 0;
#pragma unroll 1
      for (int kb = 0; kb < 24; kb++) {
        const uint32_t s1 = r.slot; mbar_wait_c(bar_full + 8 * s1, r.phase); r.adv(A_NSLOT);
        const uint32_t s2 = r.slot; mbar_wait_c(bar_full + 8 * s2, r.phase); r.adv(A_NSLOT);
        const uint32_t sa = r.slot; mbar_wait_c(bar_full + 8 * sa, r.phase); r.adv(A_NSLOT);
        const uint64_t da = mkdesc(sb + sa * A_SLOT + w * 8192, 16, 1024);
        const uint64_t d1 = mkdesc(sb + s1 * A_SLOT, 8192, 1024), d2 = mkdesc(sb + s2 * A_SLOT, 8192, 1024);
        wg_fence();
#pragma unroll
        for (int kk = 0; kk < 4; kk++) {
          wgmma_ss_n192<1>(acc1, da + kk * 2, d1 + kk * 128, (kb | kk) != 0);
          wgmma_ss_n128<1>(acc2, da + kk * 2, d2 + kk * 128, (kb | kk) != 0);
        }
        wg_commit();
        if (kb > 0) { wg_wait<1>(); A_RELEASE(p0); A_RELEASE(p1); A_RELEASE(p2); }
        p0 = s1; p1 = s2; p2 = sa;
      }
      wg_wait<0>();
      fence_regs(acc1); fence_regs(acc2);
      A_RELEASE(p2);
      bar_sync(6, 288);
      TS(0, 0);
      const uint32_t stg = sb + (w ? p1 : p0) * A_SLOT;
#define OACC(e) (((e) < 96) ? acc1[(e) < 96 ? (e) : 0] : acc2[(e) >= 96 ? (e) - 96 : 0])
#define PACK10(BASE)                                                                                                   \
      _Pragma("unroll") for (int nb = 0; nb < 10; nb++) {                                                              \
        sts_u1(xo + nb * 16, pack_bf16(OACC(BASE + 4 * nb), OACC(BASE + 4 * nb + 1)));                                 \
        sts_u1(xo + nb * 16 + 8 * 160, pack_bf16(OACC(BASE + 4 * nb + 2), OACC(BASE + 4 * nb + 3)));                   \
      }
      const uint32_t f1 = r.slot + 4 >= A_NSLOT ? r.slot + 4 - A_NSLOT : r.slot + 4, f2 = f1 + 1 >= A_NSLOT ? 0 : f1 + 1;
#pragma unroll
      for (int d = 0; d < 4; d++) {
        if (d != o_ks) {
          const int i = (d - o_ks - 1) & 3;
          const uint32_t xo = sb + (i == 0 ? p2 : i == 1 ? f1 : f2) * A_SLOT + (w * 64 + warp * 16 + (lane >> 2)) * 160 + (lane & 3) * 4;
          PACK10(d * 40)
        }
      }
      fence_async_smem();
      bar_sync(3 + w, 128);
      if (leader) {
#pragma unroll 1
        for (int i = 0; i < 3; i++)
          bulk_store(g_xch + (size_t)((((o_qt * 2 + o_nh) * 4 + ((o_ks + 1 + i) & 3)) * 4) + o_ks) * (E_TILE / 2) + w * (E_TILE / 4),
                     sb + (i == 0 ? p2 : i == 1 ? f1 : f2) * A_SLOT + w * (E_TILE / 2), E_TILE / 2);
        bulk_done();
#pragma unroll 1
        for (int i = 0; i < 3; i++) flag_add(g_flag + F_XCH + (o_qt * 2 + o_nh) * 4 + ((o_ks + 1 + i) & 3));
        TX(40 + w);
      }
      if (o_ks == 0) { STAGE10(OACC, 0) } else if (o_ks == 1) { STAGE10(OACC, 40) } else if (o_ks == 2) { STAGE10(OACC, 80) } else { STAGE10(OACC, 120) }
      bar_sync(3 + w, 128);
      const uint32_t sx = r.slot; mbar_wait_c(bar_full + 8 * sx, r.phase); r.adv(A_NSLOT);
      const uint32_t q0 = r.slot; mbar_wait_c(bar_full + 8 * q0, r.phase); r.adv(A_NSLOT);
      const uint32_t q1 = r.slot; mbar_wait_c(bar_full + 8 * q1, r.phase); r.adv(A_NSLOT);
      const uint32_t q2 = r.slot; mbar_wait_c(bar_full + 8 * q2, r.phase); r.adv(A_NSLOT);
      TS(0, 1);
      float st[6] = {0.f, 0.f, 0.f, 0.f, 0.f, 0.f};
      const uint32_t ot = sb + p2 * A_SLOT;
#pragma unroll 1
      for (int c = 0; c < 5; c++) {
        float v[8], t0[8], t1[8], t2[8], xv[8], pg[8], pa_[8], pb_[8];
        lds8(stg + st_r + c * 64, v);
        lds8_bf(sb + q0 * A_SLOT + e_r + c * 32, t0); lds8_bf(sb + q1 * A_SLOT + e_r + c * 32, t1); lds8_bf(sb + q2 * A_SLOT + e_r + c * 32, t2);
        lds8_bf(sb + sx * A_SLOT + e_r + c * 32, xv);
        lds8(p_r + P_OGA * 4 + c * 64, pg); lds8(p_r + P_OA * 4 + c * 64, pa_); lds8(p_r + P_OB * 4 + c * 64, pb_);
#pragma unroll
        for (int e = 0; e < 8; e++) v[e] = fmaf(pg[e], v[e] + ((t0[e] + t1[e]) + t2[e]), xv[e]);
        const uint4 pk = pack8(v);
        sts_u4(ot + e_r + c * 32, pk);
        v[0] = bf_lo(pk.x); v[1] = bf_hi(pk.x); v[2] = bf_lo(pk.y); v[3] = bf_hi(pk.y); v[4] = bf_lo(pk.z); v[5] = bf_hi(pk.z); v[6] = bf_lo(pk.w); v[7] = bf_hi(pk.w);
#pragma unroll
        for (int e = 0; e < 8; e++) {
          const float y = pa_[e] * v[e];
          st[0] += v[e]; st[1] = fmaf(v[e], v[e], st[1]); st[2] += y; st[3] = fmaf(pa_[e], y, st[3]); st[4] = fmaf(y, y, st[4]); st[5] = fmaf(pb_[e], y, st[5]);
        }
      }
#pragma unroll
      for (int i = 0; i < 6; i++) st[i] += __shfl_xor_sync(0xffffffffu, st[i], 1);
      sts_u4(stat + er * 32 + eh * 16, eh ? make_uint4(__float_as_uint(st[4]), __float_as_uint(st[5]), 0u, 0u)
                                          : make_uint4(__float_as_uint(st[0]), __float_as_uint(st[1]), __float_as_uint(st[2]), __float_as_uint(st[3])));
      fence_async_smem();
      bar_sync(3 + w, 128);
      if (leader) {
        tma_store2d(&tm.sxa, ot + w * (E_TILE / 2), o_col, o_qt * 128 + w * 64);
        bulk_red_f32(g_st1 + (size_t)(o_qt * 128 + w * 64) * 8, stat, 2048);
        bulk_done();
        flag_add(g_flag + F_XA + o_qt * 2 + w);
      }
      bar_sync(5, 256);
      A_RELEASE(p0); A_RELEASE(p1); A_RELEASE(sx); A_RELEASE(q0); A_RELEASE(q1); A_RELEASE(q2);
      TS(0, 2);
    }

    Ring ra{0, 0}, rb{0, 0};
    const uint32_t rel_a = mapa(mb_empty + 40, w);
    const uint32_t aring = sb + M_AOFF + w * M_ARING;
#define B_NEXT(s_) do { s_ = rb.slot; mbar_wait_c(mb_full + 8 * s_, rb.phase); rb.adv(5); } while (0)
#define A_NEXT(s_) do { s_ = ra.slot; mbar_wait_c(mb_full + 40 + w * 48 + 8 * s_, ra.phase); ra.adv(M_NA); } while (0)
#define B_RELEASE(s_) do { if (lane == 0) mbar_arrive(mb_empty + 8 * (s_)); } while (0)
#define MA_RELEASE(s_) do { if (lane == 0) mbar_arrive_remote(rel_a + 8 * (s_)); } while (0)
    const int grow = qt * 128 + w * 64 + er;
    float mu = 0.f, rs = 0.f;
#pragma unroll 1
    for (int ph = 0; ph < 4; ph++) {
      float acc[96];
      float (&acc80)[40] = *reinterpret_cast<float(*)[40]>(&acc[0]);
      uint32_t pa = 0, pa2 = 0, pb = 0;
      float4 s03 = make_float4(0.f, 0.f, 0.f, 0.f);
      float2 s45 = make_float2(0.f, 0.f);
      const int nit = ph == 3 ? 12 : ph == 2 ? 10 : 5;
      if (w == 1 && ph < 2) bar_sync(5, 256);
#pragma unroll 1
      for (int it = 0; it < nit; it++) {
        uint32_t sbq, sa, sa2;
        B_NEXT(sbq);
        A_NEXT(sa);
        if (it == 0) TXC(ph);
        const uint64_t da = mkdesc(aring + sa * 8192, 16, 1024);
        if (ph == 2) {
          sa2 = sa;
          const uint64_t db = mkdesc(sb + sbq * A_SLOT, 8192, 1024);
          wg_fence();
#pragma unroll
          for (int kk = 0; kk < 4; kk++) wgmma_ss_n192<1>(acc, da + kk * 2, db + kk * 128, (it | kk) != 0);
          wg_commit();
        } else {
          A_NEXT(sa2);
          const uint64_t da2 = mkdesc(aring + sa2 * 8192, 16, 1024);
          const uint64_t db = mkdesc(sb + sbq * A_SLOT, 16, 1024);
          wg_fence();
#pragma unroll
          for (int kk = 0; kk < 4; kk++) wgmma_ss_n80<0>(acc80, da + kk * 2, db + kk * 2, (it | kk) != 0);
#pragma unroll
          for (int kk = 0; kk < 4; kk++) wgmma_ss_n80<0>(acc80, da2 + kk * 2, db + 640 + kk * 2, 1);
          wg_commit();
        }
        if (it > 0) { wg_wait<1>(); MA_RELEASE(pa); if (ph != 2) MA_RELEASE(pa2); B_RELEASE(pb); }
        else {
          if (ph == 0) { s03 = __ldcg(reinterpret_cast<const float4*>(g_st1 + (size_t)grow * 8)); s45 = __ldcg(reinterpret_cast<const float2*>(g_st1 + (size_t)grow * 8 + 4)); }
          if (ph == 2) s45 = __ldcg(reinterpret_cast<const float2*>(g_st2 + (size_t)grow * 2));
        }
        pa = sa; pa2 = sa2; pb = sbq;
      }
      if (w == 0 && ph < 2) bar_arrive(5, 256);
      wg_wait<0>();
      fence_regs(acc);
      MA_RELEASE(pa); if (ph != 2) MA_RELEASE(pa2);
      B_RELEASE(pb);
      bar_sync(3 + w, 128);
      TS(1 + (ph == 3 ? 0 : ph), ph == 3 ? 2 : 0);
      const uint32_t stg = aring, ot = aring + 20480;
#define MACC(e) acc[e]
      if (!(ph & 1)) {
        float c0, c1, c2 = 0.f, c3 = 0.f;
        if (ph == 0) {
          const float4 sc = lds_f4(par + P_SC * 4);
          const float sbb = lds_f(par + (P_SC + 4) * 4);
          mu = s03.x * (1.f / D_);
          rs = rsqrtf(fmaxf(s03.y * (1.f / D_) - mu * mu, 0.f) + LN_EPS);
          const float m2 = (rs * (s03.z - mu * sc.x) + sc.w) * (1.f / D_);
          const float e2 = (rs * rs * (s45.x - 2.f * mu * s03.w + mu * mu * sc.y) + 2.f * rs * (s45.y - mu * sc.z) + sbb) * (1.f / D_);
          c2 = rsqrtf(fmaxf(e2 - m2 * m2, 0.f) + LN_EPS);
          c0 = c2 * rs; c1 = -c0 * mu; c3 = -c2 * m2;
          if ((tid & 127) < 10) sts_u4(stat + (tid & 127) * 16, make_uint4(0, 0, 0, 0));
        } else {
          const float m = s45.x * (1.f / D_);
          c0 = rsqrtf(fmaxf(s45.y * (1.f / D_) - m * m, 0.f) + LN_EPS);
          c1 = -c0 * m;
        }
        const int npass = ph == 0 ? 1 : 3, nch = ph == 0 ? 5 : 4;
#pragma unroll 1
        for (int ps = 0; ps < npass; ps++) {
          if (ps == 0) { STAGE10(MACC, 0) } else if (ps == 1) { STAGE10(MACC, 32) } else { STAGE10(MACC, 56) }
          bar_sync(3 + w, 128);
          const uint32_t cofs = ps == 2 ? 64 : 0;
          const uint32_t pp = p_r + (ph == 0 ? P_VA : P_CS3 + ps * 64) * 4, pq = p_r + P_VB * 4;
#pragma unroll 1
          for (int c = 0; c < nch; c++) {
            float v[8], t[8], t2[8], t3[8];
            lds8(stg + st_r + cofs + c * 64, v);
            lds8(pp + c * 64, t);
            if (ph == 0) {
              lds8(pq + c * 64, t2); lds8(pq + 320 + c * 64, t3);
#pragma unroll
              for (int e = 0; e < 8; e++) t[e] = fmaf(c1, t[e], fmaf(c2, t2[e], c3 * t3[e]));
            } else {
#pragma unroll
              for (int e = 0; e < 8; e++) t[e] *= c1;
            }
#pragma unroll
            for (int e = 0; e < 8; e++) v[e] = gelu_tanh(fmaf(c0, v[e], t[e]));
            sts_u4(ot + (ph == 0 ? er * 160 + eh * 16 + c * 32 : ps * 8192 + er * 128 + (((2 * c + eh) ^ (er & 7)) << 4)), pack8(v));
          }
          fence_async_smem();
          bar_sync(3 + w, 128);
          if (leader) {
            if (ph == 0) {
              const int grp = js >> 1;
              const int sh = (grp & 2 ? 2 : 1) * (grp & 1 ? -1 : 1);
              tma_store2d(&tm.sus, ot, js * 80, qt * 128 + w * 64 + sh + 2);
              if (qt * 2 + w == (sh > 0 ? 0 : 31)) {
                const int r0 = sh > 0 ? 0 : S_ + sh, n = sh > 0 ? sh : -sh;
                for (int i = 0; i < n; i++) bulk_store(g_us + (size_t)(r0 + i + 2) * D_ + js * 80, stat, 160);
              }
            } else {
              tma_store2d(&tm.g, ot + ps * 8192, js * 192 + ps * 64, qt * 128 + w * 64);
            }
          }
        }
      } else {
        const uint32_t e1 = aring + 30720;
        if (warp == 0) {
          fence_async_global();
          mbar_expect_e(mb_e + 8 * w, ph == 1 ? 10240 : 20480);
          tma2d(e1, &tm.sxa, mb_e + 8 * w, js * 80, qt * 128 + w * 64);
          if (ph == 3) tma2d(ot, &tm.sx1, mb_e + 8 * w, js * 80, qt * 128 + w * 64);
        }
        STAGE10(MACC, 0)
        bar_sync(3 + w, 128);
        mbar_wait_c(mb_e + 8 * w, ph >> 1);
        float s1 = 0.f, s2 = 0.f;
#pragma unroll 1
        for (int c = 0; c < 5; c++) {
          float v[8], xa[8], x1[8], ta[8], tb[8];
          lds8(stg + st_r + c * 64, v);
          lds8_bf(e1 + er * 160 + eh * 16 + c * 32, xa); lds8_bf(ot + er * 160 + eh * 16 + c * 32, x1);
          lds8(p_r + (ph == 1 ? P_A2 : P_GB) * 4 + c * 64, ta); lds8(p_r + P_B2 * 4 + c * 64, tb);
          if (ph == 1) {
#pragma unroll
            for (int e = 0; e < 8; e++) v[e] += fmaf(ta[e] * rs, xa[e] - mu, tb[e]);
          } else {
#pragma unroll
            for (int e = 0; e < 8; e++) v[e] = fmaf(ta[e], v[e] + x1[e], xa[e]);
          }
          const uint4 pk = pack8(v);
          sts_u4(ot + er * 160 + eh * 16 + c * 32, pk);
          v[0] = bf_lo(pk.x); v[1] = bf_hi(pk.x); v[2] = bf_lo(pk.y); v[3] = bf_hi(pk.y); v[4] = bf_lo(pk.z); v[5] = bf_hi(pk.z); v[6] = bf_lo(pk.w); v[7] = bf_hi(pk.w);
#pragma unroll
          for (int e = 0; e < 8; e++) { s1 += v[e]; s2 = fmaf(v[e], v[e], s2); }
        }
        s1 += __shfl_xor_sync(0xffffffffu, s1, 1); s2 += __shfl_xor_sync(0xffffffffu, s2, 1);
        if (eh == 0) sts_f2(stat + er * 8, s1, s2);
        fence_async_smem();
        bar_sync(3 + w, 128);
        if (leader) {
          tma_store2d(ph == 1 ? &tm.sx1 : &tm.sout, ot, js * 80, qt * 128 + w * 64);
          if (ph == 1) bulk_red_f32(g_st2 + (size_t)(qt * 128 + w * 64) * 2, stat, 512);
        }
      }
      if (leader) {
        bulk_done();
        if (ph < 3) flag_add(g_flag + F_US + 32 * ph + qt * 2 + w);
      }
      __syncwarp();
      TS(1 + (ph == 3 ? 0 : ph), ph == 3 ? 3 : 1);
    }
    if ((threadIdx.x & 127) == 0) TL_END(2);
    cluster_sync();
  }
}

typedef CUresult (*EncFn)(CUtensorMap*, CUtensorMapDataType, cuuint32_t, void*, const cuuint64_t*, const cuuint64_t*,
                          const cuuint32_t*, const cuuint32_t*, CUtensorMapInterleave, CUtensorMapSwizzle,
                          CUtensorMapL2promotion, CUtensorMapFloatOOBfill);
static EncFn g_enc = nullptr;

static CUtensorMap map2d(const void* p, uint64_t rows, uint64_t cols, uint32_t box_rows) {
  CUtensorMap m;
  cuuint64_t gd[2] = {cols, rows}; cuuint64_t gs[1] = {cols * 2};
  cuuint32_t bx[2] = {64, box_rows}; cuuint32_t es[2] = {1, 1};
  g_enc(&m, CU_TENSOR_MAP_DATA_TYPE_BFLOAT16, 2, const_cast<void*>(p), gd, gs, bx, es, CU_TENSOR_MAP_INTERLEAVE_NONE,
        CU_TENSOR_MAP_SWIZZLE_128B, CU_TENSOR_MAP_L2_PROMOTION_L2_256B, CU_TENSOR_MAP_FLOAT_OOB_FILL_NONE);
  return m;
}
static CUtensorMap map3d(const void* p, uint64_t rows, uint64_t cols, uint32_t box_rows, uint32_t nblk) {
  CUtensorMap m;
  cuuint64_t gd[3] = {64, rows, cols / 64}; cuuint64_t gs[2] = {cols * 2, 128};
  cuuint32_t bx[3] = {64, box_rows, nblk}; cuuint32_t es[3] = {1, 1, 1};
  g_enc(&m, CU_TENSOR_MAP_DATA_TYPE_BFLOAT16, 3, const_cast<void*>(p), gd, gs, bx, es, CU_TENSOR_MAP_INTERLEAVE_NONE,
        CU_TENSOR_MAP_SWIZZLE_128B, CU_TENSOR_MAP_L2_PROMOTION_L2_256B, CU_TENSOR_MAP_FLOAT_OOB_FILL_NONE);
  return m;
}

static CUtensorMap map_e(const void* p, uint32_t rows, uint64_t total_rows = S_) {
  CUtensorMap m;
  cuuint64_t gd[2] = {D_, total_rows}; cuuint64_t gs[1] = {D_ * 2};
  cuuint32_t bx[2] = {80, rows}; cuuint32_t es[2] = {1, 1};
  g_enc(&m, CU_TENSOR_MAP_DATA_TYPE_BFLOAT16, 2, const_cast<void*>(p), gd, gs, bx, es, CU_TENSOR_MAP_INTERLEAVE_NONE,
        CU_TENSOR_MAP_SWIZZLE_NONE, CU_TENSOR_MAP_L2_PROMOTION_L2_256B, CU_TENSOR_MAP_FLOAT_OOB_FILL_NONE);
  return m;
}

template <typename... KArgs, typename... Args>
static void launch(void (*kern)(KArgs...), dim3 grid, dim3 block, int smem, bool pdl, Args... args) {
  cudaLaunchConfig_t cfg = {};
  cfg.gridDim = grid; cfg.blockDim = block; cfg.dynamicSmemBytes = smem; cfg.stream = cudaStreamPerThread;
  cudaLaunchAttribute at[1];
  at[0].id = cudaLaunchAttributeProgrammaticStreamSerialization;
  at[0].val.programmaticStreamSerializationAllowed = 1;
  cfg.attrs = at; cfg.numAttrs = pdl ? 1 : 0;
  cudaLaunchKernelEx(&cfg, kern, KArgs(args)...);
}

extern "C" void kernel_launch(void* const* d_in, const int* in_sizes, int n_in, void* d_out, int out_size) {
  const bf16* x = (const bf16*)d_in[0];
  const bf16* kc = (const bf16*)d_in[1];
  const bf16* vc = (const bf16*)d_in[2];
  const bf16* wq = (const bf16*)d_in[3];
  const bf16* wo = (const bf16*)d_in[4];
  const bf16* w1 = (const bf16*)d_in[6];
  const bf16* w2 = (const bf16*)d_in[7];
  const bf16* w3 = (const bf16*)d_in[8];
  const bf16* w4 = (const bf16*)d_in[9];
  const bf16* c = (const bf16*)d_in[10];
  const bf16* wmod = (const bf16*)d_in[11];
  bf16* out = (bf16*)d_out;

  static void *p_h, *p_o, *p_xa, *p_us, *p_x1, *p_g, *p_w1t, *p_w2t, *p_w4t;
  if (!g_enc) {
    void* fn = nullptr; cudaDriverEntryPointQueryResult qr;
    cudaGetDriverEntryPoint("cuTensorMapEncodeTiled", &fn, cudaEnableDefault, &qr);
    g_enc = (EncFn)fn;
    cudaGetSymbolAddress(&p_h, g_h); cudaGetSymbolAddress(&p_o, g_o); cudaGetSymbolAddress(&p_xa, g_xa);
    cudaGetSymbolAddress(&p_us, g_us); cudaGetSymbolAddress(&p_x1, g_x1); cudaGetSymbolAddress(&p_g, g_g);
    cudaGetSymbolAddress(&p_w1t, g_w1t); cudaGetSymbolAddress(&p_w2t, g_w2t); cudaGetSymbolAddress(&p_w4t, g_w4t);
    cudaFuncSetAttribute(fused_kernel, cudaFuncAttributeMaxDynamicSharedMemorySize, T_SMEM);
  }
  Maps tm;
  tm.h = map2d(p_h, S_, D_, 128);
  tm.wq = map3d(wq, D_, HD_, 64, 3);
  tm.k = map3d(kc, (uint64_t)H_ * S_, DH_, 64, 3);
  tm.v = map3d(vc, (uint64_t)H_ * S_, DH_, 64, 3);
  tm.o = map2d(p_o, S_, HD_, 128);
  tm.wo3 = map3d(wo, HD_, D_, 64, 3);
  tm.wo2 = map3d(wo, HD_, D_, 64, 2);
  tm.xa = map2d(p_xa, S_, D_, 64);
  tm.w1t = map3d(p_w1t, D_, D_, 80, 2);
  tm.us = map2d((const bf16*)p_us + 2 * D_, S_, D_, 64);
  tm.w2t = map3d(p_w2t, D_, D_, 80, 2);
  tm.x1 = map2d(p_x1, S_, D_, 64);
  tm.w3 = map3d(w3, D_, F_, 64, 3);
  tm.g = map2d(p_g, S_, F_, 64);
  tm.w4t = map3d(p_w4t, D_, F_, 80, 2);
  tm.ex = map_e(x, 128);
  tm.sxa = map_e(p_xa, 64); tm.sus = map_e(p_us, 64, S_ + 4); tm.sx1 = map_e(p_x1, 64); tm.sout = map_e(out, 64);
  PfList pf;
  pf.p[0] = (const uint8_t*)wo; pf.p[1] = (const uint8_t*)w3; pf.p[2] = (const uint8_t*)p_w4t;
  pf.p[3] = (const uint8_t*)x; pf.p[4] = (const uint8_t*)p_w1t; pf.p[5] = (const uint8_t*)p_w2t;

  launch(mod_kernel, dim3(80), dim3(256), 0, false, c, wmod);
  launch(ln1_kernel, dim3(256), dim3(256), 0, true, x);
  launch(fused_kernel, dim3(128), dim3(384), T_SMEM, true, tm, pf, PrepW{w1, w2, w3, w4, c, wmod}, x, out);
}
```

```cpp
#include <cuda_runtime.h>
#include <cuda.h>
#include <cuda_bf16.h>
#include <stdint.h>

typedef __nv_bfloat16 bf16;

constexpr int S_  = 2048;
constexpr int D_  = 640;
constexpr int H_  = 32;
constexpr int DH_ = 192;
constexpr int HD_ = H_ * DH_;
constexpr int F_  = 1536;
constexpr float LN_EPS = 1e-5f;

__device__ __forceinline__ uint32_t smem_u32(const void* p) { return (uint32_t)__cvta_generic_to_shared(p); }
__device__ __forceinline__ void mbar_init(uint32_t a, uint32_t c) { asm volatile("mbarrier.init.shared::cta.b64 [%0], %1;" :: "r"(a), "r"(c) : "memory"); }
__device__ __forceinline__ void mbar_expect(uint32_t a, uint32_t b) { asm volatile("mbarrier.arrive.expect_tx.shared::cta.b64 _, [%0], %1;" :: "r"(a), "r"(b) : "memory"); }
__device__ __forceinline__ void mbar_arrive(uint32_t a) { asm volatile("mbarrier.arrive.shared::cta.b64 _, [%0];" :: "r"(a) : "memory"); }
__device__ __forceinline__ void mbar_arrive_remote(uint32_t ra) { asm volatile("mbarrier.arrive.shared::cluster.b64 _, [%0];" :: "r"(ra) : "memory"); }
__device__ __forceinline__ uint32_t mapa(uint32_t a, uint32_t cta) { uint32_t r; asm volatile("mapa.shared::cluster.u32 %0, %1, %2;" : "=r"(r) : "r"(a), "r"(cta)); return r; }
__device__ __forceinline__ uint32_t mbar_try(uint32_t a, uint32_t ph) {
  uint32_t ok;
  asm volatile("{\n.reg .pred p;\nmbarrier.test_wait.parity.shared::cta.b64 p, [%1], %2;\nselp.u32 %0, 1, 0, p;\n}\n" : "=r"(ok) : "r"(a), "r"(ph) : "memory");
  return ok;
}
__device__ __forceinline__ void mbar_wait(uint32_t a, uint32_t ph) {
  asm volatile(
      "{\n.reg .pred p;\n.reg .u32 n;\n"
      "mov.u32 n, 0;\n"
      "SPIN:\n"
      "mbarrier.try_wait.parity.shared::cta.b64 p, [%0], %1;\n"
      "@p bra DONE;\n"
      "add.u32 n, n, 1;\n"
      "setp.le.u32 p, n, 16777216;\n"
      "@p bra SPIN;\n"
      "trap;\n"
      "DONE:\n}\n" :: "r"(a), "r"(ph) : "memory");
}
#define ELECT_ "{\n.reg .pred p;\nelect.sync _|p, 0xffffffff;\n@p "
__device__ __forceinline__ void mbar_expect_e(uint32_t a, uint32_t b) { asm volatile(ELECT_ "mbarrier.arrive.expect_tx.shared::cta.b64 _, [%0], %1;\n}\n" :: "r"(a), "r"(b) : "memory"); }
__device__ __forceinline__ void tma2d(uint32_t dst, const CUtensorMap* m, uint32_t bar, int c0, int c1) {
  asm volatile(ELECT_ "cp.async.bulk.tensor.2d.shared::cluster.global.mbarrier::complete_tx::bytes [%0], [%1, {%3, %4}], [%2];\n}\n"
               :: "r"(dst), "l"(m), "r"(bar), "r"(c0), "r"(c1) : "memory");
}
__device__ __forceinline__ void tma2d_mc(uint32_t dst, const CUtensorMap* m, uint32_t bar, int c0, int c1, uint16_t mask) {
  asm volatile(ELECT_ "cp.async.bulk.tensor.2d.shared::cluster.global.mbarrier::complete_tx::bytes.multicast::cluster [%0], [%1, {%3, %4}], [%2], %5;\n}\n"
               :: "r"(dst), "l"(m), "r"(bar), "r"(c0), "r"(c1), "h"(mask) : "memory");
}
__device__ __forceinline__ void tma3d(uint32_t dst, const CUtensorMap* m, uint32_t bar, int c0, int c1, int c2) {
  asm volatile(ELECT_ "cp.async.bulk.tensor.3d.shared::cluster.global.mbarrier::complete_tx::bytes [%0], [%1, {%3, %4, %5}], [%2];\n}\n"
               :: "r"(dst), "l"(m), "r"(bar), "r"(c0), "r"(c1), "r"(c2) : "memory");
}
__device__ __forceinline__ void tma3d_mc(uint32_t dst, const CUtensorMap* m, uint32_t bar, int c0, int c1, int c2, uint16_t mask) {
  asm volatile(ELECT_ "cp.async.bulk.tensor.3d.shared::cluster.global.mbarrier::complete_tx::bytes.multicast::cluster [%0], [%1, {%3, %4, %5}], [%2], %6;\n}\n"
               :: "r"(dst), "l"(m), "r"(bar), "r"(c0), "r"(c1), "r"(c2), "h"(mask) : "memory");
}
__device__ __forceinline__ void tma3d_mc_hint(uint32_t dst, const CUtensorMap* m, uint32_t bar, int c0, int c1, int c2, uint16_t mask, uint64_t pol) {
  asm volatile(ELECT_ "cp.async.bulk.tensor.3d.shared::cluster.global.mbarrier::complete_tx::bytes.multicast::cluster.L2::cache_hint [%0], [%1, {%3, %4, %5}], [%2], %6, %7;\n}\n"
               :: "r"(dst), "l"(m), "r"(bar), "r"(c0), "r"(c1), "r"(c2), "h"(mask), "l"(pol) : "memory");
}
__device__ __forceinline__ void bulk_load(uint32_t dst, const void* src, uint32_t bytes, uint32_t bar) {
  asm volatile(ELECT_ "cp.async.bulk.shared::cluster.global.mbarrier::complete_tx::bytes [%0], [%1], %2, [%3];\n}\n"
               :: "r"(dst), "l"(src), "r"(bytes), "r"(bar) : "memory");
}
__device__ __forceinline__ void l2_prefetch16k(const void* p) { asm volatile(ELECT_ "cp.async.bulk.prefetch.L2.global [%0], 16384;\n}\n" :: "l"(p) : "memory"); }
__device__ __forceinline__ void l2_prefetch_t2d(const CUtensorMap* m, int c0, int c1) {
  asm volatile(ELECT_ "cp.async.bulk.prefetch.tensor.2d.L2.global [%0, {%1, %2}];\n}\n" :: "l"(m), "r"(c0), "r"(c1) : "memory");
}
__device__ __forceinline__ void l2_prefetch_t3d(const CUtensorMap* m, int c0, int c1, int c2) {
  asm volatile(ELECT_ "cp.async.bulk.prefetch.tensor.3d.L2.global [%0, {%1, %2, %3}];\n}\n" :: "l"(m), "r"(c0), "r"(c1), "r"(c2) : "memory");
}
__device__ __forceinline__ void stg128(void* p, uint4 v) {
  asm volatile("st.global.v4.u32 [%0], {%1, %2, %3, %4};" :: "l"(p), "r"(v.x), "r"(v.y), "r"(v.z), "r"(v.w) : "memory");
}
__device__ __forceinline__ void prefetch_tmap(const CUtensorMap* m) { asm volatile("prefetch.tensormap [%0];" :: "l"(m) : "memory"); }
__device__ __forceinline__ void wg_fence() { asm volatile("wgmma.fence.sync.aligned;" ::: "memory"); }
__device__ __forceinline__ void wg_commit() { asm volatile("wgmma.commit_group.sync.aligned;" ::: "memory"); }
template <int N> __device__ __forceinline__ void wg_wait() { asm volatile("wgmma.wait_group.sync.aligned %0;" :: "n"(N) : "memory"); }
template <int N> __device__ __forceinline__ void fence_regs(float (&r)[N]) {
#pragma unroll
  for (int i = 0; i < N; i++) asm volatile("" : "+f"(r[i]) :: "memory");
}
template <int N> __device__ __forceinline__ void fence_regs(uint32_t (&r)[N]) {
#pragma unroll
  for (int i = 0; i < N; i++) asm volatile("" : "+r"(r[i]) :: "memory");
}
__device__ __forceinline__ uint64_t mkdesc(uint32_t addr, uint32_t lbo, uint32_t sbo) {
  return (uint64_t)((addr & 0x3FFFF) >> 4) | ((uint64_t)(lbo >> 4) << 16) | ((uint64_t)(sbo >> 4) << 32) | (1ull << 62);
}
__device__ __forceinline__ void bar_sync(int id, int n) { asm volatile("bar.sync %0, %1;" :: "r"(id), "r"(n) : "memory"); }
__device__ __forceinline__ void bar_arrive(int id, int n) { asm volatile("bar.arrive %0, %1;" :: "r"(id), "r"(n) : "memory"); }
__device__ __forceinline__ void cluster_sync() { asm volatile("barrier.cluster.arrive.aligned;\nbarrier.cluster.wait.aligned;" ::: "memory"); }
__device__ __forceinline__ void pdl_wait() { asm volatile("griddepcontrol.wait;" ::: "memory"); }
__device__ __forceinline__ void pdl_launch() { asm volatile("griddepcontrol.launch_dependents;" ::: "memory"); }
__device__ __forceinline__ float ex2(float x) { float y; asm("ex2.approx.ftz.f32 %0, %1;" : "=f"(y) : "f"(x)); return y; }
__device__ __forceinline__ uint32_t pack_bf16(float lo, float hi) { uint32_t r; asm("cvt.rn.bf16x2.f32 %0, %1, %2;" : "=r"(r) : "f"(hi), "f"(lo)); return r; }
__device__ __forceinline__ float bf_lo(uint32_t u) { return __uint_as_float(u << 16); }
__device__ __forceinline__ float bf_hi(uint32_t u) { return __uint_as_float(u & 0xffff0000u); }
__device__ __forceinline__ float bf_round(float x) { return __bfloat162float(__float2bfloat16_rn(x)); }
__device__ __forceinline__ float tanh_fast(float x) { float y; asm("tanh.approx.f32 %0, %1;" : "=f"(y) : "f"(x)); return y; }
__device__ __forceinline__ float gelu_tanh(float x) {
  float u = x * (0.7978845608028654f + 0.035677408136300125f * x * x);
  float hx = 0.5f * x;
  return fmaf(hx, tanh_fast(u), hx);
}
__device__ __forceinline__ float warp_sum(float v) {
#pragma unroll
  for (int o = 16; o > 0; o >>= 1) v += __shfl_xor_sync(0xffffffffu, v, o);
  return v;
}
__device__ __forceinline__ void quad_transpose(uint32_t& v0, uint32_t& v1, uint32_t& v2, uint32_t& v3, int lane) {
  const bool b0 = lane & 1, b1 = lane & 2;
  uint32_t s0 = b0 ? v0 : v1, s1 = b0 ? v2 : v3;
  s0 = __shfl_xor_sync(0xffffffffu, s0, 1); s1 = __shfl_xor_sync(0xffffffffu, s1, 1);
  if (b0) { v0 = s0; v2 = s1; } else { v1 = s0; v3 = s1; }
  uint32_t t0 = b1 ? v0 : v2, t1 = b1 ? v1 : v3;
  t0 = __shfl_xor_sync(0xffffffffu, t0, 2); t1 = __shfl_xor_sync(0xffffffffu, t1, 2);
  if (b1) { v0 = t0; v1 = t1; } else { v2 = t0; v3 = t1; }
}

#define TG(i)
#define TX(i)
#define TXC(i)
#define TSA(item, i)
#define TL_ENTRY(k)
#define TL_WAITED(k)
#define TL_END(k)
#define TS(item, i)
template<int TB> __device__ __forceinline__ void wgmma_rs_n64(float (&d)[32], uint32_t a0, uint32_t a1, uint32_t a2, uint32_t a3, uint64_t db, int scale_d) {
  asm volatile("{\n.reg .pred p;\nsetp.ne.b32 p, %37, 0;\n"
    "wgmma.mma_async.sync.aligned.m64n64k16.f32.bf16.bf16 {%0, %1, %2, %3, %4, %5, %6, %7, %8, %9, %10, %11, %12, %13, %14, %15, %16, %17, %18, %19, %20, %21, %22, %23, %24, %25, %26, %27, %28, %29, %30, %31}, {%32, %33, %34, %35}, %36, p, 1, 1, %38;\n}\n"
    : "+f"(d[0]), "+f"(d[1]), "+f"(d[2]), "+f"(d[3]), "+f"(d[4]), "+f"(d[5]), "+f"(d[6]), "+f"(d[7]), "+f"(d[8]), "+f"(d[9]), "+f"(d[10]), "+f"(d[11]), "+f"(d[12]), "+f"(d[13]), "+f"(d[14]), "+f"(d[15]), "+f"(d[16]), "+f"(d[17]), "+f"(d[18]), "+f"(d[19]), "+f"(d[20]), "+f"(d[21]), "+f"(d[22]), "+f"(d[23]), "+f"(d[24]), "+f"(d[25]), "+f"(d[26]), "+f"(d[27]), "+f"(d[28]), "+f"(d[29]), "+f"(d[30]), "+f"(d[31])
    : "r"(a0), "r"(a1), "r"(a2), "r"(a3), "l"(db), "r"(scale_d), "n"(TB));
}
template<int TB> __device__ __forceinline__ void wgmma_rs_n192(float (&d)[96], uint32_t a0, uint32_t a1, uint32_t a2, uint32_t a3, uint64_t db, int scale_d) {
  asm volatile("{\n.reg .pred p;\nsetp.ne.b32 p, %101, 0;\n"
    "wgmma.mma_async.sync.aligned.m64n192k16.f32.bf16.bf16 {%0, %1, %2, %3, %4, %5, %6, %7, %8, %9, %10, %11, %12, %13, %14, %15, %16, %17, %18, %19, %20, %21, %22, %23, %24, %25, %26, %27, %28, %29, %30, %31, %32, %33, %34, %35, %36, %37, %38, %39, %40, %41, %42, %43, %44, %45, %46, %47, %48, %49, %50, %51, %52, %53, %54, %55, %56, %57, %58, %59, %60, %61, %62, %63, %64, %65, %66, %67, %68, %69, %70, %71, %72, %73, %74, %75, %76, %77, %78, %79, %80, %81, %82, %83, %84, %85, %86, %87, %88, %89, %90, %91, %92, %93, %94, %95}, {%96, %97, %98, %99}, %100, p, 1, 1, %102;\n}\n"
    : "+f"(d[0]), "+f"(d[1]), "+f"(d[2]), "+f"(d[3]), "+f"(d[4]), "+f"(d[5]), "+f"(d[6]), "+f"(d[7]), "+f"(d[8]), "+f"(d[9]), "+f"(d[10]), "+f"(d[11]), "+f"(d[12]), "+f"(d[13]), "+f"(d[14]), "+f"(d[15]), "+f"(d[16]), "+f"(d[17]), "+f"(d[18]), "+f"(d[19]), "+f"(d[20]), "+f"(d[21]), "+f"(d[22]), "+f"(d[23]), "+f"(d[24]), "+f"(d[25]), "+f"(d[26]), "+f"(d[27]), "+f"(d[28]), "+f"(d[29]), "+f"(d[30]), "+f"(d[31]), "+f"(d[32]), "+f"(d[33]), "+f"(d[34]), "+f"(d[35]), "+f"(d[36]), "+f"(d[37]), "+f"(d[38]), "+f"(d[39]), "+f"(d[40]), "+f"(d[41]), "+f"(d[42]), "+f"(d[43]), "+f"(d[44]), "+f"(d[45]), "+f"(d[46]), "+f"(d[47]), "+f"(d[48]), "+f"(d[49]), "+f"(d[50]), "+f"(d[51]), "+f"(d[52]), "+f"(d[53]), "+f"(d[54]), "+f"(d[55]), "+f"(d[56]), "+f"(d[57]), "+f"(d[58]), "+f"(d[59]), "+f"(d[60]), "+f"(d[61]), "+f"(d[62]), "+f"(d[63]), "+f"(d[64]), "+f"(d[65]), "+f"(d[66]), "+f"(d[67]), "+f"(d[68]), "+f"(d[69]), "+f"(d[70]), "+f"(d[71]), "+f"(d[72]), "+f"(d[73]), "+f"(d[74]), "+f"(d[75]), "+f"(d[76]), "+f"(d[77]), "+f"(d[78]), "+f"(d[79]), "+f"(d[80]), "+f"(d[81]), "+f"(d[82]), "+f"(d[83]), "+f"(d[84]), "+f"(d[85]), "+f"(d[86]), "+f"(d[87]), "+f"(d[88]), "+f"(d[89]), "+f"(d[90]), "+f"(d[91]), "+f"(d[92]), "+f"(d[93]), "+f"(d[94]), "+f"(d[95])
    : "r"(a0), "r"(a1), "r"(a2), "r"(a3), "l"(db), "r"(scale_d), "n"(TB));
}
template<int TB> __device__ __forceinline__ void wgmma_ss_n128(float (&d)[64], uint64_t da, uint64_t db, int scale_d) {
  asm volatile("{\n.reg .pred p;\nsetp.ne.b32 p, %66, 0;\n"
    "wgmma.mma_async.sync.aligned.m64n128k16.f32.bf16.bf16 {%0, %1, %2, %3, %4, %5, %6, %7, %8, %9, %10, %11, %12, %13, %14, %15, %16, %17, %18, %19, %20, %21, %22, %23, %24, %25, %26, %27, %28, %29, %30, %31, %32, %33, %34, %35, %36, %37, %38, %39, %40, %41, %42, %43, %44, %45, %46, %47, %48, %49, %50, %51, %52, %53, %54, %55, %56, %57, %58, %59, %60, %61, %62, %63}, %64, %65, p, 1, 1, 0, %67;\n}\n"
    : "+f"(d[0]), "+f"(d[1]), "+f"(d[2]), "+f"(d[3]), "+f"(d[4]), "+f"(d[5]), "+f"(d[6]), "+f"(d[7]), "+f"(d[8]), "+f"(d[9]), "+f"(d[10]), "+f"(d[11]), "+f"(d[12]), "+f"(d[13]), "+f"(d[14]), "+f"(d[15]), "+f"(d[16]), "+f"(d[17]), "+f"(d[18]), "+f"(d[19]), "+f"(d[20]), "+f"(d[21]), "+f"(d[22]), "+f"(d[23]), "+f"(d[24]), "+f"(d[25]), "+f"(d[26]), "+f"(d[27]), "+f"(d[28]), "+f"(d[29]), "+f"(d[30]), "+f"(d[31]), "+f"(d[32]), "+f"(d[33]), "+f"(d[34]), "+f"(d[35]), "+f"(d[36]), "+f"(d[37]), "+f"(d[38]), "+f"(d[39]), "+f"(d[40]), "+f"(d[41]), "+f"(d[42]), "+f"(d[43]), "+f"(d[44]), "+f"(d[45]), "+f"(d[46]), "+f"(d[47]), "+f"(d[48]), "+f"(d[49]), "+f"(d[50]), "+f"(d[51]), "+f"(d[52]), "+f"(d[53]), "+f"(d[54]), "+f"(d[55]), "+f"(d[56]), "+f"(d[57]), "+f"(d[58]), "+f"(d[59]), "+f"(d[60]), "+f"(d[61]), "+f"(d[62]), "+f"(d[63])
    : "l"(da), "l"(db), "r"(scale_d), "n"(TB));
}
template<int TB> __device__ __forceinline__ void wgmma_ss_n192(float (&d)[96], uint64_t da, uint64_t db, int scale_d) {
  asm volatile("{\n.reg .pred p;\nsetp.ne.b32 p, %98, 0;\n"
    "wgmma.mma_async.sync.aligned.m64n192k16.f32.bf16.bf16 {%0, %1, %2, %3, %4, %5, %6, %7, %8, %9, %10, %11, %12, %13, %14, %15, %16, %17, %18, %19, %20, %21, %22, %23, %24, %25, %26, %27, %28, %29, %30, %31, %32, %33, %34, %35, %36, %37, %38, %39, %40, %41, %42, %43, %44, %45, %46, %47, %48, %49, %50, %51, %52, %53, %54, %55, %56, %57, %58, %59, %60, %61, %62, %63, %64, %65, %66, %67, %68, %69, %70, %71, %72, %73, %74, %75, %76, %77, %78, %79, %80, %81, %82, %83, %84, %85, %86, %87, %88, %89, %90, %91, %92, %93, %94, %95}, %96, %97, p, 1, 1, 0, %99;\n}\n"
    : "+f"(d[0]), "+f"(d[1]), "+f"(d[2]), "+f"(d[3]), "+f"(d[4]), "+f"(d[5]), "+f"(d[6]), "+f"(d[7]), "+f"(d[8]), "+f"(d[9]), "+f"(d[10]), "+f"(d[11]), "+f"(d[12]), "+f"(d[13]), "+f"(d[14]), "+f"(d[15]), "+f"(d[16]), "+f"(d[17]), "+f"(d[18]), "+f"(d[19]), "+f"(d[20]), "+f"(d[21]), "+f"(d[22]), "+f"(d[23]), "+f"(d[24]), "+f"(d[25]), "+f"(d[26]), "+f"(d[27]), "+f"(d[28]), "+f"(d[29]), "+f"(d[30]), "+f"(d[31]), "+f"(d[32]), "+f"(d[33]), "+f"(d[34]), "+f"(d[35]), "+f"(d[36]), "+f"(d[37]), "+f"(d[38]), "+f"(d[39]), "+f"(d[40]), "+f"(d[41]), "+f"(d[42]), "+f"(d[43]), "+f"(d[44]), "+f"(d[45]), "+f"(d[46]), "+f"(d[47]), "+f"(d[48]), "+f"(d[49]), "+f"(d[50]), "+f"(d[51]), "+f"(d[52]), "+f"(d[53]), "+f"(d[54]), "+f"(d[55]), "+f"(d[56]), "+f"(d[57]), "+f"(d[58]), "+f"(d[59]), "+f"(d[60]), "+f"(d[61]), "+f"(d[62]), "+f"(d[63]), "+f"(d[64]), "+f"(d[65]), "+f"(d[66]), "+f"(d[67]), "+f"(d[68]), "+f"(d[69]), "+f"(d[70]), "+f"(d[71]), "+f"(d[72]), "+f"(d[73]), "+f"(d[74]), "+f"(d[75]), "+f"(d[76]), "+f"(d[77]), "+f"(d[78]), "+f"(d[79]), "+f"(d[80]), "+f"(d[81]), "+f"(d[82]), "+f"(d[83]), "+f"(d[84]), "+f"(d[85]), "+f"(d[86]), "+f"(d[87]), "+f"(d[88]), "+f"(d[89]), "+f"(d[90]), "+f"(d[91]), "+f"(d[92]), "+f"(d[93]), "+f"(d[94]), "+f"(d[95])
    : "l"(da), "l"(db), "r"(scale_d), "n"(TB));
}
template<int TB> __device__ __forceinline__ void wgmma_ss_n80(float (&d)[40], uint64_t da, uint64_t db, int scale_d) {
  asm volatile("{\n.reg .pred p;\nsetp.ne.b32 p, %42, 0;\n"
    "wgmma.mma_async.sync.aligned.m64n80k16.f32.bf16.bf16 {%0, %1, %2, %3, %4, %5, %6, %7, %8, %9, %10, %11, %12, %13, %14, %15, %16, %17, %18, %19, %20, %21, %22, %23, %24, %25, %26, %27, %28, %29, %30, %31, %32, %33, %34, %35, %36, %37, %38, %39}, %40, %41, p, 1, 1, 0, %43;\n}\n"
    : "+f"(d[0]), "+f"(d[1]), "+f"(d[2]), "+f"(d[3]), "+f"(d[4]), "+f"(d[5]), "+f"(d[6]), "+f"(d[7]), "+f"(d[8]), "+f"(d[9]), "+f"(d[10]), "+f"(d[11]), "+f"(d[12]), "+f"(d[13]), "+f"(d[14]), "+f"(d[15]), "+f"(d[16]), "+f"(d[17]), "+f"(d[18]), "+f"(d[19]), "+f"(d[20]), "+f"(d[21]), "+f"(d[22]), "+f"(d[23]), "+f"(d[24]), "+f"(d[25]), "+f"(d[26]), "+f"(d[27]), "+f"(d[28]), "+f"(d[29]), "+f"(d[30]), "+f"(d[31]), "+f"(d[32]), "+f"(d[33]), "+f"(d[34]), "+f"(d[35]), "+f"(d[36]), "+f"(d[37]), "+f"(d[38]), "+f"(d[39])
    : "l"(da), "l"(db), "r"(scale_d), "n"(TB));
}

__device__ __align__(128) float g_mod[6 * D_];
__device__ __align__(128) float g_modp[2][2 * D_];
__device__ __align__(1024) bf16 g_h[S_ * D_];
__device__ __align__(1024) bf16 g_o[S_ * HD_];
__device__ __align__(1024) bf16 g_xch[16 * 2 * 4 * 4 * 128 * 80];
__device__ __align__(1024) bf16 g_w1t[D_ * D_];
__device__ __align__(1024) bf16 g_w2t[D_ * D_];
__device__ __align__(1024) bf16 g_w4t[D_ * F_];
__device__ __align__(32) float g_st1[S_ * 8];
__device__ __align__(32) float g_st2[S_ * 2];
__device__ __align__(32) float g_vec[3 * D_ + F_ + 8];
__device__ unsigned g_flag[1024];
enum { F_XCH = 0, F_XA = 256, F_US = 288, F_X1 = 320, F_G = 352, F_PREP = 384, F_MOD2 = 416, F_O = 512 };
__device__ __align__(1024) bf16 g_xa[S_ * D_];
__device__ __align__(1024) bf16 g_us[(S_ + 4) * D_];
__device__ __align__(1024) bf16 g_x1[S_ * D_];
__device__ __align__(1024) bf16 g_g[S_ * F_];

__device__ __forceinline__ void row_stats(const float (&v)[20], float& mean, float& rstd) {
  float s = 0.f;
#pragma unroll
  for (int i = 0; i < 20; i++) s += v[i];
  mean = warp_sum(s) * (1.f / D_);
  float q = 0.f;
#pragma unroll
  for (int i = 0; i < 20; i++) { float d = v[i] - mean; q = fmaf(d, d, q); }
  rstd = rsqrtf(warp_sum(q) * (1.f / D_) + LN_EPS);
}
__device__ __forceinline__ void load_row_bf16(const bf16* p, int lane, float (&v)[20]) {
#pragma unroll
  for (int i = 0; i < 5; i++) {
    uint2 u = *reinterpret_cast<const uint2*>(p + (lane + 32 * i) * 4);
    v[4 * i] = bf_lo(u.x); v[4 * i + 1] = bf_hi(u.x); v[4 * i + 2] = bf_lo(u.y); v[4 * i + 3] = bf_hi(u.y);
  }
}
__device__ __forceinline__ void store_row_bf16(bf16* p, int lane, const float (&v)[20]) {
#pragma unroll
  for (int i = 0; i < 5; i++) {
    uint2 u; u.x = pack_bf16(v[4 * i], v[4 * i + 1]); u.y = pack_bf16(v[4 * i + 2], v[4 * i + 3]);
    *reinterpret_cast<uint2*>(p + (lane + 32 * i) * 4) = u;
  }
}
__device__ __forceinline__ void load_row_f32(const float* p, int lane, float (&v)[20]) {
#pragma unroll
  for (int i = 0; i < 5; i++) {
    float4 u = *reinterpret_cast<const float4*>(p + (lane + 32 * i) * 4);
    v[4 * i] = u.x; v[4 * i + 1] = u.y; v[4 * i + 2] = u.z; v[4 * i + 3] = u.w;
  }
}

__device__ __forceinline__ float silu_bf(float c) { return bf_round(__fdividef(c, 1.f + __expf(-c))); }
__device__ __forceinline__ void fma8(float (&acc)[8], float s, const uint4& w) {
  acc[0] = fmaf(s, bf_lo(w.x), acc[0]); acc[1] = fmaf(s, bf_hi(w.x), acc[1]); acc[2] = fmaf(s, bf_lo(w.y), acc[2]); acc[3] = fmaf(s, bf_hi(w.y), acc[3]);
  acc[4] = fmaf(s, bf_lo(w.z), acc[4]); acc[5] = fmaf(s, bf_hi(w.z), acc[5]); acc[6] = fmaf(s, bf_lo(w.w), acc[6]); acc[7] = fmaf(s, bf_hi(w.w), acc[7]);
}
__global__ void __launch_bounds__(256) mod_kernel(const bf16* __restrict__ c, const bf16* __restrict__ w_mod) {
  TL_ENTRY(0);
  pdl_launch();
  __shared__ float red[8][32];
  const int t = threadIdx.x, cg = t & 3, r0 = (blockIdx.x / 40) * 320 + (t >> 2), strip = blockIdx.x % 40;
  uint4 w[5];
  float cv[5];
#pragma unroll
  for (int i = 0; i < 5; i++) {
    w[i] = __ldg(reinterpret_cast<const uint4*>(w_mod + (size_t)(r0 + 64 * i) * (6 * D_) + strip * 32 + cg * 8));
    cv[i] = __bfloat162float(c[r0 + 64 * i]);
  }
  if (blockIdx.x < 14) { const int i = blockIdx.x * 256 + t; if (i < 3 * D_ + F_) g_vec[i] = 0.f; }
  else if (blockIdx.x < 18) g_flag[(blockIdx.x - 14) * 256 + t] = 0u;
  float acc[8];
#pragma unroll
  for (int j = 0; j < 8; j++) acc[j] = 0.f;
#pragma unroll
  for (int i = 0; i < 5; i++) fma8(acc, silu_bf(cv[i]), w[i]);
#pragma unroll 1
  for (int o = 4; o < 32; o <<= 1) {
#pragma unroll
    for (int j = 0; j < 8; j++) acc[j] += __shfl_xor_sync(0xffffffffu, acc[j], o);
  }
  if ((t & 31) < 4) {
    *reinterpret_cast<float4*>(&red[t >> 5][cg * 8]) = make_float4(acc[0], acc[1], acc[2], acc[3]);
    *reinterpret_cast<float4*>(&red[t >> 5][cg * 8 + 4]) = make_float4(acc[4], acc[5], acc[6], acc[7]);
  }
  __syncthreads();
  if (t < 32) {
    float s = 0.f;
#pragma unroll
    for (int w8 = 0; w8 < 8; w8++) s += red[w8][t];
    g_modp[blockIdx.x / 40][strip * 32 + t] = s;
    if (t == 0) TL_END(0);
  }
}

__global__ void __launch_bounds__(256) ln1_kernel(const bf16* __restrict__ x) {
  TL_ENTRY(1);
  pdl_launch();
  const int lane = threadIdx.x & 31, row = blockIdx.x * 8 + (threadIdx.x >> 5);
  float v[20];
  load_row_bf16(x + (size_t)row * D_, lane, v);
  float mean, rstd;
  row_stats(v, mean, rstd);
  if (lane < 8) g_st1[row * 8 + lane] = 0.f;
  if (lane < 2) g_st2[row * 2 + lane] = 0.f;
  pdl_wait();
  if (threadIdx.x == 0) TL_WAITED(1);
  float s0[20], s1[20], c0[20], c1[20];
  load_row_f32(g_modp[0], lane, s0); load_row_f32(g_modp[1], lane, s1);
  load_row_f32(g_modp[0] + D_, lane, c0); load_row_f32(g_modp[1] + D_, lane, c1);
#pragma unroll
  for (int i = 0; i < 20; i++) v[i] = fmaf((v[i] - mean) * rstd, bf_round(1.f + bf_round(c0[i] + c1[i])), bf_round(s0[i] + s1[i]));
  store_row_bf16(g_h + (size_t)row * D_, lane, v);
  if (threadIdx.x == 0) TL_END(1);
}

constexpr int PREP_JOBS = 200 + 200 + 480 + 480;
struct PrepW { const bf16 *w1, *w2, *w3, *w4, *c, *wmod; };
__device__ __forceinline__ void flag_wait(const unsigned* p, unsigned target);
__device__ __forceinline__ void prep_warp(const PrepW& pw, bf16 (*tile)[72], int lane) {
  if (blockIdx.x < 80) {
    const bf16* wp = pw.wmod + (size_t)(lane >> 2) * (6 * D_) + 2 * D_ + blockIdx.x * 32 + (lane & 3) * 8;
    float acc[8];
#pragma unroll
    for (int j = 0; j < 8; j++) acc[j] = 0.f;
#pragma unroll 1
    for (int i = 0; i < 80; i += 4) {
      uint4 w[4];
      float cv[4];
#pragma unroll
      for (int e = 0; e < 4; e++) { w[e] = __ldg(reinterpret_cast<const uint4*>(wp + (size_t)(i + e) * 8 * (6 * D_))); cv[e] = __bfloat162float(pw.c[(i + e) * 8 + (lane >> 2)]); }
#pragma unroll
      for (int e = 0; e < 4; e++) fma8(acc, silu_bf(cv[e]), w[e]);
    }
    const bool one = blockIdx.x >= 40 && blockIdx.x < 60;
#pragma unroll
    for (int j = 0; j < 8; j++) {
      acc[j] += __shfl_xor_sync(0xffffffffu, acc[j], 4); acc[j] += __shfl_xor_sync(0xffffffffu, acc[j], 8); acc[j] += __shfl_xor_sync(0xffffffffu, acc[j], 16);
      const float v = bf_round(acc[j]);
      if (lane < 4) g_mod[2 * D_ + blockIdx.x * 32 + lane * 8 + j] = one ? bf_round(1.f + v) : v;
    }
    __syncwarp();
    if (lane == 0) {
      asm volatile("fence.acq_rel.gpu;" ::: "memory");
      asm volatile("red.relaxed.gpu.global.add.u32 [%0], 1;" :: "l"(g_flag + F_MOD2) : "memory");
    }
  }
  flag_wait(g_flag + F_MOD2, 80);
#pragma unroll 1
  for (int job = blockIdx.x; job < PREP_JOBS; job += gridDim.x) {
    const bf16* src; bf16* dst; int ld = D_, ldd = D_, kt, nt, kind = 1;
    if (job < 200) { src = pw.w1; dst = g_w1t; kt = job / 10; nt = job % 10; kind = 0; }
    else if (job < 400) { src = pw.w2; dst = g_w2t; kt = (job - 200) / 10; nt = (job - 200) % 10; }
    else if (job < 880) { src = pw.w4; dst = g_w4t; ldd = F_; kt = (job - 400) / 10; nt = (job - 400) % 10; }
    else { src = pw.w3; dst = nullptr; ld = F_; kt = (job - 880) / 24; nt = (job - 880) % 24; kind = 2; }
    src += (size_t)(kt * 32 + (lane >> 3)) * ld + nt * 64 + (lane & 7) * 8;
    __syncwarp();
#pragma unroll
    for (int h = 0; h < 2; h++) {
      uint4 v[4];
#pragma unroll
      for (int i = 0; i < 4; i++) v[i] = __ldg(reinterpret_cast<const uint4*>(src + (size_t)(h * 16 + i * 4) * ld));
#pragma unroll
      for (int i = 0; i < 4; i++) *reinterpret_cast<uint4*>(&tile[h * 16 + i * 4 + (lane >> 3)][(lane & 7) * 8]) = v[i];
    }
    __syncwarp();
    const float* pa = g_mod + 4 * D_ + kt * 32;
    const float* pb = g_mod + 3 * D_ + kt * 32;
#pragma unroll 1
    for (int h = 0; h < 2; h++) {
      const int n = lane + 32 * h;
      float sa = 0.f, sb = 0.f, sc = 0.f;
#pragma unroll 1
      for (int c = 0; c < 4; c++) {
        uint32_t u[4];
#pragma unroll
        for (int e = 0; e < 4; e++) {
          const int k = c * 8 + 2 * e;
          float lo = __bfloat162float(tile[k][n]), hi = __bfloat162float(tile[k + 1][n]);
          sc += lo + hi;
          if (kind == 0) {
            const float2 a = __ldcg(reinterpret_cast<const float2*>(pa + k)), b = __ldcg(reinterpret_cast<const float2*>(pb + k));
            sb = fmaf(b.x, lo, fmaf(b.y, hi, sb));
            lo *= a.x; hi *= a.y;
          }
          u[e] = pack_bf16(lo, hi);
          sa += bf_lo(u[e]) + bf_hi(u[e]);
        }
        if (kind != 2) *reinterpret_cast<uint4*>(dst + (size_t)(nt * 64 + n) * ldd + kt * 32 + c * 8) = make_uint4(u[0], u[1], u[2], u[3]);
      }
      if (kind == 0) { atomicAdd(&g_vec[nt * 64 + n], sa); atomicAdd(&g_vec[D_ + nt * 64 + n], sb); atomicAdd(&g_vec[2 * D_ + nt * 64 + n], sc); }
      else if (kind == 2) atomicAdd(&g_vec[3 * D_ + nt * 64 + n], sc);
    }
  }
  __syncwarp();
  if (lane == 0) {
    asm volatile("fence.acq_rel.gpu;" ::: "memory");
    asm volatile("red.relaxed.gpu.global.add.u32 [%0], 1;" :: "l"(g_flag + F_PREP) : "memory");
  }
}

constexpr int A_NSLOT = 9;
constexpr int A_SLOT = 24576;
constexpr int A_NKV = S_ / 64;
constexpr int PREP_CTAS = 128;

struct Ring {
  uint32_t slot, phase;
  __device__ __forceinline__ void adv(int n) { if (++slot == (uint32_t)n) { slot = 0; phase ^= 1; } }
};
constexpr int T_PAR = A_NSLOT * A_SLOT + 448;
constexpr int T_PREP = T_PAR + 3712;
constexpr int T_SMEM = T_PREP + 32 * 72 * 2 + 1024;
enum { P_OGA = 0, P_OA = 80, P_OB = 160, P_VA = 240, P_VB = 320, P_VC = 400, P_A2 = 480, P_B2 = 560, P_GB = 640, P_CS3 = 720, P_SC = 912 };

__device__ __forceinline__ void flag_wait(const unsigned* p, unsigned target) {
  asm volatile(
      "{\n.reg .pred p;\n.reg .u32 n, v;\n"
      "mov.u32 n, 0;\n"
      "SPIN:\n"
      "ld.relaxed.gpu.global.u32 v, [%0];\n"
      "setp.ge.u32 p, v, %1;\n"
      "@p bra DONE;\n"
      "add.u32 n, n, 1;\n"
      "setp.gt.u32 p, n, 4194304;\n"
      "@p trap;\n"
      "bra SPIN;\n"
      "DONE:\n}\n" :: "l"(p), "r"(target) : "memory");
}
__device__ __forceinline__ void fence_async_global() { asm volatile("fence.proxy.async.global;" ::: "memory"); }
__device__ __forceinline__ float lds_f(uint32_t a) { float v; asm volatile("ld.shared.f32 %0, [%1];" : "=f"(v) : "r"(a)); return v; }
__device__ __forceinline__ float2 lds_f2(uint32_t a) { float2 v; asm volatile("ld.shared.v2.f32 {%0, %1}, [%2];" : "=f"(v.x), "=f"(v.y) : "r"(a)); return v; }
__device__ __forceinline__ uint4 ldcg4(const void* p) { return __ldcg(reinterpret_cast<const uint4*>(p)); }

__device__ __forceinline__ void sts_f2(uint32_t a, float x, float y) { asm volatile("st.shared.v2.f32 [%0], {%1, %2};" :: "r"(a), "f"(x), "f"(y) : "memory"); }
__device__ __forceinline__ void sts_u4(uint32_t a, uint4 v) { asm volatile("st.shared.v4.u32 [%0], {%1, %2, %3, %4};" :: "r"(a), "r"(v.x), "r"(v.y), "r"(v.z), "r"(v.w) : "memory"); }
__device__ __forceinline__ void sts_u1(uint32_t a, uint32_t v) { asm volatile("st.shared.u32 [%0], %1;" :: "r"(a), "r"(v) : "memory"); }
__device__ __forceinline__ void fence_async_smem() { asm volatile("fence.proxy.async.shared::cta;" ::: "memory"); }
__device__ __forceinline__ void bulk_store(void* dst, uint32_t src, uint32_t bytes) {
  asm volatile("cp.async.bulk.global.shared::cta.bulk_group [%0], [%1], %2;" :: "l"(dst), "r"(src), "r"(bytes) : "memory");
}
__device__ __forceinline__ void bulk_red_f32(void* dst, uint32_t src, uint32_t bytes) {
  asm volatile("cp.reduce.async.bulk.global.shared::cta.bulk_group.add.f32 [%0], [%1], %2;" :: "l"(dst), "r"(src), "r"(bytes) : "memory");
}
__device__ __forceinline__ void tma_store2d(const CUtensorMap* m, uint32_t src, int c0, int c1) {
  asm volatile("cp.async.bulk.tensor.2d.global.shared::cta.bulk_group [%0, {%2, %3}], [%1];" :: "l"(m), "r"(src), "r"(c0), "r"(c1) : "memory");
}
__device__ __forceinline__ void bulk_done() { asm volatile("cp.async.bulk.commit_group;\ncp.async.bulk.wait_group 0;" ::: "memory"); }
__device__ __forceinline__ void bulk_commit() { asm volatile("cp.async.bulk.commit_group;" ::: "memory"); }
__device__ __forceinline__ void bulk_wait() { asm volatile("cp.async.bulk.wait_group 0;" ::: "memory"); }
__device__ __forceinline__ void stsm4(uint32_t a, uint32_t r0, uint32_t r1, uint32_t r2, uint32_t r3) {
  asm volatile("stmatrix.sync.aligned.m8n8.x4.shared.b16 [%0], {%1, %2, %3, %4};" :: "r"(a), "r"(r0), "r"(r1), "r"(r2), "r"(r3) : "memory");
}
__device__ __forceinline__ void flag_add(unsigned* f) { asm volatile("red.relaxed.gpu.global.add.u32 [%0], 1;" :: "l"(f) : "memory"); }
__device__ __forceinline__ float4 lds_f4(uint32_t a) { return *reinterpret_cast<const float4*>(__cvta_shared_to_generic(a)); }
__device__ __forceinline__ uint4 lds_u4(uint32_t a) { return *reinterpret_cast<const uint4*>(__cvta_shared_to_generic(a)); }
__device__ __forceinline__ void lds8(uint32_t a, float (&v)[8]) {
  const float4 p = lds_f4(a), q = lds_f4(a + 16);
  v[0] = p.x; v[1] = p.y; v[2] = p.z; v[3] = p.w; v[4] = q.x; v[5] = q.y; v[6] = q.z; v[7] = q.w;
}
__device__ __forceinline__ void lds8_bf(uint32_t a, float (&v)[8]) {
  const uint4 u = lds_u4(a);
  v[0] = bf_lo(u.x); v[1] = bf_hi(u.x); v[2] = bf_lo(u.y); v[3] = bf_hi(u.y); v[4] = bf_lo(u.z); v[5] = bf_hi(u.z); v[6] = bf_lo(u.w); v[7] = bf_hi(u.w);
}
__device__ __forceinline__ uint4 pack8(const float (&v)[8]) {
  return make_uint4(pack_bf16(v[0], v[1]), pack_bf16(v[2], v[3]), pack_bf16(v[4], v[5]), pack_bf16(v[6], v[7]));
}
__device__ __forceinline__ void mbar_wait_c(uint32_t a, uint32_t ph) {
  asm volatile("{\n.reg .pred p;\nSPIN:\nmbarrier.try_wait.parity.shared::cta.b64 p, [%0], %1;\n@!p bra SPIN;\n}\n" :: "r"(a), "r"(ph) : "memory");
}
constexpr int ST_P = 80;
constexpr int E_TILE = 128 * 80 * 2;

struct Maps { CUtensorMap h, wq, k, v, so, o, wo3, wo2, xa, w1t, us, w2t, x1, w3, g, w4t, ex, sxa, sus, sx1, sout; };
struct PfList { const uint8_t* p[6]; };

constexpr int M_AOFF = 5 * A_SLOT, M_NA = 6, M_ARING = M_NA * 8192;

__global__ void __cluster_dims__(2, 1, 1) __launch_bounds__(384, 1)
fused_kernel(const __grid_constant__ Maps tm, const __grid_constant__ PfList pf, const __grid_constant__ PrepW pw, const bf16* __restrict__ x, bf16* __restrict__ out) {
  extern __shared__ uint8_t smem_raw[];
  const uint32_t sb = (smem_u32(smem_raw) + 1023) & ~1023u;
  TL_ENTRY(2);
  const uint32_t bar_full = sb + A_NSLOT * A_SLOT;
  const uint32_t bar_empty = bar_full + 8 * A_NSLOT;
  const uint32_t bar_sig = bar_empty + 8 * A_NSLOT;
  const uint32_t mb_full = bar_sig + 16;
  const uint32_t mb_e = mb_full + 136 + 88;
  const uint32_t mb_empty = mb_full + 136;
  const uint32_t par = sb + T_PAR;
  float* parf = reinterpret_cast<float*>(smem_raw + (par - smem_u32(smem_raw)));
  uint32_t rank;
  asm volatile("mov.u32 %0, %%cluster_ctarank;" : "=r"(rank));
  const int cid = blockIdx.x >> 1;
  const int wid = __shfl_sync(0xffffffffu, threadIdx.x >> 5, 0);
  const int wg = wid >> 2;
  const int qtile = (cid & 7) * 2 + rank, hbase = cid >> 3;
  const int o_qt = qtile, o_nh = (cid >> 3) & 1, o_ks = cid >> 4;
  const int o_col = o_nh * 320 + o_ks * 80;
  const int qt = cid >> 2, js = (cid & 3) * 2 + rank;
  if (threadIdx.x == 0) {
    for (int i = 0; i < A_NSLOT; i++) { mbar_init(bar_full + 8 * i, 1); mbar_init(bar_empty + 8 * i, 16); }
    for (int i = 0; i < 17; i++) mbar_init(mb_full + 8 * i, 1);
    for (int i = 0; i < 11; i++) mbar_init(mb_empty + 8 * i, 8);
    mbar_init(mb_e, 1); mbar_init(mb_e + 8, 1);
    asm volatile("fence.mbarrier_init.release.cluster;" ::: "memory");
    prefetch_tmap(&tm.h); prefetch_tmap(&tm.wq); prefetch_tmap(&tm.k); prefetch_tmap(&tm.v); prefetch_tmap(&tm.so);
  }
  __syncthreads();
  cluster_sync();

  if (wg == 0) {
    asm volatile("setmaxnreg.dec.sync.aligned.u32 40;");
    if (wid == 0) {
      Ring r{0, 1};
#define P_ACQ(bytes_) do { mbar_wait(bar_empty + 8 * r.slot, r.phase); mbar_expect_e(bar_full + 8 * r.slot, bytes_); } while (0)
#define P_DST (sb + r.slot * A_SLOT)
#define P_BAR (bar_full + 8 * r.slot)
#define P_GRANT2() do { _Pragma("unroll 1") for (int g_ = 0; g_ < 2; g_++) { P_ACQ(0); r.adv(A_NSLOT); } } while (0)
      uint64_t pol_ef;
      asm volatile("createpolicy.fractional.L2::evict_first.b64 %0, 1.0;" : "=l"(pol_ef));
      if (qtile < 10) l2_prefetch_t3d(&tm.wq, 0, qtile * 64, hbase * 3);
      else l2_prefetch_t3d((qtile & 1) ? &tm.v : &tm.k, 0, hbase * S_ + ((qtile - 10) >> 1) * 64, 0);
      pdl_wait();
      TL_WAITED(2);
#pragma unroll 1
      for (int item = 0; item < 4; item++) {
        const int head = hbase + 8 * item;
#pragma unroll 1
        for (int kb = 0; kb < 10; kb++) {
          P_ACQ(16384);
          tma2d(P_DST, &tm.h, P_BAR, kb * 64, qtile * 128);
          r.adv(A_NSLOT);
          P_ACQ(A_SLOT);
          if ((uint32_t)(kb & 1) == rank) tma3d_mc_hint(P_DST, &tm.wq, P_BAR, 0, kb * 64, head * 3, 3, pol_ef);
          r.adv(A_NSLOT);
          if (kb == 1 && item > 0) P_GRANT2();
        }
#pragma unroll 1
        for (int j = 0; j <= A_NKV; j++) {
          if (j < A_NKV) {
            P_ACQ(A_SLOT);
            if (rank == 0) tma3d_mc_hint(P_DST, &tm.k, P_BAR, 0, head * S_ + j * 64, 0, 3, pol_ef);
            r.adv(A_NSLOT);
          }
          if (j > 0) {
            P_ACQ(A_SLOT);
            if (rank == 1) tma3d_mc_hint(P_DST, &tm.v, P_BAR, 0, head * S_ + (j - 1) * 64, 0, 3, pol_ef);
            r.adv(A_NSLOT);
          }
          if (item < 3 && j == 16 && qtile < 10) l2_prefetch_t3d(&tm.wq, 0, qtile * 64, (head + 8) * 3);
          if (item == 3 && (j & 3) == 0) {
            const int c = (j >> 2) * 128 + blockIdx.x;
            if (c < 980) {
              const int li = c < 480 ? 0 : c < 600 ? 1 : c < 720 ? 2 : c < 880 ? 3 : c < 930 ? 4 : 5;
              const int c0 = c < 480 ? 0 : c < 600 ? 480 : c < 720 ? 600 : c < 880 ? 720 : c < 930 ? 880 : 930;
              l2_prefetch16k(pf.p[li] + (size_t)(c - c0) * 16384);
            }
          }
          if (item == 3) {
            if (j >= 6 && j < 24) {
              const int kb = j - 6;
              l2_prefetch_t2d(&tm.o, ((kb / 6) * 8 + 2 * o_ks + (kb % 6) / 3) * DH_ + (kb % 3) * 64, o_qt * 128);
            }
            if (j >= 24 && j < 30) flag_wait(g_flag + F_O + o_qt * 32 + ((j - 24) >> 1) * 8 + 2 * o_ks + (j & 1), 2);
            if (j == 0 && threadIdx.x == 0) {
              prefetch_tmap(&tm.o); prefetch_tmap(&tm.wo3); prefetch_tmap(&tm.wo2); prefetch_tmap(&tm.xa); prefetch_tmap(&tm.w1t); prefetch_tmap(&tm.us);
              prefetch_tmap(&tm.w2t); prefetch_tmap(&tm.x1); prefetch_tmap(&tm.w3); prefetch_tmap(&tm.g); prefetch_tmap(&tm.w4t);
              prefetch_tmap(&tm.ex);
              prefetch_tmap(&tm.sxa); prefetch_tmap(&tm.sus); prefetch_tmap(&tm.sx1); prefetch_tmap(&tm.sout);
            }
          }
        }
      }
#pragma unroll 1
      for (int kb = 0; kb < 24; kb++) {
        const int head = (kb / 6) * 8 + 2 * o_ks + (kb % 6) / 3;
        const int kcol = head * DH_ + (kb % 3) * 64;
        P_ACQ(24576);
        if (rank == 0) tma3d_mc(P_DST, &tm.wo3, P_BAR, 0, kcol, o_nh * 5, 3);
        r.adv(A_NSLOT);
        P_ACQ(16384);
        if (rank == 1) tma3d_mc(P_DST, &tm.wo2, P_BAR, 0, kcol, o_nh * 5 + 3, 3);
        r.adv(A_NSLOT);
        if (kb == 18 || kb == 21) flag_wait(g_flag + F_O + o_qt * 32 + head, 2);
        if (kb % 3 == 0) fence_async_global();
        P_ACQ(16384);
        tma2d(P_DST, &tm.o, P_BAR, kcol, o_qt * 128);
        r.adv(A_NSLOT);
        if (kb == 0) P_GRANT2();
      }
      P_ACQ(E_TILE);
      tma2d(P_DST, &tm.ex, P_BAR, o_col, o_qt * 128);
      r.adv(A_NSLOT);
      flag_wait(g_flag + F_XCH + (o_qt * 2 + o_nh) * 4 + o_ks, 6);
      fence_async_global();
#pragma unroll 1
      for (int i = 0; i < 3; i++) {
        P_ACQ(E_TILE);
        bulk_load(P_DST, g_xch + (size_t)((((o_qt * 2 + o_nh) * 4 + o_ks) * 4) + ((o_ks + 1 + i) & 3)) * (E_TILE / 2), E_TILE, P_BAR);
        r.adv(A_NSLOT);
      }
#pragma unroll 1
      for (int i = 0; i < A_NSLOT; i++) { mbar_wait(bar_empty + 8 * r.slot, r.phase); r.adv(A_NSLOT); }
      bar_arrive(7, 64);
      Ring ra{0, 1};
      const uint32_t fa = mb_full + 40 + rank * 48, fa_peer = mapa(fa, rank ^ 1);
      const int blk = qt * 2 + rank;
#pragma unroll 1
      for (int ph = 0; ph < 4; ph++) {
        const CUtensorMap* ma = ph == 0 ? &tm.xa : ph == 1 ? &tm.us : ph == 2 ? &tm.x1 : &tm.g;
        const int nkb = ph == 3 ? 24 : 10;
        const unsigned* fl = g_flag + F_XA + 32 * ph;
        TX(8 + ph * 4);
        flag_wait(fl + blk, 8);
        if (ph == 1) { if (blk > 0) flag_wait(fl + blk - 1, 8); if (blk < 31) flag_wait(fl + blk + 1, 8); }
        TX(9 + ph * 4);
        fence_async_global();
#pragma unroll 1
        for (int kb = 0; kb < nkb; kb++) {
          mbar_wait(mb_empty + 40 + 8 * ra.slot, ra.phase);
          mbar_expect_e(fa + 8 * ra.slot, 8192);
          asm volatile(ELECT_ "mbarrier.arrive.expect_tx.shared::cluster.b64 _, [%0], 8192;\n}\n" :: "r"(fa_peer + 8 * ra.slot) : "memory");
          tma2d_mc(sb + M_AOFF + rank * M_ARING + ra.slot * 8192, ma, fa + 8 * ra.slot, kb * 64, blk * 64, 3);
          ra.adv(M_NA);
        }
      }
    } else if (wid == 3) {
      const int lane = threadIdx.x & 31;
      pdl_wait();
      prep_warp(pw, reinterpret_cast<bf16(*)[72]>(smem_raw + (sb + T_PREP - smem_u32(smem_raw))), lane);
      flag_wait(g_flag + F_PREP, PREP_CTAS);
#pragma unroll 1
      for (int i = lane; i < P_SC; i += 32) {
        const int v = i < P_CS3 ? i / 80 : 9, j = i - (i < P_CS3 ? v * 80 : P_CS3);
        const float* src = v == 0 ? g_mod + 2 * D_ + o_col : v == 1 ? g_mod + 4 * D_ + o_col : v == 2 ? g_mod + 3 * D_ + o_col
                         : v < 6 ? g_vec + (v - 3) * D_ + js * 80 : v == 6 ? g_mod + 4 * D_ + js * 80 : v == 7 ? g_mod + 3 * D_ + js * 80
                         : v == 8 ? g_mod + 5 * D_ + js * 80 : g_vec + 3 * D_ + js * 192;
        parf[i] = __ldcg(src + j);
      }
      float sv[5] = {0.f, 0.f, 0.f, 0.f, 0.f};
#pragma unroll 1
      for (int i = lane; i < D_; i += 32) {
        const float a = __ldcg(g_mod + 4 * D_ + i), b = __ldcg(g_mod + 3 * D_ + i);
        sv[0] += a; sv[1] = fmaf(a, a, sv[1]); sv[2] = fmaf(a, b, sv[2]); sv[3] += b; sv[4] = fmaf(b, b, sv[4]);
      }
#pragma unroll 1
      for (int o_ = 16; o_ > 0; o_ >>= 1) {
#pragma unroll
        for (int i = 0; i < 5; i++) sv[i] += __shfl_xor_sync(0xffffffffu, sv[i], o_);
      }
      if (lane == 0) {
#pragma unroll
        for (int i = 0; i < 5; i++) parf[P_SC + i] = sv[i];
      }
      bar_arrive(6, 288);
      fence_async_global();
      bar_sync(7, 64);
      Ring rb{0, 1};
#pragma unroll 1
      for (int ph = 0; ph < 4; ph++) {
        const CUtensorMap* mb = ph == 0 ? &tm.w1t : ph == 1 ? &tm.w2t : ph == 2 ? &tm.w3 : &tm.w4t;
        const int nbl = ph == 2 ? 10 : ph == 3 ? 12 : 5;
#pragma unroll 1
        for (int bl = 0; bl < nbl; bl++) {
          mbar_wait(mb_empty + 8 * rb.slot, rb.phase);
          mbar_expect_e(mb_full + 8 * rb.slot, ph == 2 ? 24576 : 20480);
          tma3d(sb + rb.slot * A_SLOT, mb, mb_full + 8 * rb.slot, 0, ph == 2 ? bl * 64 : js * 80, ph == 2 ? js * 3 : bl * 2);
          rb.adv(5);
        }
      }
    }
    __syncwarp();
    cluster_sync();
  } else {
    asm volatile("setmaxnreg.inc.sync.aligned.u32 232;");
    const int w = wg - 1;
    const int lane = threadIdx.x & 31;
    const int warp = wid & 3;
    const int tid = threadIdx.x - 128;
    const uint32_t rel_base = mapa(bar_empty, (lane == 0) ? rank : (rank ^ 1));
    Ring r{0, 0};
#define A_RELEASE(slot_) do { if (lane < 2) mbar_arrive_remote(rel_base + 8 * (slot_)); } while (0)
    const bool leader = (tid & 127) == 0;
    uint32_t so_own = 0;
#define O_SKIP() do { const uint32_t s0_ = r.slot; r.adv(A_NSLOT); const uint32_t s1_ = r.slot; r.adv(A_NSLOT);         \
                      A_RELEASE(w ? s0_ : s1_); if (warp != 0) A_RELEASE(so_own); } while (0)
#define O_PUBLISH(head_) do { if (warp == 0) { if (lane == 0) { bulk_wait(); flag_add(g_flag + F_O + qtile * 32 + (head_)); } __syncwarp(); A_RELEASE(so_own); } } while (0)
    {
    const float SC = 0.07216878364870322f * 1.4426950408889634f;
    float o[96];
    uint32_t q[48];
    float s[32];
    uint32_t p[16], p2[16];
    if (w == 1) bar_arrive(1, 256);
#pragma unroll 1
    for (int item = 0; item < 4; item++) {
      TSA(item, 0);
      {
        uint32_t prevA = 0, prevB = 0;
#pragma unroll 1
        for (int kb = 0; kb < 10; kb++) {
          const uint32_t sA = r.slot; mbar_wait_c(bar_full + 8 * sA, r.phase); r.adv(A_NSLOT);
          const uint32_t sB = r.slot; mbar_wait_c(bar_full + 8 * sB, r.phase); r.adv(A_NSLOT);
          const uint64_t da = mkdesc(sb + sA * A_SLOT + w * 8192, 16, 1024);
          const uint64_t db = mkdesc(sb + sB * A_SLOT, 8192, 1024);
          wg_fence();
#pragma unroll
          for (int kk = 0; kk < 4; kk++) wgmma_ss_n192<1>(o, da + kk * 2, db + kk * 128, (kb | kk) != 0);
          wg_commit();
          if (item > 0) { if (kb == 1) O_SKIP(); if (kb == 4) O_PUBLISH(hbase + 8 * item - 8); }
          if (kb > 0) { wg_wait<1>(); A_RELEASE(prevA); A_RELEASE(prevB); }
          prevA = sA; prevB = sB;
        }
        wg_wait<0>();
        fence_regs(o);
        A_RELEASE(prevA); A_RELEASE(prevB);
#pragma unroll
        for (int i = 0; i < 48; i++) q[i] = pack_bf16(o[2 * i], o[2 * i + 1]);
      }

      TSA(item, 1);
      float c0, c1, l0, l1;
      {
        const uint32_t sK = r.slot; mbar_wait_c(bar_full + 8 * sK, r.phase); r.adv(A_NSLOT);
        const uint64_t dk = mkdesc(sb + sK * A_SLOT, 16, 1024);
        bar_sync(1 + w, 256);
        wg_fence();
#pragma unroll
        for (int kk = 0; kk < 12; kk++)
          wgmma_rs_n64<0>(s, q[4 * kk], q[4 * kk + 1], q[4 * kk + 2], q[4 * kk + 3], dk + (kk >> 2) * 512 + (kk & 3) * 2, kk != 0);
        wg_commit();
        bar_arrive(1 + (w ^ 1), 256);
        wg_wait<0>();
        fence_regs(s);
        A_RELEASE(sK);
        float mx0 = fmaxf(s[0], s[1]), mx1 = fmaxf(s[2], s[3]);
#pragma unroll
        for (int i = 1; i < 8; i++) { mx0 = fmaxf(mx0, fmaxf(s[4 * i], s[4 * i + 1])); mx1 = fmaxf(mx1, fmaxf(s[4 * i + 2], s[4 * i + 3])); }
        mx0 = fmaxf(mx0, __shfl_xor_sync(0xffffffffu, mx0, 1)); mx1 = fmaxf(mx1, __shfl_xor_sync(0xffffffffu, mx1, 1));
        mx0 = fmaxf(mx0, __shfl_xor_sync(0xffffffffu, mx0, 2)); mx1 = fmaxf(mx1, __shfl_xor_sync(0xffffffffu, mx1, 2));
        c0 = mx0 * SC; c1 = mx1 * SC;
        l0 = 0.f; l1 = 0.f;
#pragma unroll
        for (int i = 0; i < 8; i++) {
          s[4 * i] = ex2(fmaf(s[4 * i], SC, -c0)); s[4 * i + 1] = ex2(fmaf(s[4 * i + 1], SC, -c0));
          s[4 * i + 2] = ex2(fmaf(s[4 * i + 2], SC, -c1)); s[4 * i + 3] = ex2(fmaf(s[4 * i + 3], SC, -c1));
          l0 += s[4 * i] + s[4 * i + 1]; l1 += s[4 * i + 2] + s[4 * i + 3];
        }
#pragma unroll
        for (int i = 0; i < 16; i++) p[i] = pack_bf16(s[2 * i], s[2 * i + 1]);
      }
      TSA(item, 2);
      uint32_t okn;
      {
        Ring r2 = r; r2.adv(A_NSLOT);
        okn = mbar_try(bar_full + 8 * r.slot, r.phase) & mbar_try(bar_full + 8 * r2.slot, r2.phase);
      }
#define A_STEP(PC, PN, FIRST)                                                                                          \
      {                                                                                                                \
        const uint32_t sK = r.slot, phK = r.phase; r.adv(A_NSLOT);                                                     \
        const uint32_t sV = r.slot, phV = r.phase; r.adv(A_NSLOT);                                                     \
        const uint64_t dk = mkdesc(sb + sK * A_SLOT, 16, 1024);                                                        \
        const uint64_t dv = mkdesc(sb + sV * A_SLOT, 8192, 1024);                                                      \
        if (!okn) { mbar_wait_c(bar_full + 8 * sK, phK); mbar_wait_c(bar_full + 8 * sV, phV); }                            \
        bar_sync(1 + w, 256);                                                                                          \
        wg_fence();                                                                                                    \
        _Pragma("unroll") for (int kk = 0; kk < 12; kk++)                                                              \
          wgmma_rs_n64<0>(s, q[4 * kk], q[4 * kk + 1], q[4 * kk + 2], q[4 * kk + 3], dk + (kk >> 2) * 512 + (kk & 3) * 2, kk != 0); \
        wg_commit();                                                                                                   \
        _Pragma("unroll") for (int kk = 0; kk < 4; kk++)                                                               \
          wgmma_rs_n192<1>(o, PC[4 * kk], PC[4 * kk + 1], PC[4 * kk + 2], PC[4 * kk + 3], dv + kk * 128, !(FIRST) || (kk != 0)); \
        wg_commit();                                                                                                   \
        bar_arrive(1 + (w ^ 1), 256);                                                                                  \
        {                                                                                                              \
          Ring r2 = r; r2.adv(A_NSLOT);                                                                                \
          okn = mbar_try(bar_full + 8 * r.slot, r.phase) & mbar_try(bar_full + 8 * r2.slot, r2.phase);                 \
        }                                                                                                              \
        wg_wait<1>();                                                                                                  \
        fence_regs(s);                                                                                                 \
        A_RELEASE(sK);                                                                                                 \
        float b0 = 0.f, b1 = 0.f;                                                                                      \
        _Pragma("unroll") for (int i = 0; i < 8; i++) {                                                                \
          const float e0 = ex2(fmaf(s[4 * i], SC, -c0)), e1 = ex2(fmaf(s[4 * i + 1], SC, -c0));                        \
          const float e2 = ex2(fmaf(s[4 * i + 2], SC, -c1)), e3 = ex2(fmaf(s[4 * i + 3], SC, -c1));                    \
          b0 += e0 + e1; b1 += e2 + e3;                                                                                \
          PN[2 * i] = pack_bf16(e0, e1); PN[2 * i + 1] = pack_bf16(e2, e3);                                            \
        }                                                                                                              \
        wg_wait<0>();                                                                                                  \
        fence_regs(o);                                                                                                 \
        fence_regs(PC);                                                                                                \
        A_RELEASE(sV);                                                                                                 \
        if (__any_sync(0xffffffffu, !(b0 <= 65536.f) || !(b1 <= 65536.f))) {                                           \
          float mx0 = fmaxf(s[0], s[1]), mx1 = fmaxf(s[2], s[3]);                                                      \
          _Pragma("unroll") for (int i = 1; i < 8; i++) {                                                              \
            mx0 = fmaxf(mx0, fmaxf(s[4 * i], s[4 * i + 1])); mx1 = fmaxf(mx1, fmaxf(s[4 * i + 2], s[4 * i + 3]));     \
          }                                                                                                            \
          mx0 = fmaxf(mx0, __shfl_xor_sync(0xffffffffu, mx0, 1)); mx1 = fmaxf(mx1, __shfl_xor_sync(0xffffffffu, mx1, 1)); \
          mx0 = fmaxf(mx0, __shfl_xor_sync(0xffffffffu, mx0, 2)); mx1 = fmaxf(mx1, __shfl_xor_sync(0xffffffffu, mx1, 2)); \
          const float n0 = fmaxf(c0, mx0 * SC), n1 = fmaxf(c1, mx1 * SC);                                              \
          const float a0 = ex2(c0 - n0), a1 = ex2(c1 - n1);                                                            \
          c0 = n0; c1 = n1;                                                                                            \
          l0 *= a0; l1 *= a1;                                                                                          \
          _Pragma("unroll") for (int i = 0; i < 24; i++) { o[4 * i] *= a0; o[4 * i + 1] *= a0; o[4 * i + 2] *= a1; o[4 * i + 3] *= a1; } \
          b0 = 0.f; b1 = 0.f;                                                                                          \
          _Pragma("unroll") for (int i = 0; i < 8; i++) {                                                              \
            const float e0 = ex2(fmaf(s[4 * i], SC, -c0)), e1 = ex2(fmaf(s[4 * i + 1], SC, -c0));                      \
            const float e2 = ex2(fmaf(s[4 * i + 2], SC, -c1)), e3 = ex2(fmaf(s[4 * i + 3], SC, -c1));                  \
            b0 += e0 + e1; b1 += e2 + e3;                                                                              \
            PN[2 * i] = pack_bf16(e0, e1); PN[2 * i + 1] = pack_bf16(e2, e3);                                          \
          }                                                                                                            \
        }                                                                                                              \
        l0 += b0; l1 += b1;                                                                                            \
      }
      for (int jj = 0; jj < 15; jj++) {
        A_STEP(p, p2, jj == 0)
        A_STEP(p2, p, false)
      }
      A_STEP(p, p2, false)
      TSA(item, 3);
      {
        const uint32_t sV = r.slot; mbar_wait_c(bar_full + 8 * sV, r.phase); r.adv(A_NSLOT);
        const uint64_t dv = mkdesc(sb + sV * A_SLOT, 8192, 1024);
        bar_sync(1 + w, 256);
        wg_fence();
#pragma unroll
        for (int kk = 0; kk < 4; kk++)
          wgmma_rs_n192<1>(o, p2[4 * kk], p2[4 * kk + 1], p2[4 * kk + 2], p2[4 * kk + 3], dv + kk * 128, 1);
        wg_commit();
        bar_arrive(1 + (w ^ 1), 256);
        wg_wait<0>();
        fence_regs(o);
        A_RELEASE(sV);
      }
      TSA(item, 4);
      l0 += __shfl_xor_sync(0xffffffffu, l0, 1); l1 += __shfl_xor_sync(0xffffffffu, l1, 1);
      l0 += __shfl_xor_sync(0xffffffffu, l0, 2); l1 += __shfl_xor_sync(0xffffffffu, l1, 2);
      const float i0 = __fdividef(1.f, l0), i1 = __fdividef(1.f, l1);
      {
        Ring ro = r;
#pragma unroll 1
        for (int i = (item < 3 ? 4 : 3) + w; i > 0; i--) ro.adv(A_NSLOT);
        so_own = ro.slot;
        mbar_wait_c(bar_full + 8 * ro.slot, ro.phase);
        const uint32_t srow = warp * 16 + (lane & 15);
        const uint32_t sa = sb + so_own * A_SLOT + srow * 128, xr = (lane & 7) ^ (lane >> 4);
#pragma unroll
        for (int kk = 0; kk < 12; kk++)
          stsm4(sa + (kk >> 2) * 8192 + ((xr ^ ((kk & 3) * 2)) << 4),
                pack_bf16(o[8 * kk] * i0, o[8 * kk + 1] * i0), pack_bf16(o[8 * kk + 2] * i1, o[8 * kk + 3] * i1),
                pack_bf16(o[8 * kk + 4] * i0, o[8 * kk + 5] * i0), pack_bf16(o[8 * kk + 6] * i1, o[8 * kk + 7] * i1));
        fence_async_smem();
        bar_sync(3 + w, 128);
        if (leader) {
#pragma unroll
          for (int b = 0; b < 3; b++) tma_store2d(&tm.so, sb + so_own * A_SLOT + b * 8192, (hbase + 8 * item) * DH_ + b * 64, qtile * 128 + w * 64);
          bulk_commit();
        }
        __syncwarp();
      }
      TSA(item, 5);
    }
    }
    TS(3, 2);
    const uint32_t st_w = (uint32_t)((warp * 16 + (lane >> 2)) * ST_P + (lane & 3) * 2) * 4;
    const uint32_t st_x = (lane & 8) << 2;
    const int er = (tid & 127) >> 1, eh = tid & 1;
    const uint32_t st_r = (uint32_t)(er * ST_P + (eh ^ ((er >> 1) & 1)) * 8) * 4;
    const uint32_t e_r = (uint32_t)((w * 64 + er) * 160 + eh * 16);
    const uint32_t p_r = par + eh * 32;
    const uint32_t stat = sb + T_PREP + w * 2048;
#define STAGE10(ACC, BASE)                                                                                             \
    _Pragma("unroll") for (int nb = 0; nb < 10; nb++) {                                                                \
      sts_f2(stg + st_w + ((nb * 32) ^ st_x), ACC(BASE + 4 * nb), ACC(BASE + 4 * nb + 1));                                       \
      sts_f2(stg + st_w + ((nb * 32) ^ st_x) + 8 * ST_P * 4, ACC(BASE + 4 * nb + 2), ACC(BASE + 4 * nb + 3));                    \
    }

    {
      float acc1[96], acc2[64];
      uint32_t p0 = 0, p1 = 0, p2 = 0;
#pragma unroll 1
      for (int kb = 0; kb < 24; kb++) {
        const uint32_t s1 = r.slot; mbar_wait_c(bar_full + 8 * s1, r.phase); r.adv(A_NSLOT);
        const uint32_t s2 = r.slot; mbar_wait_c(bar_full + 8 * s2, r.phase); r.adv(A_NSLOT);
        const uint32_t sa = r.slot; mbar_wait_c(bar_full + 8 * sa, r.phase); r.adv(A_NSLOT);
        const uint64_t da = mkdesc(sb + sa * A_SLOT + w * 8192, 16, 1024);
        const uint64_t d1 = mkdesc(sb + s1 * A_SLOT, 8192, 1024), d2 = mkdesc(sb + s2 * A_SLOT, 8192, 1024);
        wg_fence();
#pragma unroll
        for (int kk = 0; kk < 4; kk++) {
          wgmma_ss_n192<1>(acc1, da + kk * 2, d1 + kk * 128, (kb | kk) != 0);
          wgmma_ss_n128<1>(acc2, da + kk * 2, d2 + kk * 128, (kb | kk) != 0);
        }
        wg_commit();
        if (kb == 0) O_SKIP();
        if (kb == 2) O_PUBLISH(hbase + 24);
        if (kb > 0) { wg_wait<1>(); A_RELEASE(p0); A_RELEASE(p1); A_RELEASE(p2); }
        p0 = s1; p1 = s2; p2 = sa;
      }
      wg_wait<0>();
      fence_regs(acc1); fence_regs(acc2);
      A_RELEASE(p2);
      bar_sync(6, 288);
      TS(0, 0);
      const uint32_t stg = sb + (w ? p1 : p0) * A_SLOT;
#define OACC(e) (((e) < 96) ? acc1[(e) < 96 ? (e) : 0] : acc2[(e) >= 96 ? (e) - 96 : 0])
#define PACK10(BASE)                                                                                                   \
      _Pragma("unroll") for (int nb = 0; nb < 10; nb++) {                                                              \
        sts_u1(xo + nb * 16, pack_bf16(OACC(BASE + 4 * nb), OACC(BASE + 4 * nb + 1)));                                 \
        sts_u1(xo + nb * 16 + 8 * 160, pack_bf16(OACC(BASE + 4 * nb + 2), OACC(BASE + 4 * nb + 3)));                   \
      }
      const uint32_t f1 = r.slot + 4 >= A_NSLOT ? r.slot + 4 - A_NSLOT : r.slot + 4, f2 = f1 + 1 >= A_NSLOT ? 0 : f1 + 1;
#pragma unroll
      for (int d = 0; d < 4; d++) {
        if (d != o_ks) {
          const int i = (d - o_ks - 1) & 3;
          const uint32_t xo = sb + (i == 0 ? p2 : i == 1 ? f1 : f2) * A_SLOT + (w * 64 + warp * 16 + (lane >> 2)) * 160 + (lane & 3) * 4;
          PACK10(d * 40)
        }
      }
      fence_async_smem();
      bar_sync(3 + w, 128);
      if (leader) {
#pragma unroll 1
        for (int i = 0; i < 3; i++)
          bulk_store(g_xch + (size_t)((((o_qt * 2 + o_nh) * 4 + ((o_ks + 1 + i) & 3)) * 4) + o_ks) * (E_TILE / 2) + w * (E_TILE / 4),
                     sb + (i == 0 ? p2 : i == 1 ? f1 : f2) * A_SLOT + w * (E_TILE / 2), E_TILE / 2);
        bulk_done();
#pragma unroll 1
        for (int i = 0; i < 3; i++) flag_add(g_flag + F_XCH + (o_qt * 2 + o_nh) * 4 + ((o_ks + 1 + i) & 3));
        TX(40 + w);
      }
      if (o_ks == 0) { STAGE10(OACC, 0) } else if (o_ks == 1) { STAGE10(OACC, 40) } else if (o_ks == 2) { STAGE10(OACC, 80) } else { STAGE10(OACC, 120) }
      bar_sync(3 + w, 128);
      const uint32_t sx = r.slot; mbar_wait_c(bar_full + 8 * sx, r.phase); r.adv(A_NSLOT);
      const uint32_t q0 = r.slot; mbar_wait_c(bar_full + 8 * q0, r.phase); r.adv(A_NSLOT);
      const uint32_t q1 = r.slot; mbar_wait_c(bar_full + 8 * q1, r.phase); r.adv(A_NSLOT);
      const uint32_t q2 = r.slot; mbar_wait_c(bar_full + 8 * q2, r.phase); r.adv(A_NSLOT);
      TS(0, 1);
      float st[6] = {0.f, 0.f, 0.f, 0.f, 0.f, 0.f};
      const uint32_t ot = sb + p2 * A_SLOT;
#pragma unroll 1
      for (int c = 0; c < 5; c++) {
        float v[8], t0[8], t1[8], t2[8], xv[8], pg[8], pa_[8], pb_[8];
        lds8(stg + st_r + c * 64, v);
        lds8_bf(sb + q0 * A_SLOT + e_r + c * 32, t0); lds8_bf(sb + q1 * A_SLOT + e_r + c * 32, t1); lds8_bf(sb + q2 * A_SLOT + e_r + c * 32, t2);
        lds8_bf(sb + sx * A_SLOT + e_r + c * 32, xv);
        lds8(p_r + P_OGA * 4 + c * 64, pg); lds8(p_r + P_OA * 4 + c * 64, pa_); lds8(p_r + P_OB * 4 + c * 64, pb_);
#pragma unroll
        for (int e = 0; e < 8; e++) v[e] = fmaf(pg[e], v[e] + ((t0[e] + t1[e]) + t2[e]), xv[e]);
        const uint4 pk = pack8(v);
        sts_u4(ot + e_r + c * 32, pk);
        v[0] = bf_lo(pk.x); v[1] = bf_hi(pk.x); v[2] = bf_lo(pk.y); v[3] = bf_hi(pk.y); v[4] = bf_lo(pk.z); v[5] = bf_hi(pk.z); v[6] = bf_lo(pk.w); v[7] = bf_hi(pk.w);
#pragma unroll
        for (int e = 0; e < 8; e++) {
          const float y = pa_[e] * v[e];
          st[0] += v[e]; st[1] = fmaf(v[e], v[e], st[1]); st[2] += y; st[3] = fmaf(pa_[e], y, st[3]); st[4] = fmaf(y, y, st[4]); st[5] = fmaf(pb_[e], y, st[5]);
        }
      }
#pragma unroll
      for (int i = 0; i < 6; i++) st[i] += __shfl_xor_sync(0xffffffffu, st[i], 1);
      sts_u4(stat + er * 32 + eh * 16, eh ? make_uint4(__float_as_uint(st[4]), __float_as_uint(st[5]), 0u, 0u)
                                          : make_uint4(__float_as_uint(st[0]), __float_as_uint(st[1]), __float_as_uint(st[2]), __float_as_uint(st[3])));
      fence_async_smem();
      bar_sync(3 + w, 128);
      if (leader) {
        tma_store2d(&tm.sxa, ot + w * (E_TILE / 2), o_col, o_qt * 128 + w * 64);
        bulk_red_f32(g_st1 + (size_t)(o_qt * 128 + w * 64) * 8, stat, 2048);
        bulk_done();
        flag_add(g_flag + F_XA + o_qt * 2 + w);
      }
      bar_sync(5, 256);
      A_RELEASE(p0); A_RELEASE(p1); A_RELEASE(sx); A_RELEASE(q0); A_RELEASE(q1); A_RELEASE(q2);
      TS(0, 2);
    }

    Ring ra{0, 0}, rb{0, 0};
    const uint32_t rel_a = mapa(mb_empty + 40, w);
    const uint32_t aring = sb + M_AOFF + w * M_ARING;
#define B_NEXT(s_) do { s_ = rb.slot; mbar_wait_c(mb_full + 8 * s_, rb.phase); rb.adv(5); } while (0)
#define A_NEXT(s_) do { s_ = ra.slot; mbar_wait_c(mb_full + 40 + w * 48 + 8 * s_, ra.phase); ra.adv(M_NA); } while (0)
#define B_RELEASE(s_) do { if (lane == 0) mbar_arrive(mb_empty + 8 * (s_)); } while (0)
#define MA_RELEASE(s_) do { if (lane == 0) mbar_arrive_remote(rel_a + 8 * (s_)); } while (0)
    const int grow = qt * 128 + w * 64 + er;
    float mu = 0.f, rs = 0.f;
#pragma unroll 1
    for (int ph = 0; ph < 4; ph++) {
      float acc[96];
      float (&acc80)[40] = *reinterpret_cast<float(*)[40]>(&acc[0]);
      uint32_t pa = 0, pa2 = 0, pb = 0;
      float4 s03 = make_float4(0.f, 0.f, 0.f, 0.f);
      float2 s45 = make_float2(0.f, 0.f);
      const int nit = ph == 3 ? 12 : ph == 2 ? 10 : 5;
      if (w == 1 && ph < 2) bar_sync(5, 256);
#pragma unroll 1
      for (int it = 0; it < nit; it++) {
        uint32_t sbq, sa, sa2;
        B_NEXT(sbq);
        A_NEXT(sa);
        if (it == 0) TXC(ph);
        const uint64_t da = mkdesc(aring + sa * 8192, 16, 1024);
        if (ph == 2) {
          sa2 = sa;
          const uint64_t db = mkdesc(sb + sbq * A_SLOT, 8192, 1024);
          wg_fence();
#pragma unroll
          for (int kk = 0; kk < 4; kk++) wgmma_ss_n192<1>(acc, da + kk * 2, db + kk * 128, (it | kk) != 0);
          wg_commit();
        } else {
          A_NEXT(sa2);
          const uint64_t da2 = mkdesc(aring + sa2 * 8192, 16, 1024);
          const uint64_t db = mkdesc(sb + sbq * A_SLOT, 16, 1024);
          wg_fence();
#pragma unroll
          for (int kk = 0; kk < 4; kk++) wgmma_ss_n80<0>(acc80, da + kk * 2, db + kk * 2, (it | kk) != 0);
#pragma unroll
          for (int kk = 0; kk < 4; kk++) wgmma_ss_n80<0>(acc80, da2 + kk * 2, db + 640 + kk * 2, 1);
          wg_commit();
        }
        if (it > 0) { wg_wait<1>(); MA_RELEASE(pa); if (ph != 2) MA_RELEASE(pa2); B_RELEASE(pb); }
        else {
          if (ph == 0) { s03 = __ldcg(reinterpret_cast<const float4*>(g_st1 + (size_t)grow * 8)); s45 = __ldcg(reinterpret_cast<const float2*>(g_st1 + (size_t)grow * 8 + 4)); }
          if (ph == 2) s45 = __ldcg(reinterpret_cast<const float2*>(g_st2 + (size_t)grow * 2));
        }
        pa = sa; pa2 = sa2; pb = sbq;
      }
      if (w == 0 && ph < 2) bar_arrive(5, 256);
      wg_wait<0>();
      fence_regs(acc);
      MA_RELEASE(pa); if (ph != 2) MA_RELEASE(pa2);
      B_RELEASE(pb);
      bar_sync(3 + w, 128);
      TS(1 + (ph == 3 ? 0 : ph), ph == 3 ? 2 : 0);
      const uint32_t stg = aring, ot = aring + 20480;
#define MACC(e) acc[e]
      if (!(ph & 1)) {
        float c0, c1, c2 = 0.f, c3 = 0.f;
        if (ph == 0) {
          const float4 sc = lds_f4(par + P_SC * 4);
          const float sbb = lds_f(par + (P_SC + 4) * 4);
          mu = s03.x * (1.f / D_);
          rs = rsqrtf(fmaxf(s03.y * (1.f / D_) - mu * mu, 0.f) + LN_EPS);
          const float m2 = (rs * (s03.z - mu * sc.x) + sc.w) * (1.f / D_);
          const float e2 = (rs * rs * (s45.x - 2.f * mu * s03.w + mu * mu * sc.y) + 2.f * rs * (s45.y - mu * sc.z) + sbb) * (1.f / D_);
          c2 = rsqrtf(fmaxf(e2 - m2 * m2, 0.f) + LN_EPS);
          c0 = c2 * rs; c1 = -c0 * mu; c3 = -c2 * m2;
          if ((tid & 127) < 10) sts_u4(stat + (tid & 127) * 16, make_uint4(0, 0, 0, 0));
        } else {
          const float m = s45.x * (1.f / D_);
          c0 = rsqrtf(fmaxf(s45.y * (1.f / D_) - m * m, 0.f) + LN_EPS);
          c1 = -c0 * m;
        }
        const int npass = ph == 0 ? 1 : 3, nch = ph == 0 ? 5 : 4;
#pragma unroll 1
        for (int ps = 0; ps < npass; ps++) {
          if (ps == 0) { STAGE10(MACC, 0) } else if (ps == 1) { STAGE10(MACC, 32) } else { STAGE10(MACC, 56) }
          bar_sync(3 + w, 128);
          const uint32_t cofs = ps == 2 ? 64 : 0;
          const uint32_t pp = p_r + (ph == 0 ? P_VA : P_CS3 + ps * 64) * 4, pq = p_r + P_VB * 4;
#pragma unroll 1
          for (int c = 0; c < nch; c++) {
            float v[8], t[8], t2[8], t3[8];
            lds8(stg + st_r + cofs + c * 64, v);
            lds8(pp + c * 64, t);
            if (ph == 0) {
              lds8(pq + c * 64, t2); lds8(pq + 320 + c * 64, t3);
#pragma unroll
              for (int e = 0; e < 8; e++) t[e] = fmaf(c1, t[e], fmaf(c2, t2[e], c3 * t3[e]));
            } else {
#pragma unroll
              for (int e = 0; e < 8; e++) t[e] *= c1;
            }
#pragma unroll
            for (int e = 0; e < 8; e++) v[e] = gelu_tanh(fmaf(c0, v[e], t[e]));
            sts_u4(ot + (ph == 0 ? er * 160 + eh * 16 + c * 32 : ps * 8192 + er * 128 + (((2 * c + eh) ^ (er & 7)) << 4)), pack8(v));
          }
          fence_async_smem();
          bar_sync(3 + w, 128);
          if (leader) {
            if (ph == 0) {
              const int grp = js >> 1;
              const int sh = (grp & 2 ? 2 : 1) * (grp & 1 ? -1 : 1);
              tma_store2d(&tm.sus, ot, js * 80, qt * 128 + w * 64 + sh + 2);
              if (qt * 2 + w == (sh > 0 ? 0 : 31)) {
                const int r0 = sh > 0 ? 0 : S_ + sh, n = sh > 0 ? sh : -sh;
                for (int i = 0; i < n; i++) bulk_store(g_us + (size_t)(r0 + i + 2) * D_ + js * 80, stat, 160);
              }
            } else {
              tma_store2d(&tm.g, ot + ps * 8192, js * 192 + ps * 64, qt * 128 + w * 64);
            }
          }
        }
      } else {
        const uint32_t e1 = aring + 30720;
        if (warp == 0) {
          fence_async_global();
          mbar_expect_e(mb_e + 8 * w, ph == 1 ? 10240 : 20480);
          tma2d(e1, &tm.sxa, mb_e + 8 * w, js * 80, qt * 128 + w * 64);
          if (ph == 3) tma2d(ot, &tm.sx1, mb_e + 8 * w, js * 80, qt * 128 + w * 64);
        }
        STAGE10(MACC, 0)
        bar_sync(3 + w, 128);
        mbar_wait_c(mb_e + 8 * w, ph >> 1);
        float s1 = 0.f, s2 = 0.f;
#pragma unroll 1
        for (int c = 0; c < 5; c++) {
          float v[8], xa[8], x1[8], ta[8], tb[8];
          lds8(stg + st_r + c * 64, v);
          lds8_bf(e1 + er * 160 + eh * 16 + c * 32, xa); lds8_bf(ot + er * 160 + eh * 16 + c * 32, x1);
          lds8(p_r + (ph == 1 ? P_A2 : P_GB) * 4 + c * 64, ta); lds8(p_r + P_B2 * 4 + c * 64, tb);
          if (ph == 1) {
#pragma unroll
            for (int e = 0; e < 8; e++) v[e] += fmaf(ta[e] * rs, xa[e] - mu, tb[e]);
          } else {
#pragma unroll
            for (int e = 0; e < 8; e++) v[e] = fmaf(ta[e], v[e] + x1[e], xa[e]);
          }
          const uint4 pk = pack8(v);
          sts_u4(ot + er * 160 + eh * 16 + c * 32, pk);
          v[0] = bf_lo(pk.x); v[1] = bf_hi(pk.x); v[2] = bf_lo(pk.y); v[3] = bf_hi(pk.y); v[4] = bf_lo(pk.z); v[5] = bf_hi(pk.z); v[6] = bf_lo(pk.w); v[7] = bf_hi(pk.w);
#pragma unroll
          for (int e = 0; e < 8; e++) { s1 += v[e]; s2 = fmaf(v[e], v[e], s2); }
        }
        s1 += __shfl_xor_sync(0xffffffffu, s1, 1); s2 += __shfl_xor_sync(0xffffffffu, s2, 1);
        if (eh == 0) sts_f2(stat + er * 8, s1, s2);
        fence_async_smem();
        bar_sync(3 + w, 128);
        if (leader) {
          tma_store2d(ph == 1 ? &tm.sx1 : &tm.sout, ot, js * 80, qt * 128 + w * 64);
          if (ph == 1) bulk_red_f32(g_st2 + (size_t)(qt * 128 + w * 64) * 2, stat, 512);
        }
      }
      if (leader) {
        bulk_done();
        if (ph < 3) flag_add(g_flag + F_US + 32 * ph + qt * 2 + w);
      }
      __syncwarp();
      TS(1 + (ph == 3 ? 0 : ph), ph == 3 ? 3 : 1);
    }
    if ((threadIdx.x & 127) == 0) TL_END(2);
    cluster_sync();
  }
}

typedef CUresult (*EncFn)(CUtensorMap*, CUtensorMapDataType, cuuint32_t, void*, const cuuint64_t*, const cuuint64_t*,
                          const cuuint32_t*, const cuuint32_t*, CUtensorMapInterleave, CUtensorMapSwizzle,
                          CUtensorMapL2promotion, CUtensorMapFloatOOBfill);
static EncFn g_enc = nullptr;

static CUtensorMap map2d(const void* p, uint64_t rows, uint64_t cols, uint32_t box_rows) {
  CUtensorMap m;
  cuuint64_t gd[2] = {cols, rows}; cuuint64_t gs[1] = {cols * 2};
  cuuint32_t bx[2] = {64, box_rows}; cuuint32_t es[2] = {1, 1};
  g_enc(&m, CU_TENSOR_MAP_DATA_TYPE_BFLOAT16, 2, const_cast<void*>(p), gd, gs, bx, es, CU_TENSOR_MAP_INTERLEAVE_NONE,
        CU_TENSOR_MAP_SWIZZLE_128B, CU_TENSOR_MAP_L2_PROMOTION_L2_256B, CU_TENSOR_MAP_FLOAT_OOB_FILL_NONE);
  return m;
}
static CUtensorMap map3d(const void* p, uint64_t rows, uint64_t cols, uint32_t box_rows, uint32_t nblk) {
  CUtensorMap m;
  cuuint64_t gd[3] = {64, rows, cols / 64}; cuuint64_t gs[2] = {cols * 2, 128};
  cuuint32_t bx[3] = {64, box_rows, nblk}; cuuint32_t es[3] = {1, 1, 1};
  g_enc(&m, CU_TENSOR_MAP_DATA_TYPE_BFLOAT16, 3, const_cast<void*>(p), gd, gs, bx, es, CU_TENSOR_MAP_INTERLEAVE_NONE,
        CU_TENSOR_MAP_SWIZZLE_128B, CU_TENSOR_MAP_L2_PROMOTION_L2_256B, CU_TENSOR_MAP_FLOAT_OOB_FILL_NONE);
  return m;
}

static CUtensorMap map_e(const void* p, uint32_t rows, uint64_t total_rows = S_) {
  CUtensorMap m;
  cuuint64_t gd[2] = {D_, total_rows}; cuuint64_t gs[1] = {D_ * 2};
  cuuint32_t bx[2] = {80, rows}; cuuint32_t es[2] = {1, 1};
  g_enc(&m, CU_TENSOR_MAP_DATA_TYPE_BFLOAT16, 2, const_cast<void*>(p), gd, gs, bx, es, CU_TENSOR_MAP_INTERLEAVE_NONE,
        CU_TENSOR_MAP_SWIZZLE_NONE, CU_TENSOR_MAP_L2_PROMOTION_L2_256B, CU_TENSOR_MAP_FLOAT_OOB_FILL_NONE);
  return m;
}

template <typename... KArgs, typename... Args>
static void launch(void (*kern)(KArgs...), dim3 grid, dim3 block, int smem, bool pdl, Args... args) {
  cudaLaunchConfig_t cfg = {};
  cfg.gridDim = grid; cfg.blockDim = block; cfg.dynamicSmemBytes = smem; cfg.stream = cudaStreamPerThread;
  cudaLaunchAttribute at[1];
  at[0].id = cudaLaunchAttributeProgrammaticStreamSerialization;
  at[0].val.programmaticStreamSerializationAllowed = 1;
  cfg.attrs = at; cfg.numAttrs = pdl ? 1 : 0;
  cudaLaunchKernelEx(&cfg, kern, KArgs(args)...);
}

extern "C" void kernel_launch(void* const* d_in, const int* in_sizes, int n_in, void* d_out, int out_size) {
  const bf16* x = (const bf16*)d_in[0];
  const bf16* kc = (const bf16*)d_in[1];
  const bf16* vc = (const bf16*)d_in[2];
  const bf16* wq = (const bf16*)d_in[3];
  const bf16* wo = (const bf16*)d_in[4];
  const bf16* w1 = (const bf16*)d_in[6];
  const bf16* w2 = (const bf16*)d_in[7];
  const bf16* w3 = (const bf16*)d_in[8];
  const bf16* w4 = (const bf16*)d_in[9];
  const bf16* c = (const bf16*)d_in[10];
  const bf16* wmod = (const bf16*)d_in[11];
  bf16* out = (bf16*)d_out;

  static void *p_h, *p_o, *p_xa, *p_us, *p_x1, *p_g, *p_w1t, *p_w2t, *p_w4t;
  if (!g_enc) {
    void* fn = nullptr; cudaDriverEntryPointQueryResult qr;
    cudaGetDriverEntryPoint("cuTensorMapEncodeTiled", &fn, cudaEnableDefault, &qr);
    g_enc = (EncFn)fn;
    cudaGetSymbolAddress(&p_h, g_h); cudaGetSymbolAddress(&p_o, g_o); cudaGetSymbolAddress(&p_xa, g_xa);
    cudaGetSymbolAddress(&p_us, g_us); cudaGetSymbolAddress(&p_x1, g_x1); cudaGetSymbolAddress(&p_g, g_g);
    cudaGetSymbolAddress(&p_w1t, g_w1t); cudaGetSymbolAddress(&p_w2t, g_w2t); cudaGetSymbolAddress(&p_w4t, g_w4t);
    cudaFuncSetAttribute(fused_kernel, cudaFuncAttributeMaxDynamicSharedMemorySize, T_SMEM);
  }
  Maps tm;
  tm.h = map2d(p_h, S_, D_, 128);
  tm.wq = map3d(wq, D_, HD_, 64, 3);
  tm.k = map3d(kc, (uint64_t)H_ * S_, DH_, 64, 3);
  tm.v = map3d(vc, (uint64_t)H_ * S_, DH_, 64, 3);
  tm.o = map2d(p_o, S_, HD_, 128);
  tm.so = map2d(p_o, S_, HD_, 64);
  tm.wo3 = map3d(wo, HD_, D_, 64, 3);
  tm.wo2 = map3d(wo, HD_, D_, 64, 2);
  tm.xa = map2d(p_xa, S_, D_, 64);
  tm.w1t = map3d(p_w1t, D_, D_, 80, 2);
  tm.us = map2d((const bf16*)p_us + 2 * D_, S_, D_, 64);
  tm.w2t = map3d(p_w2t, D_, D_, 80, 2);
  tm.x1 = map2d(p_x1, S_, D_, 64);
  tm.w3 = map3d(w3, D_, F_, 64, 3);
  tm.g = map2d(p_g, S_, F_, 64);
  tm.w4t = map3d(p_w4t, D_, F_, 80, 2);
  tm.ex = map_e(x, 128);
  tm.sxa = map_e(p_xa, 64); tm.sus = map_e(p_us, 64, S_ + 4); tm.sx1 = map_e(p_x1, 64); tm.sout = map_e(out, 64);
  PfList pf;
  pf.p[0] = (const uint8_t*)wo; pf.p[1] = (const uint8_t*)w3; pf.p[2] = (const uint8_t*)p_w4t;
  pf.p[3] = (const uint8_t*)x; pf.p[4] = (const uint8_t*)p_w1t; pf.p[5] = (const uint8_t*)p_w2t;

  launch(mod_kernel, dim3(80), dim3(256), 0, false, c, wmod);
  launch(ln1_kernel, dim3(256), dim3(256), 0, true, x);
  launch(fused_kernel, dim3(128), dim3(384), T_SMEM, true, tm, pf, PrepW{w1, w2, w3, w4, c, wmod}, x, out);
}
```

```cpp
#include <cuda_runtime.h>
#include <cuda.h>
#include <cuda_bf16.h>
#include <stdint.h>

typedef __nv_bfloat16 bf16;

constexpr int S_  = 2048;
constexpr int D_  = 640;
constexpr int H_  = 32;
constexpr int DH_ = 192;
constexpr int HD_ = H_ * DH_;
constexpr int F_  = 1536;
constexpr float LN_EPS = 1e-5f;

__device__ __forceinline__ uint32_t smem_u32(const void* p) { return (uint32_t)__cvta_generic_to_shared(p); }
__device__ __forceinline__ void mbar_init(uint32_t a, uint32_t c) { asm volatile("mbarrier.init.shared::cta.b64 [%0], %1;" :: "r"(a), "r"(c) : "memory"); }
__device__ __forceinline__ void mbar_arrive(uint32_t a) { asm volatile("mbarrier.arrive.shared::cta.b64 _, [%0];" :: "r"(a) : "memory"); }
__device__ __forceinline__ void mbar_arrive_remote(uint32_t ra) { asm volatile("mbarrier.arrive.shared::cluster.b64 _, [%0];" :: "r"(ra) : "memory"); }
__device__ __forceinline__ uint32_t mapa(uint32_t a, uint32_t cta) { uint32_t r; asm volatile("mapa.shared::cluster.u32 %0, %1, %2;" : "=r"(r) : "r"(a), "r"(cta)); return r; }
__device__ __forceinline__ uint32_t mbar_try(uint32_t a, uint32_t ph) {
  uint32_t ok;
  asm volatile("{\n.reg .pred p;\nmbarrier.test_wait.parity.shared::cta.b64 p, [%1], %2;\nselp.u32 %0, 1, 0, p;\n}\n" : "=r"(ok) : "r"(a), "r"(ph) : "memory");
  return ok;
}
__device__ __forceinline__ void mbar_wait(uint32_t a, uint32_t ph) {
  asm volatile(
      "{\n.reg .pred p;\n.reg .u32 n;\n"
      "mov.u32 n, 0;\n"
      "SPIN:\n"
      "mbarrier.try_wait.parity.shared::cta.b64 p, [%0], %1;\n"
      "@p bra DONE;\n"
      "add.u32 n, n, 1;\n"
      "setp.le.u32 p, n, 16777216;\n"
      "@p bra SPIN;\n"
      "trap;\n"
      "DONE:\n}\n" :: "r"(a), "r"(ph) : "memory");
}
#define ELECT_ "{\n.reg .pred p;\nelect.sync _|p, 0xffffffff;\n@p "
__device__ __forceinline__ void mbar_expect_e(uint32_t a, uint32_t b) { asm volatile(ELECT_ "mbarrier.arrive.expect_tx.shared::cta.b64 _, [%0], %1;\n}\n" :: "r"(a), "r"(b) : "memory"); }
__device__ __forceinline__ void tma2d(uint32_t dst, const CUtensorMap* m, uint32_t bar, int c0, int c1) {
  asm volatile(ELECT_ "cp.async.bulk.tensor.2d.shared::cluster.global.mbarrier::complete_tx::bytes [%0], [%1, {%3, %4}], [%2];\n}\n"
               :: "r"(dst), "l"(m), "r"(bar), "r"(c0), "r"(c1) : "memory");
}
__device__ __forceinline__ void tma2d_mc(uint32_t dst, const CUtensorMap* m, uint32_t bar, int c0, int c1, uint16_t mask) {
  asm volatile(ELECT_ "cp.async.bulk.tensor.2d.shared::cluster.global.mbarrier::complete_tx::bytes.multicast::cluster [%0], [%1, {%3, %4}], [%2], %5;\n}\n"
               :: "r"(dst), "l"(m), "r"(bar), "r"(c0), "r"(c1), "h"(mask) : "memory");
}
__device__ __forceinline__ void tma3d(uint32_t dst, const CUtensorMap* m, uint32_t bar, int c0, int c1, int c2) {
  asm volatile(ELECT_ "cp.async.bulk.tensor.3d.shared::cluster.global.mbarrier::complete_tx::bytes [%0], [%1, {%3, %4, %5}], [%2];\n}\n"
               :: "r"(dst), "l"(m), "r"(bar), "r"(c0), "r"(c1), "r"(c2) : "memory");
}
__device__ __forceinline__ void tma3d_mc(uint32_t dst, const CUtensorMap* m, uint32_t bar, int c0, int c1, int c2, uint16_t mask) {
  asm volatile(ELECT_ "cp.async.bulk.tensor.3d.shared::cluster.global.mbarrier::complete_tx::bytes.multicast::cluster [%0], [%1, {%3, %4, %5}], [%2], %6;\n}\n"
               :: "r"(dst), "l"(m), "r"(bar), "r"(c0), "r"(c1), "r"(c2), "h"(mask) : "memory");
}
__device__ __forceinline__ void tma3d_mc_hint(uint32_t dst, const CUtensorMap* m, uint32_t bar, int c0, int c1, int c2, uint16_t mask, uint64_t pol) {
  asm volatile(ELECT_ "cp.async.bulk.tensor.3d.shared::cluster.global.mbarrier::complete_tx::bytes.multicast::cluster.L2::cache_hint [%0], [%1, {%3, %4, %5}], [%2], %6, %7;\n}\n"
               :: "r"(dst), "l"(m), "r"(bar), "r"(c0), "r"(c1), "r"(c2), "h"(mask), "l"(pol) : "memory");
}
__device__ __forceinline__ void bulk_load(uint32_t dst, const void* src, uint32_t bytes, uint32_t bar) {
  asm volatile(ELECT_ "cp.async.bulk.shared::cluster.global.mbarrier::complete_tx::bytes [%0], [%1], %2, [%3];\n}\n"
               :: "r"(dst), "l"(src), "r"(bytes), "r"(bar) : "memory");
}
__device__ __forceinline__ void l2_prefetch_t3d(const CUtensorMap* m, int c0, int c1, int c2) {
  asm volatile(ELECT_ "cp.async.bulk.prefetch.tensor.3d.L2.global [%0, {%1, %2, %3}];\n}\n" :: "l"(m), "r"(c0), "r"(c1), "r"(c2) : "memory");
}
__device__ __forceinline__ void stg128(void* p, uint4 v) {
  asm volatile("st.global.v4.u32 [%0], {%1, %2, %3, %4};" :: "l"(p), "r"(v.x), "r"(v.y), "r"(v.z), "r"(v.w) : "memory");
}
__device__ __forceinline__ void prefetch_tmap(const CUtensorMap* m) { asm volatile("prefetch.tensormap [%0];" :: "l"(m) : "memory"); }
__device__ __forceinline__ void wg_fence() { asm volatile("wgmma.fence.sync.aligned;" ::: "memory"); }
__device__ __forceinline__ void wg_commit() { asm volatile("wgmma.commit_group.sync.aligned;" ::: "memory"); }
template <int N> __device__ __forceinline__ void wg_wait() { asm volatile("wgmma.wait_group.sync.aligned %0;" :: "n"(N) : "memory"); }
template <int N> __device__ __forceinline__ void fence_regs(float (&r)[N]) {
#pragma unroll
  for (int i = 0; i < N; i++) asm volatile("" : "+f"(r[i]) :: "memory");
}
template <int N> __device__ __forceinline__ void fence_regs(uint32_t (&r)[N]) {
#pragma unroll
  for (int i = 0; i < N; i++) asm volatile("" : "+r"(r[i]) :: "memory");
}
__device__ __forceinline__ uint64_t mkdesc(uint32_t addr, uint32_t lbo, uint32_t sbo) {
  return (uint64_t)((addr & 0x3FFFF) >> 4) | ((uint64_t)(lbo >> 4) << 16) | ((uint64_t)(sbo >> 4) << 32) | (1ull << 62);
}
__device__ __forceinline__ void bar_sync(int id, int n) { asm volatile("bar.sync %0, %1;" :: "r"(id), "r"(n) : "memory"); }
__device__ __forceinline__ void bar_arrive(int id, int n) { asm volatile("bar.arrive %0, %1;" :: "r"(id), "r"(n) : "memory"); }
__device__ __forceinline__ void cluster_sync() { asm volatile("barrier.cluster.arrive.aligned;\nbarrier.cluster.wait.aligned;" ::: "memory"); }
__device__ __forceinline__ void pdl_wait() { asm volatile("griddepcontrol.wait;" ::: "memory"); }
__device__ __forceinline__ void pdl_launch() { asm volatile("griddepcontrol.launch_dependents;" ::: "memory"); }
__device__ __forceinline__ float ex2(float x) { float y; asm("ex2.approx.ftz.f32 %0, %1;" : "=f"(y) : "f"(x)); return y; }
__device__ __forceinline__ uint32_t pack_bf16(float lo, float hi) { uint32_t r; asm("cvt.rn.bf16x2.f32 %0, %1, %2;" : "=r"(r) : "f"(hi), "f"(lo)); return r; }
__device__ __forceinline__ float bf_lo(uint32_t u) { return __uint_as_float(u << 16); }
__device__ __forceinline__ float bf_hi(uint32_t u) { return __uint_as_float(u & 0xffff0000u); }
__device__ __forceinline__ float bf_round(float x) { return __bfloat162float(__float2bfloat16_rn(x)); }
__device__ __forceinline__ float tanh_fast(float x) { float y; asm("tanh.approx.f32 %0, %1;" : "=f"(y) : "f"(x)); return y; }
__device__ __forceinline__ float gelu_tanh(float x) {
  float u = x * (0.7978845608028654f + 0.035677408136300125f * x * x);
  float hx = 0.5f * x;
  return fmaf(hx, tanh_fast(u), hx);
}
__device__ __forceinline__ float warp_sum(float v) {
#pragma unroll
  for (int o = 16; o > 0; o >>= 1) v += __shfl_xor_sync(0xffffffffu, v, o);
  return v;
}
__device__ __forceinline__ void quad_transpose(uint32_t& v0, uint32_t& v1, uint32_t& v2, uint32_t& v3, int lane) {
  const bool b0 = lane & 1, b1 = lane & 2;
  uint32_t s0 = b0 ? v0 : v1, s1 = b0 ? v2 : v3;
  s0 = __shfl_xor_sync(0xffffffffu, s0, 1); s1 = __shfl_xor_sync(0xffffffffu, s1, 1);
  if (b0) { v0 = s0; v2 = s1; } else { v1 = s0; v3 = s1; }
  uint32_t t0 = b1 ? v0 : v2, t1 = b1 ? v1 : v3;
  t0 = __shfl_xor_sync(0xffffffffu, t0, 2); t1 = __shfl_xor_sync(0xffffffffu, t1, 2);
  if (b1) { v0 = t0; v1 = t1; } else { v2 = t0; v3 = t1; }
}


template<int TB> __device__ __forceinline__ void wgmma_rs_n64(float (&d)[32], uint32_t a0, uint32_t a1, uint32_t a2, uint32_t a3, uint64_t db, int scale_d) {
  asm volatile("{\n.reg .pred p;\nsetp.ne.b32 p, %37, 0;\n"
    "wgmma.mma_async.sync.aligned.m64n64k16.f32.bf16.bf16 {%0, %1, %2, %3, %4, %5, %6, %7, %8, %9, %10, %11, %12, %13, %14, %15, %16, %17, %18, %19, %20, %21, %22, %23, %24, %25, %26, %27, %28, %29, %30, %31}, {%32, %33, %34, %35}, %36, p, 1, 1, %38;\n}\n"
    : "+f"(d[0]), "+f"(d[1]), "+f"(d[2]), "+f"(d[3]), "+f"(d[4]), "+f"(d[5]), "+f"(d[6]), "+f"(d[7]), "+f"(d[8]), "+f"(d[9]), "+f"(d[10]), "+f"(d[11]), "+f"(d[12]), "+f"(d[13]), "+f"(d[14]), "+f"(d[15]), "+f"(d[16]), "+f"(d[17]), "+f"(d[18]), "+f"(d[19]), "+f"(d[20]), "+f"(d[21]), "+f"(d[22]), "+f"(d[23]), "+f"(d[24]), "+f"(d[25]), "+f"(d[26]), "+f"(d[27]), "+f"(d[28]), "+f"(d[29]), "+f"(d[30]), "+f"(d[31])
    : "r"(a0), "r"(a1), "r"(a2), "r"(a3), "l"(db), "r"(scale_d), "n"(TB));
}
template<int TB> __device__ __forceinline__ void wgmma_rs_n192(float (&d)[96], uint32_t a0, uint32_t a1, uint32_t a2, uint32_t a3, uint64_t db, int scale_d) {
  asm volatile("{\n.reg .pred p;\nsetp.ne.b32 p, %101, 0;\n"
    "wgmma.mma_async.sync.aligned.m64n192k16.f32.bf16.bf16 {%0, %1, %2, %3, %4, %5, %6, %7, %8, %9, %10, %11, %12, %13, %14, %15, %16, %17, %18, %19, %20, %21, %22, %23, %24, %25, %26, %27, %28, %29, %30, %31, %32, %33, %34, %35, %36, %37, %38, %39, %40, %41, %42, %43, %44, %45, %46, %47, %48, %49, %50, %51, %52, %53, %54, %55, %56, %57, %58, %59, %60, %61, %62, %63, %64, %65, %66, %67, %68, %69, %70, %71, %72, %73, %74, %75, %76, %77, %78, %79, %80, %81, %82, %83, %84, %85, %86, %87, %88, %89, %90, %91, %92, %93, %94, %95}, {%96, %97, %98, %99}, %100, p, 1, 1, %102;\n}\n"
    : "+f"(d[0]), "+f"(d[1]), "+f"(d[2]), "+f"(d[3]), "+f"(d[4]), "+f"(d[5]), "+f"(d[6]), "+f"(d[7]), "+f"(d[8]), "+f"(d[9]), "+f"(d[10]), "+f"(d[11]), "+f"(d[12]), "+f"(d[13]), "+f"(d[14]), "+f"(d[15]), "+f"(d[16]), "+f"(d[17]), "+f"(d[18]), "+f"(d[19]), "+f"(d[20]), "+f"(d[21]), "+f"(d[22]), "+f"(d[23]), "+f"(d[24]), "+f"(d[25]), "+f"(d[26]), "+f"(d[27]), "+f"(d[28]), "+f"(d[29]), "+f"(d[30]), "+f"(d[31]), "+f"(d[32]), "+f"(d[33]), "+f"(d[34]), "+f"(d[35]), "+f"(d[36]), "+f"(d[37]), "+f"(d[38]), "+f"(d[39]), "+f"(d[40]), "+f"(d[41]), "+f"(d[42]), "+f"(d[43]), "+f"(d[44]), "+f"(d[45]), "+f"(d[46]), "+f"(d[47]), "+f"(d[48]), "+f"(d[49]), "+f"(d[50]), "+f"(d[51]), "+f"(d[52]), "+f"(d[53]), "+f"(d[54]), "+f"(d[55]), "+f"(d[56]), "+f"(d[57]), "+f"(d[58]), "+f"(d[59]), "+f"(d[60]), "+f"(d[61]), "+f"(d[62]), "+f"(d[63]), "+f"(d[64]), "+f"(d[65]), "+f"(d[66]), "+f"(d[67]), "+f"(d[68]), "+f"(d[69]), "+f"(d[70]), "+f"(d[71]), "+f"(d[72]), "+f"(d[73]), "+f"(d[74]), "+f"(d[75]), "+f"(d[76]), "+f"(d[77]), "+f"(d[78]), "+f"(d[79]), "+f"(d[80]), "+f"(d[81]), "+f"(d[82]), "+f"(d[83]), "+f"(d[84]), "+f"(d[85]), "+f"(d[86]), "+f"(d[87]), "+f"(d[88]), "+f"(d[89]), "+f"(d[90]), "+f"(d[91]), "+f"(d[92]), "+f"(d[93]), "+f"(d[94]), "+f"(d[95])
    : "r"(a0), "r"(a1), "r"(a2), "r"(a3), "l"(db), "r"(scale_d), "n"(TB));
}
template<int TB> __device__ __forceinline__ void wgmma_rs_n128(float (&d)[64], uint32_t a0, uint32_t a1, uint32_t a2, uint32_t a3, uint64_t db, int scale_d) {
  asm volatile("{\n.reg .pred p;\nsetp.ne.b32 p, %69, 0;\n"
    "wgmma.mma_async.sync.aligned.m64n128k16.f32.bf16.bf16 {%0, %1, %2, %3, %4, %5, %6, %7, %8, %9, %10, %11, %12, %13, %14, %15, %16, %17, %18, %19, %20, %21, %22, %23, %24, %25, %26, %27, %28, %29, %30, %31, %32, %33, %34, %35, %36, %37, %38, %39, %40, %41, %42, %43, %44, %45, %46, %47, %48, %49, %50, %51, %52, %53, %54, %55, %56, %57, %58, %59, %60, %61, %62, %63}, {%64, %65, %66, %67}, %68, p, 1, 1, %70;\n}\n"
    : "+f"(d[0]), "+f"(d[1]), "+f"(d[2]), "+f"(d[3]), "+f"(d[4]), "+f"(d[5]), "+f"(d[6]), "+f"(d[7]), "+f"(d[8]), "+f"(d[9]), "+f"(d[10]), "+f"(d[11]), "+f"(d[12]), "+f"(d[13]), "+f"(d[14]), "+f"(d[15]), "+f"(d[16]), "+f"(d[17]), "+f"(d[18]), "+f"(d[19]), "+f"(d[20]), "+f"(d[21]), "+f"(d[22]), "+f"(d[23]), "+f"(d[24]), "+f"(d[25]), "+f"(d[26]), "+f"(d[27]), "+f"(d[28]), "+f"(d[29]), "+f"(d[30]), "+f"(d[31]), "+f"(d[32]), "+f"(d[33]), "+f"(d[34]), "+f"(d[35]), "+f"(d[36]), "+f"(d[37]), "+f"(d[38]), "+f"(d[39]), "+f"(d[40]), "+f"(d[41]), "+f"(d[42]), "+f"(d[43]), "+f"(d[44]), "+f"(d[45]), "+f"(d[46]), "+f"(d[47]), "+f"(d[48]), "+f"(d[49]), "+f"(d[50]), "+f"(d[51]), "+f"(d[52]), "+f"(d[53]), "+f"(d[54]), "+f"(d[55]), "+f"(d[56]), "+f"(d[57]), "+f"(d[58]), "+f"(d[59]), "+f"(d[60]), "+f"(d[61]), "+f"(d[62]), "+f"(d[63])
    : "r"(a0), "r"(a1), "r"(a2), "r"(a3), "l"(db), "r"(scale_d), "n"(TB));
}
template<int TB> __device__ __forceinline__ void wgmma_ss_n80(float (&d)[40], uint64_t da, uint64_t db, int scale_d) {
  asm volatile("{\n.reg .pred p;\nsetp.ne.b32 p, %42, 0;\n"
    "wgmma.mma_async.sync.aligned.m64n80k16.f32.bf16.bf16 {%0, %1, %2, %3, %4, %5, %6, %7, %8, %9, %10, %11, %12, %13, %14, %15, %16, %17, %18, %19, %20, %21, %22, %23, %24, %25, %26, %27, %28, %29, %30, %31, %32, %33, %34, %35, %36, %37, %38, %39}, %40, %41, p, 1, 1, 0, %43;\n}\n"
    : "+f"(d[0]), "+f"(d[1]), "+f"(d[2]), "+f"(d[3]), "+f"(d[4]), "+f"(d[5]), "+f"(d[6]), "+f"(d[7]), "+f"(d[8]), "+f"(d[9]), "+f"(d[10]), "+f"(d[11]), "+f"(d[12]), "+f"(d[13]), "+f"(d[14]), "+f"(d[15]), "+f"(d[16]), "+f"(d[17]), "+f"(d[18]), "+f"(d[19]), "+f"(d[20]), "+f"(d[21]), "+f"(d[22]), "+f"(d[23]), "+f"(d[24]), "+f"(d[25]), "+f"(d[26]), "+f"(d[27]), "+f"(d[28]), "+f"(d[29]), "+f"(d[30]), "+f"(d[31]), "+f"(d[32]), "+f"(d[33]), "+f"(d[34]), "+f"(d[35]), "+f"(d[36]), "+f"(d[37]), "+f"(d[38]), "+f"(d[39])
    : "l"(da), "l"(db), "r"(scale_d), "n"(TB));
}
template<int TB> __device__ __forceinline__ void wgmma_ss_n192(float (&d)[96], uint64_t da, uint64_t db, int scale_d) {
  asm volatile("{\n.reg .pred p;\nsetp.ne.b32 p, %98, 0;\n"
    "wgmma.mma_async.sync.aligned.m64n192k16.f32.bf16.bf16 {%0, %1, %2, %3, %4, %5, %6, %7, %8, %9, %10, %11, %12, %13, %14, %15, %16, %17, %18, %19, %20, %21, %22, %23, %24, %25, %26, %27, %28, %29, %30, %31, %32, %33, %34, %35, %36, %37, %38, %39, %40, %41, %42, %43, %44, %45, %46, %47, %48, %49, %50, %51, %52, %53, %54, %55, %56, %57, %58, %59, %60, %61, %62, %63, %64, %65, %66, %67, %68, %69, %70, %71, %72, %73, %74, %75, %76, %77, %78, %79, %80, %81, %82, %83, %84, %85, %86, %87, %88, %89, %90, %91, %92, %93, %94, %95}, %96, %97, p, 1, 1, 0, %99;\n}\n"
    : "+f"(d[0]), "+f"(d[1]), "+f"(d[2]), "+f"(d[3]), "+f"(d[4]), "+f"(d[5]), "+f"(d[6]), "+f"(d[7]), "+f"(d[8]), "+f"(d[9]), "+f"(d[10]), "+f"(d[11]), "+f"(d[12]), "+f"(d[13]), "+f"(d[14]), "+f"(d[15]), "+f"(d[16]), "+f"(d[17]), "+f"(d[18]), "+f"(d[19]), "+f"(d[20]), "+f"(d[21]), "+f"(d[22]), "+f"(d[23]), "+f"(d[24]), "+f"(d[25]), "+f"(d[26]), "+f"(d[27]), "+f"(d[28]), "+f"(d[29]), "+f"(d[30]), "+f"(d[31]), "+f"(d[32]), "+f"(d[33]), "+f"(d[34]), "+f"(d[35]), "+f"(d[36]), "+f"(d[37]), "+f"(d[38]), "+f"(d[39]), "+f"(d[40]), "+f"(d[41]), "+f"(d[42]), "+f"(d[43]), "+f"(d[44]), "+f"(d[45]), "+f"(d[46]), "+f"(d[47]), "+f"(d[48]), "+f"(d[49]), "+f"(d[50]), "+f"(d[51]), "+f"(d[52]), "+f"(d[53]), "+f"(d[54]), "+f"(d[55]), "+f"(d[56]), "+f"(d[57]), "+f"(d[58]), "+f"(d[59]), "+f"(d[60]), "+f"(d[61]), "+f"(d[62]), "+f"(d[63]), "+f"(d[64]), "+f"(d[65]), "+f"(d[66]), "+f"(d[67]), "+f"(d[68]), "+f"(d[69]), "+f"(d[70]), "+f"(d[71]), "+f"(d[72]), "+f"(d[73]), "+f"(d[74]), "+f"(d[75]), "+f"(d[76]), "+f"(d[77]), "+f"(d[78]), "+f"(d[79]), "+f"(d[80]), "+f"(d[81]), "+f"(d[82]), "+f"(d[83]), "+f"(d[84]), "+f"(d[85]), "+f"(d[86]), "+f"(d[87]), "+f"(d[88]), "+f"(d[89]), "+f"(d[90]), "+f"(d[91]), "+f"(d[92]), "+f"(d[93]), "+f"(d[94]), "+f"(d[95])
    : "l"(da), "l"(db), "r"(scale_d), "n"(TB));
}


__device__ __align__(128) float g_mod[6 * D_];
__device__ __align__(128) float g_modp[2][2 * D_];
__device__ __align__(1024) bf16 g_h[S_ * D_];
__device__ __align__(1024) bf16 g_o[S_ * HD_];
__device__ __align__(1024) bf16 g_xch[16 * 2 * 4 * 4 * 128 * 80];
__device__ __align__(1024) bf16 g_w1t[D_ * D_];
__device__ __align__(1024) bf16 g_w2t[D_ * D_];
__device__ __align__(1024) bf16 g_w4t[D_ * F_];
__device__ __align__(32) float g_st1[S_ * 8];
__device__ __align__(32) float g_st2[S_ * 2];
__device__ __align__(32) float g_vec[3 * D_ + F_ + 8];
__device__ unsigned g_flag[1024];
enum { F_XCH = 0, F_XA = 256, F_US = 288, F_X1 = 320, F_G = 352, F_PREP = 384, F_MOD2 = 416, F_ST1 = 448, F_ST2 = 480, F_O = 512 };
__device__ __align__(1024) bf16 g_xa[S_ * D_];
__device__ __align__(1024) bf16 g_us[(S_ + 4) * D_];
__device__ __align__(1024) bf16 g_x1[S_ * D_];
__device__ __align__(1024) bf16 g_g[S_ * F_];

__device__ __forceinline__ void row_stats(const float (&v)[20], float& mean, float& rstd) {
  float s = 0.f;
#pragma unroll
  for (int i = 0; i < 20; i++) s += v[i];
  mean = warp_sum(s) * (1.f / D_);
  float q = 0.f;
#pragma unroll
  for (int i = 0; i < 20; i++) { float d = v[i] - mean; q = fmaf(d, d, q); }
  rstd = rsqrtf(warp_sum(q) * (1.f / D_) + LN_EPS);
}
__device__ __forceinline__ void load_row_bf16(const bf16* p, int lane, float (&v)[20]) {
#pragma unroll
  for (int i = 0; i < 5; i++) {
    uint2 u = *reinterpret_cast<const uint2*>(p + (lane + 32 * i) * 4);
    v[4 * i] = bf_lo(u.x); v[4 * i + 1] = bf_hi(u.x); v[4 * i + 2] = bf_lo(u.y); v[4 * i + 3] = bf_hi(u.y);
  }
}
__device__ __forceinline__ void store_row_bf16(bf16* p, int lane, const float (&v)[20]) {
#pragma unroll
  for (int i = 0; i < 5; i++) {
    uint2 u; u.x = pack_bf16(v[4 * i], v[4 * i + 1]); u.y = pack_bf16(v[4 * i + 2], v[4 * i + 3]);
    *reinterpret_cast<uint2*>(p + (lane + 32 * i) * 4) = u;
  }
}
__device__ __forceinline__ void load_row_f32(const float* p, int lane, float (&v)[20]) {
#pragma unroll
  for (int i = 0; i < 5; i++) {
    float4 u = *reinterpret_cast<const float4*>(p + (lane + 32 * i) * 4);
    v[4 * i] = u.x; v[4 * i + 1] = u.y; v[4 * i + 2] = u.z; v[4 * i + 3] = u.w;
  }
}

__device__ __forceinline__ float silu_bf(float c) { return bf_round(__fdividef(c, 1.f + __expf(-c))); }
__device__ __forceinline__ void fma8(float (&acc)[8], float s, const uint4& w) {
  acc[0] = fmaf(s, bf_lo(w.x), acc[0]); acc[1] = fmaf(s, bf_hi(w.x), acc[1]); acc[2] = fmaf(s, bf_lo(w.y), acc[2]); acc[3] = fmaf(s, bf_hi(w.y), acc[3]);
  acc[4] = fmaf(s, bf_lo(w.z), acc[4]); acc[5] = fmaf(s, bf_hi(w.z), acc[5]); acc[6] = fmaf(s, bf_lo(w.w), acc[6]); acc[7] = fmaf(s, bf_hi(w.w), acc[7]);
}
__global__ void __launch_bounds__(256) mod_kernel(const bf16* __restrict__ c, const bf16* __restrict__ w_mod) {
  pdl_launch();
  __shared__ float red[8][32];
  const int t = threadIdx.x, cg = t & 3, r0 = (blockIdx.x / 40) * 320 + (t >> 2), strip = blockIdx.x % 40;
  uint4 w[5];
  float cv[5];
#pragma unroll
  for (int i = 0; i < 5; i++) {
    w[i] = __ldg(reinterpret_cast<const uint4*>(w_mod + (size_t)(r0 + 64 * i) * (6 * D_) + strip * 32 + cg * 8));
    cv[i] = __bfloat162float(c[r0 + 64 * i]);
  }
  if (blockIdx.x < 14) { const int i = blockIdx.x * 256 + t; if (i < 3 * D_ + F_) g_vec[i] = 0.f; }
  else if (blockIdx.x < 18) g_flag[(blockIdx.x - 14) * 256 + t] = 0u;
  float acc[8];
#pragma unroll
  for (int j = 0; j < 8; j++) acc[j] = 0.f;
#pragma unroll
  for (int i = 0; i < 5; i++) fma8(acc, silu_bf(cv[i]), w[i]);
#pragma unroll 1
  for (int o = 4; o < 32; o <<= 1) {
#pragma unroll
    for (int j = 0; j < 8; j++) acc[j] += __shfl_xor_sync(0xffffffffu, acc[j], o);
  }
  if ((t & 31) < 4) {
    *reinterpret_cast<float4*>(&red[t >> 5][cg * 8]) = make_float4(acc[0], acc[1], acc[2], acc[3]);
    *reinterpret_cast<float4*>(&red[t >> 5][cg * 8 + 4]) = make_float4(acc[4], acc[5], acc[6], acc[7]);
  }
  __syncthreads();
  if (t < 32) {
    float s = 0.f;
#pragma unroll
    for (int w8 = 0; w8 < 8; w8++) s += red[w8][t];
    g_modp[blockIdx.x / 40][strip * 32 + t] = s;
  }
}

__global__ void __launch_bounds__(256) ln1_kernel(const bf16* __restrict__ x) {
  pdl_launch();
  const int lane = threadIdx.x & 31, row = blockIdx.x * 8 + (threadIdx.x >> 5);
  float v[20];
  load_row_bf16(x + (size_t)row * D_, lane, v);
  float mean, rstd;
  row_stats(v, mean, rstd);
  if (lane < 8) g_st1[row * 8 + lane] = 0.f;
  if (lane < 2) g_st2[row * 2 + lane] = 0.f;
  pdl_wait();
  float s0[20], s1[20], c0[20], c1[20];
  load_row_f32(g_modp[0], lane, s0); load_row_f32(g_modp[1], lane, s1);
  load_row_f32(g_modp[0] + D_, lane, c0); load_row_f32(g_modp[1] + D_, lane, c1);
#pragma unroll
  for (int i = 0; i < 20; i++) v[i] = fmaf((v[i] - mean) * rstd, bf_round(1.f + bf_round(c0[i] + c1[i])), bf_round(s0[i] + s1[i]));
  store_row_bf16(g_h + (size_t)row * D_, lane, v);
}

__device__ __forceinline__ uint4 ldg_na(const void* p) {
  uint4 v;
  asm volatile("ld.global.nc.L1::no_allocate.L2::128B.v4.u32 {%0, %1, %2, %3}, [%4];" : "=r"(v.x), "=r"(v.y), "=r"(v.z), "=r"(v.w) : "l"(p));
  return v;
}
struct PrepW { const bf16 *w1, *w2, *w3, *w4, *c, *wmod; };
__device__ __forceinline__ void flag_wait(const unsigned* p, unsigned target);
__device__ __forceinline__ void warp_publish(unsigned* f, int lane) {
  __syncwarp();
  if (lane == 0) {
    asm volatile("fence.acq_rel.gpu;" ::: "memory");
    asm volatile("red.relaxed.gpu.global.add.u32 [%0], 1;" :: "l"(f) : "memory");
  }
  __syncwarp();
}
__device__ __forceinline__ void prep_mod(const PrepW& pw, const float* sc, int lane, int job) {
  const bf16* wp = pw.wmod + (size_t)(lane >> 3) * (6 * D_) + 2 * D_ + job * 64 + (lane & 7) * 8;
  float acc[8];
#pragma unroll
  for (int j = 0; j < 8; j++) acc[j] = 0.f;
#pragma unroll 1
  for (int i = 0; i < 160; i += 20) {
    uint4 w[20];
#pragma unroll
    for (int e = 0; e < 20; e++) w[e] = ldg_na(wp + (size_t)(i + e) * 4 * (6 * D_));
#pragma unroll
    for (int e = 0; e < 20; e++) fma8(acc, sc[(i + e) * 4 + (lane >> 3)], w[e]);
  }
  const bool one = job >= 20 && job < 30;
#pragma unroll
  for (int j = 0; j < 8; j++) {
    acc[j] += __shfl_xor_sync(0xffffffffu, acc[j], 8); acc[j] += __shfl_xor_sync(0xffffffffu, acc[j], 16);
    const float v = bf_round(acc[j]);
    if (lane < 8) g_mod[2 * D_ + job * 64 + lane * 8 + j] = one ? bf_round(1.f + v) : v;
  }
  warp_publish(g_flag + F_MOD2, lane);
}
__device__ __forceinline__ void prep_cs3(const PrepW& pw, int lane, int job) {
  {
    const bf16* wp = pw.w3 + (size_t)((job / 24) * 128 + (lane >> 3)) * F_ + (job % 24) * 64 + (lane & 7) * 8;
    float acc[8];
#pragma unroll
    for (int j = 0; j < 8; j++) acc[j] = 0.f;
#pragma unroll 1
    for (int i = 0; i < 32; i += 16) {
      uint4 w[16];
#pragma unroll
      for (int e = 0; e < 16; e++) w[e] = ldg_na((wp + (size_t)(i + e) * 4 * F_));
#pragma unroll
      for (int e = 0; e < 16; e++) fma8(acc, 1.f, w[e]);
    }
#pragma unroll
    for (int j = 0; j < 8; j++) {
      acc[j] += __shfl_xor_sync(0xffffffffu, acc[j], 8); acc[j] += __shfl_xor_sync(0xffffffffu, acc[j], 16);
      if (lane < 8) atomicAdd(&g_vec[3 * D_ + (job % 24) * 64 + lane * 8 + j], acc[j]);
    }
  }
}
__device__ __forceinline__ const bf16* prep_src(const PrepW& pw, int job, int lane) {
  const bf16* src = job < 480 ? pw.w4 : job < 680 ? pw.w2 : pw.w1;
  const int jj = job < 480 ? job : job < 680 ? job - 480 : job - 680;
  return src + (size_t)((jj / 10) * 32 + (lane >> 3)) * D_ + (jj % 10) * 64 + (lane & 7) * 8;
}
__device__ __forceinline__ void prep_transpose(const PrepW& pw, bf16 (*tile)[72], int lane, int job0, int stride) {
  uint4 v[8];
#pragma unroll
  for (int i = 0; i < 8; i++) v[i] = ldg_na((prep_src(pw, job0, lane) + (size_t)i * 4 * D_));
#pragma unroll 1
  for (int job = job0; job < 880; job += stride) {
    bf16* dst; int ldd = D_, jj;
    if (job < 480) { dst = g_w4t; ldd = F_; jj = job; }
    else if (job < 680) { dst = g_w2t; jj = job - 480; }
    else { dst = g_w1t; jj = job - 680; flag_wait(g_flag + F_MOD2, 40); }
    const int kt = jj / 10, nt = jj % 10;
    __syncwarp();
#pragma unroll
    for (int i = 0; i < 8; i++) *reinterpret_cast<uint4*>(&tile[i * 4 + (lane >> 3)][(lane & 7) * 8]) = v[i];
    if (job + stride < 880) {
#pragma unroll
      for (int i = 0; i < 8; i++) v[i] = ldg_na((prep_src(pw, job + stride, lane) + (size_t)i * 4 * D_));
    }
    __syncwarp();
    float2 a[4], b[4];
    if (job >= 680) {
#pragma unroll
      for (int j = 0; j < 4; j++) {
        a[j] = __ldcg(reinterpret_cast<const float2*>(g_mod + 4 * D_ + kt * 32 + j * 8 + (lane & 3) * 2));
        b[j] = __ldcg(reinterpret_cast<const float2*>(g_mod + 3 * D_ + kt * 32 + j * 8 + (lane & 3) * 2));
      }
    }
    bf16* dp = dst + (size_t)(nt * 64 + (lane >> 2)) * ldd + kt * 32 + (lane & 3) * 8;
    const uint32_t la = smem_u32(&tile[lane][0]);
#pragma unroll 2
    for (int nb = 0; nb < 8; nb++) {
      uint32_t u[4];
      asm volatile("ldmatrix.sync.aligned.m8n8.x4.trans.shared.b16 {%0, %1, %2, %3}, [%4];" : "=r"(u[0]), "=r"(u[1]), "=r"(u[2]), "=r"(u[3]) : "r"(la + nb * 16) : "memory");
      if (job >= 680) {
        float sa = 0.f, sb = 0.f, sc = 0.f;
#pragma unroll
        for (int j = 0; j < 4; j++) {
          const float lo = bf_lo(u[j]), hi = bf_hi(u[j]);
          sc += lo + hi; sb = fmaf(b[j].x, lo, fmaf(b[j].y, hi, sb));
          u[j] = pack_bf16(a[j].x * lo, a[j].y * hi);
          sa += bf_lo(u[j]) + bf_hi(u[j]);
        }
        sa += __shfl_xor_sync(0xffffffffu, sa, 1); sb += __shfl_xor_sync(0xffffffffu, sb, 1); sc += __shfl_xor_sync(0xffffffffu, sc, 1);
        sa += __shfl_xor_sync(0xffffffffu, sa, 2); sb += __shfl_xor_sync(0xffffffffu, sb, 2); sc += __shfl_xor_sync(0xffffffffu, sc, 2);
        if ((lane & 3) < 3) atomicAdd(&g_vec[(lane & 3) * D_ + nt * 64 + nb * 8 + (lane >> 2)], (lane & 3) == 0 ? sa : (lane & 3) == 1 ? sb : sc);
      }
      quad_transpose(u[0], u[1], u[2], u[3], lane);
      stg128(dp + (size_t)nb * 8 * ldd, make_uint4(u[0], u[1], u[2], u[3]));
    }
  }
  warp_publish(g_flag + F_PREP, lane);
}

constexpr int A_NSLOT = 9;
constexpr int A_SLOT = 24576;
constexpr int A_NKV = S_ / 64;
constexpr int PREP_CTAS = 48;

struct Ring {
  uint32_t slot, phase;
  __device__ __forceinline__ void adv(int n) { if (++slot == (uint32_t)n) { slot = 0; phase ^= 1; } }
};
constexpr int T_PAR = A_NSLOT * A_SLOT + 448;
constexpr int T_PREP = T_PAR + 3712;
constexpr int T_SMEM = T_PREP + 32 * 72 * 2 + 1024;
enum { P_OGA = 0, P_OA = 80, P_OB = 160, P_VA = 240, P_VB = 320, P_VC = 400, P_A2 = 480, P_B2 = 560, P_GB = 640, P_CS3 = 720, P_SC = 912 };

__device__ __forceinline__ void flag_wait(const unsigned* p, unsigned target) {
  asm volatile(
      "{\n.reg .pred p;\n.reg .u32 n, v;\n"
      "mov.u32 n, 0;\n"
      "SPIN:\n"
      "ld.relaxed.gpu.global.u32 v, [%0];\n"
      "setp.ge.u32 p, v, %1;\n"
      "@p bra DONE;\n"
      "add.u32 n, n, 1;\n"
      "setp.gt.u32 p, n, 4194304;\n"
      "@p trap;\n"
      "bra SPIN;\n"
      "DONE:\n}\n" :: "l"(p), "r"(target) : "memory");
}
__device__ __forceinline__ void fence_async_global() { asm volatile("fence.proxy.async.global;" ::: "memory"); }
__device__ __forceinline__ float lds_f(uint32_t a) { float v; asm volatile("ld.shared.f32 %0, [%1];" : "=f"(v) : "r"(a)); return v; }

__device__ __forceinline__ void sts_f2(uint32_t a, float x, float y) { asm volatile("st.shared.v2.f32 [%0], {%1, %2};" :: "r"(a), "f"(x), "f"(y) : "memory"); }
__device__ __forceinline__ void sts_u4(uint32_t a, uint4 v) { asm volatile("st.shared.v4.u32 [%0], {%1, %2, %3, %4};" :: "r"(a), "r"(v.x), "r"(v.y), "r"(v.z), "r"(v.w) : "memory"); }
__device__ __forceinline__ void fence_async_smem() { asm volatile("fence.proxy.async.shared::cta;" ::: "memory"); }
__device__ __forceinline__ void bulk_store(void* dst, uint32_t src, uint32_t bytes) {
  asm volatile("cp.async.bulk.global.shared::cta.bulk_group [%0], [%1], %2;" :: "l"(dst), "r"(src), "r"(bytes) : "memory");
}
__device__ __forceinline__ void bulk_red_f32(void* dst, uint32_t src, uint32_t bytes) {
  asm volatile("cp.reduce.async.bulk.global.shared::cta.bulk_group.add.f32 [%0], [%1], %2;" :: "l"(dst), "r"(src), "r"(bytes) : "memory");
}
__device__ __forceinline__ void tma_store2d(const CUtensorMap* m, uint32_t src, int c0, int c1) {
  asm volatile("cp.async.bulk.tensor.2d.global.shared::cta.bulk_group [%0, {%2, %3}], [%1];" :: "l"(m), "r"(src), "r"(c0), "r"(c1) : "memory");
}
__device__ __forceinline__ void bulk_wait() { asm volatile("cp.async.bulk.commit_group;\ncp.async.bulk.wait_group 0;" ::: "memory"); }
__device__ __forceinline__ void bulk_done() { bulk_wait(); asm volatile("fence.acq_rel.gpu;" ::: "memory"); }
__device__ __forceinline__ void stsm4(uint32_t a, uint32_t r0, uint32_t r1, uint32_t r2, uint32_t r3) {
  asm volatile("stmatrix.sync.aligned.m8n8.x4.shared.b16 [%0], {%1, %2, %3, %4};" :: "r"(a), "r"(r0), "r"(r1), "r"(r2), "r"(r3) : "memory");
}
__device__ __forceinline__ void flag_add(unsigned* f) { asm volatile("red.relaxed.gpu.global.add.u32 [%0], 1;" :: "l"(f) : "memory"); }
__device__ __forceinline__ float4 lds_f4(uint32_t a) { return *reinterpret_cast<const float4*>(__cvta_shared_to_generic(a)); }
__device__ __forceinline__ void lds8(uint32_t a, float (&v)[8]) {
  const float4 p = lds_f4(a), q = lds_f4(a + 16);
  v[0] = p.x; v[1] = p.y; v[2] = p.z; v[3] = p.w; v[4] = q.x; v[5] = q.y; v[6] = q.z; v[7] = q.w;
}
__device__ __forceinline__ uint4 pack8(const float (&v)[8]) {
  return make_uint4(pack_bf16(v[0], v[1]), pack_bf16(v[2], v[3]), pack_bf16(v[4], v[5]), pack_bf16(v[6], v[7]));
}
__device__ __forceinline__ float quad_sum(float v) {
  v += __shfl_xor_sync(0xffffffffu, v, 1);
  v += __shfl_xor_sync(0xffffffffu, v, 2);
  return v;
}
__device__ __forceinline__ void mbar_wait_c(uint32_t a, uint32_t ph) {
  asm volatile("{\n.reg .pred p;\nSPIN:\nmbarrier.try_wait.parity.shared::cta.b64 p, [%0], %1;\n@!p bra SPIN;\n}\n" :: "r"(a), "r"(ph) : "memory");
}
constexpr int ST_P = 80;
constexpr int E_TILE = 128 * 80 * 2;

struct Maps { CUtensorMap h, wq, k, v, o, wo, xa, w1t, us, w2t, x1, w3, g, w4t, ex, sxa, sus, sx1, sout; };

constexpr int M_AOFF = 5 * A_SLOT, M_NA = 6, M_ARING = M_NA * 8192;

__global__ void __cluster_dims__(2, 1, 1) __launch_bounds__(384, 1)
fused_kernel(const __grid_constant__ Maps tm, const __grid_constant__ PrepW pw, const bf16* __restrict__ x, bf16* __restrict__ out) {
  extern __shared__ uint8_t smem_raw[];
  const uint32_t sb = (smem_u32(smem_raw) + 1023) & ~1023u;
  const uint32_t bar_full = sb + A_NSLOT * A_SLOT;
  const uint32_t bar_empty = bar_full + 8 * A_NSLOT;
  const uint32_t bar_sig = bar_empty + 8 * A_NSLOT;
  const uint32_t mb_full = bar_sig + 16;
  const uint32_t mb_empty = mb_full + 136;
  const uint32_t par = sb + T_PAR;
  float* parf = reinterpret_cast<float*>(smem_raw + (par - smem_u32(smem_raw)));
  uint32_t rank;
  asm volatile("mov.u32 %0, %%cluster_ctarank;" : "=r"(rank));
  if (blockIdx.x < 4) {
    const int lane = threadIdx.x & 31, gw = blockIdx.x * 12 + (threadIdx.x >> 5);
    float* sc = reinterpret_cast<float*>(smem_raw);
    for (int i = threadIdx.x; i < D_; i += 384) sc[i] = silu_bf(__bfloat162float(pw.c[i]));
    __syncthreads();
    pdl_wait();
    if (gw < 40) prep_mod(pw, sc, lane, gw);
#pragma unroll 1
    for (int job = 47 - gw; job < 120; job += 48) prep_cs3(pw, lane, job);
    prep_transpose(pw, reinterpret_cast<bf16(*)[72]>(smem_raw + 4096 + (threadIdx.x >> 5) * 4608), lane, gw, 48);
    return;
  }
  const int bid = blockIdx.x - 4;
  const int cid = bid >> 1;
  const int wid = __shfl_sync(0xffffffffu, threadIdx.x >> 5, 0);
  const int wg = wid >> 2;
  const int qtile = (cid & 7) * 2 + rank, hbase = cid >> 3;
  const int o_qt = qtile, o_nh = (cid >> 3) & 1, o_ks = cid >> 4;
  const int o_col = o_nh * 320 + o_ks * 80;
  const int qt = cid >> 2, js = (cid & 3) * 2 + rank;
  if (threadIdx.x == 0) {
    for (int i = 0; i < A_NSLOT; i++) { mbar_init(bar_full + 8 * i, 1); mbar_init(bar_empty + 8 * i, 16); }
    mbar_init(bar_sig, 4); mbar_init(bar_sig + 8, 4);
    for (int i = 0; i < 17; i++) mbar_init(mb_full + 8 * i, 1);
    for (int i = 0; i < 11; i++) mbar_init(mb_empty + 8 * i, 8);
    asm volatile("fence.mbarrier_init.release.cluster;" ::: "memory");
    prefetch_tmap(&tm.h); prefetch_tmap(&tm.wq); prefetch_tmap(&tm.k); prefetch_tmap(&tm.v);
  }
  __syncthreads();
  cluster_sync();

  if (wg == 0) {
    asm volatile("setmaxnreg.dec.sync.aligned.u32 40;");
    if (wid == 0) {
      Ring r{0, 1};
#define P_ACQ(bytes_) do { mbar_wait(bar_empty + 8 * r.slot, r.phase); mbar_expect_e(bar_full + 8 * r.slot, bytes_); } while (0)
#define P_DST (sb + r.slot * A_SLOT)
#define P_BAR (bar_full + 8 * r.slot)
      uint64_t pol_ef;
      asm volatile("createpolicy.fractional.L2::evict_first.b64 %0, 1.0;" : "=l"(pol_ef));
      if (qtile < 10) l2_prefetch_t3d(&tm.wq, 0, qtile * 64, hbase * 3);
      else l2_prefetch_t3d((qtile & 1) ? &tm.v : &tm.k, 0, hbase * S_ + ((qtile - 10) >> 1) * 64, 0);
      pdl_wait();
#pragma unroll 1
      for (int item = 0; item < 4; item++) {
        const int head = hbase + 8 * item;
#pragma unroll 1
        for (int kb = 0; kb < 10; kb++) {
          P_ACQ(16384);
          tma2d(P_DST, &tm.h, P_BAR, kb * 64, qtile * 128);
          r.adv(A_NSLOT);
          P_ACQ(A_SLOT);
          if ((uint32_t)(kb & 1) == rank) tma3d_mc_hint(P_DST, &tm.wq, P_BAR, 0, kb * 64, head * 3, 3, pol_ef);
          r.adv(A_NSLOT);
        }
#pragma unroll 1
        for (int j = 0; j <= A_NKV; j++) {
          if (j < A_NKV) {
            P_ACQ(A_SLOT);
            if (rank == 0) tma3d_mc_hint(P_DST, &tm.k, P_BAR, 0, head * S_ + j * 64, 0, 3, pol_ef);
            r.adv(A_NSLOT);
          }
          if (j > 0) {
            P_ACQ(A_SLOT);
            if (rank == 1) tma3d_mc_hint(P_DST, &tm.v, P_BAR, 0, head * S_ + (j - 1) * 64, 0, 3, pol_ef);
            r.adv(A_NSLOT);
          }
          if (item < 3 && j == 16 && qtile < 10) l2_prefetch_t3d(&tm.wq, 0, qtile * 64, (head + 8) * 3);
          if (item == 3) {
            if (j >= 24 && j < 30) flag_wait(g_flag + F_O + o_qt * 32 + ((j - 24) >> 1) * 8 + 2 * o_ks + (j & 1), 2);
            if (j == 0 && threadIdx.x == 0) {
              prefetch_tmap(&tm.o); prefetch_tmap(&tm.wo); prefetch_tmap(&tm.xa); prefetch_tmap(&tm.w1t); prefetch_tmap(&tm.us);
              prefetch_tmap(&tm.w2t); prefetch_tmap(&tm.x1); prefetch_tmap(&tm.w3); prefetch_tmap(&tm.g); prefetch_tmap(&tm.w4t);
              prefetch_tmap(&tm.ex);
              prefetch_tmap(&tm.sxa); prefetch_tmap(&tm.sus); prefetch_tmap(&tm.sx1); prefetch_tmap(&tm.sout);
            }
          }
        }
      }
#pragma unroll 1
      for (int kb = 0; kb < 24; kb++) {
        const int head = (kb / 6) * 8 + 2 * o_ks + (kb % 6) / 3;
        const int kcol = head * DH_ + (kb % 3) * 64;
        if (kb == 18 || kb == 21) flag_wait(g_flag + F_O + o_qt * 32 + head, 2);
        if (kb % 3 == 0) fence_async_global();
        P_ACQ(16384);
        tma2d(P_DST, &tm.o, P_BAR, kcol, o_qt * 128);
        r.adv(A_NSLOT);
        P_ACQ(20480);
        if (rank == 0) tma3d_mc(P_DST, &tm.wo, P_BAR, 0, kcol, o_nh * 5, 3);
        r.adv(A_NSLOT);
        P_ACQ(20480);
        if (rank == 1) tma3d_mc(P_DST, &tm.wo, P_BAR, 0, kcol + 32, o_nh * 5, 3);
        r.adv(A_NSLOT);
      }
      P_ACQ(E_TILE);
      tma2d(P_DST, &tm.ex, P_BAR, o_col, o_qt * 128);
      r.adv(A_NSLOT);
      flag_wait(g_flag + F_XCH + (o_qt * 2 + o_nh) * 4 + o_ks, 6);
      fence_async_global();
#pragma unroll 1
      for (int i = 0; i < 3; i++) {
        P_ACQ(E_TILE);
        bulk_load(P_DST, g_xch + (size_t)((((o_qt * 2 + o_nh) * 4 + o_ks) * 4) + ((o_ks + 1 + i) & 3)) * (E_TILE / 2), E_TILE, P_BAR);
        r.adv(A_NSLOT);
      }
#pragma unroll 1
      for (int i = 0; i < A_NSLOT; i++) { mbar_wait(bar_empty + 8 * r.slot, r.phase); r.adv(A_NSLOT); }
      bar_arrive(7, 64);
      Ring ra{0, 1};
      const uint32_t fa = mb_full + 40 + rank * 48, fa_peer = mapa(fa, rank ^ 1);
      const int blk = qt * 2 + rank;
#pragma unroll 1
      for (int ph = 0; ph < 4; ph++) {
        const CUtensorMap* ma = ph == 0 ? &tm.xa : ph == 1 ? &tm.us : ph == 2 ? &tm.x1 : &tm.g;
        const int nkb = ph == 3 ? 24 : 10;
        const unsigned* fl = g_flag + F_XA + 32 * ph;
        flag_wait(fl + blk, 8);
        if (ph == 1) { if (blk > 0) flag_wait(fl + blk - 1, 8); if (blk < 31) flag_wait(fl + blk + 1, 8); }
        fence_async_global();
#pragma unroll 1
        for (int kb = 0; kb < nkb; kb++) {
          mbar_wait(mb_empty + 40 + 8 * ra.slot, ra.phase);
          mbar_expect_e(fa + 8 * ra.slot, 8192);
          asm volatile(ELECT_ "mbarrier.arrive.expect_tx.shared::cluster.b64 _, [%0], 8192;\n}\n" :: "r"(fa_peer + 8 * ra.slot) : "memory");
          tma2d_mc(sb + M_AOFF + rank * M_ARING + ra.slot * 8192, ma, fa + 8 * ra.slot, kb * 64, blk * 64, 3);
          ra.adv(M_NA);
        }
      }
    } else if (wid < 3) {
      const int w = wid - 1, lane = threadIdx.x & 31;
#pragma unroll 1
      for (int sig = 0; sig < 4; sig++) {
        mbar_wait(bar_sig + 8 * w, sig & 1);
        if (lane == 0) {
          asm volatile("fence.acq_rel.gpu;" ::: "memory");
          flag_add(g_flag + F_O + qtile * 32 + hbase + 8 * sig);
        }
        __syncwarp();
      }
    } else {
      const int lane = threadIdx.x & 31;
      pdl_wait();
#pragma unroll 1
      for (int i = 0; i < 200; i++) {
        unsigned v;
        asm volatile("ld.relaxed.gpu.global.u32 %0, [%1];" : "=r"(v) : "l"(g_flag + F_PREP) : "memory");
        if (v >= PREP_CTAS) break;
        __nanosleep(2000);
      }
      flag_wait(g_flag + F_PREP, PREP_CTAS);
#pragma unroll 1
      for (int i = lane; i < P_SC; i += 32) {
        const int v = i < P_CS3 ? i / 80 : 9, j = i - (i < P_CS3 ? v * 80 : P_CS3);
        const float* src = v == 0 ? g_mod + 2 * D_ + o_col : v == 1 ? g_mod + 4 * D_ + o_col : v == 2 ? g_mod + 3 * D_ + o_col
                         : v < 6 ? g_vec + (v - 3) * D_ + js * 80 : v == 6 ? g_mod + 4 * D_ + js * 80 : v == 7 ? g_mod + 3 * D_ + js * 80
                         : v == 8 ? g_mod + 5 * D_ + js * 80 : g_vec + 3 * D_ + js * 192;
        parf[i] = __ldcg(src + j);
      }
      float sv[5] = {0.f, 0.f, 0.f, 0.f, 0.f};
#pragma unroll 1
      for (int i = lane; i < D_; i += 32) {
        const float a = __ldcg(g_mod + 4 * D_ + i), b = __ldcg(g_mod + 3 * D_ + i);
        sv[0] += a; sv[1] = fmaf(a, a, sv[1]); sv[2] = fmaf(a, b, sv[2]); sv[3] += b; sv[4] = fmaf(b, b, sv[4]);
      }
#pragma unroll 1
      for (int o_ = 16; o_ > 0; o_ >>= 1) {
#pragma unroll
        for (int i = 0; i < 5; i++) sv[i] += __shfl_xor_sync(0xffffffffu, sv[i], o_);
      }
      if (lane == 0) {
#pragma unroll
        for (int i = 0; i < 5; i++) parf[P_SC + i] = sv[i];
      }
      bar_arrive(6, 288);
      fence_async_global();
      bar_sync(7, 64);
      Ring rb{0, 1};
#pragma unroll 1
      for (int ph = 0; ph < 4; ph++) {
        const CUtensorMap* mb = ph == 0 ? &tm.w1t : ph == 1 ? &tm.w2t : ph == 2 ? &tm.w3 : &tm.w4t;
        const int nbl = ph == 2 ? 10 : ph == 3 ? 12 : 5;
#pragma unroll 1
        for (int bl = 0; bl < nbl; bl++) {
          mbar_wait(mb_empty + 8 * rb.slot, rb.phase);
          mbar_expect_e(mb_full + 8 * rb.slot, ph == 2 ? 24576 : 20480);
          tma3d(sb + rb.slot * A_SLOT, mb, mb_full + 8 * rb.slot, 0, ph == 2 ? bl * 64 : js * 80, ph == 2 ? js * 3 : bl * 2);
          rb.adv(5);
        }
      }
    }
    __syncwarp();
    cluster_sync();
  } else {
    asm volatile("setmaxnreg.inc.sync.aligned.u32 232;");
    const int w = wg - 1;
    const int lane = threadIdx.x & 31;
    const int warp = wid & 3;
    const int tid = threadIdx.x - 128;
    const uint32_t rel_base = mapa(bar_empty, (lane == 0) ? rank : (rank ^ 1));
    Ring r{0, 0};
#define A_RELEASE(slot_) do { if (lane < 2) mbar_arrive_remote(rel_base + 8 * (slot_)); } while (0)
#define lrow (sb + (uint32_t)(((threadIdx.x - 128) >> 5) * 16 + (threadIdx.x & 15)) * 128)
#define lx ((threadIdx.x & 7) ^ ((threadIdx.x >> 4) & 1))
#define SIGNAL() do { __syncwarp(); if (lane == 0) mbar_arrive(bar_sig + 8 * w); } while (0)
    {
    const float SC = 0.07216878364870322f * 1.4426950408889634f;
    float o[96];
    uint32_t q[48];
    float s[32];
    uint32_t p[16], p2[16];
    if (w == 1) bar_arrive(1, 256);
    bf16* orow = g_o + (size_t)(qtile * 128 + w * 64 + warp * 16 + (lane >> 2)) * HD_ + (hbase - 8) * DH_ + (lane & 3) * 8;
#define O_STORE(g)                                                                                                     \
      {                                                                                                                \
        quad_transpose(q[8 * g], q[8 * g + 2], q[8 * g + 4], q[8 * g + 6], lane);                                      \
        stg128(orow + g * 32, make_uint4(q[8 * g], q[8 * g + 2], q[8 * g + 4], q[8 * g + 6]));                         \
        quad_transpose(q[8 * g + 1], q[8 * g + 3], q[8 * g + 5], q[8 * g + 7], lane);                                  \
        stg128(orow + (size_t)8 * HD_ + g * 32, make_uint4(q[8 * g + 1], q[8 * g + 3], q[8 * g + 5], q[8 * g + 7]));   \
      }
#pragma unroll 1
    for (int item = 0; item < 4; item++) {
      {
        uint32_t prevB = 0;
        uint32_t fh[2][16];
#pragma unroll
        for (int kb = 0; kb < 10; kb++) {
          uint32_t (&F)[16] = fh[kb & 1];
          const uint32_t sA = r.slot; mbar_wait_c(bar_full + 8 * sA, r.phase); r.adv(A_NSLOT);
#pragma unroll
          for (int kk = 0; kk < 4; kk++)
            asm volatile("ldmatrix.sync.aligned.m8n8.x4.shared.b16 {%0, %1, %2, %3}, [%4];"
                         : "=r"(F[4 * kk]), "=r"(F[4 * kk + 1]), "=r"(F[4 * kk + 2]), "=r"(F[4 * kk + 3])
                         : "r"(lrow + sA * A_SLOT + ((lx ^ (kk * 2)) << 4)) : "memory");
          fence_regs(F);
          const uint32_t sB = r.slot; mbar_wait_c(bar_full + 8 * sB, r.phase); r.adv(A_NSLOT);
          const uint64_t db = mkdesc(sb + sB * A_SLOT, 8192, 1024);
          wg_fence();
#pragma unroll
          for (int kk = 0; kk < 4; kk++) wgmma_rs_n192<1>(o, F[4 * kk], F[4 * kk + 1], F[4 * kk + 2], F[4 * kk + 3], db + kk * 128, (kb | kk) != 0);
          wg_commit();
          A_RELEASE(sA);
          if (kb >= 4 && item > 0) { O_STORE((kb >= 4 ? kb - 4 : 0)) }
          if (kb == 9 && item > 0) SIGNAL();
          if (kb > 0) { wg_wait<1>(); fence_regs(fh[(kb & 1) ^ 1]); A_RELEASE(prevB); }
          prevB = sB;
        }
        wg_wait<0>();
        fence_regs(o);
        A_RELEASE(prevB);
#pragma unroll
        for (int i = 0; i < 48; i++) q[i] = pack_bf16(o[2 * i], o[2 * i + 1]);
      }
      orow += 8 * DH_;

      float c0, c1, l0, l1;
      {
        const uint32_t sK = r.slot; mbar_wait_c(bar_full + 8 * sK, r.phase); r.adv(A_NSLOT);
        const uint64_t dk = mkdesc(sb + sK * A_SLOT, 16, 1024);
        bar_sync(1 + w, 256);
        wg_fence();
#pragma unroll
        for (int kk = 0; kk < 12; kk++)
          wgmma_rs_n64<0>(s, q[4 * kk], q[4 * kk + 1], q[4 * kk + 2], q[4 * kk + 3], dk + (kk >> 2) * 512 + (kk & 3) * 2, kk != 0);
        wg_commit();
        bar_arrive(1 + (w ^ 1), 256);
        wg_wait<0>();
        fence_regs(s);
        A_RELEASE(sK);
        float mx0 = fmaxf(s[0], s[1]), mx1 = fmaxf(s[2], s[3]);
#pragma unroll
        for (int i = 1; i < 8; i++) { mx0 = fmaxf(mx0, fmaxf(s[4 * i], s[4 * i + 1])); mx1 = fmaxf(mx1, fmaxf(s[4 * i + 2], s[4 * i + 3])); }
        mx0 = fmaxf(mx0, __shfl_xor_sync(0xffffffffu, mx0, 1)); mx1 = fmaxf(mx1, __shfl_xor_sync(0xffffffffu, mx1, 1));
        mx0 = fmaxf(mx0, __shfl_xor_sync(0xffffffffu, mx0, 2)); mx1 = fmaxf(mx1, __shfl_xor_sync(0xffffffffu, mx1, 2));
        c0 = mx0 * SC; c1 = mx1 * SC;
        l0 = 0.f; l1 = 0.f;
#pragma unroll
        for (int i = 0; i < 8; i++) {
          s[4 * i] = ex2(fmaf(s[4 * i], SC, -c0)); s[4 * i + 1] = ex2(fmaf(s[4 * i + 1], SC, -c0));
          s[4 * i + 2] = ex2(fmaf(s[4 * i + 2], SC, -c1)); s[4 * i + 3] = ex2(fmaf(s[4 * i + 3], SC, -c1));
          l0 += s[4 * i] + s[4 * i + 1]; l1 += s[4 * i + 2] + s[4 * i + 3];
        }
#pragma unroll
        for (int i = 0; i < 16; i++) p[i] = pack_bf16(s[2 * i], s[2 * i + 1]);
      }
      uint32_t okn;
      {
        Ring r2 = r; r2.adv(A_NSLOT);
        okn = mbar_try(bar_full + 8 * r.slot, r.phase) & mbar_try(bar_full + 8 * r2.slot, r2.phase);
      }
#define A_STEP(PC, PN, FIRST)                                                                                          \
      {                                                                                                                \
        const uint32_t sK = r.slot, phK = r.phase; r.adv(A_NSLOT);                                                     \
        const uint32_t sV = r.slot, phV = r.phase; r.adv(A_NSLOT);                                                     \
        const uint64_t dk = mkdesc(sb + sK * A_SLOT, 16, 1024);                                                        \
        const uint64_t dv = mkdesc(sb + sV * A_SLOT, 8192, 1024);                                                      \
        if (!okn) { mbar_wait_c(bar_full + 8 * sK, phK); mbar_wait_c(bar_full + 8 * sV, phV); }                            \
        bar_sync(1 + w, 256);                                                                                          \
        wg_fence();                                                                                                    \
        _Pragma("unroll") for (int kk = 0; kk < 12; kk++)                                                              \
          wgmma_rs_n64<0>(s, q[4 * kk], q[4 * kk + 1], q[4 * kk + 2], q[4 * kk + 3], dk + (kk >> 2) * 512 + (kk & 3) * 2, kk != 0); \
        wg_commit();                                                                                                   \
        _Pragma("unroll") for (int kk = 0; kk < 4; kk++)                                                               \
          wgmma_rs_n192<1>(o, PC[4 * kk], PC[4 * kk + 1], PC[4 * kk + 2], PC[4 * kk + 3], dv + kk * 128, !(FIRST) || (kk != 0)); \
        wg_commit();                                                                                                   \
        bar_arrive(1 + (w ^ 1), 256);                                                                                  \
        {                                                                                                              \
          Ring r2 = r; r2.adv(A_NSLOT);                                                                                \
          okn = mbar_try(bar_full + 8 * r.slot, r.phase) & mbar_try(bar_full + 8 * r2.slot, r2.phase);                 \
        }                                                                                                              \
        wg_wait<1>();                                                                                                  \
        fence_regs(s);                                                                                                 \
        A_RELEASE(sK);                                                                                                 \
        float b0 = 0.f, b1 = 0.f;                                                                                      \
        _Pragma("unroll") for (int i = 0; i < 8; i++) {                                                                \
          const float e0 = ex2(fmaf(s[4 * i], SC, -c0)), e1 = ex2(fmaf(s[4 * i + 1], SC, -c0));                        \
          const float e2 = ex2(fmaf(s[4 * i + 2], SC, -c1)), e3 = ex2(fmaf(s[4 * i + 3], SC, -c1));                    \
          b0 += e0 + e1; b1 += e2 + e3;                                                                                \
          PN[2 * i] = pack_bf16(e0, e1); PN[2 * i + 1] = pack_bf16(e2, e3);                                            \
        }                                                                                                              \
        wg_wait<0>();                                                                                                  \
        fence_regs(o);                                                                                                 \
        fence_regs(PC);                                                                                                \
        A_RELEASE(sV);                                                                                                 \
        if (__any_sync(0xffffffffu, !(b0 <= 65536.f) || !(b1 <= 65536.f))) {                                           \
          float mx0 = fmaxf(s[0], s[1]), mx1 = fmaxf(s[2], s[3]);                                                      \
          _Pragma("unroll") for (int i = 1; i < 8; i++) {                                                              \
            mx0 = fmaxf(mx0, fmaxf(s[4 * i], s[4 * i + 1])); mx1 = fmaxf(mx1, fmaxf(s[4 * i + 2], s[4 * i + 3]));     \
          }                                                                                                            \
          mx0 = fmaxf(mx0, __shfl_xor_sync(0xffffffffu, mx0, 1)); mx1 = fmaxf(mx1, __shfl_xor_sync(0xffffffffu, mx1, 1)); \
          mx0 = fmaxf(mx0, __shfl_xor_sync(0xffffffffu, mx0, 2)); mx1 = fmaxf(mx1, __shfl_xor_sync(0xffffffffu, mx1, 2)); \
          const float n0 = fmaxf(c0, mx0 * SC), n1 = fmaxf(c1, mx1 * SC);                                              \
          const float a0 = ex2(c0 - n0), a1 = ex2(c1 - n1);                                                            \
          c0 = n0; c1 = n1;                                                                                            \
          l0 *= a0; l1 *= a1;                                                                                          \
          _Pragma("unroll") for (int i = 0; i < 24; i++) { o[4 * i] *= a0; o[4 * i + 1] *= a0; o[4 * i + 2] *= a1; o[4 * i + 3] *= a1; } \
          b0 = 0.f; b1 = 0.f;                                                                                          \
          _Pragma("unroll") for (int i = 0; i < 8; i++) {                                                              \
            const float e0 = ex2(fmaf(s[4 * i], SC, -c0)), e1 = ex2(fmaf(s[4 * i + 1], SC, -c0));                      \
            const float e2 = ex2(fmaf(s[4 * i + 2], SC, -c1)), e3 = ex2(fmaf(s[4 * i + 3], SC, -c1));                  \
            b0 += e0 + e1; b1 += e2 + e3;                                                                              \
            PN[2 * i] = pack_bf16(e0, e1); PN[2 * i + 1] = pack_bf16(e2, e3);                                          \
          }                                                                                                            \
        }                                                                                                              \
        l0 += b0; l1 += b1;                                                                                            \
      }
      for (int jj = 0; jj < 15; jj++) {
        A_STEP(p, p2, jj == 0)
        A_STEP(p2, p, false)
      }
      A_STEP(p, p2, false)
      float i0, i1;
      {
        const uint32_t sV = r.slot; mbar_wait_c(bar_full + 8 * sV, r.phase); r.adv(A_NSLOT);
        const uint64_t dv = mkdesc(sb + sV * A_SLOT, 8192, 1024);
        bar_sync(1 + w, 256);
        wg_fence();
#pragma unroll
        for (int kk = 0; kk < 4; kk++)
          wgmma_rs_n192<1>(o, p2[4 * kk], p2[4 * kk + 1], p2[4 * kk + 2], p2[4 * kk + 3], dv + kk * 128, 1);
        wg_commit();
        bar_arrive(1 + (w ^ 1), 256);
        l0 += __shfl_xor_sync(0xffffffffu, l0, 1); l1 += __shfl_xor_sync(0xffffffffu, l1, 1);
        l0 += __shfl_xor_sync(0xffffffffu, l0, 2); l1 += __shfl_xor_sync(0xffffffffu, l1, 2);
        i0 = __fdividef(1.f, l0); i1 = __fdividef(1.f, l1);
        asm volatile("" : "+f"(i0), "+f"(i1));
        wg_wait<0>();
        fence_regs(o);
        A_RELEASE(sV);
      }
#pragma unroll
      for (int i = 0; i < 24; i++) { q[2 * i] = pack_bf16(o[4 * i] * i0, o[4 * i + 1] * i0); q[2 * i + 1] = pack_bf16(o[4 * i + 2] * i1, o[4 * i + 3] * i1); }
    }
#pragma unroll
    for (int g = 0; g < 6; g++) { O_STORE(g) }
    SIGNAL();
    }
    const uint32_t st_w = (uint32_t)((warp * 16 + (lane >> 2)) * ST_P + (lane & 3) * 2) * 4;
    const uint32_t st_x = (lane & 8) << 2;
    const int er = (tid & 127) >> 1, eh = tid & 1;
    const uint32_t st_r = (uint32_t)(er * ST_P + (eh ^ ((er >> 1) & 1)) * 8) * 4;
    const uint32_t p_r = par + eh * 32;
    const uint32_t stat = sb + T_PREP + w * 2048;
    const bool leader = (tid & 127) == 0;
    const float2* const pf2 = reinterpret_cast<const float2*>(parf) + (lane & 3);
    const uint32_t m_e = (uint32_t)((w * 64 + warp * 16 + (lane & 15)) * 160 + (lane >> 4) * 16);
#define LDSM4(R, i_, addr_) asm volatile("ldmatrix.sync.aligned.m8n8.x4.shared.b16 {%0, %1, %2, %3}, [%4];" : "=r"(R[i_]), "=r"(R[i_ + 1]), "=r"(R[i_ + 2]), "=r"(R[i_ + 3]) : "r"(addr_) : "memory")
#define STAGE10(ACC, BASE)                                                                                             \
    _Pragma("unroll") for (int nb = 0; nb < 10; nb++) {                                                                \
      sts_f2(stg + st_w + ((nb * 32) ^ st_x), ACC(BASE + 4 * nb), ACC(BASE + 4 * nb + 1));                                       \
      sts_f2(stg + st_w + ((nb * 32) ^ st_x) + 8 * ST_P * 4, ACC(BASE + 4 * nb + 2), ACC(BASE + 4 * nb + 3));                    \
    }

    {
      float acc1[96], acc2[64];
      uint32_t p0 = 0, p1 = 0, p2 = 0;
      uint32_t fa[16], fb[16];
#define O_STEP(F, kb_)                                                                                                 \
      {                                                                                                                \
        p2 = r.slot; mbar_wait_c(bar_full + 8 * p2, r.phase); r.adv(A_NSLOT);                                          \
        _Pragma("unroll") for (int kk = 0; kk < 4; kk++)                                                               \
          asm volatile("ldmatrix.sync.aligned.m8n8.x4.shared.b16 {%0, %1, %2, %3}, [%4];"                              \
                       : "=r"(F[4 * kk]), "=r"(F[4 * kk + 1]), "=r"(F[4 * kk + 2]), "=r"(F[4 * kk + 3])                \
                       : "r"(lrow + p2 * A_SLOT + ((lx ^ (kk * 2)) << 4)) : "memory");                                 \
        fence_regs(F);                                                                                                 \
        _Pragma("unroll") for (int hf = 0; hf < 2; hf++) {                                                             \
          const uint32_t s1 = r.slot; mbar_wait_c(bar_full + 8 * s1, r.phase); r.adv(A_NSLOT);                         \
          const uint64_t d1 = mkdesc(sb + s1 * A_SLOT, 4096, 1024);                                                    \
          wg_fence();                                                                                                  \
          _Pragma("unroll") for (int k2 = 0; k2 < 2; k2++) {                                                           \
            const int kk = hf * 2 + k2;                                                                                \
            wgmma_rs_n192<1>(acc1, F[4 * kk], F[4 * kk + 1], F[4 * kk + 2], F[4 * kk + 3], d1 + k2 * 128, ((kb_) | kk) != 0); \
            wgmma_rs_n128<1>(acc2, F[4 * kk], F[4 * kk + 1], F[4 * kk + 2], F[4 * kk + 3], d1 + k2 * 128 + 768, ((kb_) | kk) != 0); \
          }                                                                                                            \
          wg_commit();                                                                                                 \
          if (hf == 0 && (kb_) < 23) A_RELEASE(p2);         \
          if (((kb_) | hf) != 0) { wg_wait<1>(); if ((kb_) < 23 || hf == 0) A_RELEASE(p1); }                           \
          p0 = p1; p1 = s1;                                                                                            \
        }                                                                                                              \
      }
#pragma unroll 1
      for (int kb = 0; kb < 24; kb += 2) {
        O_STEP(fa, kb)
        fence_regs(fb);
        O_STEP(fb, kb + 1)
        fence_regs(fa);
      }
      wg_wait<0>();
      fence_regs(acc1); fence_regs(acc2);
      A_RELEASE(p2);
      bar_sync(6, 288);
      float at[40];
#define OACC(e) (((e) < 96) ? acc1[(e) < 96 ? (e) : 0] : acc2[(e) >= 96 ? (e) - 96 : 0])
      const uint32_t f1 = r.slot + 4 >= A_NSLOT ? r.slot + 4 - A_NSLOT : r.slot + 4, f2 = f1 + 1 >= A_NSLOT ? 0 : f1 + 1;
#pragma unroll
      for (int d = 0; d < 4; d++) {
        if (d != o_ks) {
          const int i = (d - o_ks - 1) & 3;
          const uint32_t xs = sb + (i == 0 ? p2 : i == 1 ? f1 : f2) * A_SLOT;
          const uint32_t xo = xs + m_e;
#pragma unroll
          for (int kk = 0; kk < 5; kk++)
            stsm4(xo + kk * 32, pack_bf16(OACC(d * 40 + 8 * kk), OACC(d * 40 + 8 * kk + 1)), pack_bf16(OACC(d * 40 + 8 * kk + 2), OACC(d * 40 + 8 * kk + 3)),
                  pack_bf16(OACC(d * 40 + 8 * kk + 4), OACC(d * 40 + 8 * kk + 5)), pack_bf16(OACC(d * 40 + 8 * kk + 6), OACC(d * 40 + 8 * kk + 7)));
          fence_async_smem();
          bar_sync(3 + w, 128);
          if (leader) bulk_store(g_xch + (size_t)((((o_qt * 2 + o_nh) * 4 + d) * 4) + o_ks) * (E_TILE / 2) + w * (E_TILE / 4), xs + w * (E_TILE / 2), E_TILE / 2);
          __syncwarp();
        } else {
#pragma unroll
          for (int i = 0; i < 40; i++) at[i] = OACC(d * 40 + i);
        }
      }
      if (leader) {
        bulk_done();
#pragma unroll 1
        for (int i = 0; i < 3; i++) flag_add(g_flag + F_XCH + (o_qt * 2 + o_nh) * 4 + ((o_ks + 1 + i) & 3));
      }
      __syncwarp();
      const uint32_t sx = r.slot; mbar_wait_c(bar_full + 8 * sx, r.phase); r.adv(A_NSLOT);
      float2 ga[10];
      uint32_t u0[20], u1[20], u2[20];
#pragma unroll
      for (int kk = 0; kk < 5; kk++) LDSM4(u0, 4 * kk, sb + sx * A_SLOT + m_e + kk * 32);
#pragma unroll
      for (int nb = 0; nb < 10; nb++) {
        ga[nb] = pf2[(P_OGA + 8 * nb) / 2];
#pragma unroll
        for (int h = 0; h < 2; h++) {
          at[4 * nb + 2 * h] = fmaf(ga[nb].x, at[4 * nb + 2 * h], bf_lo(u0[2 * nb + h]));
          at[4 * nb + 2 * h + 1] = fmaf(ga[nb].y, at[4 * nb + 2 * h + 1], bf_hi(u0[2 * nb + h]));
        }
      }
      fence_regs(at);
      const uint32_t q0 = r.slot; mbar_wait_c(bar_full + 8 * q0, r.phase); r.adv(A_NSLOT);
      const uint32_t q1 = r.slot; mbar_wait_c(bar_full + 8 * q1, r.phase); r.adv(A_NSLOT);
      const uint32_t q2 = r.slot; mbar_wait_c(bar_full + 8 * q2, r.phase); r.adv(A_NSLOT);
#pragma unroll
      for (int kk = 0; kk < 5; kk++) {
        LDSM4(u0, 4 * kk, sb + q0 * A_SLOT + m_e + kk * 32); LDSM4(u1, 4 * kk, sb + q1 * A_SLOT + m_e + kk * 32); LDSM4(u2, 4 * kk, sb + q2 * A_SLOT + m_e + kk * 32);
      }
#pragma unroll
      for (int i = 0; i < 20; i++)
        u0[i] = pack_bf16(fmaf(ga[i >> 1].x, (bf_lo(u0[i]) + bf_lo(u1[i])) + bf_lo(u2[i]), at[2 * i]),
                          fmaf(ga[i >> 1].y, (bf_hi(u0[i]) + bf_hi(u1[i])) + bf_hi(u2[i]), at[2 * i + 1]));
      const uint32_t ot = sb + p0 * A_SLOT;
#pragma unroll
      for (int kk = 0; kk < 5; kk++) stsm4(ot + m_e + kk * 32, u0[4 * kk], u0[4 * kk + 1], u0[4 * kk + 2], u0[4 * kk + 3]);
      fence_async_smem();
      bar_sync(3 + w, 128);
      if (leader) {
        tma_store2d(&tm.sxa, ot + w * (E_TILE / 2), o_col, o_qt * 128 + w * 64);
        bulk_done();
        flag_add(g_flag + F_XA + o_qt * 2 + w);
      }
      __syncwarp();
      A_RELEASE(p0); A_RELEASE(p1); A_RELEASE(sx); A_RELEASE(q0); A_RELEASE(q1); A_RELEASE(q2);
#pragma unroll 1
      for (int h = 0; h < 2; h++) {
        float st[6] = {0.f, 0.f, 0.f, 0.f, 0.f, 0.f};
#pragma unroll
        for (int nb = 0; nb < 10; nb++) {
          const float2 a = pf2[(P_OA + 8 * nb) / 2], b = pf2[(P_OB + 8 * nb) / 2];
          const uint32_t pk = h ? u0[2 * nb + 1] : u0[2 * nb];
          const float v0 = bf_lo(pk), v1 = bf_hi(pk), y0 = a.x * v0, y1 = a.y * v1;
          st[0] += v0 + v1; st[1] = fmaf(v0, v0, fmaf(v1, v1, st[1]));
          st[2] += y0 + y1; st[3] = fmaf(a.x, y0, fmaf(a.y, y1, st[3]));
          st[4] = fmaf(y0, y0, fmaf(y1, y1, st[4])); st[5] = fmaf(b.x, y0, fmaf(b.y, y1, st[5]));
        }
#pragma unroll
        for (int i = 0; i < 6; i++) st[i] = quad_sum(st[i]);
        if ((lane & 3) < 2)
          sts_u4(stat + (warp * 16 + (lane >> 2) + 8 * h) * 32 + (lane & 1) * 16,
                 (lane & 1) ? make_uint4(__float_as_uint(st[4]), __float_as_uint(st[5]), 0u, 0u)
                            : make_uint4(__float_as_uint(st[0]), __float_as_uint(st[1]), __float_as_uint(st[2]), __float_as_uint(st[3])));
      }
      fence_async_smem();
      bar_sync(3 + w, 128);
      if (leader) {
        bulk_red_f32(g_st1 + (size_t)(o_qt * 128 + w * 64) * 8, stat, 2048);
        bulk_done();
        flag_add(g_flag + F_ST1 + o_qt * 2 + w);
      }
      __syncwarp();
    }

    Ring ra{0, 0}, rb{0, 0};
    const uint32_t rel_a = mapa(mb_empty + 40, w);
    const uint32_t aring = sb + M_AOFF + w * M_ARING;
#define B_NEXT(s_) do { s_ = rb.slot; mbar_wait_c(mb_full + 8 * s_, rb.phase); rb.adv(5); } while (0)
#define A_NEXT(s_) do { s_ = ra.slot; mbar_wait_c(mb_full + 40 + w * 48 + 8 * s_, ra.phase); ra.adv(M_NA); } while (0)
#define B_RELEASE(s_) do { if (lane == 0) mbar_arrive(mb_empty + 8 * (s_)); } while (0)
#define MA_RELEASE(s_) do { if (lane == 0) mbar_arrive_remote(rel_a + 8 * (s_)); } while (0)
    const int grow = qt * 128 + w * 64 + er;
    const int frow = qt * 128 + w * 64 + warp * 16 + (lane >> 2);
    uint32_t xau[20], x1u[20];
#pragma unroll
    for (int i = 0; i < 20; i++) { xau[i] = 0u; x1u[i] = 0u; }
    const uint32_t stg = aring, ot = aring + 20480;
#define M_PUBLISH(ph_) do { if (leader) { if ((ph_) < 3) { bulk_done(); flag_add(g_flag + F_US + 32 * (ph_) + qt * 2 + w); } else bulk_wait(); } __syncwarp(); } while (0)
#pragma unroll 1
    for (int ph = 0; ph < 4; ph++) {
      uint32_t pa = 0, pa2 = 0, pb = 0;
      if (ph == 2) {
        float acc[96];
        float2 s2 = make_float2(0.f, 0.f);
#pragma unroll 1
        for (int it = 0; it < 10; it++) {
          uint32_t sbq, sa;
          B_NEXT(sbq);
          A_NEXT(sa);
          const uint64_t da = mkdesc(aring + sa * 8192, 16, 1024);
          const uint64_t db = mkdesc(sb + sbq * A_SLOT, 8192, 1024);
          wg_fence();
#pragma unroll
          for (int kk = 0; kk < 4; kk++) wgmma_ss_n192<1>(acc, da + kk * 2, db + kk * 128, (it | kk) != 0);
          wg_commit();
          if (it > 0) { wg_wait<1>(); MA_RELEASE(pa); B_RELEASE(pb); }
          if (it == 5) { flag_wait(g_flag + F_ST2 + qt * 2 + w, 8); s2 = __ldcg(reinterpret_cast<const float2*>(g_st2 + (size_t)grow * 2)); }
          pa = sa; pb = sbq;
        }
        wg_wait<0>();
        fence_regs(acc);
        MA_RELEASE(pa); B_RELEASE(pb);
        bar_sync(3 + w, 128);
        const float m = s2.x * (1.f / D_);
        const float c0 = rsqrtf(fmaxf(s2.y * (1.f / D_) - m * m, 0.f) + LN_EPS), c1 = -c0 * m;
#define MACC(e) acc[e]
#pragma unroll 1
        for (int ps = 0; ps < 3; ps++) {
          if (ps == 0) { STAGE10(MACC, 0) } else if (ps == 1) { STAGE10(MACC, 32) } else { STAGE10(MACC, 56) }
          bar_sync(3 + w, 128);
          const uint32_t cofs = ps == 2 ? 64 : 0;
#pragma unroll 1
          for (int c = 0; c < 4; c++) {
            float v[8], t[8];
            lds8(stg + st_r + cofs + c * 64, v);
            lds8(p_r + (P_CS3 + ps * 64) * 4 + c * 64, t);
#pragma unroll
            for (int e = 0; e < 8; e++) v[e] = gelu_tanh(fmaf(c0, v[e], c1 * t[e]));
            sts_u4(ot + ps * 8192 + er * 128 + (((2 * c + eh) ^ (er & 7)) << 4), pack8(v));
          }
          fence_async_smem();
          bar_sync(3 + w, 128);
          if (leader) tma_store2d(&tm.g, ot + ps * 8192, js * 192 + ps * 64, qt * 128 + w * 64);
          __syncwarp();
        }
        M_PUBLISH(2);
        continue;
      }
      float acc[40];
      float4 s03 = make_float4(0.f, 0.f, 0.f, 0.f);
      float2 s45 = make_float2(0.f, 0.f);
      if (ph == 1) {
        const uint32_t* xp = reinterpret_cast<const uint32_t*>(g_xa + (size_t)frow * D_ + js * 80) + (lane & 3);
        float2 sv[2];
#pragma unroll
        for (int h = 0; h < 2; h++) sv[h] = __ldcg(reinterpret_cast<const float2*>(g_st1 + (size_t)(frow + 8 * h) * 8));
#pragma unroll
        for (int i = 0; i < 20; i++) xau[i] = __ldcg(xp + (i >> 1) * 4 + (i & 1) * (8 * D_ / 2));
#pragma unroll
        for (int h = 0; h < 2; h++) {
          const float m = sv[h].x * (1.f / D_), rr = rsqrtf(fmaxf(sv[h].y * (1.f / D_) - m * m, 0.f) + LN_EPS);
#pragma unroll
          for (int nb = 0; nb < 10; nb++) {
            const float2 a = pf2[(P_A2 + 8 * nb) / 2], b = pf2[(P_B2 + 8 * nb) / 2];
            acc[4 * nb + 2 * h] = fmaf(a.x * rr, bf_lo(xau[2 * nb + h]) - m, b.x);
            acc[4 * nb + 2 * h + 1] = fmaf(a.y * rr, bf_hi(xau[2 * nb + h]) - m, b.y);
          }
        }
      } else {
#pragma unroll
        for (int i = 0; i < 20; i++) { acc[2 * i] = ph ? bf_lo(x1u[i]) : 0.f; acc[2 * i + 1] = ph ? bf_hi(x1u[i]) : 0.f; }
      }
      fence_regs(acc);
      const int nit = ph == 3 ? 12 : 5;
#pragma unroll 1
      for (int it = 0; it < nit; it++) {
        uint32_t sbq, sa, sa2;
        B_NEXT(sbq);
        A_NEXT(sa);
        A_NEXT(sa2);
        const uint64_t da = mkdesc(aring + sa * 8192, 16, 1024), da2 = mkdesc(aring + sa2 * 8192, 16, 1024);
        const uint64_t db = mkdesc(sb + sbq * A_SLOT, 16, 1024);
        wg_fence();
#pragma unroll
        for (int kk = 0; kk < 4; kk++) wgmma_ss_n80<0>(acc, da + kk * 2, db + kk * 2, 1);
#pragma unroll
        for (int kk = 0; kk < 4; kk++) wgmma_ss_n80<0>(acc, da2 + kk * 2, db + 640 + kk * 2, 1);
        wg_commit();
        if (it > 0) { wg_wait<1>(); MA_RELEASE(pa); MA_RELEASE(pa2); B_RELEASE(pb); }
        if (ph == 0 && it == 2) {
          flag_wait(g_flag + F_ST1 + qt * 2 + w, 8);
          s03 = __ldcg(reinterpret_cast<const float4*>(g_st1 + (size_t)grow * 8)); s45 = __ldcg(reinterpret_cast<const float2*>(g_st1 + (size_t)grow * 8 + 4));
        }
        pa = sa; pa2 = sa2; pb = sbq;
      }
      wg_wait<0>();
      fence_regs(acc);
      MA_RELEASE(pa); MA_RELEASE(pa2); B_RELEASE(pb);
      bar_sync(3 + w, 128);
      if (ph == 0) {
        STAGE10(MACC, 0)
        const float4 sc = lds_f4(par + P_SC * 4);
        const float sbb = lds_f(par + (P_SC + 4) * 4);
        const float mu = s03.x * (1.f / D_);
        const float rs = rsqrtf(fmaxf(s03.y * (1.f / D_) - mu * mu, 0.f) + LN_EPS);
        const float m2 = (rs * (s03.z - mu * sc.x) + sc.w) * (1.f / D_);
        const float e2 = (rs * rs * (s45.x - 2.f * mu * s03.w + mu * mu * sc.y) + 2.f * rs * (s45.y - mu * sc.z) + sbb) * (1.f / D_);
        const float c2 = rsqrtf(fmaxf(e2 - m2 * m2, 0.f) + LN_EPS);
        const float c0 = c2 * rs, c1 = -c0 * mu, c3 = -c2 * m2;
        if ((tid & 127) < 10) sts_u4(stat + (tid & 127) * 16, make_uint4(0, 0, 0, 0));
        bar_sync(3 + w, 128);
#pragma unroll 1
        for (int c = 0; c < 5; c++) {
          float v[8], t[8], t2[8], t3[8];
          lds8(stg + st_r + c * 64, v);
          lds8(p_r + P_VA * 4 + c * 64, t); lds8(p_r + P_VB * 4 + c * 64, t2); lds8(p_r + P_VC * 4 + c * 64, t3);
#pragma unroll
          for (int e = 0; e < 8; e++) v[e] = gelu_tanh(fmaf(c0, v[e], fmaf(c1, t[e], fmaf(c2, t2[e], c3 * t3[e]))));
          sts_u4(ot + er * 160 + eh * 16 + c * 32, pack8(v));
        }
        fence_async_smem();
        bar_sync(3 + w, 128);
        if (leader) {
          const int grp = js >> 1;
          const int sh = (grp & 2 ? 2 : 1) * (grp & 1 ? -1 : 1);
          tma_store2d(&tm.sus, ot, js * 80, qt * 128 + w * 64 + sh + 2);
          if (qt * 2 + w == (sh > 0 ? 0 : 31)) {
            const int r0 = sh > 0 ? 0 : S_ + sh, n = sh > 0 ? sh : -sh;
#pragma unroll 1
            for (int i = 0; i < n; i++) bulk_store(g_us + (size_t)(r0 + i + 2) * D_ + js * 80, stat, 160);
          }
        }
      } else {
        if (ph == 3) {
#pragma unroll
          for (int nb = 0; nb < 10; nb++) {
            const float2 gb = pf2[(P_GB + 8 * nb) / 2];
#pragma unroll
            for (int h = 0; h < 2; h++) {
              acc[4 * nb + 2 * h] = fmaf(gb.x, acc[4 * nb + 2 * h], bf_lo(xau[2 * nb + h]));
              acc[4 * nb + 2 * h + 1] = fmaf(gb.y, acc[4 * nb + 2 * h + 1], bf_hi(xau[2 * nb + h]));
            }
          }
        }
#pragma unroll
        for (int i = 0; i < 20; i++) x1u[i] = pack_bf16(acc[2 * i], acc[2 * i + 1]);
#pragma unroll
        for (int kk = 0; kk < 5; kk++)
          stsm4(ot + (warp * 16 + (lane & 15)) * 160 + (lane >> 4) * 16 + kk * 32, x1u[4 * kk], x1u[4 * kk + 1], x1u[4 * kk + 2], x1u[4 * kk + 3]);
        fence_async_smem();
        bar_sync(3 + w, 128);
        if (leader) {
          tma_store2d(ph == 1 ? &tm.sx1 : &tm.sout, ot, js * 80, qt * 128 + w * 64);
        }
      }
      M_PUBLISH(ph);
        if (ph == 1) {
#pragma unroll
          for (int h = 0; h < 2; h++) {
            float s1 = 0.f, s2 = 0.f;
#pragma unroll
            for (int nb = 0; nb < 10; nb++) {
              const float y0 = bf_lo(x1u[2 * nb + h]), y1 = bf_hi(x1u[2 * nb + h]);
              s1 += y0 + y1; s2 = fmaf(y0, y0, fmaf(y1, y1, s2));
            }
            s1 = quad_sum(s1); s2 = quad_sum(s2);
            if ((lane & 3) == 0) sts_f2(stat + (warp * 16 + (lane >> 2) + 8 * h) * 8, s1, s2);
          }
          fence_async_smem();
          bar_sync(3 + w, 128);
          if (leader) {
            bulk_red_f32(g_st2 + (size_t)(qt * 128 + w * 64) * 2, stat, 512);
            bulk_done();
            flag_add(g_flag + F_ST2 + qt * 2 + w);
          }
          __syncwarp();
        }
    }
    cluster_sync();
  }
}

typedef CUresult (*EncFn)(CUtensorMap*, CUtensorMapDataType, cuuint32_t, void*, const cuuint64_t*, const cuuint64_t*,
                          const cuuint32_t*, const cuuint32_t*, CUtensorMapInterleave, CUtensorMapSwizzle,
                          CUtensorMapL2promotion, CUtensorMapFloatOOBfill);
static EncFn g_enc = nullptr;

static CUtensorMap map2d(const void* p, uint64_t rows, uint64_t cols, uint32_t box_rows) {
  CUtensorMap m;
  cuuint64_t gd[2] = {cols, rows}; cuuint64_t gs[1] = {cols * 2};
  cuuint32_t bx[2] = {64, box_rows}; cuuint32_t es[2] = {1, 1};
  g_enc(&m, CU_TENSOR_MAP_DATA_TYPE_BFLOAT16, 2, const_cast<void*>(p), gd, gs, bx, es, CU_TENSOR_MAP_INTERLEAVE_NONE,
        CU_TENSOR_MAP_SWIZZLE_128B, CU_TENSOR_MAP_L2_PROMOTION_L2_256B, CU_TENSOR_MAP_FLOAT_OOB_FILL_NONE);
  return m;
}
static CUtensorMap map3d(const void* p, uint64_t rows, uint64_t cols, uint32_t box_rows, uint32_t nblk) {
  CUtensorMap m;
  cuuint64_t gd[3] = {64, rows, cols / 64}; cuuint64_t gs[2] = {cols * 2, 128};
  cuuint32_t bx[3] = {64, box_rows, nblk}; cuuint32_t es[3] = {1, 1, 1};
  g_enc(&m, CU_TENSOR_MAP_DATA_TYPE_BFLOAT16, 3, const_cast<void*>(p), gd, gs, bx, es, CU_TENSOR_MAP_INTERLEAVE_NONE,
        CU_TENSOR_MAP_SWIZZLE_128B, CU_TENSOR_MAP_L2_PROMOTION_L2_256B, CU_TENSOR_MAP_FLOAT_OOB_FILL_NONE);
  return m;
}

static CUtensorMap map_e(const void* p, uint32_t rows, uint64_t total_rows = S_) {
  CUtensorMap m;
  cuuint64_t gd[2] = {D_, total_rows}; cuuint64_t gs[1] = {D_ * 2};
  cuuint32_t bx[2] = {80, rows}; cuuint32_t es[2] = {1, 1};
  g_enc(&m, CU_TENSOR_MAP_DATA_TYPE_BFLOAT16, 2, const_cast<void*>(p), gd, gs, bx, es, CU_TENSOR_MAP_INTERLEAVE_NONE,
        CU_TENSOR_MAP_SWIZZLE_NONE, CU_TENSOR_MAP_L2_PROMOTION_L2_256B, CU_TENSOR_MAP_FLOAT_OOB_FILL_NONE);
  return m;
}

template <typename... KArgs, typename... Args>
static void launch(void (*kern)(KArgs...), dim3 grid, dim3 block, int smem, bool pdl, Args... args) {
  cudaLaunchConfig_t cfg = {};
  cfg.gridDim = grid; cfg.blockDim = block; cfg.dynamicSmemBytes = smem; cfg.stream = cudaStreamPerThread;
  cudaLaunchAttribute at[1];
  at[0].id = cudaLaunchAttributeProgrammaticStreamSerialization;
  at[0].val.programmaticStreamSerializationAllowed = 1;
  cfg.attrs = at; cfg.numAttrs = pdl ? 1 : 0;
  cudaLaunchKernelEx(&cfg, kern, KArgs(args)...);
}

extern "C" void kernel_launch(void* const* d_in, const int* in_sizes, int n_in, void* d_out, int out_size) {
  const bf16* x = (const bf16*)d_in[0];
  const bf16* kc = (const bf16*)d_in[1];
  const bf16* vc = (const bf16*)d_in[2];
  const bf16* wq = (const bf16*)d_in[3];
  const bf16* wo = (const bf16*)d_in[4];
  const bf16* w1 = (const bf16*)d_in[6];
  const bf16* w2 = (const bf16*)d_in[7];
  const bf16* w3 = (const bf16*)d_in[8];
  const bf16* w4 = (const bf16*)d_in[9];
  const bf16* c = (const bf16*)d_in[10];
  const bf16* wmod = (const bf16*)d_in[11];
  bf16* out = (bf16*)d_out;

  static void *p_h, *p_o, *p_xa, *p_us, *p_x1, *p_g, *p_w1t, *p_w2t, *p_w4t;
  if (!g_enc) {
    void* fn = nullptr; cudaDriverEntryPointQueryResult qr;
    cudaGetDriverEntryPoint("cuTensorMapEncodeTiled", &fn, cudaEnableDefault, &qr);
    g_enc = (EncFn)fn;
    cudaGetSymbolAddress(&p_h, g_h); cudaGetSymbolAddress(&p_o, g_o); cudaGetSymbolAddress(&p_xa, g_xa);
    cudaGetSymbolAddress(&p_us, g_us); cudaGetSymbolAddress(&p_x1, g_x1); cudaGetSymbolAddress(&p_g, g_g);
    cudaGetSymbolAddress(&p_w1t, g_w1t); cudaGetSymbolAddress(&p_w2t, g_w2t); cudaGetSymbolAddress(&p_w4t, g_w4t);
    cudaFuncSetAttribute(fused_kernel, cudaFuncAttributeMaxDynamicSharedMemorySize, T_SMEM);
  }
  Maps tm;
  tm.h = map2d(p_h, S_, D_, 128);
  tm.wq = map3d(wq, D_, HD_, 64, 3);
  tm.k = map3d(kc, (uint64_t)H_ * S_, DH_, 64, 3);
  tm.v = map3d(vc, (uint64_t)H_ * S_, DH_, 64, 3);
  tm.o = map2d(p_o, S_, HD_, 128);
  tm.wo = map3d(wo, HD_, D_, 32, 5);
  tm.xa = map2d(p_xa, S_, D_, 64);
  tm.w1t = map3d(p_w1t, D_, D_, 80, 2);
  tm.us = map2d((const bf16*)p_us + 2 * D_, S_, D_, 64);
  tm.w2t = map3d(p_w2t, D_, D_, 80, 2);
  tm.x1 = map2d(p_x1, S_, D_, 64);
  tm.w3 = map3d(w3, D_, F_, 64, 3);
  tm.g = map2d(p_g, S_, F_, 64);
  tm.w4t = map3d(p_w4t, D_, F_, 80, 2);
  tm.ex = map_e(x, 128);
  tm.sxa = map_e(p_xa, 64); tm.sus = map_e(p_us, 64, S_ + 4); tm.sx1 = map_e(p_x1, 64); tm.sout = map_e(out, 64);

  launch(mod_kernel, dim3(80), dim3(256), 0, false, c, wmod);
  launch(ln1_kernel, dim3(256), dim3(256), 0, true, x);
  launch(fused_kernel, dim3(132), dim3(384), T_SMEM, true, tm, PrepW{w1, w2, w3, w4, c, wmod}, x, out);
}
```
